```python
import torch

def _softmax(x, axis=-1):
    return torch.softmax(x, dim=axis)

def _gelu(x):
    return torch.nn.functional.gelu(x, approximate='tanh')

def _silu(x):
    return torch.nn.functional.silu(x)

def _sigmoid(x):
    return torch.sigmoid(x)

def _layernorm(x, axis=-1, eps=1e-05):
    m = x.mean(dim=axis, keepdim=True)
    v = x.var(dim=axis, keepdim=True, unbiased=False)
    return (x - m) / torch.sqrt(v + eps)

def _scatter_add(tgt, idx, src, axis=0):
    return tgt.clone().index_add_(axis, idx, src)

def _segment_sum(src, seg, n):
    out = torch.zeros((n,) + src.shape[1:], dtype=src.dtype)
    return out.index_add_(0, seg, src)

def _pad(x, pw):
    flat = tuple((v for pair in reversed(pw) for v in pair))
    return torch.nn.functional.pad(x, flat)
kernel_name = 'adaLN_cond__ssm_conv_h3__glu_gated_bilinear__prompt'

def setup_inputs():

    _w = lambda a: (lambda t: t.to(torch.bfloat16) if t.is_floating_point() else t)(torch.as_tensor(a))

    def _A_setup():
        B, S, D = (1, 2048, 640)
        ks = 4
        return {'q': _w((lambda *s: torch.randn(*s, dtype=torch.bfloat16) * 0.05)(B, S, D)), 'k': _w((lambda *s: torch.randn(*s, dtype=torch.bfloat16) * 1.6)(B, S, D)), 'v': _w((lambda *s: torch.randn(*s, dtype=torch.bfloat16) * 1.6)(B, S, D)), 'shift_k': _w((lambda *s: torch.randn(*s, dtype=torch.bfloat16) * 1.6)(D, ks) * 0.5), 'ssm_k': _w((lambda *s: torch.randn(*s, dtype=torch.bfloat16) * 1.6)(D, S) * (1.0 / S ** 0.5)), 'ssm_D': _w((lambda *s: torch.randn(*s, dtype=torch.bfloat16) * 1.6)(D))}
    _A_in = _A_setup()

    def _B_setup():
        B, S, D, F = (1, 2048, 640, 1536)
        return {'x': _w((lambda *s: torch.randn(*s, dtype=torch.bfloat16) * 0.05)(B, S, D)), 'w_gate': _w((lambda *s: torch.randn(*s, dtype=torch.bfloat16) * 3.2)(D, F) * D ** (-0.5)), 'w_up': _w((lambda *s: torch.randn(*s, dtype=torch.bfloat16) * 3.2)(D, F) * D ** (-0.5)), 'w_down': _w((lambda *s: torch.randn(*s, dtype=torch.bfloat16) * 3.2)(F, D) * F ** (-0.5))}
    _B_in = _B_setup()
    return {'A_q': _A_in['q'], 'A_k': _A_in['k'], 'A_v': _A_in['v'], 'A_shift_k': _A_in['shift_k'], 'A_ssm_k': _A_in['ssm_k'], 'A_ssm_D': _A_in['ssm_D'], 'B_x': _B_in['x'], 'B_w_gate': _B_in['w_gate'], 'B_w_up': _B_in['w_up'], 'B_w_down': _B_in['w_down'], 'c': _w((lambda *s: torch.randn(*s, dtype=torch.bfloat16) * 0.2)(1, 640) * 8.0), 'w_mod': _w((lambda *s: torch.randn(*s, dtype=torch.bfloat16) * 0.2)(640, 6 * 640) * 640 ** (-0.5) * 8.0)}

def reference(A_q, A_k, A_v, A_shift_k, A_ssm_k, A_ssm_D, B_x, B_w_gate, B_w_up, B_w_down, c, w_mod):

    def _A_ref(q, k, v, shift_k, ssm_k, ssm_D):
        B, S, D = q.shape
        ks = shift_k.shape[-1]
        k_pad = _pad(k, ((0, 0), (ks - 1, 0), (0, 0)))
        k_shift = torch.zeros_like(k)
        for t in range(ks):
            k_shift = k_shift + k_pad[:, t:t + S, :] * shift_k[:, ks - 1 - t][None, None, :]
        kv = k_shift * v
        L = 2 * S
        kv_pad = _pad(kv, ((0, 0), (0, S), (0, 0)))
        kf_pad = _pad(ssm_k, ((0, 0), (0, S)))
        kv_f = (lambda x, axes=(-2, -1): torch.fft.rfft2(x.float(), dim=axes))(kv_pad[:, None, :, :], axes=(1, 2))
        kf_f = (lambda x, axes=(-2, -1): torch.fft.rfft2(x.float(), dim=axes))(kf_pad[:, None, :], axes=(1, 2))
        kf_f = (lambda x, *d: x.permute(*d))(kf_f, 1, 2, 0)
        y_f = kv_f * kf_f[None, :, :, :]
        y = (lambda x, s, axes=(-2, -1): torch.fft.irfft2(x, s=s, dim=axes).to(torch.bfloat16))(y_f, (1, L), axes=(1, 2))[:, 0, :S, :]
        y = y + kv * ssm_D[None, None, :]
        return q * y

    def _B_ref(x, w_gate, w_up, w_down):
        g = torch.einsum('bsd,df->bsf', x, w_gate)
        u = torch.einsum('bsd,df->bsf', x, w_up)
        h = g * u
        return torch.einsum('bsf,fd->bsd', h, w_down)
    x = A_q
    mod = (_silu(c) @ w_mod).reshape(c.shape[0], 6, 1, -1)
    sa, ca, ga, sb, cb, gb = (mod[:, 0].clone(), mod[:, 1].clone(), mod[:, 2].clone(), mod[:, 3].clone(), mod[:, 4].clone(), mod[:, 5].clone())
    h = _layernorm(x, axis=-1) * (1 + ca) + sa
    x = x + ga * _A_ref(h, A_k, A_v, A_shift_k, A_ssm_k, A_ssm_D)
    h = _layernorm(x, axis=-1) * (1 + cb) + sb
    x = x + gb * _B_ref(h, B_w_gate, B_w_up, B_w_down)
    return x
```

```cpp
#include <cuda_runtime.h>
#include <cuda.h>
#include <cuda_bf16.h>
#include <stdio.h>
#include <stdint.h>
typedef __nv_bfloat16 bf16;
#define PACE 2
__device__ __forceinline__ uint32_t smem_u32(const void* p) { return (uint32_t)__cvta_generic_to_shared(p); }
__device__ __forceinline__ void mbar_init(uint32_t bar, int cnt) { asm volatile("mbarrier.init.shared::cta.b64 [%0], %1;" ::"r"(bar), "r"(cnt) : "memory"); }
__device__ __forceinline__ void mbar_expect(uint32_t bar, int bytes) { asm volatile("mbarrier.arrive.expect_tx.shared::cta.b64 _, [%0], %1;" ::"r"(bar), "r"(bytes) : "memory"); }
__device__ __forceinline__ void mbar_arrive(uint32_t bar) { asm volatile("mbarrier.arrive.shared::cta.b64 _, [%0];" ::"r"(bar) : "memory"); }
__device__ __forceinline__ void mbar_arrive_remote(uint32_t bar) { asm volatile("mbarrier.arrive.release.cluster.shared::cluster.b64 _, [%0];" ::"r"(bar) : "memory"); }
__device__ __forceinline__ uint32_t mapa(uint32_t a, uint32_t cta) { uint32_t r; asm("mapa.shared::cluster.u32 %0, %1, %2;" : "=r"(r) : "r"(a), "r"(cta)); return r; }
__device__ __forceinline__ bool mbar_try(uint32_t bar, int parity) {
  uint32_t ok;
  asm volatile("{\n.reg .pred p;\nmbarrier.try_wait.parity.shared::cta.b64 p, [%1], %2;\nselp.u32 %0, 1, 0, p;\n}" : "=r"(ok) : "r"(bar), "r"(parity) : "memory");
  return ok;
}
__device__ __forceinline__ void mbar_wait(uint32_t bar, int parity) {
#pragma unroll 1
  for (int i = 0; i < (1 << 20); i++) { if (mbar_try(bar, parity)) return; }
  __trap();
}
__device__ __forceinline__ void tma2d(uint32_t dst, const CUtensorMap* m, int c0, int c1, uint32_t bar) {
  asm volatile("cp.async.bulk.tensor.2d.shared::cluster.global.mbarrier::complete_tx::bytes [%0], [%1, {%3, %4}], [%2];" ::"r"(dst), "l"(m), "r"(bar), "r"(c0), "r"(c1) : "memory");
}
__device__ __forceinline__ void tma3d(uint32_t dst, const CUtensorMap* m, int c0, int c1, int c2, uint32_t bar) {
  asm volatile("cp.async.bulk.tensor.3d.shared::cluster.global.mbarrier::complete_tx::bytes [%0], [%1, {%3, %4, %5}], [%2];" ::"r"(dst), "l"(m), "r"(bar), "r"(c0), "r"(c1), "r"(c2) : "memory");
}
__device__ __forceinline__ void tma5d(uint32_t dst, const CUtensorMap* m, int c0, int c1, int c2, int c3, int c4, uint32_t bar) {
  asm volatile("cp.async.bulk.tensor.5d.shared::cluster.global.mbarrier::complete_tx::bytes [%0], [%1, {%3, %4, %5, %6, %7}], [%2];" ::"r"(dst), "l"(m), "r"(bar), "r"(c0), "r"(c1), "r"(c2), "r"(c3), "r"(c4) : "memory");
}
__device__ __forceinline__ void tma_prefetch2d(const CUtensorMap* m, int c0, int c1) {
  asm volatile("cp.async.bulk.prefetch.tensor.2d.L2.global [%0, {%1, %2}];" ::"l"(m), "r"(c0), "r"(c1) : "memory");
}
__device__ __forceinline__ void bulk_g2s(uint32_t dst, const void* src, int bytes, uint32_t bar) {
  asm volatile("cp.async.bulk.shared::cluster.global.mbarrier::complete_tx::bytes [%0], [%1], %2, [%3];" ::"r"(dst), "l"(src), "r"(bytes), "r"(bar) : "memory");
}
__device__ __forceinline__ void bulk_s2g(void* dst, uint32_t src, int bytes) {
  asm volatile("cp.async.bulk.global.shared::cta.bulk_group [%0], [%1], %2;" ::"l"(dst), "r"(src), "r"(bytes) : "memory");
}
__device__ __forceinline__ void st_async4(uint32_t dst, float a, float b, float c, float d, uint32_t bar) {
  asm volatile("st.async.weak.shared::cluster.mbarrier::complete_tx::bytes.v4.f32 [%0], {%1, %2, %3, %4}, [%5];" ::"r"(dst), "f"(a), "f"(b), "f"(c), "f"(d), "r"(bar) : "memory");
}
__device__ __forceinline__ void wg_fence() { asm volatile("wgmma.fence.sync.aligned;" ::: "memory"); }
__device__ __forceinline__ void wg_commit() { asm volatile("wgmma.commit_group.sync.aligned;" ::: "memory"); }
template <int N> __device__ __forceinline__ void wg_wait() { asm volatile("wgmma.wait_group.sync.aligned %0;" ::"n"(N) : "memory"); }
__device__ __forceinline__ uint64_t mkdesc(uint32_t addr, uint32_t lbo, uint32_t sbo, uint32_t swz) {
  return (uint64_t)((addr & 0x3FFFF) >> 4) | ((uint64_t)(lbo >> 4) << 16) | ((uint64_t)(sbo >> 4) << 32) | ((uint64_t)swz << 62);
}
__device__ __forceinline__ void ldsm4t(uint32_t* r, uint32_t a) {
  asm volatile("ldmatrix.sync.aligned.m8n8.x4.trans.shared.b16 {%0,%1,%2,%3}, [%4];" : "=r"(r[0]), "=r"(r[1]), "=r"(r[2]), "=r"(r[3]) : "r"(a) : "memory");
}
__device__ __forceinline__ void stsm4(uint32_t a, const uint32_t* r) {
  asm volatile("stmatrix.sync.aligned.m8n8.x4.shared.b16 [%0], {%1,%2,%3,%4};" ::"r"(a), "r"(r[0]), "r"(r[1]), "r"(r[2]), "r"(r[3]) : "memory");
}
__device__ __forceinline__ void bar_sync(int id, int n) { asm volatile("bar.sync %0, %1;" ::"r"(id), "r"(n) : "memory"); }
__device__ __forceinline__ void bar_arrive(int id, int n) { asm volatile("bar.arrive %0, %1;" ::"r"(id), "r"(n) : "memory"); }
__device__ __forceinline__ uint32_t lds32(uint32_t a) { uint32_t v; asm volatile("ld.shared.b32 %0, [%1];" : "=r"(v) : "r"(a) : "memory"); return v; }
__device__ __forceinline__ uint2 lds64(uint32_t a) { uint2 v; asm volatile("ld.shared.v2.b32 {%0,%1}, [%2];" : "=r"(v.x), "=r"(v.y) : "r"(a) : "memory"); return v; }
__device__ __forceinline__ uint4 lds128(uint32_t a) { uint4 v; asm volatile("ld.shared.v4.b32 {%0,%1,%2,%3}, [%4];" : "=r"(v.x), "=r"(v.y), "=r"(v.z), "=r"(v.w) : "r"(a) : "memory"); return v; }
__device__ __forceinline__ void sts16(uint32_t a, uint32_t v) { asm volatile("st.shared.b16 [%0], %1;" ::"r"(a), "h"((uint16_t)v) : "memory"); }
__device__ __forceinline__ void sts32(uint32_t a, uint32_t v) { asm volatile("st.shared.b32 [%0], %1;" ::"r"(a), "r"(v) : "memory"); }
__device__ __forceinline__ void sts128(uint32_t a, uint4 v) { asm volatile("st.shared.v4.b32 [%0], {%1,%2,%3,%4};" ::"r"(a), "r"(v.x), "r"(v.y), "r"(v.z), "r"(v.w) : "memory"); }
template<int TB> __device__ __forceinline__ void wgmma_rs_n128(float* d, const uint32_t* a, uint64_t db, int sd) {
  asm volatile("{\n.reg .pred p;\nsetp.ne.b32 p, %69, 0;\n"
    "wgmma.mma_async.sync.aligned.m64n128k16.f32.bf16.bf16 {%0, %1, %2, %3, %4, %5, %6, %7, %8, %9, %10, %11, %12, %13, %14, %15, %16, %17, %18, %19, %20, %21, %22, %23, %24, %25, %26, %27, %28, %29, %30, %31, %32, %33, %34, %35, %36, %37, %38, %39, %40, %41, %42, %43, %44, %45, %46, %47, %48, %49, %50, %51, %52, %53, %54, %55, %56, %57, %58, %59, %60, %61, %62, %63}, {%64, %65, %66, %67}, %68, p, 1, 1, %70;\n}"
    : "+f"(d[0]), "+f"(d[1]), "+f"(d[2]), "+f"(d[3]), "+f"(d[4]), "+f"(d[5]), "+f"(d[6]), "+f"(d[7]), "+f"(d[8]), "+f"(d[9]), "+f"(d[10]), "+f"(d[11]), "+f"(d[12]), "+f"(d[13]), "+f"(d[14]), "+f"(d[15]), "+f"(d[16]), "+f"(d[17]), "+f"(d[18]), "+f"(d[19]), "+f"(d[20]), "+f"(d[21]), "+f"(d[22]), "+f"(d[23]), "+f"(d[24]), "+f"(d[25]), "+f"(d[26]), "+f"(d[27]), "+f"(d[28]), "+f"(d[29]), "+f"(d[30]), "+f"(d[31]), "+f"(d[32]), "+f"(d[33]), "+f"(d[34]), "+f"(d[35]), "+f"(d[36]), "+f"(d[37]), "+f"(d[38]), "+f"(d[39]), "+f"(d[40]), "+f"(d[41]), "+f"(d[42]), "+f"(d[43]), "+f"(d[44]), "+f"(d[45]), "+f"(d[46]), "+f"(d[47]), "+f"(d[48]), "+f"(d[49]), "+f"(d[50]), "+f"(d[51]), "+f"(d[52]), "+f"(d[53]), "+f"(d[54]), "+f"(d[55]), "+f"(d[56]), "+f"(d[57]), "+f"(d[58]), "+f"(d[59]), "+f"(d[60]), "+f"(d[61]), "+f"(d[62]), "+f"(d[63])
    : "r"(a[0]), "r"(a[1]), "r"(a[2]), "r"(a[3]), "l"(db), "r"(sd), "n"(TB));
}

template<int TB> __device__ __forceinline__ void wgmma_rs_n160(float* d, const uint32_t* a, uint64_t db, int sd) {
  asm volatile("{\n.reg .pred p;\nsetp.ne.b32 p, %85, 0;\n"
    "wgmma.mma_async.sync.aligned.m64n160k16.f32.bf16.bf16 {%0, %1, %2, %3, %4, %5, %6, %7, %8, %9, %10, %11, %12, %13, %14, %15, %16, %17, %18, %19, %20, %21, %22, %23, %24, %25, %26, %27, %28, %29, %30, %31, %32, %33, %34, %35, %36, %37, %38, %39, %40, %41, %42, %43, %44, %45, %46, %47, %48, %49, %50, %51, %52, %53, %54, %55, %56, %57, %58, %59, %60, %61, %62, %63, %64, %65, %66, %67, %68, %69, %70, %71, %72, %73, %74, %75, %76, %77, %78, %79}, {%80, %81, %82, %83}, %84, p, 1, 1, %86;\n}"
    : "+f"(d[0]), "+f"(d[1]), "+f"(d[2]), "+f"(d[3]), "+f"(d[4]), "+f"(d[5]), "+f"(d[6]), "+f"(d[7]), "+f"(d[8]), "+f"(d[9]), "+f"(d[10]), "+f"(d[11]), "+f"(d[12]), "+f"(d[13]), "+f"(d[14]), "+f"(d[15]), "+f"(d[16]), "+f"(d[17]), "+f"(d[18]), "+f"(d[19]), "+f"(d[20]), "+f"(d[21]), "+f"(d[22]), "+f"(d[23]), "+f"(d[24]), "+f"(d[25]), "+f"(d[26]), "+f"(d[27]), "+f"(d[28]), "+f"(d[29]), "+f"(d[30]), "+f"(d[31]), "+f"(d[32]), "+f"(d[33]), "+f"(d[34]), "+f"(d[35]), "+f"(d[36]), "+f"(d[37]), "+f"(d[38]), "+f"(d[39]), "+f"(d[40]), "+f"(d[41]), "+f"(d[42]), "+f"(d[43]), "+f"(d[44]), "+f"(d[45]), "+f"(d[46]), "+f"(d[47]), "+f"(d[48]), "+f"(d[49]), "+f"(d[50]), "+f"(d[51]), "+f"(d[52]), "+f"(d[53]), "+f"(d[54]), "+f"(d[55]), "+f"(d[56]), "+f"(d[57]), "+f"(d[58]), "+f"(d[59]), "+f"(d[60]), "+f"(d[61]), "+f"(d[62]), "+f"(d[63]), "+f"(d[64]), "+f"(d[65]), "+f"(d[66]), "+f"(d[67]), "+f"(d[68]), "+f"(d[69]), "+f"(d[70]), "+f"(d[71]), "+f"(d[72]), "+f"(d[73]), "+f"(d[74]), "+f"(d[75]), "+f"(d[76]), "+f"(d[77]), "+f"(d[78]), "+f"(d[79])
    : "r"(a[0]), "r"(a[1]), "r"(a[2]), "r"(a[3]), "l"(db), "r"(sd), "n"(TB));
}

template<int TB> __device__ __forceinline__ void wgmma_rs_n192(float* d, const uint32_t* a, uint64_t db, int sd) {
  asm volatile("{\n.reg .pred p;\nsetp.ne.b32 p, %101, 0;\n"
    "wgmma.mma_async.sync.aligned.m64n192k16.f32.bf16.bf16 {%0, %1, %2, %3, %4, %5, %6, %7, %8, %9, %10, %11, %12, %13, %14, %15, %16, %17, %18, %19, %20, %21, %22, %23, %24, %25, %26, %27, %28, %29, %30, %31, %32, %33, %34, %35, %36, %37, %38, %39, %40, %41, %42, %43, %44, %45, %46, %47, %48, %49, %50, %51, %52, %53, %54, %55, %56, %57, %58, %59, %60, %61, %62, %63, %64, %65, %66, %67, %68, %69, %70, %71, %72, %73, %74, %75, %76, %77, %78, %79, %80, %81, %82, %83, %84, %85, %86, %87, %88, %89, %90, %91, %92, %93, %94, %95}, {%96, %97, %98, %99}, %100, p, 1, 1, %102;\n}"
    : "+f"(d[0]), "+f"(d[1]), "+f"(d[2]), "+f"(d[3]), "+f"(d[4]), "+f"(d[5]), "+f"(d[6]), "+f"(d[7]), "+f"(d[8]), "+f"(d[9]), "+f"(d[10]), "+f"(d[11]), "+f"(d[12]), "+f"(d[13]), "+f"(d[14]), "+f"(d[15]), "+f"(d[16]), "+f"(d[17]), "+f"(d[18]), "+f"(d[19]), "+f"(d[20]), "+f"(d[21]), "+f"(d[22]), "+f"(d[23]), "+f"(d[24]), "+f"(d[25]), "+f"(d[26]), "+f"(d[27]), "+f"(d[28]), "+f"(d[29]), "+f"(d[30]), "+f"(d[31]), "+f"(d[32]), "+f"(d[33]), "+f"(d[34]), "+f"(d[35]), "+f"(d[36]), "+f"(d[37]), "+f"(d[38]), "+f"(d[39]), "+f"(d[40]), "+f"(d[41]), "+f"(d[42]), "+f"(d[43]), "+f"(d[44]), "+f"(d[45]), "+f"(d[46]), "+f"(d[47]), "+f"(d[48]), "+f"(d[49]), "+f"(d[50]), "+f"(d[51]), "+f"(d[52]), "+f"(d[53]), "+f"(d[54]), "+f"(d[55]), "+f"(d[56]), "+f"(d[57]), "+f"(d[58]), "+f"(d[59]), "+f"(d[60]), "+f"(d[61]), "+f"(d[62]), "+f"(d[63]), "+f"(d[64]), "+f"(d[65]), "+f"(d[66]), "+f"(d[67]), "+f"(d[68]), "+f"(d[69]), "+f"(d[70]), "+f"(d[71]), "+f"(d[72]), "+f"(d[73]), "+f"(d[74]), "+f"(d[75]), "+f"(d[76]), "+f"(d[77]), "+f"(d[78]), "+f"(d[79]), "+f"(d[80]), "+f"(d[81]), "+f"(d[82]), "+f"(d[83]), "+f"(d[84]), "+f"(d[85]), "+f"(d[86]), "+f"(d[87]), "+f"(d[88]), "+f"(d[89]), "+f"(d[90]), "+f"(d[91]), "+f"(d[92]), "+f"(d[93]), "+f"(d[94]), "+f"(d[95])
    : "r"(a[0]), "r"(a[1]), "r"(a[2]), "r"(a[3]), "l"(db), "r"(sd), "n"(TB));
}

template<int TB> __device__ __forceinline__ void wgmma_rs_n32(float* d, const uint32_t* a, uint64_t db, int sd) {
  asm volatile("{\n.reg .pred p;\nsetp.ne.b32 p, %21, 0;\n"
    "wgmma.mma_async.sync.aligned.m64n32k16.f32.bf16.bf16 {%0, %1, %2, %3, %4, %5, %6, %7, %8, %9, %10, %11, %12, %13, %14, %15}, {%16, %17, %18, %19}, %20, p, 1, 1, %22;\n}"
    : "+f"(d[0]), "+f"(d[1]), "+f"(d[2]), "+f"(d[3]), "+f"(d[4]), "+f"(d[5]), "+f"(d[6]), "+f"(d[7]), "+f"(d[8]), "+f"(d[9]), "+f"(d[10]), "+f"(d[11]), "+f"(d[12]), "+f"(d[13]), "+f"(d[14]), "+f"(d[15])
    : "r"(a[0]), "r"(a[1]), "r"(a[2]), "r"(a[3]), "l"(db), "r"(sd), "n"(TB));
}

template<int TB> __device__ __forceinline__ void wgmma_rs_n64(float* d, const uint32_t* a, uint64_t db, int sd) {
  asm volatile("{\n.reg .pred p;\nsetp.ne.b32 p, %37, 0;\n"
    "wgmma.mma_async.sync.aligned.m64n64k16.f32.bf16.bf16 {%0, %1, %2, %3, %4, %5, %6, %7, %8, %9, %10, %11, %12, %13, %14, %15, %16, %17, %18, %19, %20, %21, %22, %23, %24, %25, %26, %27, %28, %29, %30, %31}, {%32, %33, %34, %35}, %36, p, 1, 1, %38;\n}"
    : "+f"(d[0]), "+f"(d[1]), "+f"(d[2]), "+f"(d[3]), "+f"(d[4]), "+f"(d[5]), "+f"(d[6]), "+f"(d[7]), "+f"(d[8]), "+f"(d[9]), "+f"(d[10]), "+f"(d[11]), "+f"(d[12]), "+f"(d[13]), "+f"(d[14]), "+f"(d[15]), "+f"(d[16]), "+f"(d[17]), "+f"(d[18]), "+f"(d[19]), "+f"(d[20]), "+f"(d[21]), "+f"(d[22]), "+f"(d[23]), "+f"(d[24]), "+f"(d[25]), "+f"(d[26]), "+f"(d[27]), "+f"(d[28]), "+f"(d[29]), "+f"(d[30]), "+f"(d[31])
    : "r"(a[0]), "r"(a[1]), "r"(a[2]), "r"(a[3]), "l"(db), "r"(sd), "n"(TB));
}

template<int TB> __device__ __forceinline__ void wgmma_rs_n96(float* d, const uint32_t* a, uint64_t db, int sd) {
  asm volatile("{\n.reg .pred p;\nsetp.ne.b32 p, %53, 0;\n"
    "wgmma.mma_async.sync.aligned.m64n96k16.f32.bf16.bf16 {%0, %1, %2, %3, %4, %5, %6, %7, %8, %9, %10, %11, %12, %13, %14, %15, %16, %17, %18, %19, %20, %21, %22, %23, %24, %25, %26, %27, %28, %29, %30, %31, %32, %33, %34, %35, %36, %37, %38, %39, %40, %41, %42, %43, %44, %45, %46, %47}, {%48, %49, %50, %51}, %52, p, 1, 1, %54;\n}"
    : "+f"(d[0]), "+f"(d[1]), "+f"(d[2]), "+f"(d[3]), "+f"(d[4]), "+f"(d[5]), "+f"(d[6]), "+f"(d[7]), "+f"(d[8]), "+f"(d[9]), "+f"(d[10]), "+f"(d[11]), "+f"(d[12]), "+f"(d[13]), "+f"(d[14]), "+f"(d[15]), "+f"(d[16]), "+f"(d[17]), "+f"(d[18]), "+f"(d[19]), "+f"(d[20]), "+f"(d[21]), "+f"(d[22]), "+f"(d[23]), "+f"(d[24]), "+f"(d[25]), "+f"(d[26]), "+f"(d[27]), "+f"(d[28]), "+f"(d[29]), "+f"(d[30]), "+f"(d[31]), "+f"(d[32]), "+f"(d[33]), "+f"(d[34]), "+f"(d[35]), "+f"(d[36]), "+f"(d[37]), "+f"(d[38]), "+f"(d[39]), "+f"(d[40]), "+f"(d[41]), "+f"(d[42]), "+f"(d[43]), "+f"(d[44]), "+f"(d[45]), "+f"(d[46]), "+f"(d[47])
    : "r"(a[0]), "r"(a[1]), "r"(a[2]), "r"(a[3]), "l"(db), "r"(sd), "n"(TB));
}

template<int TA, int TB> __device__ __forceinline__ void wgmma_ss_n160(float* d, uint64_t da, uint64_t db, int sd) {
  asm volatile("{\n.reg .pred p;\nsetp.ne.b32 p, %82, 0;\n"
    "wgmma.mma_async.sync.aligned.m64n160k16.f32.bf16.bf16 {%0, %1, %2, %3, %4, %5, %6, %7, %8, %9, %10, %11, %12, %13, %14, %15, %16, %17, %18, %19, %20, %21, %22, %23, %24, %25, %26, %27, %28, %29, %30, %31, %32, %33, %34, %35, %36, %37, %38, %39, %40, %41, %42, %43, %44, %45, %46, %47, %48, %49, %50, %51, %52, %53, %54, %55, %56, %57, %58, %59, %60, %61, %62, %63, %64, %65, %66, %67, %68, %69, %70, %71, %72, %73, %74, %75, %76, %77, %78, %79}, %80, %81, p, 1, 1, %83, %84;\n}"
    : "+f"(d[0]), "+f"(d[1]), "+f"(d[2]), "+f"(d[3]), "+f"(d[4]), "+f"(d[5]), "+f"(d[6]), "+f"(d[7]), "+f"(d[8]), "+f"(d[9]), "+f"(d[10]), "+f"(d[11]), "+f"(d[12]), "+f"(d[13]), "+f"(d[14]), "+f"(d[15]), "+f"(d[16]), "+f"(d[17]), "+f"(d[18]), "+f"(d[19]), "+f"(d[20]), "+f"(d[21]), "+f"(d[22]), "+f"(d[23]), "+f"(d[24]), "+f"(d[25]), "+f"(d[26]), "+f"(d[27]), "+f"(d[28]), "+f"(d[29]), "+f"(d[30]), "+f"(d[31]), "+f"(d[32]), "+f"(d[33]), "+f"(d[34]), "+f"(d[35]), "+f"(d[36]), "+f"(d[37]), "+f"(d[38]), "+f"(d[39]), "+f"(d[40]), "+f"(d[41]), "+f"(d[42]), "+f"(d[43]), "+f"(d[44]), "+f"(d[45]), "+f"(d[46]), "+f"(d[47]), "+f"(d[48]), "+f"(d[49]), "+f"(d[50]), "+f"(d[51]), "+f"(d[52]), "+f"(d[53]), "+f"(d[54]), "+f"(d[55]), "+f"(d[56]), "+f"(d[57]), "+f"(d[58]), "+f"(d[59]), "+f"(d[60]), "+f"(d[61]), "+f"(d[62]), "+f"(d[63]), "+f"(d[64]), "+f"(d[65]), "+f"(d[66]), "+f"(d[67]), "+f"(d[68]), "+f"(d[69]), "+f"(d[70]), "+f"(d[71]), "+f"(d[72]), "+f"(d[73]), "+f"(d[74]), "+f"(d[75]), "+f"(d[76]), "+f"(d[77]), "+f"(d[78]), "+f"(d[79])
    : "l"(da), "l"(db), "r"(sd), "n"(TA), "n"(TB));
}

template<int TA, int TB> __device__ __forceinline__ void wgmma_ss_n192(float* d, uint64_t da, uint64_t db, int sd) {
  asm volatile("{\n.reg .pred p;\nsetp.ne.b32 p, %98, 0;\n"
    "wgmma.mma_async.sync.aligned.m64n192k16.f32.bf16.bf16 {%0, %1, %2, %3, %4, %5, %6, %7, %8, %9, %10, %11, %12, %13, %14, %15, %16, %17, %18, %19, %20, %21, %22, %23, %24, %25, %26, %27, %28, %29, %30, %31, %32, %33, %34, %35, %36, %37, %38, %39, %40, %41, %42, %43, %44, %45, %46, %47, %48, %49, %50, %51, %52, %53, %54, %55, %56, %57, %58, %59, %60, %61, %62, %63, %64, %65, %66, %67, %68, %69, %70, %71, %72, %73, %74, %75, %76, %77, %78, %79, %80, %81, %82, %83, %84, %85, %86, %87, %88, %89, %90, %91, %92, %93, %94, %95}, %96, %97, p, 1, 1, %99, %100;\n}"
    : "+f"(d[0]), "+f"(d[1]), "+f"(d[2]), "+f"(d[3]), "+f"(d[4]), "+f"(d[5]), "+f"(d[6]), "+f"(d[7]), "+f"(d[8]), "+f"(d[9]), "+f"(d[10]), "+f"(d[11]), "+f"(d[12]), "+f"(d[13]), "+f"(d[14]), "+f"(d[15]), "+f"(d[16]), "+f"(d[17]), "+f"(d[18]), "+f"(d[19]), "+f"(d[20]), "+f"(d[21]), "+f"(d[22]), "+f"(d[23]), "+f"(d[24]), "+f"(d[25]), "+f"(d[26]), "+f"(d[27]), "+f"(d[28]), "+f"(d[29]), "+f"(d[30]), "+f"(d[31]), "+f"(d[32]), "+f"(d[33]), "+f"(d[34]), "+f"(d[35]), "+f"(d[36]), "+f"(d[37]), "+f"(d[38]), "+f"(d[39]), "+f"(d[40]), "+f"(d[41]), "+f"(d[42]), "+f"(d[43]), "+f"(d[44]), "+f"(d[45]), "+f"(d[46]), "+f"(d[47]), "+f"(d[48]), "+f"(d[49]), "+f"(d[50]), "+f"(d[51]), "+f"(d[52]), "+f"(d[53]), "+f"(d[54]), "+f"(d[55]), "+f"(d[56]), "+f"(d[57]), "+f"(d[58]), "+f"(d[59]), "+f"(d[60]), "+f"(d[61]), "+f"(d[62]), "+f"(d[63]), "+f"(d[64]), "+f"(d[65]), "+f"(d[66]), "+f"(d[67]), "+f"(d[68]), "+f"(d[69]), "+f"(d[70]), "+f"(d[71]), "+f"(d[72]), "+f"(d[73]), "+f"(d[74]), "+f"(d[75]), "+f"(d[76]), "+f"(d[77]), "+f"(d[78]), "+f"(d[79]), "+f"(d[80]), "+f"(d[81]), "+f"(d[82]), "+f"(d[83]), "+f"(d[84]), "+f"(d[85]), "+f"(d[86]), "+f"(d[87]), "+f"(d[88]), "+f"(d[89]), "+f"(d[90]), "+f"(d[91]), "+f"(d[92]), "+f"(d[93]), "+f"(d[94]), "+f"(d[95])
    : "l"(da), "l"(db), "r"(sd), "n"(TA), "n"(TB));
}

constexpr int S_ = 2048, D_ = 640, F_ = 1536;

__device__ __align__(1024) bf16 g_kvT[D_ * S_];
__device__ __align__(1024) bf16 g_XH[D_ * S_ * 2];
__device__ __align__(1024) bf16 g_x1T[D_ * S_];
__device__ __align__(1024) bf16 g_AT[D_ * S_];
__device__ __align__(1024) bf16 g_HH[S_ * F_];
__device__ __align__(1024) float g_modP[32 * 3840];
__device__ __align__(1024) uint32_t g_cbsb[D_];
__device__ __align__(1024) bf16 g_gb[D_];
__device__ __align__(1024) uint4 g_stat[S_];
__device__ __align__(1024) bf16 g_cimg[8 * 6 * 512];
__device__ __align__(1024) uint32_t g_flag[256 * 8];
__device__ uint32_t g_epoch[128];
#define STAMP(id)
#define STAMPIF(c, id)
constexpr int FL_KV = 0, FL_X = 10, FL_R = 11, FL_S = 16, FL_C = 32, FL_M = 40, FL_H = 128;

constexpr int SM_Z = 1024, SM_EXT = 21504, SM_STAT = 27648, SM_SMALL = 29696, SM_RING = 30720, SM_TOTAL = SM_RING + 6 * 32768;
constexpr int SMALL_S = 0, SMALL_XM = 192, SMALL_RED = 320, SMALL_GB = 848;
constexpr int JOB_SZ = 8576, R_STG = 42880, R_RAW = 55168, R_X = 75648, XPITCH = 1296;
constexpr int K1OFF = 4672, KSZ = 9344, USZ = 4224;
enum { B_B = 0, B_X = 5, B_U = 6, B_K = 11, B_Z = 16, B_AUXFREE = 21, B_F1 = 22, B_E1 = 28, B_FB = 34, B_EB = 46, B_FA = 58, B_EA = 64,
       B_EXT = 70, B_X1 = 71, B_PEER = 72, B_RECV = 73, B_NUM = 75 };

struct Params {
  CUtensorMap mK, mV, mWm, mA, mG, mU, mDn, mDp, mX1;
  const bf16 *x, *shift_k, *ssm_k, *ssm_D, *wg, *wu, *c, *wmod;
  bf16* out;
};

__device__ __forceinline__ uint32_t* flagp(int id) { return g_flag + id * 8; }
__device__ __forceinline__ void flag_add(int id) { asm volatile("red.release.gpu.global.add.u32 [%0], 1;" ::"l"(flagp(id)) : "memory"); }
__device__ __forceinline__ void flag_wait(int id, uint32_t target) {
  const uint32_t* p = flagp(id);
#pragma unroll 1
  for (int i = 0; i < (1 << 20); i++) {
    uint32_t v;
    asm volatile("ld.acquire.gpu.global.u32 %0, [%1];" : "=r"(v) : "l"(p) : "memory");
    if ((int)(v - target) >= 0) return;
  }
  __trap();
}
__device__ __forceinline__ int ibase(int pb) {
  int w = pb >> 5, g = (pb >> 2) & 7, q = pb & 3;
  return 128 * (g >> 2) + 8 * ((2 * q - ((g >> 1) & 1)) & 7) + 2 * w + (g & 1);
}
__device__ __forceinline__ uint32_t hmul(uint32_t a, uint32_t b) { uint32_t d; asm("mul.rn.bf16x2 %0, %1, %2;" : "=r"(d) : "r"(a), "r"(b)); return d; }
__device__ __forceinline__ uint32_t hadd(uint32_t a, uint32_t b) { uint32_t d; asm("add.rn.bf16x2 %0, %1, %2;" : "=r"(d) : "r"(a), "r"(b)); return d; }
__device__ __forceinline__ uint32_t hsub(uint32_t a, uint32_t b) { uint32_t d; asm("sub.rn.bf16x2 %0, %1, %2;" : "=r"(d) : "r"(a), "r"(b)); return d; }
__device__ __forceinline__ uint32_t pack2(float lo, float hi) { uint32_t d; asm("cvt.rn.bf16x2.f32 %0, %1, %2;" : "=r"(d) : "f"(hi), "f"(lo)); return d; }
__device__ __forceinline__ float blo(uint32_t v) { return __uint_as_float(v << 16); }
__device__ __forceinline__ float bhi(uint32_t v) { return __uint_as_float(v & 0xffff0000u); }
__device__ __forceinline__ float rbf(float v) { return blo(pack2(v, 0.f)); }
template <int N> __device__ __forceinline__ void bfly(float* v, int mask, bool up) {
#pragma unroll
  for (int i = 0; i < N / 2; i++) {
    float send = up ? v[i] : v[i + N / 2], keep = up ? v[i + N / 2] : v[i];
    v[i] = keep + __shfl_xor_sync(0xffffffffu, send, mask);
  }
}
__device__ __forceinline__ int mod_col(int idx) {
  if (idx < 40) { int v = (idx >> 1) & 3; return (v == 3 ? 4 : v) * 640 + 128 * (idx >> 3) + 64 * (idx & 1); }
  int l = idx - 40;
  return l < 10 ? 3 * 640 + 64 * l : 5 * 640 + 64 * (l - 10);
}

__device__ __forceinline__ void kv_job(const Params& P, uint32_t sb, int b, int r, int stg, int tid, int barid) {
  const int lane = tid & 31, w = tid >> 5;
  const int d0 = 128 * r + 64 * (b & 1), t0 = 32 * (b >> 1);
  uint4 sk = __ldg((const uint4*)(P.shift_k + (d0 + 2 * lane) * 4));
  float Dv = 0.f;
  if (tid == 0) Dv = __bfloat162float(P.ssm_D[128 * r + b]);
  uint32_t s0 = __byte_perm(sk.x, sk.z, 0x5410), s1 = __byte_perm(sk.x, sk.z, 0x7632), s2 = __byte_perm(sk.y, sk.w, 0x5410), s3 = __byte_perm(sk.y, sk.w, 0x7632);
  const uint32_t ring = sb + SM_RING;
  mbar_wait(sb + 8 * (B_B + r), 0);
  uint32_t ka = ring + r * JOB_SZ + w * 1024 + lane * 4;
  uint32_t kk[11], o[8];
#pragma unroll
  for (int i = 0; i < 11; i++) kk[i] = lds32(ka + 128 * i);
#pragma unroll
  for (int i = 0; i < 8; i++) {
    uint32_t v = lds32(ka + 4480 + 128 * i);
    uint32_t a = hadd(hadd(hadd(hmul(kk[i], s3), hmul(kk[i + 1], s2)), hmul(kk[i + 2], s1)), hmul(kk[i + 3], s0));
    o[i] = hmul(a, v);
  }
  uint32_t sg = ring + R_STG + stg * 4096;
  sts128(sg + lane * 128 + (((3 - w) ^ (lane & 7)) << 4),
         make_uint4(__byte_perm(o[7], o[6], 0x5410), __byte_perm(o[5], o[4], 0x5410), __byte_perm(o[3], o[2], 0x5410), __byte_perm(o[1], o[0], 0x5410)));
  sts128(sg + lane * 128 + (((7 - w) ^ (lane & 7)) << 4),
         make_uint4(__byte_perm(o[7], o[6], 0x7632), __byte_perm(o[5], o[4], 0x7632), __byte_perm(o[3], o[2], 0x7632), __byte_perm(o[1], o[0], 0x7632)));
  bar_sync(barid, 128);
#pragma unroll
  for (int n = 0; n < 2; n++) {
    int rho = (tid >> 3) + 16 * n, c = tid & 7;
    uint4 v = lds128(sg + rho * 128 + ((c ^ (rho & 7)) << 4));
    *(uint4*)(g_kvT + (d0 + 2 * rho + (c >> 2)) * S_ + (2016 - t0) + 8 * (c & 3)) = v;
  }
  bar_sync(barid, 128);
  if (tid == 0) flag_add(FL_KV + 2 * r + (b & 1));
  uint32_t raw = ring + R_RAW + r * 4096, kb = ring + (3 + (r >> 1)) * 32768 + (r & 1) * KSZ;
#pragma unroll
  for (int n = 0; n < 2; n++) {
    int ch = tid + 128 * n;
    uint4 a = lds128(raw + 16 * ch);
    uint32_t pv = 0;
    if (ch > 0) pv = lds32(raw + 16 * ch - 4);
    else a.x = (a.x & 0xffff0000u) | (pack2(blo(a.x) + Dv, 0.f) & 0xffffu);
    uint32_t dst = kb + 48 + 16 * ch + 32 * (ch >> 4);
    sts128(dst, a);
    sts128(dst + K1OFF, make_uint4(__byte_perm(pv, a.x, 0x5432), __byte_perm(a.x, a.y, 0x5432), __byte_perm(a.y, a.z, 0x5432), __byte_perm(a.z, a.w, 0x5432)));
  }
  bar_sync(barid, 128);
}

__device__ __forceinline__ void mod_box(const Params& P, uint32_t sb, int b, int cls, int tid) {
  const int lane = tid & 31, w = tid >> 5, ks = b & 7;
  const int col = mod_col(16 * cls + (b >> 3)) + 2 * lane;
  const uint32_t* p = (const uint32_t*)(P.wmod + (80 * ks + 20 * w) * 3840 + col);
  uint32_t v[20];
#pragma unroll
  for (int n = 0; n < 20; n++) v[n] = __ldg(p + n * 1920);
  float a0 = 0.f, a1 = 0.f;
#pragma unroll
  for (int n = 0; n < 5; n++) {
    uint2 s = lds64(sb + SM_SMALL + SMALL_S + 40 * w + 8 * n);
    a0 += blo(s.x) * blo(v[4 * n]);     a1 += blo(s.x) * bhi(v[4 * n]);
    a0 += bhi(s.x) * blo(v[4 * n + 1]); a1 += bhi(s.x) * bhi(v[4 * n + 1]);
    a0 += blo(s.y) * blo(v[4 * n + 2]); a1 += blo(s.y) * bhi(v[4 * n + 2]);
    a0 += bhi(s.y) * blo(v[4 * n + 3]); a1 += bhi(s.y) * bhi(v[4 * n + 3]);
  }
  *(float2*)(g_modP + (ks * 4 + w) * 3840 + col) = make_float2(a0, a1);
}
__device__ __forceinline__ float mod_sum(int col, int lane) {
  const float* p = g_modP + (lane & 7) * 4 * 3840 + col;
  float a = (__ldcg(p) + __ldcg(p + 3840)) + (__ldcg(p + 2 * 3840) + __ldcg(p + 3 * 3840));
  a += __shfl_xor_sync(0xffffffffu, a, 1);
  a += __shfl_xor_sync(0xffffffffu, a, 2);
  a += __shfl_xor_sync(0xffffffffu, a, 4);
  return rbf(a);
}

__global__ void __launch_bounds__(512, 1) fused_kernel(const __grid_constant__ Params P) {
  extern __shared__ __align__(1024) char smem_raw[];
  const uint32_t sb = smem_u32(smem_raw), ring = sb + SM_RING;
  const int b = blockIdx.x, m = b >> 3, s = b & 7;
  STAMPIF(threadIdx.x == 0, 0);
  if (threadIdx.x == 384) {
#pragma unroll 1
    for (int i = 0; i < B_NUM; i++) {
      int cnt = 1;
      if (i >= B_Z && i < B_Z + 5) cnt = 4;
      if ((i >= B_F1 && i < B_FB) || (i >= B_EB && i < B_FA) || (i >= B_EA && i < B_EXT)) cnt = 2;
      mbar_init(sb + 8 * i, cnt);
    }
    asm volatile("fence.mbarrier_init.release.cluster;" ::: "memory");
  }
  if (threadIdx.x < 40) {
    int ch = threadIdx.x >> 3, c = threadIdx.x & 7;
    uint32_t base = ring + (3 + (ch >> 1)) * 32768;
    sts128(c < 2 ? base + (ch & 1) * KSZ + c * K1OFF : base + 2 * KSZ + (ch & 1) * USZ + 4096 + (c - 2) * 16, make_uint4(0, 0, 0, 0));
    asm volatile("fence.proxy.async.shared::cta;" ::: "memory");
  }
  __syncthreads();
  asm volatile("barrier.cluster.arrive.release.aligned;" ::: "memory");
  const int wg = __shfl_sync(0xffffffffu, threadIdx.x >> 7, 0);
  const int tid = threadIdx.x & 127, lane = tid & 31;
  const int w = __shfl_sync(0xffffffffu, tid >> 5, 0);

  if (wg == 3) {
    asm volatile("setmaxnreg.dec.sync.aligned.u32 24;");
    if (w == 0) {
#pragma unroll 1
      for (int r = 0; r < 5; r++) {
        if (lane == 0) {
          if (r >= PACE) mbar_wait(sb + 8 * (B_B + r - PACE), 0);
          uint32_t bar = sb + 8 * (B_B + r);
          mbar_expect(bar, 4480 + 4096 + 4096);
          tma2d(ring + r * JOB_SZ, &P.mK, 128 * r + 64 * (b & 1), 32 * (b >> 1) - 3, bar);
          tma2d(ring + r * JOB_SZ + 4480, &P.mV, 128 * r + 64 * (b & 1), 32 * (b >> 1), bar);
          bulk_g2s(ring + R_RAW + r * 4096, P.ssm_k + (128 * r + b) * S_, 4096, bar);
        }
      }
      if (lane == 0) { mbar_wait(sb + 8 * (B_B + 5 - PACE), 0); mbar_expect(sb + 8 * B_X, 16 * 1280); }
      __syncwarp();
      if (lane < 16) {
        int t = 2047 - (256 * (lane >> 1) + 64 * (lane & 1) + ibase(b));
        int rho = 8 * ((lane >> 1) & 1) + 2 * (lane >> 2) + (lane & 1);
        bulk_g2s(ring + R_X + rho * XPITCH, P.x + t * D_, 1280, sb + 8 * B_X);
      }
      __syncwarp();
      asm volatile("barrier.cluster.wait.acquire.aligned;" ::: "memory");
      if (lane == 0) {
        mbar_wait(sb + 8 * (B_B + 4), 0);
        tma_prefetch2d(&P.mWm, mod_col(b >> 3), 80 * (b & 7));
        mbar_wait(sb + 8 * B_AUXFREE, 0);
#pragma unroll 1
        for (int it = 0; it < 20; it++) {
          int st = it % 6;
          mbar_wait(sb + 8 * (B_E1 + st), (it / 6) & 1);
          uint32_t a = ring + st * 32768, fb = sb + 8 * (B_F1 + st);
          mbar_expect(fb, 24576);
          tma3d(a + 8192, &P.mG, 0, 32 * it, s * 3, fb);
          tma3d(a + 20480, &P.mU, 0, 32 * it, s * 3, fb);
          if (it == 2) {
            tma_prefetch2d(&P.mWm, mod_col(16 + (b >> 3)), 80 * (b & 7));
            tma_prefetch2d(&P.mWm, mod_col(32 + (b >> 3)), 80 * (b & 7));
            if (b < 96) tma_prefetch2d(&P.mWm, mod_col(48 + (b >> 3)), 80 * (b & 7));
          }
        }
#pragma unroll 1
        for (int k = 0; k < 24; k++) {
          int sl = k < 12 ? k : k - 12;
          int g1 = (sl >> 1) + 2; if (g1 >= 6) g1 -= 6;
          if (k < 12) mbar_wait(sb + 8 * (B_E1 + g1), g1 >= 2); else mbar_wait(sb + 8 * (B_EB + sl), 0);
          uint32_t a = ring + g1 * 32768 + 8192 + (sl & 1) * 12288, fb = sb + 8 * (B_FB + sl);
          int n = k / 6, kg = 4 * (6 * ((s + 2 * n) & 7) + k - 6 * n);
          mbar_expect(fb, 12288);
#pragma unroll 1
          for (int at = 0; at < 3; at++) {
            if (k < 6) tma5d(a + at * 4096, &P.mDn, 64 * at, 0, 0, kg, s >> 1, fb);
            else tma5d(a + at * 4096, &P.mDp, 64 * at, 0, kg, 0, s >> 1, fb);
          }
        }
      }
    } else if (w == 1) {
      asm volatile("barrier.cluster.wait.acquire.aligned;" ::: "memory");
      if (lane == 0) {
        const uint32_t e1 = __ldcg(g_epoch + b) + 1;
#pragma unroll 1
        for (int r = 0; r < 5; r++) {
          flag_wait(FL_KV + 2 * r + (b >> 6), e1 * 64);
          asm volatile("fence.proxy.async;" ::: "memory");
          uint32_t bar = sb + 8 * (B_U + r);
          mbar_expect(bar, 4096);
          bulk_g2s(ring + (3 + (r >> 1)) * 32768 + 2 * KSZ + (r & 1) * USZ, g_kvT + (128 * r + b) * S_, 4096, bar);
          STAMP(40 + r);
        }
        mbar_wait(sb + 8 * B_AUXFREE, 0);
#pragma unroll 1
        for (int it = 0; it < 20; it++) {
          int st = it % 6;
          if ((it & 3) == 0) { flag_wait(FL_R + (it >> 2), e1 * 128); asm volatile("fence.proxy.async;" ::: "memory"); STAMP(45 + (it >> 2)); }
          mbar_wait(sb + 8 * (B_E1 + st), (it / 6) & 1);
          uint32_t fb = sb + 8 * (B_F1 + st);
          mbar_expect(fb, 8192);
          tma3d(ring + st * 32768, &P.mA, 0, 32 * it, m * 2, fb);
        }
#pragma unroll 1
        for (int n = 1; n < 4; n++) {
          int src = 8 * m + ((s + 2 * n) & 7);
          flag_wait(FL_H + src, e1 * 2);
          asm volatile("fence.proxy.async;" ::: "memory");
          STAMP(50 + n);
#pragma unroll 1
          for (int k = 0; k < 6; k++) {
            int g1 = k + 2; if (g1 >= 6) g1 -= 6;
            if (n == 1) mbar_wait(sb + 8 * (B_E1 + g1), g1 >= 2); else mbar_wait(sb + 8 * (B_EA + k), n & 1);
            uint32_t fb = sb + 8 * (B_FA + k);
            mbar_expect(fb, 8192);
            bulk_g2s(ring + g1 * 32768, g_HH + (src * 6 + k) * 4096, 8192, fb);
          }
        }
      }
    } else if (w == 2) {
      asm volatile("barrier.cluster.wait.acquire.aligned;" ::: "memory");
      if (lane == 0) {
        const uint32_t e1 = __ldcg(g_epoch + b) + 1;
        mbar_expect(sb + 8 * B_RECV, 20480);
        mbar_expect(sb + 8 * (B_RECV + 1), 20480);
        mbar_wait(sb + 8 * (B_Z + 4), 0);
        flag_wait(FL_R + 4, e1 * 128);
        asm volatile("fence.proxy.async;" ::: "memory");
        mbar_expect(sb + 8 * B_X1, 20480 + 160);
        tma3d(sb + SM_Z, &P.mX1, 0, 80 * s, m * 2, sb + 8 * B_X1);
        bulk_g2s(sb + SM_SMALL + SMALL_GB, g_gb + 80 * s, 160, sb + 8 * B_X1);
        flag_wait(FL_S + m, e1 * 8);
        flag_wait(FL_C + s, e1 * 16);
        asm volatile("fence.proxy.async;" ::: "memory");
        STAMP(54);
        mbar_expect(sb + 8 * B_EXT, 6144 + 2048);
        bulk_g2s(sb + SM_EXT, g_cimg + s * 3072, 6144, sb + 8 * B_EXT);
        bulk_g2s(sb + SM_STAT, g_stat + 128 * m, 2048, sb + 8 * B_EXT);
        mbar_wait(sb + 8 * (B_EB + 3), 0);
        mbar_wait(sb + 8 * (B_EB + 3), 1);
        mbar_arrive_remote(mapa(sb + 8 * B_PEER, (b & 1) ^ 1));
      }
    } else {
      asm volatile("barrier.cluster.wait.acquire.aligned;" ::: "memory");
    }
  } else if (wg == 2) {
    asm volatile("setmaxnreg.dec.sync.aligned.u32 40;");
    const uint32_t e1 = __ldcg(g_epoch + b) + 1;
    if (tid < 80) {
      float c = __bfloat162float(P.c[80 * (b & 7) + tid]);
      sts16(sb + SM_SMALL + SMALL_S + 2 * tid, pack2(c / (1.f + __expf(-c)), 0.f));
    }
    asm volatile("barrier.cluster.wait.acquire.aligned;" ::: "memory");
#pragma unroll 1
    for (int r = 2; r < 5; r++) {
      kv_job(P, sb, b, r, 2, tid, 5);
      if (tid == 0) mbar_arrive(sb + 8 * (B_K + r));
      STAMPIF(tid == 0, 20 + r);
    }
    {
      mbar_wait(sb + 8 * B_X, 0);
      STAMPIF(tid == 0, 25);
      uint32_t xr = ring + R_X + (tid >> 3) * XPITCH;
      float pv = blo(lds32(xr)), s1 = 0.f, s2 = 0.f;
#pragma unroll
      for (int n = 0; n < 10; n++) {
        uint4 v = lds128(xr + 16 * ((tid & 7) + 8 * n));
        uint32_t u[4] = {v.x, v.y, v.z, v.w};
#pragma unroll
        for (int j = 0; j < 4; j++) {
          float a = blo(u[j]) - pv, c = bhi(u[j]) - pv;
          s1 += a + c; s2 += a * a; s2 += c * c;
        }
      }
#pragma unroll
      for (int o = 1; o < 8; o <<= 1) { s1 += __shfl_xor_sync(0xffffffffu, s1, o); s2 += __shfl_xor_sync(0xffffffffu, s2, o); }
      if ((tid & 7) == 0) {
        float mu = s1 * (1.f / D_), var = fmaxf(s2 * (1.f / D_) - mu * mu, 0.f);
        float sd = rbf(sqrtf(rbf(rbf(var) + 1e-5f)));
        sts16(sb + SM_SMALL + SMALL_XM + 2 * (tid >> 3), pack2(pv + mu, 0.f));
        sts32(sb + SM_SMALL + SMALL_XM + 32 + 4 * (tid >> 3), __float_as_uint(1.f / sd));
      }
      bar_sync(5, 128);
      const int q = lane & 3, g = lane >> 2;
      uint32_t m0 = lds32(sb + SM_SMALL + SMALL_XM + 4 * q), m1 = lds32(sb + SM_SMALL + SMALL_XM + 16 + 4 * q);
      uint2 r0 = lds64(sb + SM_SMALL + SMALL_XM + 32 + 8 * q), r1 = lds64(sb + SM_SMALL + SMALL_XM + 64 + 8 * q);
      uint32_t la = ring + R_X + (lane & 15) * XPITCH + (lane >> 4) * 16 + w * 32;
      bf16* dst = g_XH + (16 * w + g) * (2 * S_) + b * 32 + q * 8;
#pragma unroll
      for (int n = 0; n < 10; n++) {
        uint32_t r[4];
        ldsm4t(r, la + n * 128);
#pragma unroll
        for (int j = 0; j < 2; j++) {
          uint32_t a = hsub(r[2 * j], m0), c = hsub(r[2 * j + 1], m1);
          *(uint4*)(dst + (64 * n + 8 * j) * (2 * S_)) =
              make_uint4(r[2 * j], r[2 * j + 1], pack2(blo(a) * __uint_as_float(r0.x), bhi(a) * __uint_as_float(r0.y)),
                         pack2(blo(c) * __uint_as_float(r1.x), bhi(c) * __uint_as_float(r1.y)));
        }
      }
      asm volatile("fence.proxy.async.shared::cta;" ::: "memory");
      bar_sync(5, 128);
      if (tid == 0) { mbar_arrive(sb + 8 * B_AUXFREE); flag_add(FL_X); }
      STAMPIF(tid == 0, 26);
    }
    mod_box(P, sb, b, 0, tid);
    bar_sync(5, 128);
    if (tid == 0) flag_add(FL_M + (b >> 3));
    STAMPIF(tid == 0, 27);
    if (lane == 0) flag_wait(FL_X, e1 * 128);
    __syncwarp();
    STAMPIF(tid == 0, 28);
#pragma unroll 1
    for (int r = 0; r < 5; r++) {
      const int d = 128 * r + b;
      uint4 xh[4];
#pragma unroll
      for (int n = 0; n < 4; n++) xh[n] = __ldcg((const uint4*)(g_XH + d * (2 * S_)) + tid + 128 * n);
      if (lane < 4) flag_wait(FL_M + 8 * r + 2 * lane + (b >> 6), e1 * 8);
      __syncwarp();
      int v = lane >> 3;
      float mv = mod_sum((v == 3 ? 4 : v) * 640 + d, lane);
      if (v & 1) mv = rbf(1.f + mv);
      uint32_t mp = pack2(mv, mv);
      uint32_t sa = __shfl_sync(0xffffffffu, mp, 0), ca = __shfl_sync(0xffffffffu, mp, 8), ga = __shfl_sync(0xffffffffu, mp, 16), cb = __shfl_sync(0xffffffffu, mp, 24);
      if (tid == 0) *(uint16_t*)(g_cbsb + d) = (uint16_t)cb;
      mbar_wait(sb + 8 * (B_Z + r), 0);
#pragma unroll
      for (int n = 0; n < 4; n++) {
        uint2 z = lds64(sb + SM_Z + r * 4096 + 8 * (tid + 128 * n));
        uint32_t x0 = hadd(xh[n].x, hmul(ga, hmul(hadd(hmul(xh[n].z, ca), sa), z.x)));
        uint32_t x1 = hadd(xh[n].y, hmul(ga, hmul(hadd(hmul(xh[n].w, ca), sa), z.y)));
        *((uint2*)(g_AT + d * S_) + tid + 128 * n) = make_uint2(hmul(x0, cb), hmul(x1, cb));
        *((uint2*)(g_x1T + d * S_) + tid + 128 * n) = make_uint2(x0, x1);
      }
      if (r == 4 && w < 3) {
        int cmb = min(4 * w + (lane >> 3), 9), vec = cmb >= 5, dd = 128 * (cmb - 5 * vec) + b;
        if ((lane & 7) == 0) flag_wait(FL_M + 40 + 10 * vec + (dd >> 6), e1 * 8);
        __syncwarp();
        uint32_t val = pack2(mod_sum((vec ? 5 : 3) * 640 + dd, lane), 0.f);
        if ((lane & 7) == 0) { if (vec) *(uint16_t*)(g_gb + dd) = (uint16_t)val; else *((uint16_t*)(g_cbsb + dd) + 1) = (uint16_t)val; }
      }
      bar_sync(5, 128);
      if (tid == 0) flag_add(FL_R + r);
      STAMPIF(tid == 0, 29 + r);
      if (r == 1) {
        mod_box(P, sb, b, 1, tid);
        mod_box(P, sb, b, 2, tid);
        if (b < 96) mod_box(P, sb, b, 3, tid);
        bar_sync(5, 128);
        if (tid < 3 && (tid < 2 || b < 96)) flag_add(FL_M + 16 * (tid + 1) + (b >> 3));
      }
    }
    if (lane == 0) flag_wait(FL_R + 4, e1 * 128);
    __syncwarp();
    STAMPIF(tid == 0, 34);
    {
      const bf16* src = g_x1T + 16 * b + 8 * (lane & 1);
      uint4 pq = __ldcg((const uint4*)src);
      float pv[8] = {blo(pq.x), bhi(pq.x), blo(pq.y), bhi(pq.y), blo(pq.z), bhi(pq.z), blo(pq.w), bhi(pq.w)};
      float a[16];
#pragma unroll
      for (int j = 0; j < 16; j++) a[j] = 0.f;
      src += ((lane >> 1) + 16 * w) * S_;
#pragma unroll
      for (int n0 = 0; n0 < 10; n0 += 5) {
        uint4 v[5];
#pragma unroll
        for (int n = 0; n < 5; n++) v[n] = __ldcg((const uint4*)(src + (n0 + n) * 64 * S_));
#pragma unroll
        for (int n = 0; n < 5; n++) {
          uint32_t u[4] = {v[n].x, v[n].y, v[n].z, v[n].w};
#pragma unroll
          for (int j = 0; j < 4; j++) {
            float e0 = blo(u[j]) - pv[2 * j], e1_ = bhi(u[j]) - pv[2 * j + 1];
            a[2 * j] += e0; a[8 + 2 * j] += e0 * e0; a[2 * j + 1] += e1_; a[9 + 2 * j] += e1_ * e1_;
          }
        }
      }
      bfly<16>(a, 16, lane & 16); bfly<8>(a, 8, lane & 8); bfly<4>(a, 4, lane & 4); bfly<2>(a, 2, lane & 2);
      sts32(sb + SM_SMALL + SMALL_RED + w * 128 + (lane >> 4) * 64 + (8 * (lane & 1) + ((lane >> 1) & 7)) * 4, __float_as_uint(a[0]));
      bar_sync(5, 128);
      if (w == 3) {
        if (lane < 16) {
          float s1 = 0.f, s2 = 0.f;
#pragma unroll
          for (int j = 0; j < 4; j++) {
            s1 += __uint_as_float(lds32(sb + SM_SMALL + SMALL_RED + j * 128 + lane * 4));
            s2 += __uint_as_float(lds32(sb + SM_SMALL + SMALL_RED + j * 128 + 64 + lane * 4));
          }
          float p0 = __bfloat162float(__ldcg(g_x1T + 16 * b + lane));
          float mu = s1 * (1.f / D_), var = fmaxf(s2 * (1.f / D_) - mu * mu, 0.f);
          float sd = rbf(sqrtf(rbf(rbf(var) + 1e-5f)));
          g_stat[16 * b + lane] = make_uint4(pack2(-(p0 + mu), -(p0 + mu)), pack2(sd, sd), __float_as_uint(1.f / (sd * sd)), 0);
        }
        __syncwarp();
        if (lane == 0) flag_add(FL_S + m);
      } else {
        const int lc0 = 24 * (m & 7) + 8 * w;
        const bf16* wp = (m < 8 ? P.wg : P.wu) + lane * F_ + 192 * s + lc0;
#pragma unroll
        for (int j = 0; j < 16; j++) a[j] = 0.f;
#pragma unroll 1
        for (int n0 = 0; n0 < 20; n0 += 5) {
          uint4 v[5]; uint32_t cf[5];
#pragma unroll
          for (int n = 0; n < 5; n++) { v[n] = __ldg((const uint4*)(wp + (n0 + n) * 32 * F_)); cf[n] = __ldcg(g_cbsb + lane + 32 * (n0 + n)); }
#pragma unroll
          for (int n = 0; n < 5; n++) {
            uint32_t u[4] = {v[n].x, v[n].y, v[n].z, v[n].w};
            float k1 = blo(cf[n]), k2 = bhi(cf[n]);
#pragma unroll
            for (int j = 0; j < 4; j++) {
              a[2 * j] += k1 * blo(u[j]); a[2 * j + 1] += k1 * bhi(u[j]); a[8 + 2 * j] += k2 * blo(u[j]); a[9 + 2 * j] += k2 * bhi(u[j]);
            }
          }
        }
        bfly<16>(a, 16, lane & 16); bfly<8>(a, 8, lane & 8); bfly<4>(a, 4, lane & 4); bfly<2>(a, 2, lane & 2);
        float t = a[0] + __shfl_xor_sync(0xffffffffu, a[0], 1);
        float hi = rbf(t);
        int lc = lc0 + ((lane >> 1) & 7), cc = lc & 63, r0 = 2 * (lane >> 4) + 4 * (lane & 1);
        uint16_t* dst = (uint16_t*)g_cimg + s * 3072 + ((m >> 3) * 3 + (lc >> 6)) * 512 + (cc & 7);
        dst[r0 * 64 + (((cc >> 3) ^ r0) << 3)] = (uint16_t)pack2(hi, 0.f);
        dst[(r0 + 1) * 64 + (((cc >> 3) ^ (r0 + 1)) << 3)] = (uint16_t)pack2(t - hi, 0.f);
        bar_sync(6, 96);
        if (tid == 0) flag_add(FL_C + s);
        STAMPIF(tid == 0, 35);
      }
    }
  } else {
    asm volatile("setmaxnreg.inc.sync.aligned.u32 224;");
    const int g = lane >> 2, q = lane & 3;
    if (wg == 1) bar_arrive(1, 256);
    kv_job(P, sb, b, wg, wg, tid, 3 + wg);
    if (tid < 3) mbar_arrive(sb + 8 * (B_E1 + tid));
    if (tid == 3 && wg == 1) mbar_arrive(sb + 8 * (B_E1 + 5));
    STAMPIF(tid == 0, 1 + wg);
    asm volatile("barrier.cluster.wait.acquire.aligned;" ::: "memory");
    {
      const int b0 = (g >> 1) & 1, b1 = g >> 2, u = q + 4 * b0 - w;
      const uint32_t fo = 48 + (g & 1) * K1OFF + 288 * b1 + 4 * u, fo0 = fo - (u < 0 ? 32 : 0);
      const bool wrap = b0 && q == 0;
      const int src1 = b0 ? ((lane & 20) | ((q - 1) & 3)) : (lane | 8);
#pragma unroll 1
      for (int ch = wg; ch < 5; ch += 2) {
        const uint32_t base = ring + (3 + (ch >> 1)) * 32768;
        if (ch >= 2) mbar_wait(sb + 8 * (B_K + ch), 0);
        const uint32_t fa = base + wg * KSZ + fo, fa0 = base + wg * KSZ + fo0;
        uint32_t af[16][4];
#pragma unroll
        for (int j = 0; j < 16; j++) {
          const int o = 64 * (j & 1) + 576 * (j >> 1);
          af[j][0] = lds32(((j & 1) ? fa : fa0) + o); af[j][1] = lds32(fa + o + 128); af[j][2] = lds32(fa + o + 32); af[j][3] = lds32(fa + o + 160);
        }
        mbar_wait(sb + 8 * (B_U + ch), 0);
        float acc[128];
        const uint64_t db = mkdesc(base + 2 * KSZ + wg * USZ, 32, 128, 0);
        bar_sync(1 + wg, 256);
        STAMPIF(tid == 0, 3 + ch);
        wg_fence();
        wgmma_rs_n64<0>(acc + 96, af[0], db + 192, 0);
        wgmma_rs_n192<0>(acc, af[0], db, 0);
        wgmma_rs_n64<0>(acc + 96, af[1], db + 196, 1);
        wgmma_rs_n192<0>(acc, af[1], db + 4, 1);
        wgmma_rs_n32<0>(acc + 96, af[2], db + 224, 1);
        wgmma_rs_n192<0>(acc, af[2], db + 32, 1);
        wgmma_rs_n32<0>(acc + 96, af[3], db + 228, 1);
        wgmma_rs_n192<0>(acc, af[3], db + 36, 1);
        wgmma_rs_n192<0>(acc, af[4], db + 64, 1);
        wgmma_rs_n192<0>(acc, af[5], db + 68, 1);
        wgmma_rs_n160<0>(acc, af[6], db + 96, 1);
        wgmma_rs_n160<0>(acc, af[7], db + 100, 1);
        wgmma_rs_n128<0>(acc, af[8], db + 128, 1);
        wgmma_rs_n128<0>(acc, af[9], db + 132, 1);
        wgmma_rs_n96<0>(acc, af[10], db + 160, 1);
        wgmma_rs_n96<0>(acc, af[11], db + 164, 1);
        bar_arrive(2 - wg, 256);
        wgmma_rs_n64<0>(acc, af[12], db + 192, 1);
        wgmma_rs_n64<0>(acc, af[13], db + 196, 1);
        wgmma_rs_n32<0>(acc, af[14], db + 224, 1);
        wgmma_rs_n32<0>(acc, af[15], db + 228, 1);
        wg_commit();
        wg_wait<0>();
#pragma unroll
        for (int i = 0; i < 128; i++) asm volatile("" : "+f"(acc[i])::"memory");
        bar_sync(3 + wg, 128);
        if (tid == 0) mbar_arrive(sb + 8 * (B_E1 + 3 + (ch >> 1)));
        float S0[33], T[34];
#pragma unroll
        for (int i = 0; i < 31; i++) S0[i] = acc[4 * i] + acc[4 * i + 6];
        S0[31] = acc[124]; S0[32] = 0.f;
#pragma unroll
        for (int i = 0; i < 32; i++) {
          float s1 = i < 31 ? acc[4 * i + 1] + acc[4 * i + 7] : acc[125];
          T[i] = (wrap ? S0[i + 1] : S0[i]) + __shfl_sync(0xffffffffu, s1, src1);
        }
        T[32] = 0.f; T[33] = 0.f;
        uint32_t zz[8];
#pragma unroll
        for (int mu = 0; mu < 8; mu++) {
          float y0 = (b1 ? T[4 * mu + 4] : T[4 * mu]) + __shfl_xor_sync(0xffffffffu, T[4 * mu + 2], 16);
          float y1 = (b1 ? T[4 * mu + 5] : T[4 * mu + 1]) + __shfl_xor_sync(0xffffffffu, T[4 * mu + 3], 16);
          zz[mu] = pack2(y0, y1);
        }
        sts128(sb + SM_Z + ch * 4096 + tid * 32, make_uint4(zz[0], zz[1], zz[2], zz[3]));
        sts128(sb + SM_Z + ch * 4096 + tid * 32 + 16, make_uint4(zz[4], zz[5], zz[6], zz[7]));
        __syncwarp();
        if (lane == 0) mbar_arrive(sb + 8 * (B_Z + ch));
        STAMPIF(tid == 0, 8 + ch);
      }
      if (wg == 1) bar_sync(2, 256);
    }
    uint32_t hh[48];
    {
      float ga[96], ua[96];
      const uint64_t da0 = mkdesc(ring + wg * 4096, 4096, 1024, 1), db0 = mkdesc(ring + 8192, 4096, 1024, 1);
      int st = 0, ph = 0;
#pragma unroll 1
      for (int it = 0; it < 20; it++) {
        mbar_wait(sb + 8 * (B_F1 + st), ph);
        STAMPIF(tid == 0 && it == 0, 13 + wg);
        const uint64_t da = da0 + st * 2048, db = db0 + st * 2048;
        wg_fence();
        wgmma_ss_n192<1, 1>(ga, da, db, it != 0);
        wgmma_ss_n192<1, 1>(ua, da, db + 768, it != 0);
        wgmma_ss_n192<1, 1>(ga, da + 128, db + 128, 1);
        wgmma_ss_n192<1, 1>(ua, da + 128, db + 128 + 768, 1);
        wg_commit();
        wg_wait<1>();
        if (it > 0 && tid == 0) mbar_arrive(sb + 8 * (B_E1 + (st == 0 ? 5 : st - 1)));
        if (++st == 6) { st = 0; ph ^= 1; }
      }
      mbar_wait(sb + 8 * B_EXT, 0);
      uint32_t ae[4];
      const uint32_t sa = sb + SM_STAT + (64 * wg + 16 * w + g) * 16 + 4 * (q & 1);
      ae[0] = lds32(sa); ae[1] = lds32(sa + 128); ae[2] = 0; ae[3] = 0;
      if (q >= 2) { ae[0] = 0; ae[1] = 0; }
      const uint64_t de = mkdesc(sb + SM_EXT, 1024, 0, 1);
      wg_fence();
      wgmma_rs_n192<1>(ga, ae, de, 1);
      wgmma_rs_n192<1>(ua, ae, de + 192, 1);
      wg_commit();
      wg_wait<1>();
      if (tid == 0) mbar_arrive(sb + 8 * (B_E1 + 1));
      wg_wait<0>();
#pragma unroll
      for (int i = 0; i < 96; i++) asm volatile("" : "+f"(ga[i]), "+f"(ua[i])::"memory");
      STAMPIF(tid == 0, 15 + wg);
#pragma unroll
      for (int i = 0; i < 48; i++) hh[i] = pack2(ga[2 * i] * ua[2 * i], ga[2 * i + 1] * ua[2 * i + 1]);
    }
    float acc[80];
    {
      bf16* dst = g_HH + b * 6 * 4096 + (64 * wg + 16 * w + g) * 32 + ((q ^ ((g >> 1) & 3)) << 3);
#pragma unroll
      for (int k = 0; k < 6; k++) {
        *(uint4*)(dst + k * 4096) = make_uint4(hh[8 * k], hh[8 * k + 2], hh[8 * k + 4], hh[8 * k + 6]);
        *(uint4*)(dst + k * 4096 + 256) = make_uint4(hh[8 * k + 1], hh[8 * k + 3], hh[8 * k + 5], hh[8 * k + 7]);
      }
      bar_sync(3 + wg, 128);
      if (tid == 0) flag_add(FL_H + b);
      const uint64_t db0 = mkdesc(ring + 8192, 4096, 1024, 1), da0 = mkdesc(ring + wg * 4096, 16, 512, 2);
#pragma unroll
      for (int k = 0; k < 6; k++) {
        mbar_wait(sb + 8 * (B_FB + k), 0);
        const uint64_t db = db0 + ((k >> 1) + 2) * 2048 + (k & 1) * 768;
        wg_fence();
        wgmma_rs_n160<1>(acc, hh + 8 * k, db, k != 0);
        wgmma_rs_n160<1>(acc, hh + 8 * k + 4, db + 128, 1);
        wg_commit();
        wg_wait<1>();
        if (k > 0 && tid == 0) mbar_arrive(sb + 8 * (B_EB + k - 1));
      }
      STAMPIF(tid == 0, 17);
      int ka = 0, pa = 0;
#pragma unroll 1
      for (int k = 6; k < 24; k++) {
        const int sl = k < 12 ? k : k - 12;
        int gb_ = (sl >> 1) + 2; if (gb_ >= 6) gb_ -= 6;
        int ga_ = ka + 2; if (ga_ >= 6) ga_ -= 6;
        mbar_wait(sb + 8 * (B_FB + sl), k >= 12);
        mbar_wait(sb + 8 * (B_FA + ka), pa);
        const uint64_t db = db0 + gb_ * 2048 + (sl & 1) * 768, da = da0 + ga_ * 2048;
        wg_fence();
        wgmma_ss_n160<0, 1>(acc, da, db, 1);
        wgmma_ss_n160<0, 1>(acc, da + 2, db + 128, 1);
        wg_commit();
        wg_wait<1>();
        if (tid == 0) {
          mbar_arrive(sb + 8 * (B_EB + (sl == 0 ? 11 : sl - 1)));
          if (k > 6) mbar_arrive(sb + 8 * (B_EA + (ka == 0 ? 5 : ka - 1)));
        }
        if (++ka == 6) { ka = 0; pa ^= 1; }
      }
    }
    uint32_t xr[20], gbv[10];
    mbar_wait(sb + 8 * B_X1, 0);
    {
      const uint32_t la = sb + SM_Z + wg * 10240 + (8 * (lane >> 4) + (lane & 7)) * 128 + (((2 * w + ((lane >> 3) & 1)) ^ (lane & 7)) << 4);
#pragma unroll
      for (int i = 0; i < 5; i++) ldsm4t(xr + 4 * i, la + i * 2048);
#pragma unroll
      for (int i = 0; i < 10; i++) gbv[i] = lds32(sb + SM_SMALL + SMALL_GB + 16 * i + 4 * q);
    }
    const float rs0 = __uint_as_float(lds32(sb + SM_STAT + (64 * wg + 16 * w + g) * 16 + 8)), rs1 = __uint_as_float(lds32(sb + SM_STAT + (64 * wg + 16 * w + g) * 16 + 136));
    mbar_wait(sb + 8 * B_PEER, 0);
    wg_wait<0>();
#pragma unroll
    for (int i = 0; i < 80; i++) asm volatile("" : "+f"(acc[i])::"memory");
    STAMPIF(tid == 0, 18);
    const uint32_t rbuf = ring + (2 + wg) * 32768 + 8192 + w * 5120;
    {
      const uint32_t rd = mapa(rbuf + lane * 16, (b & 1) ^ 1), rb = mapa(sb + 8 * (B_RECV + wg), (b & 1) ^ 1);
      if (b & 1) {
#pragma unroll
        for (int i = 0; i < 10; i++) st_async4(rd + i * 512, acc[4 * i], acc[4 * i + 1], acc[4 * i + 2], acc[4 * i + 3], rb);
#pragma unroll
        for (int i = 0; i < 40; i++) acc[i] = acc[40 + i];
      } else {
#pragma unroll
        for (int i = 0; i < 10; i++) st_async4(rd + i * 512, acc[40 + 4 * i], acc[41 + 4 * i], acc[42 + 4 * i], acc[43 + 4 * i], rb);
      }
    }
    mbar_wait(sb + 8 * (B_RECV + wg), 0);
    uint32_t ov[20];
#pragma unroll
    for (int i = 0; i < 10; i++) {
      uint4 v = lds128(rbuf + i * 512 + lane * 16);
      uint32_t o0 = pack2((acc[4 * i] + __uint_as_float(v.x)) * rs0, (acc[4 * i + 1] + __uint_as_float(v.y)) * rs0);
      uint32_t o1 = pack2((acc[4 * i + 2] + __uint_as_float(v.z)) * rs1, (acc[4 * i + 3] + __uint_as_float(v.w)) * rs1);
      ov[2 * i] = hadd(xr[2 * i], hmul(gbv[i], o0));
      ov[2 * i + 1] = hadd(xr[2 * i + 1], hmul(gbv[i], o1));
    }
    __syncwarp();
#pragma unroll
    for (int i = 0; i < 5; i++) stsm4(rbuf + (lane & 15) * 176 + (lane >> 4) * 16 + i * 32, ov + 4 * i);
    asm volatile("fence.proxy.async.shared::cta;" ::: "memory");
    __syncwarp();
    if (lane < 16) {
      int t = 2047 - (256 * (lane >> 1) + 64 * (lane & 1) + ibase(8 * m + 4 * wg + w));
      bulk_s2g(P.out + t * D_ + 80 * s, rbuf + lane * 176, 160);
      asm volatile("cp.async.bulk.commit_group;" ::: "memory");
      asm volatile("cp.async.bulk.wait_group.read 0;" ::: "memory");
    }
    if (threadIdx.x == 0) g_epoch[b] = __ldcg(g_epoch + b) + 1;
    STAMPIF(tid == 0, 19);
  }
}

typedef CUresult (*EncFn)(CUtensorMap*, CUtensorMapDataType, cuuint32_t, void*, const cuuint64_t*, const cuuint64_t*, const cuuint32_t*, const cuuint32_t*,
                          CUtensorMapInterleave, CUtensorMapSwizzle, CUtensorMapL2promotion, CUtensorMapFloatOOBfill);
static void mkmap(EncFn enc, CUtensorMap* m, const void* p, int rank, const cuuint64_t* dims, const cuuint64_t* strides, const cuuint32_t* box, CUtensorMapSwizzle sw) {
  cuuint32_t es[5] = {1, 1, 1, 1, 1};
  CUresult r = enc(m, CU_TENSOR_MAP_DATA_TYPE_BFLOAT16, rank, (void*)p, dims, strides, box, es, CU_TENSOR_MAP_INTERLEAVE_NONE, sw,
                   CU_TENSOR_MAP_L2_PROMOTION_L2_128B, CU_TENSOR_MAP_FLOAT_OOB_FILL_NONE);
  if (r != CUDA_SUCCESS) fprintf(stderr, "tensor map encode failed: %d\n", (int)r);
}

extern "C" void kernel_launch(void* const* d_in, const int* in_sizes, int n_in, void* d_out, int out_size) {
  void* fn = nullptr;
  cudaDriverEntryPointQueryResult qr;
  cudaGetDriverEntryPoint("cuTensorMapEncodeTiled", &fn, cudaEnableDefault, &qr);
  EncFn enc = (EncFn)fn;
  void *pAT, *pX1;
  cudaGetSymbolAddress(&pAT, g_AT);
  cudaGetSymbolAddress(&pX1, g_x1T);
  Params P;
  { cuuint64_t d[] = {640, 2048}, st[] = {1280}; cuuint32_t bx[] = {64, 35}; mkmap(enc, &P.mK, d_in[1], 2, d, st, bx, CU_TENSOR_MAP_SWIZZLE_NONE); }
  { cuuint64_t d[] = {640, 2048}, st[] = {1280}; cuuint32_t bx[] = {64, 32}; mkmap(enc, &P.mV, d_in[2], 2, d, st, bx, CU_TENSOR_MAP_SWIZZLE_NONE); }
  { cuuint64_t d[] = {3840, 640}, st[] = {7680}; cuuint32_t bx[] = {64, 80}; mkmap(enc, &P.mWm, d_in[11], 2, d, st, bx, CU_TENSOR_MAP_SWIZZLE_NONE); }
  { cuuint64_t d[] = {64, 640, 32}, st[] = {4096, 128}; cuuint32_t bx[] = {64, 32, 2}; mkmap(enc, &P.mA, pAT, 3, d, st, bx, CU_TENSOR_MAP_SWIZZLE_128B); }
  { cuuint64_t d[] = {64, 640, 32}, st[] = {4096, 128}; cuuint32_t bx[] = {64, 80, 2}; mkmap(enc, &P.mX1, pX1, 3, d, st, bx, CU_TENSOR_MAP_SWIZZLE_128B); }
  { cuuint64_t d[] = {64, 640, 24}, st[] = {3072, 128}; cuuint32_t bx[] = {64, 32, 3};
    mkmap(enc, &P.mG, d_in[7], 3, d, st, bx, CU_TENSOR_MAP_SWIZZLE_128B); mkmap(enc, &P.mU, d_in[8], 3, d, st, bx, CU_TENSOR_MAP_SWIZZLE_128B); }
  { cuuint64_t d[] = {160, 2, 4, 192, 4}, st[] = {1280, 2560, 10240, 320}; cuuint32_t bx[] = {64, 2, 4, 4, 1}; mkmap(enc, &P.mDn, d_in[9], 5, d, st, bx, CU_TENSOR_MAP_SWIZZLE_128B); }
  { cuuint64_t d[] = {160, 2, 192, 4, 4}, st[] = {1280, 10240, 2560, 320}; cuuint32_t bx[] = {64, 2, 4, 4, 1}; mkmap(enc, &P.mDp, d_in[9], 5, d, st, bx, CU_TENSOR_MAP_SWIZZLE_128B); }
  P.x = (const bf16*)d_in[0]; P.shift_k = (const bf16*)d_in[3]; P.ssm_k = (const bf16*)d_in[4]; P.ssm_D = (const bf16*)d_in[5];
  P.wg = (const bf16*)d_in[7]; P.wu = (const bf16*)d_in[8]; P.c = (const bf16*)d_in[10]; P.wmod = (const bf16*)d_in[11];
  P.out = (bf16*)d_out;
  cudaFuncSetAttribute(fused_kernel, cudaFuncAttributeMaxDynamicSharedMemorySize, SM_TOTAL);
  cudaLaunchConfig_t cfg = {};
  cfg.gridDim = dim3(128); cfg.blockDim = dim3(512); cfg.dynamicSmemBytes = SM_TOTAL; cfg.stream = cudaStreamPerThread;
  cudaLaunchAttribute at[1];
  at[0].id = cudaLaunchAttributeClusterDimension; at[0].val.clusterDim.x = 2; at[0].val.clusterDim.y = 1; at[0].val.clusterDim.z = 1;
  cfg.attrs = at; cfg.numAttrs = 1;
  cudaLaunchKernelEx(&cfg, fused_kernel, P);
}
```

```cpp
#include <cuda_runtime.h>
#include <cuda.h>
#include <cuda_bf16.h>
#include <stdio.h>
#include <stdint.h>
typedef __nv_bfloat16 bf16;
#define SIG 1
__device__ __forceinline__ uint32_t smem_u32(const void* p) { return (uint32_t)__cvta_generic_to_shared(p); }
__device__ __forceinline__ void mbar_init(uint32_t bar, int cnt) { asm volatile("mbarrier.init.shared::cta.b64 [%0], %1;" ::"r"(bar), "r"(cnt) : "memory"); }
__device__ __forceinline__ void mbar_expect(uint32_t bar, int bytes) { asm volatile("mbarrier.arrive.expect_tx.shared::cta.b64 _, [%0], %1;" ::"r"(bar), "r"(bytes) : "memory"); }
__device__ __forceinline__ void mbar_arrive(uint32_t bar) { asm volatile("mbarrier.arrive.shared::cta.b64 _, [%0];" ::"r"(bar) : "memory"); }
__device__ __forceinline__ void mbar_arrive_remote(uint32_t bar) { asm volatile("mbarrier.arrive.release.cluster.shared::cluster.b64 _, [%0];" ::"r"(bar) : "memory"); }
__device__ __forceinline__ uint32_t mapa(uint32_t a, uint32_t cta) { uint32_t r; asm("mapa.shared::cluster.u32 %0, %1, %2;" : "=r"(r) : "r"(a), "r"(cta)); return r; }
__device__ __forceinline__ bool mbar_try(uint32_t bar, int parity) {
  uint32_t ok;
  asm volatile("{\n.reg .pred p;\nmbarrier.try_wait.parity.shared::cta.b64 p, [%1], %2;\nselp.u32 %0, 1, 0, p;\n}" : "=r"(ok) : "r"(bar), "r"(parity) : "memory");
  return ok;
}
__device__ __forceinline__ void mbar_wait(uint32_t bar, int parity) {
#pragma unroll 1
  for (int i = 0; i < (1 << 20); i++) { if (mbar_try(bar, parity)) return; }
  __trap();
}
__device__ __forceinline__ void tma2d(uint32_t dst, const CUtensorMap* m, int c0, int c1, uint32_t bar) {
  asm volatile("cp.async.bulk.tensor.2d.shared::cluster.global.mbarrier::complete_tx::bytes [%0], [%1, {%3, %4}], [%2];" ::"r"(dst), "l"(m), "r"(bar), "r"(c0), "r"(c1) : "memory");
}
__device__ __forceinline__ void tma3d(uint32_t dst, const CUtensorMap* m, int c0, int c1, int c2, uint32_t bar) {
  asm volatile("cp.async.bulk.tensor.3d.shared::cluster.global.mbarrier::complete_tx::bytes [%0], [%1, {%3, %4, %5}], [%2];" ::"r"(dst), "l"(m), "r"(bar), "r"(c0), "r"(c1), "r"(c2) : "memory");
}
__device__ __forceinline__ void tma5d(uint32_t dst, const CUtensorMap* m, int c0, int c1, int c2, int c3, int c4, uint32_t bar) {
  asm volatile("cp.async.bulk.tensor.5d.shared::cluster.global.mbarrier::complete_tx::bytes [%0], [%1, {%3, %4, %5, %6, %7}], [%2];" ::"r"(dst), "l"(m), "r"(bar), "r"(c0), "r"(c1), "r"(c2), "r"(c3), "r"(c4) : "memory");
}
__device__ __forceinline__ void tma_store2d(const CUtensorMap* m, uint32_t src, int c0, int c1) {
  asm volatile("cp.async.bulk.tensor.2d.global.shared::cta.bulk_group [%0, {%2, %3}], [%1];" ::"l"(m), "r"(src), "r"(c0), "r"(c1) : "memory");
}
__device__ __forceinline__ void tma_prefetch2d(const CUtensorMap* m, int c0, int c1) {
  asm volatile("cp.async.bulk.prefetch.tensor.2d.L2.global [%0, {%1, %2}];" ::"l"(m), "r"(c0), "r"(c1) : "memory");
}
__device__ __forceinline__ void bulk_g2s(uint32_t dst, const void* src, int bytes, uint32_t bar) {
  asm volatile("cp.async.bulk.shared::cluster.global.mbarrier::complete_tx::bytes [%0], [%1], %2, [%3];" ::"r"(dst), "l"(src), "r"(bytes), "r"(bar) : "memory");
}
__device__ __forceinline__ void bulk_s2g(void* dst, uint32_t src, int bytes) {
  asm volatile("cp.async.bulk.global.shared::cta.bulk_group [%0], [%1], %2;" ::"l"(dst), "r"(src), "r"(bytes) : "memory");
}
__device__ __forceinline__ void st_async4(uint32_t dst, float a, float b, float c, float d, uint32_t bar) {
  asm volatile("st.async.weak.shared::cluster.mbarrier::complete_tx::bytes.v4.f32 [%0], {%1, %2, %3, %4}, [%5];" ::"r"(dst), "f"(a), "f"(b), "f"(c), "f"(d), "r"(bar) : "memory");
}
__device__ __forceinline__ void wg_fence() { asm volatile("wgmma.fence.sync.aligned;" ::: "memory"); }
__device__ __forceinline__ void wg_commit() { asm volatile("wgmma.commit_group.sync.aligned;" ::: "memory"); }
template <int N> __device__ __forceinline__ void wg_wait() { asm volatile("wgmma.wait_group.sync.aligned %0;" ::"n"(N) : "memory"); }
__device__ __forceinline__ uint64_t mkdesc(uint32_t addr, uint32_t lbo, uint32_t sbo, uint32_t swz) {
  return (uint64_t)((addr & 0x3FFFF) >> 4) | ((uint64_t)(lbo >> 4) << 16) | ((uint64_t)(sbo >> 4) << 32) | ((uint64_t)swz << 62);
}
__device__ __forceinline__ void ldsm4t(uint32_t* r, uint32_t a) {
  asm volatile("ldmatrix.sync.aligned.m8n8.x4.trans.shared.b16 {%0,%1,%2,%3}, [%4];" : "=r"(r[0]), "=r"(r[1]), "=r"(r[2]), "=r"(r[3]) : "r"(a) : "memory");
}
__device__ __forceinline__ void stsm4(uint32_t a, const uint32_t* r) {
  asm volatile("stmatrix.sync.aligned.m8n8.x4.shared.b16 [%0], {%1,%2,%3,%4};" ::"r"(a), "r"(r[0]), "r"(r[1]), "r"(r[2]), "r"(r[3]) : "memory");
}
__device__ __forceinline__ void bar_sync(int id, int n) { asm volatile("bar.sync %0, %1;" ::"r"(id), "r"(n) : "memory"); }
__device__ __forceinline__ void bar_arrive(int id, int n) { asm volatile("bar.arrive %0, %1;" ::"r"(id), "r"(n) : "memory"); }
__device__ __forceinline__ uint32_t lds32(uint32_t a) { uint32_t v; asm volatile("ld.shared.b32 %0, [%1];" : "=r"(v) : "r"(a) : "memory"); return v; }
__device__ __forceinline__ uint2 lds64(uint32_t a) { uint2 v; asm volatile("ld.shared.v2.b32 {%0,%1}, [%2];" : "=r"(v.x), "=r"(v.y) : "r"(a) : "memory"); return v; }
__device__ __forceinline__ uint4 lds128(uint32_t a) { uint4 v; asm volatile("ld.shared.v4.b32 {%0,%1,%2,%3}, [%4];" : "=r"(v.x), "=r"(v.y), "=r"(v.z), "=r"(v.w) : "r"(a) : "memory"); return v; }
__device__ __forceinline__ void sts16(uint32_t a, uint32_t v) { asm volatile("st.shared.b16 [%0], %1;" ::"r"(a), "h"((uint16_t)v) : "memory"); }
__device__ __forceinline__ void sts32(uint32_t a, uint32_t v) { asm volatile("st.shared.b32 [%0], %1;" ::"r"(a), "r"(v) : "memory"); }
__device__ __forceinline__ void sts64(uint32_t a, uint32_t x, uint32_t y) { asm volatile("st.shared.v2.b32 [%0], {%1,%2};" ::"r"(a), "r"(x), "r"(y) : "memory"); }
__device__ __forceinline__ void sts128(uint32_t a, uint4 v) { asm volatile("st.shared.v4.b32 [%0], {%1,%2,%3,%4};" ::"r"(a), "r"(v.x), "r"(v.y), "r"(v.z), "r"(v.w) : "memory"); }
template<int TB> __device__ __forceinline__ void wgmma_rs_n128(float* d, const uint32_t* a, uint64_t db, int sd) {
  asm volatile("{\n.reg .pred p;\nsetp.ne.b32 p, %69, 0;\n"
    "wgmma.mma_async.sync.aligned.m64n128k16.f32.bf16.bf16 {%0, %1, %2, %3, %4, %5, %6, %7, %8, %9, %10, %11, %12, %13, %14, %15, %16, %17, %18, %19, %20, %21, %22, %23, %24, %25, %26, %27, %28, %29, %30, %31, %32, %33, %34, %35, %36, %37, %38, %39, %40, %41, %42, %43, %44, %45, %46, %47, %48, %49, %50, %51, %52, %53, %54, %55, %56, %57, %58, %59, %60, %61, %62, %63}, {%64, %65, %66, %67}, %68, p, 1, 1, %70;\n}"
    : "+f"(d[0]), "+f"(d[1]), "+f"(d[2]), "+f"(d[3]), "+f"(d[4]), "+f"(d[5]), "+f"(d[6]), "+f"(d[7]), "+f"(d[8]), "+f"(d[9]), "+f"(d[10]), "+f"(d[11]), "+f"(d[12]), "+f"(d[13]), "+f"(d[14]), "+f"(d[15]), "+f"(d[16]), "+f"(d[17]), "+f"(d[18]), "+f"(d[19]), "+f"(d[20]), "+f"(d[21]), "+f"(d[22]), "+f"(d[23]), "+f"(d[24]), "+f"(d[25]), "+f"(d[26]), "+f"(d[27]), "+f"(d[28]), "+f"(d[29]), "+f"(d[30]), "+f"(d[31]), "+f"(d[32]), "+f"(d[33]), "+f"(d[34]), "+f"(d[35]), "+f"(d[36]), "+f"(d[37]), "+f"(d[38]), "+f"(d[39]), "+f"(d[40]), "+f"(d[41]), "+f"(d[42]), "+f"(d[43]), "+f"(d[44]), "+f"(d[45]), "+f"(d[46]), "+f"(d[47]), "+f"(d[48]), "+f"(d[49]), "+f"(d[50]), "+f"(d[51]), "+f"(d[52]), "+f"(d[53]), "+f"(d[54]), "+f"(d[55]), "+f"(d[56]), "+f"(d[57]), "+f"(d[58]), "+f"(d[59]), "+f"(d[60]), "+f"(d[61]), "+f"(d[62]), "+f"(d[63])
    : "r"(a[0]), "r"(a[1]), "r"(a[2]), "r"(a[3]), "l"(db), "r"(sd), "n"(TB));
}

template<int TB> __device__ __forceinline__ void wgmma_rs_n160(float* d, const uint32_t* a, uint64_t db, int sd) {
  asm volatile("{\n.reg .pred p;\nsetp.ne.b32 p, %85, 0;\n"
    "wgmma.mma_async.sync.aligned.m64n160k16.f32.bf16.bf16 {%0, %1, %2, %3, %4, %5, %6, %7, %8, %9, %10, %11, %12, %13, %14, %15, %16, %17, %18, %19, %20, %21, %22, %23, %24, %25, %26, %27, %28, %29, %30, %31, %32, %33, %34, %35, %36, %37, %38, %39, %40, %41, %42, %43, %44, %45, %46, %47, %48, %49, %50, %51, %52, %53, %54, %55, %56, %57, %58, %59, %60, %61, %62, %63, %64, %65, %66, %67, %68, %69, %70, %71, %72, %73, %74, %75, %76, %77, %78, %79}, {%80, %81, %82, %83}, %84, p, 1, 1, %86;\n}"
    : "+f"(d[0]), "+f"(d[1]), "+f"(d[2]), "+f"(d[3]), "+f"(d[4]), "+f"(d[5]), "+f"(d[6]), "+f"(d[7]), "+f"(d[8]), "+f"(d[9]), "+f"(d[10]), "+f"(d[11]), "+f"(d[12]), "+f"(d[13]), "+f"(d[14]), "+f"(d[15]), "+f"(d[16]), "+f"(d[17]), "+f"(d[18]), "+f"(d[19]), "+f"(d[20]), "+f"(d[21]), "+f"(d[22]), "+f"(d[23]), "+f"(d[24]), "+f"(d[25]), "+f"(d[26]), "+f"(d[27]), "+f"(d[28]), "+f"(d[29]), "+f"(d[30]), "+f"(d[31]), "+f"(d[32]), "+f"(d[33]), "+f"(d[34]), "+f"(d[35]), "+f"(d[36]), "+f"(d[37]), "+f"(d[38]), "+f"(d[39]), "+f"(d[40]), "+f"(d[41]), "+f"(d[42]), "+f"(d[43]), "+f"(d[44]), "+f"(d[45]), "+f"(d[46]), "+f"(d[47]), "+f"(d[48]), "+f"(d[49]), "+f"(d[50]), "+f"(d[51]), "+f"(d[52]), "+f"(d[53]), "+f"(d[54]), "+f"(d[55]), "+f"(d[56]), "+f"(d[57]), "+f"(d[58]), "+f"(d[59]), "+f"(d[60]), "+f"(d[61]), "+f"(d[62]), "+f"(d[63]), "+f"(d[64]), "+f"(d[65]), "+f"(d[66]), "+f"(d[67]), "+f"(d[68]), "+f"(d[69]), "+f"(d[70]), "+f"(d[71]), "+f"(d[72]), "+f"(d[73]), "+f"(d[74]), "+f"(d[75]), "+f"(d[76]), "+f"(d[77]), "+f"(d[78]), "+f"(d[79])
    : "r"(a[0]), "r"(a[1]), "r"(a[2]), "r"(a[3]), "l"(db), "r"(sd), "n"(TB));
}

template<int TB> __device__ __forceinline__ void wgmma_rs_n192(float* d, const uint32_t* a, uint64_t db, int sd) {
  asm volatile("{\n.reg .pred p;\nsetp.ne.b32 p, %101, 0;\n"
    "wgmma.mma_async.sync.aligned.m64n192k16.f32.bf16.bf16 {%0, %1, %2, %3, %4, %5, %6, %7, %8, %9, %10, %11, %12, %13, %14, %15, %16, %17, %18, %19, %20, %21, %22, %23, %24, %25, %26, %27, %28, %29, %30, %31, %32, %33, %34, %35, %36, %37, %38, %39, %40, %41, %42, %43, %44, %45, %46, %47, %48, %49, %50, %51, %52, %53, %54, %55, %56, %57, %58, %59, %60, %61, %62, %63, %64, %65, %66, %67, %68, %69, %70, %71, %72, %73, %74, %75, %76, %77, %78, %79, %80, %81, %82, %83, %84, %85, %86, %87, %88, %89, %90, %91, %92, %93, %94, %95}, {%96, %97, %98, %99}, %100, p, 1, 1, %102;\n}"
    : "+f"(d[0]), "+f"(d[1]), "+f"(d[2]), "+f"(d[3]), "+f"(d[4]), "+f"(d[5]), "+f"(d[6]), "+f"(d[7]), "+f"(d[8]), "+f"(d[9]), "+f"(d[10]), "+f"(d[11]), "+f"(d[12]), "+f"(d[13]), "+f"(d[14]), "+f"(d[15]), "+f"(d[16]), "+f"(d[17]), "+f"(d[18]), "+f"(d[19]), "+f"(d[20]), "+f"(d[21]), "+f"(d[22]), "+f"(d[23]), "+f"(d[24]), "+f"(d[25]), "+f"(d[26]), "+f"(d[27]), "+f"(d[28]), "+f"(d[29]), "+f"(d[30]), "+f"(d[31]), "+f"(d[32]), "+f"(d[33]), "+f"(d[34]), "+f"(d[35]), "+f"(d[36]), "+f"(d[37]), "+f"(d[38]), "+f"(d[39]), "+f"(d[40]), "+f"(d[41]), "+f"(d[42]), "+f"(d[43]), "+f"(d[44]), "+f"(d[45]), "+f"(d[46]), "+f"(d[47]), "+f"(d[48]), "+f"(d[49]), "+f"(d[50]), "+f"(d[51]), "+f"(d[52]), "+f"(d[53]), "+f"(d[54]), "+f"(d[55]), "+f"(d[56]), "+f"(d[57]), "+f"(d[58]), "+f"(d[59]), "+f"(d[60]), "+f"(d[61]), "+f"(d[62]), "+f"(d[63]), "+f"(d[64]), "+f"(d[65]), "+f"(d[66]), "+f"(d[67]), "+f"(d[68]), "+f"(d[69]), "+f"(d[70]), "+f"(d[71]), "+f"(d[72]), "+f"(d[73]), "+f"(d[74]), "+f"(d[75]), "+f"(d[76]), "+f"(d[77]), "+f"(d[78]), "+f"(d[79]), "+f"(d[80]), "+f"(d[81]), "+f"(d[82]), "+f"(d[83]), "+f"(d[84]), "+f"(d[85]), "+f"(d[86]), "+f"(d[87]), "+f"(d[88]), "+f"(d[89]), "+f"(d[90]), "+f"(d[91]), "+f"(d[92]), "+f"(d[93]), "+f"(d[94]), "+f"(d[95])
    : "r"(a[0]), "r"(a[1]), "r"(a[2]), "r"(a[3]), "l"(db), "r"(sd), "n"(TB));
}

template<int TB> __device__ __forceinline__ void wgmma_rs_n32(float* d, const uint32_t* a, uint64_t db, int sd) {
  asm volatile("{\n.reg .pred p;\nsetp.ne.b32 p, %21, 0;\n"
    "wgmma.mma_async.sync.aligned.m64n32k16.f32.bf16.bf16 {%0, %1, %2, %3, %4, %5, %6, %7, %8, %9, %10, %11, %12, %13, %14, %15}, {%16, %17, %18, %19}, %20, p, 1, 1, %22;\n}"
    : "+f"(d[0]), "+f"(d[1]), "+f"(d[2]), "+f"(d[3]), "+f"(d[4]), "+f"(d[5]), "+f"(d[6]), "+f"(d[7]), "+f"(d[8]), "+f"(d[9]), "+f"(d[10]), "+f"(d[11]), "+f"(d[12]), "+f"(d[13]), "+f"(d[14]), "+f"(d[15])
    : "r"(a[0]), "r"(a[1]), "r"(a[2]), "r"(a[3]), "l"(db), "r"(sd), "n"(TB));
}

template<int TB> __device__ __forceinline__ void wgmma_rs_n64(float* d, const uint32_t* a, uint64_t db, int sd) {
  asm volatile("{\n.reg .pred p;\nsetp.ne.b32 p, %37, 0;\n"
    "wgmma.mma_async.sync.aligned.m64n64k16.f32.bf16.bf16 {%0, %1, %2, %3, %4, %5, %6, %7, %8, %9, %10, %11, %12, %13, %14, %15, %16, %17, %18, %19, %20, %21, %22, %23, %24, %25, %26, %27, %28, %29, %30, %31}, {%32, %33, %34, %35}, %36, p, 1, 1, %38;\n}"
    : "+f"(d[0]), "+f"(d[1]), "+f"(d[2]), "+f"(d[3]), "+f"(d[4]), "+f"(d[5]), "+f"(d[6]), "+f"(d[7]), "+f"(d[8]), "+f"(d[9]), "+f"(d[10]), "+f"(d[11]), "+f"(d[12]), "+f"(d[13]), "+f"(d[14]), "+f"(d[15]), "+f"(d[16]), "+f"(d[17]), "+f"(d[18]), "+f"(d[19]), "+f"(d[20]), "+f"(d[21]), "+f"(d[22]), "+f"(d[23]), "+f"(d[24]), "+f"(d[25]), "+f"(d[26]), "+f"(d[27]), "+f"(d[28]), "+f"(d[29]), "+f"(d[30]), "+f"(d[31])
    : "r"(a[0]), "r"(a[1]), "r"(a[2]), "r"(a[3]), "l"(db), "r"(sd), "n"(TB));
}

template<int TB> __device__ __forceinline__ void wgmma_rs_n96(float* d, const uint32_t* a, uint64_t db, int sd) {
  asm volatile("{\n.reg .pred p;\nsetp.ne.b32 p, %53, 0;\n"
    "wgmma.mma_async.sync.aligned.m64n96k16.f32.bf16.bf16 {%0, %1, %2, %3, %4, %5, %6, %7, %8, %9, %10, %11, %12, %13, %14, %15, %16, %17, %18, %19, %20, %21, %22, %23, %24, %25, %26, %27, %28, %29, %30, %31, %32, %33, %34, %35, %36, %37, %38, %39, %40, %41, %42, %43, %44, %45, %46, %47}, {%48, %49, %50, %51}, %52, p, 1, 1, %54;\n}"
    : "+f"(d[0]), "+f"(d[1]), "+f"(d[2]), "+f"(d[3]), "+f"(d[4]), "+f"(d[5]), "+f"(d[6]), "+f"(d[7]), "+f"(d[8]), "+f"(d[9]), "+f"(d[10]), "+f"(d[11]), "+f"(d[12]), "+f"(d[13]), "+f"(d[14]), "+f"(d[15]), "+f"(d[16]), "+f"(d[17]), "+f"(d[18]), "+f"(d[19]), "+f"(d[20]), "+f"(d[21]), "+f"(d[22]), "+f"(d[23]), "+f"(d[24]), "+f"(d[25]), "+f"(d[26]), "+f"(d[27]), "+f"(d[28]), "+f"(d[29]), "+f"(d[30]), "+f"(d[31]), "+f"(d[32]), "+f"(d[33]), "+f"(d[34]), "+f"(d[35]), "+f"(d[36]), "+f"(d[37]), "+f"(d[38]), "+f"(d[39]), "+f"(d[40]), "+f"(d[41]), "+f"(d[42]), "+f"(d[43]), "+f"(d[44]), "+f"(d[45]), "+f"(d[46]), "+f"(d[47])
    : "r"(a[0]), "r"(a[1]), "r"(a[2]), "r"(a[3]), "l"(db), "r"(sd), "n"(TB));
}

template<int TA, int TB> __device__ __forceinline__ void wgmma_ss_n160(float* d, uint64_t da, uint64_t db, int sd) {
  asm volatile("{\n.reg .pred p;\nsetp.ne.b32 p, %82, 0;\n"
    "wgmma.mma_async.sync.aligned.m64n160k16.f32.bf16.bf16 {%0, %1, %2, %3, %4, %5, %6, %7, %8, %9, %10, %11, %12, %13, %14, %15, %16, %17, %18, %19, %20, %21, %22, %23, %24, %25, %26, %27, %28, %29, %30, %31, %32, %33, %34, %35, %36, %37, %38, %39, %40, %41, %42, %43, %44, %45, %46, %47, %48, %49, %50, %51, %52, %53, %54, %55, %56, %57, %58, %59, %60, %61, %62, %63, %64, %65, %66, %67, %68, %69, %70, %71, %72, %73, %74, %75, %76, %77, %78, %79}, %80, %81, p, 1, 1, %83, %84;\n}"
    : "+f"(d[0]), "+f"(d[1]), "+f"(d[2]), "+f"(d[3]), "+f"(d[4]), "+f"(d[5]), "+f"(d[6]), "+f"(d[7]), "+f"(d[8]), "+f"(d[9]), "+f"(d[10]), "+f"(d[11]), "+f"(d[12]), "+f"(d[13]), "+f"(d[14]), "+f"(d[15]), "+f"(d[16]), "+f"(d[17]), "+f"(d[18]), "+f"(d[19]), "+f"(d[20]), "+f"(d[21]), "+f"(d[22]), "+f"(d[23]), "+f"(d[24]), "+f"(d[25]), "+f"(d[26]), "+f"(d[27]), "+f"(d[28]), "+f"(d[29]), "+f"(d[30]), "+f"(d[31]), "+f"(d[32]), "+f"(d[33]), "+f"(d[34]), "+f"(d[35]), "+f"(d[36]), "+f"(d[37]), "+f"(d[38]), "+f"(d[39]), "+f"(d[40]), "+f"(d[41]), "+f"(d[42]), "+f"(d[43]), "+f"(d[44]), "+f"(d[45]), "+f"(d[46]), "+f"(d[47]), "+f"(d[48]), "+f"(d[49]), "+f"(d[50]), "+f"(d[51]), "+f"(d[52]), "+f"(d[53]), "+f"(d[54]), "+f"(d[55]), "+f"(d[56]), "+f"(d[57]), "+f"(d[58]), "+f"(d[59]), "+f"(d[60]), "+f"(d[61]), "+f"(d[62]), "+f"(d[63]), "+f"(d[64]), "+f"(d[65]), "+f"(d[66]), "+f"(d[67]), "+f"(d[68]), "+f"(d[69]), "+f"(d[70]), "+f"(d[71]), "+f"(d[72]), "+f"(d[73]), "+f"(d[74]), "+f"(d[75]), "+f"(d[76]), "+f"(d[77]), "+f"(d[78]), "+f"(d[79])
    : "l"(da), "l"(db), "r"(sd), "n"(TA), "n"(TB));
}

template<int TA, int TB> __device__ __forceinline__ void wgmma_ss_n192(float* d, uint64_t da, uint64_t db, int sd) {
  asm volatile("{\n.reg .pred p;\nsetp.ne.b32 p, %98, 0;\n"
    "wgmma.mma_async.sync.aligned.m64n192k16.f32.bf16.bf16 {%0, %1, %2, %3, %4, %5, %6, %7, %8, %9, %10, %11, %12, %13, %14, %15, %16, %17, %18, %19, %20, %21, %22, %23, %24, %25, %26, %27, %28, %29, %30, %31, %32, %33, %34, %35, %36, %37, %38, %39, %40, %41, %42, %43, %44, %45, %46, %47, %48, %49, %50, %51, %52, %53, %54, %55, %56, %57, %58, %59, %60, %61, %62, %63, %64, %65, %66, %67, %68, %69, %70, %71, %72, %73, %74, %75, %76, %77, %78, %79, %80, %81, %82, %83, %84, %85, %86, %87, %88, %89, %90, %91, %92, %93, %94, %95}, %96, %97, p, 1, 1, %99, %100;\n}"
    : "+f"(d[0]), "+f"(d[1]), "+f"(d[2]), "+f"(d[3]), "+f"(d[4]), "+f"(d[5]), "+f"(d[6]), "+f"(d[7]), "+f"(d[8]), "+f"(d[9]), "+f"(d[10]), "+f"(d[11]), "+f"(d[12]), "+f"(d[13]), "+f"(d[14]), "+f"(d[15]), "+f"(d[16]), "+f"(d[17]), "+f"(d[18]), "+f"(d[19]), "+f"(d[20]), "+f"(d[21]), "+f"(d[22]), "+f"(d[23]), "+f"(d[24]), "+f"(d[25]), "+f"(d[26]), "+f"(d[27]), "+f"(d[28]), "+f"(d[29]), "+f"(d[30]), "+f"(d[31]), "+f"(d[32]), "+f"(d[33]), "+f"(d[34]), "+f"(d[35]), "+f"(d[36]), "+f"(d[37]), "+f"(d[38]), "+f"(d[39]), "+f"(d[40]), "+f"(d[41]), "+f"(d[42]), "+f"(d[43]), "+f"(d[44]), "+f"(d[45]), "+f"(d[46]), "+f"(d[47]), "+f"(d[48]), "+f"(d[49]), "+f"(d[50]), "+f"(d[51]), "+f"(d[52]), "+f"(d[53]), "+f"(d[54]), "+f"(d[55]), "+f"(d[56]), "+f"(d[57]), "+f"(d[58]), "+f"(d[59]), "+f"(d[60]), "+f"(d[61]), "+f"(d[62]), "+f"(d[63]), "+f"(d[64]), "+f"(d[65]), "+f"(d[66]), "+f"(d[67]), "+f"(d[68]), "+f"(d[69]), "+f"(d[70]), "+f"(d[71]), "+f"(d[72]), "+f"(d[73]), "+f"(d[74]), "+f"(d[75]), "+f"(d[76]), "+f"(d[77]), "+f"(d[78]), "+f"(d[79]), "+f"(d[80]), "+f"(d[81]), "+f"(d[82]), "+f"(d[83]), "+f"(d[84]), "+f"(d[85]), "+f"(d[86]), "+f"(d[87]), "+f"(d[88]), "+f"(d[89]), "+f"(d[90]), "+f"(d[91]), "+f"(d[92]), "+f"(d[93]), "+f"(d[94]), "+f"(d[95])
    : "l"(da), "l"(db), "r"(sd), "n"(TA), "n"(TB));
}

constexpr int S_ = 2048, D_ = 640, F_ = 1536;

__device__ __align__(1024) bf16 g_kvT[D_ * S_];
__device__ __align__(1024) bf16 g_XH[D_ * S_ * 2];
__device__ __align__(1024) bf16 g_x1T[D_ * S_];
__device__ __align__(1024) bf16 g_AT[D_ * S_];
__device__ __align__(1024) bf16 g_HH[S_ * F_];
__device__ __align__(1024) float g_modP[8 * 3840];
__device__ __align__(1024) uint32_t g_cbsb[D_];
__device__ __align__(1024) bf16 g_gb[D_];
__device__ __align__(1024) uint4 g_stat[S_];
__device__ __align__(1024) bf16 g_cimg[8 * 6 * 512];
__device__ __align__(1024) uint32_t g_flag[256 * 8];
__device__ uint32_t g_epoch[128];
#define DEVSM 0
#define STAMP(id)
#define STAMPIF(c, id)
constexpr int FL_KV = 0, FL_X = 10, FL_R = 11, FL_S = 16, FL_C = 32, FL_M = 40, FL_F = 100, FL_H = 128;

constexpr int SM_Z = 1024, SM_EXT = 21504, SM_STAT = 27648, SM_SMALL = 29696, SM_BOX = 30720, SM_RING = 34816, SM_TOTAL = SM_RING + 6 * 32768;
constexpr int SMALL_S = 0, SMALL_XM = 160, SMALL_MOD = 256, SMALL_RED = 336, SMALL_GB = 848, SMALL_DUMMY = 1008;
constexpr int JOB_SZ = 8576, R_STG = 43008, R_X = 63488, XPITCH = 1296;
constexpr int K1OFF = 4672, KSZ = 9472, USZ = 4224;
enum { B_B = 0, B_X = 5, B_U = 6, B_S = 11, B_F1 = 16, B_E1 = 22, B_EB = 28, B_EA = 40, B_FB = 46, B_FA = 58, B_EXT = 64, B_X1 = 65, B_PEER = 66, B_RECV = 67,
       B_MF = 69, B_EWF = 72, B_AUXFREE = 75, B_Z = 76, B_KVS = 81, B_EW = 84, B_MB = 89, B_HH = 92, B_K = 94, B_NUM = 97 };

struct Params {
  CUtensorMap mK, mV, mS, mKV, mWm, mA, mG, mU, mDn, mDp, mX1;
  const bf16 *x, *shift_k, *ssm_D, *wg, *wu, *c, *wmod;
  bf16* out;
};

__device__ __forceinline__ uint32_t* flagp(int id) { return g_flag + id * 8; }
__device__ __forceinline__ void flag_add(int id) { asm volatile("red.relaxed.gpu.global.add.u32 [%0], 1;" ::"l"(flagp(id)) : "memory"); }
__device__ __forceinline__ uint32_t rdback(const void* p) { uint32_t v; asm volatile("ld.relaxed.gpu.global.u32 %0, [%1];" : "=r"(v) : "l"(p) : "memory"); return v; }
__device__ __forceinline__ void rdwait(uint32_t sb, uint32_t v) { sts32(sb + SM_SMALL + SMALL_DUMMY, v); }
__device__ __forceinline__ void fence_async_s() { asm volatile("fence.proxy.async.shared::cta;" ::: "memory"); }
__device__ __forceinline__ void fence_async_g() { asm volatile("fence.proxy.async.global;" ::: "memory"); }
__device__ __forceinline__ void bulk_done() { asm volatile("cp.async.bulk.commit_group;\n\tcp.async.bulk.wait_group 0;" ::: "memory"); }
__device__ __forceinline__ void flag_wait(int id, uint32_t target) {
  const uint32_t* p = flagp(id);
#pragma unroll 1
  for (int i = 0; i < (1 << 20); i++) {
    uint32_t v;
    asm volatile("ld.acquire.gpu.global.u32 %0, [%1];" : "=r"(v) : "l"(p) : "memory");
    if ((int)(v - target) >= 0) return;
  }
  __trap();
}
__device__ __forceinline__ int ibase(int pb) {
  int w = pb >> 5, g = (pb >> 2) & 7, q = pb & 3;
  return 128 * (g >> 2) + 8 * ((2 * q - ((g >> 1) & 1)) & 7) + 2 * w + (g & 1);
}
__device__ __forceinline__ uint32_t hmul(uint32_t a, uint32_t b) { uint32_t d; asm("mul.rn.bf16x2 %0, %1, %2;" : "=r"(d) : "r"(a), "r"(b)); return d; }
__device__ __forceinline__ uint32_t hadd(uint32_t a, uint32_t b) { uint32_t d; asm("add.rn.bf16x2 %0, %1, %2;" : "=r"(d) : "r"(a), "r"(b)); return d; }
__device__ __forceinline__ uint32_t hsub(uint32_t a, uint32_t b) { uint32_t d; asm("sub.rn.bf16x2 %0, %1, %2;" : "=r"(d) : "r"(a), "r"(b)); return d; }
__device__ __forceinline__ uint32_t pack2(float lo, float hi) { uint32_t d; asm("cvt.rn.bf16x2.f32 %0, %1, %2;" : "=r"(d) : "f"(hi), "f"(lo)); return d; }
__device__ __forceinline__ float blo(uint32_t v) { return __uint_as_float(v << 16); }
__device__ __forceinline__ float bhi(uint32_t v) { return __uint_as_float(v & 0xffff0000u); }
__device__ __forceinline__ float rbf(float v) { return blo(pack2(v, 0.f)); }
template <int N> __device__ __forceinline__ void bfly(float* v, int mask, bool up) {
#pragma unroll
  for (int i = 0; i < N / 2; i++) {
    float send = up ? v[i] : v[i + N / 2], keep = up ? v[i + N / 2] : v[i];
    v[i] = keep + __shfl_xor_sync(0xffffffffu, send, mask);
  }
}
__device__ __forceinline__ int mod_col(int idx) {
  if (idx < 40) { int v = (idx >> 1) & 3; return (v == 3 ? 4 : v) * 640 + 128 * (idx >> 3) + 64 * (idx & 1); }
  int l = idx - 40;
  return l < 10 ? 3 * 640 + 64 * l : 5 * 640 + 64 * (l - 10);
}

__device__ __forceinline__ void kv_job(const Params& P, uint32_t sb, int b, int r, int tid) {
  const int lane = tid & 31, w = tid >> 5;
  uint4 sk = __ldg((const uint4*)(P.shift_k + (128 * r + 64 * (b & 1) + 2 * lane) * 4));
  uint32_t s0 = __byte_perm(sk.x, sk.z, 0x5410), s1 = __byte_perm(sk.x, sk.z, 0x7632), s2 = __byte_perm(sk.y, sk.w, 0x5410), s3 = __byte_perm(sk.y, sk.w, 0x7632);
  const uint32_t ring = sb + SM_RING;
  mbar_wait(sb + 8 * (B_B + r), 0);
  STAMPIF(tid == 0, 56 + r);
  uint32_t ka = ring + r * JOB_SZ + w * 1024 + lane * 4;
  uint32_t kk[11], o[8];
#pragma unroll
  for (int i = 0; i < 11; i++) kk[i] = lds32(ka + 128 * i);
#pragma unroll
  for (int i = 0; i < 8; i++) {
    uint32_t v = lds32(ka + 4480 + 128 * i);
    uint32_t a = hadd(hadd(hadd(hmul(kk[i], s3), hmul(kk[i + 1], s2)), hmul(kk[i + 2], s1)), hmul(kk[i + 3], s0));
    o[i] = hmul(a, v);
  }
  const uint32_t sg = ring + R_STG + r * 4096 + lane * 128 + (((3 - w) ^ (lane & 3)) << 4) + ((lane & 4) << 4);
  const uint32_t p0 = (lane & 4) ? 0x7632 : 0x5410, p1 = p0 ^ 0x2222;
  sts128(sg, make_uint4(__byte_perm(o[7], o[6], p0), __byte_perm(o[5], o[4], p0), __byte_perm(o[3], o[2], p0), __byte_perm(o[1], o[0], p0)));
  sts128(sg ^ 64, make_uint4(__byte_perm(o[7], o[6], p1), __byte_perm(o[5], o[4], p1), __byte_perm(o[3], o[2], p1), __byte_perm(o[1], o[0], p1)));
}
__device__ __forceinline__ void kv_signal(const Params& P, uint32_t sb, int b, int r, int lane) {
  const int d0 = 128 * r + 64 * (b & 1), i0 = 2016 - 32 * (b >> 1);
  if (lane == 0) {
    fence_async_s();
    tma_store2d(&P.mKV, sb + SM_RING + R_STG + r * 4096, i0, d0);
    bulk_done();
  }
  __syncwarp();
  const bf16* p = g_kvT + (d0 + lane) * S_ + i0;
  uint32_t v0 = rdback(p), v1 = rdback(p + 32 * S_);
  rdwait(sb, v0 ^ v1);
  __syncwarp();
  if (lane == 0) flag_add(FL_KV + 2 * r + (b & 1));
}

__device__ __forceinline__ void mod_box(const Params& P, uint32_t sb, int b, int cls, int tid) {
  const int lane = tid & 31, w = tid >> 5;
  const uint32_t* p = (const uint32_t*)(P.wmod + (80 * (b & 7) + 20 * w) * 3840 + mod_col(16 * cls + (b >> 3)) + 2 * lane);
  uint32_t v[20];
#pragma unroll
  for (int n = 0; n < 20; n++) v[n] = __ldg(p + n * 1920);
  float a0 = 0.f, a1 = 0.f;
#pragma unroll
  for (int n = 0; n < 10; n++) {
    uint32_t s = lds32(sb + SM_SMALL + SMALL_S + 40 * w + 4 * n);
    a0 += blo(s) * blo(v[2 * n]);     a1 += blo(s) * bhi(v[2 * n]);
    a0 += bhi(s) * blo(v[2 * n + 1]); a1 += bhi(s) * bhi(v[2 * n + 1]);
  }
  sts64(sb + SM_BOX + cls * 1024 + tid * 8, __float_as_uint(a0), __float_as_uint(a1));
}
__device__ __forceinline__ uint32_t box_store(uint32_t sb, int b, int cls, int lane) {
  const uint32_t a = sb + SM_BOX + cls * 1024 + lane * 8;
  uint2 v0 = lds64(a), v1 = lds64(a + 256), v2 = lds64(a + 512), v3 = lds64(a + 768);
  float* p = g_modP + (b & 7) * 3840 + mod_col(16 * cls + (b >> 3)) + 2 * lane;
  *(float2*)p = make_float2((__uint_as_float(v0.x) + __uint_as_float(v1.x)) + (__uint_as_float(v2.x) + __uint_as_float(v3.x)),
                            (__uint_as_float(v0.y) + __uint_as_float(v1.y)) + (__uint_as_float(v2.y) + __uint_as_float(v3.y)));
  return rdback(p);
}
__device__ __forceinline__ float sum8(float a) {
  a += __shfl_xor_sync(0xffffffffu, a, 1);
  a += __shfl_xor_sync(0xffffffffu, a, 2);
  a += __shfl_xor_sync(0xffffffffu, a, 4);
  return rbf(a);
}
template <int NR> __device__ __forceinline__ void mod_fin(uint32_t sb, int b, int r0, uint32_t e1, int lane) {
  if (lane < 4 * NR) flag_wait(FL_M + 8 * r0 + 2 * lane + (b >> 6), e1 * 8);
  __syncwarp();
  const int v = lane >> 3;
  const float* p = g_modP + (lane & 7) * 3840 + (v == 3 ? 4 : v) * 640 + 128 * r0 + b;
  float a[NR];
#pragma unroll
  for (int n = 0; n < NR; n++) a[n] = __ldcg(p + 128 * n);
#pragma unroll
  for (int n = 0; n < NR; n++) {
    float t = sum8(a[n]);
    if (v & 1) t += 1.f;
    if ((lane & 7) == 0) sts32(sb + SM_SMALL + SMALL_MOD + 16 * (r0 + n) + 4 * v, pack2(t, t));
  }
  __syncwarp();
  if (lane == 0) mbar_arrive(sb + 8 * (B_MF + (r0 >> 1)));
}
__device__ __forceinline__ void load_kv(const Params& P, uint32_t sb, int b, int r) {
  const uint32_t bar = sb + 8 * (B_B + r), a = sb + SM_RING + r * JOB_SZ;
  mbar_expect(bar, 4480 + 4096);
  tma2d(a, &P.mK, 128 * r + 64 * (b & 1), 32 * (b >> 1) - 3, bar);
  tma2d(a + 4480, &P.mV, 128 * r + 64 * (b & 1), 32 * (b >> 1), bar);
}
__device__ __forceinline__ void load_ssm(const Params& P, uint32_t sb, int b, int r) {
  const uint32_t bar = sb + 8 * (B_S + r);
  mbar_expect(bar, 16 * 288);
  tma3d(sb + SM_RING + (3 + (r >> 1)) * 32768 + (r & 1) * KSZ + 128, &P.mS, 0, 0, 128 * r + b, bar);
}
__device__ __forceinline__ void k1_job(uint32_t sb, int r, int tid) {
  const uint32_t a0 = sb + SM_RING + (3 + (r >> 1)) * 32768 + (r & 1) * KSZ + 128 + 16 * tid + 32 * (tid >> 4);
  mbar_wait(sb + 8 * (B_S + r), 0);
#pragma unroll
  for (int n = 0; n < 2; n++) {
    const uint32_t a = a0 + 2304 * n;
    const uint4 v = lds128(a);
    const uint32_t pv = lds32(a - ((tid & 15) ? 4 : 36));
    sts128(a + K1OFF, make_uint4(__byte_perm(pv, v.x, 0x5432), __byte_perm(v.x, v.y, 0x5432), __byte_perm(v.y, v.z, 0x5432), __byte_perm(v.z, v.w, 0x5432)));
  }
}

__global__ void __launch_bounds__(512, 1) fused_kernel(const __grid_constant__ Params P) {
  extern __shared__ __align__(1024) char smem_raw[];
  const uint32_t sb = smem_u32(smem_raw), ring = sb + SM_RING;
  const int b = blockIdx.x, m = b >> 3, s = b & 7;
  if ((threadIdx.x >> 5) == 12) {
    const int l = threadIdx.x & 31;
#pragma unroll
    for (int i = l; i < B_NUM; i += 32) mbar_init(sb + 8 * i, i >= B_Z ? 4 : i == B_AUXFREE ? 3 : (i >= B_F1 && i < B_FB) ? 2 : 1);
    asm volatile("fence.mbarrier_init.release.cluster;" ::: "memory");
    fence_async_s();
    __syncwarp();
    if (l == 0) mbar_expect(sb + 8 * B_X, 16 * 1280);
    __syncwarp();
    if (l < 16) {
      int t = 2047 - (256 * (l >> 1) + 64 * (l & 1) + ibase(b));
      int rho = 8 * ((l >> 1) & 1) + 2 * (l >> 2) + (l & 1);
      bulk_g2s(ring + R_X + rho * XPITCH, P.x + t * D_, 1280, sb + 8 * B_X);
    }
    if (l == 0) { load_kv(P, sb, b, 0); load_kv(P, sb, b, 1); }
    if (l >= 2 && l < 11) asm volatile("prefetch.tensormap [%0];" ::"l"(&P.mK + l) : "memory");
  }
  if (threadIdx.x < 40) {
    int ch = threadIdx.x >> 3, c = threadIdx.x & 7;
    uint32_t base = ring + (3 + (ch >> 1)) * 32768;
    sts128(c < 2 ? base + (ch & 1) * KSZ + 80 + c * K1OFF : base + 2 * KSZ + (ch & 1) * USZ + 4096 + (c - 2) * 16, make_uint4(0, 0, 0, 0));
    fence_async_s();
  }
  __syncthreads();
  STAMPIF(threadIdx.x == 0, 55);
  asm volatile("barrier.cluster.arrive.relaxed.aligned;" ::: "memory");
  const int wg = __shfl_sync(0xffffffffu, threadIdx.x >> 7, 0);
  const int tid = threadIdx.x & 127, lane = tid & 31;
  const int w = __shfl_sync(0xffffffffu, tid >> 5, 0);

  if (wg == 3) {
    asm volatile("setmaxnreg.dec.sync.aligned.u32 24;");
    asm volatile("barrier.cluster.wait.aligned;" ::: "memory");
    if (w == 0) {
      if (lane == 0) {
        mbar_wait(sb + 8 * B_X, 0);
        tma_prefetch2d(&P.mWm, mod_col(b >> 3), 80 * (b & 7));
        mbar_wait(sb + 8 * (B_B + 0), 0);
        load_kv(P, sb, b, 2);
        mbar_wait(sb + 8 * (B_B + 1), 0);
        load_ssm(P, sb, b, 0);
        load_ssm(P, sb, b, 1);
        load_kv(P, sb, b, 3);
        mbar_wait(sb + 8 * (B_B + 2), 0);
        load_ssm(P, sb, b, 2);
        load_kv(P, sb, b, 4);
        mbar_wait(sb + 8 * (B_B + 3), 0);
        load_ssm(P, sb, b, 3);
        load_ssm(P, sb, b, 4);
        mbar_wait(sb + 8 * (B_B + 4), 0);
        tma_prefetch2d(&P.mWm, mod_col(16 + (b >> 3)), 80 * (b & 7));
        mbar_wait(sb + 8 * B_AUXFREE, 0);
#pragma unroll 1
        for (int it = 0; it < 20; it++) {
          int st = it % 6;
          mbar_wait(sb + 8 * (B_E1 + st), (it / 6) & 1);
          uint32_t a = ring + st * 32768, fb = sb + 8 * (B_F1 + st);
          mbar_expect(fb, 24576);
          tma3d(a + 8192, &P.mG, 0, 32 * it, s * 3, fb);
          tma3d(a + 20480, &P.mU, 0, 32 * it, s * 3, fb);
          if (it == 2) {
            tma_prefetch2d(&P.mWm, mod_col(32 + (b >> 3)), 80 * (b & 7));
            if (b < 96) tma_prefetch2d(&P.mWm, mod_col(48 + (b >> 3)), 80 * (b & 7));
          }
        }
#pragma unroll 1
        for (int k = 0; k < 24; k++) {
          int sl = k < 12 ? k : k - 12;
          int g1 = (sl >> 1) + 2; if (g1 >= 6) g1 -= 6;
          if (k < 12) mbar_wait(sb + 8 * (B_E1 + g1), g1 >= 2); else mbar_wait(sb + 8 * (B_EB + sl), 0);
          uint32_t a = ring + g1 * 32768 + 8192 + (sl & 1) * 12288, fb = sb + 8 * (B_FB + sl);
          int n = k / 6, kg = 4 * (6 * ((s + 2 * n) & 7) + k - 6 * n);
          mbar_expect(fb, 12288);
#pragma unroll 1
          for (int at = 0; at < 3; at++) {
            if (k < 6) tma5d(a + at * 4096, &P.mDn, 64 * at, 0, 0, kg, s >> 1, fb);
            else tma5d(a + at * 4096, &P.mDp, 64 * at, 0, kg, 0, s >> 1, fb);
          }
        }
      }
    } else if (w == 1) {
      if (lane == 0) {
        const uint32_t e1 = __ldcg(g_epoch + b) + 1;
#pragma unroll 1
        for (int r = 0; r < 5; r++) {
          flag_wait(FL_KV + 2 * r + (b >> 6), e1 * 64);
          fence_async_g();
          uint32_t bar = sb + 8 * (B_U + r);
          mbar_expect(bar, 4096);
          bulk_g2s(ring + (3 + (r >> 1)) * 32768 + 2 * KSZ + (r & 1) * USZ, g_kvT + (128 * r + b) * S_, 4096, bar);
          STAMP(40 + r);
        }
        mbar_wait(sb + 8 * B_AUXFREE, 0);
#pragma unroll 1
        for (int it = 0; it < 20; it++) {
          int st = it % 6;
          if ((it & 3) == 0) { flag_wait(FL_R + (it >> 2), e1 * 128); fence_async_g(); STAMP(45 + (it >> 2)); }
          mbar_wait(sb + 8 * (B_E1 + st), (it / 6) & 1);
          uint32_t fb = sb + 8 * (B_F1 + st);
          mbar_expect(fb, 8192);
          tma3d(ring + st * 32768, &P.mA, 0, 32 * it, m * 2, fb);
        }
#pragma unroll 1
        for (int n = 1; n < 4; n++) {
          int src = 8 * m + ((s + 2 * n) & 7);
          flag_wait(FL_H + src, e1 * 4);
          fence_async_g();
          STAMP(50 + n);
#pragma unroll 1
          for (int k = 0; k < 6; k++) {
            int g1 = k + 2; if (g1 >= 6) g1 -= 6;
            if (n == 1) mbar_wait(sb + 8 * (B_E1 + g1), g1 >= 2); else mbar_wait(sb + 8 * (B_EA + k), n & 1);
            uint32_t fb = sb + 8 * (B_FA + k);
            mbar_expect(fb, 8192);
            bulk_g2s(ring + g1 * 32768, g_HH + (src * 6 + k) * 4096, 8192, fb);
          }
        }
      }
    } else if (w == 2) {
      const uint32_t e1 = __ldcg(g_epoch + b) + 1;
      if (lane == 0) {
        mbar_expect(sb + 8 * B_RECV, 20480);
        mbar_expect(sb + 8 * (B_RECV + 1), 20480);
      }
      mbar_wait(sb + 8 * B_MB, 0);
      rdwait(sb, box_store(sb, b, 0, lane));
      __syncwarp();
      if (lane == 0) flag_add(FL_M + (b >> 3));
      mod_fin<2>(sb, b, 0, e1, lane);
      STAMPIF(lane == 0, 36);
#pragma unroll 1
      for (int r = 0; r < 5; r++) {
        const bf16 *p0 = g_AT + (128 * r + b) * S_, *p1 = g_x1T + (128 * r + b) * S_;
        if (lane == 0) {
          mbar_wait(sb + 8 * (B_EW + r), 0);
          fence_async_s();
          bulk_s2g((void*)p0, sb + SM_EXT + (r & 1) * 4096, 4096);
          bulk_s2g((void*)p1, sb + SM_Z + r * 4096, 4096);
          bulk_done();
          if (r < 3) mbar_arrive(sb + 8 * (B_EWF + r));
        }
        __syncwarp();
        uint32_t v0 = rdback(p0 + 64 * lane), v1 = rdback(p1 + 64 * lane);
        rdwait(sb, v0 ^ v1);
        __syncwarp();
        if (lane == 0) flag_add(FL_R + r);
      }
      if (lane == 0) {
        flag_wait(FL_R + 4, e1 * 128);
        flag_wait(FL_F, e1 * 128);
        fence_async_g();
        mbar_expect(sb + 8 * B_X1, 20480 + 160);
        tma3d(sb + SM_Z, &P.mX1, 0, 80 * s, m * 2, sb + 8 * B_X1);
        bulk_g2s(sb + SM_SMALL + SMALL_GB, g_gb + 80 * s, 160, sb + 8 * B_X1);
        flag_wait(FL_S + m, e1 * 8);
        flag_wait(FL_C + s, e1 * 48);
        fence_async_g();
        STAMP(54);
        mbar_expect(sb + 8 * B_EXT, 6144 + 2048);
        bulk_g2s(sb + SM_EXT, g_cimg + s * 3072, 6144, sb + 8 * B_EXT);
        bulk_g2s(sb + SM_STAT, g_stat + 128 * m, 2048, sb + 8 * B_EXT);
        mbar_wait(sb + 8 * (B_EB + 3), 0);
        mbar_wait(sb + 8 * (B_EB + 3), 1);
        mbar_arrive_remote(mapa(sb + 8 * B_PEER, (b & 1) ^ 1));
      }
    } else {
      const uint32_t e1 = __ldcg(g_epoch + b) + 1;
#pragma unroll 1
      for (int r = 2; r < 5; r++) {
        mbar_wait(sb + 8 * (B_KVS + r - 2), 0);
        kv_signal(P, sb, b, r, lane);
        STAMPIF(lane == 0, 20 + r);
      }
      if (lane == 0) mbar_arrive(sb + 8 * B_AUXFREE);
      mbar_wait(sb + 8 * (B_MB + 1), 0);
      rdwait(sb, box_store(sb, b, 1, lane));
      __syncwarp();
      if (lane == 0) flag_add(FL_M + 16 + (b >> 3));
      mod_fin<2>(sb, b, 2, e1, lane);
      STAMPIF(lane == 0, 37);
      mbar_wait(sb + 8 * (B_MB + 2), 0);
      uint32_t v = box_store(sb, b, 2, lane);
      if (b < 96) v ^= box_store(sb, b, 3, lane);
      rdwait(sb, v);
      __syncwarp();
      if (lane == 0 || (lane == 1 && b < 96)) flag_add(FL_M + 32 + 16 * lane + (b >> 3));
      mod_fin<1>(sb, b, 4, e1, lane);
      STAMPIF(lane == 0, 38);
      if (lane < 10) flag_wait(FL_M + 40 + 2 * lane + (b >> 6), e1 * 8);
      __syncwarp();
      const int r = lane >> 3;
      const float* p = g_modP + (lane & 7) * 3840 + 3 * 640 + b;
      float a0 = __ldcg(p + 128 * r), a1 = __ldcg(p + 1280 + 128 * r), a2 = __ldcg(p + 512 + (r & 1) * 1280);
      a0 = sum8(a0); a1 = sum8(a1); a2 = sum8(a2);
      float a3 = __shfl_sync(0xffffffffu, a2, 8);
      int rr = r;
      if (lane == 1) { a0 = a2; a1 = a3; rr = 4; }
      mbar_wait(sb + 8 * B_MF, 0);
      v = 0;
      if ((lane & 7) == 0 || lane == 1) {
        uint32_t* pc = g_cbsb + 128 * rr + b;
        bf16* pg = g_gb + 128 * rr + b;
        *pc = __byte_perm(lds32(sb + SM_SMALL + SMALL_MOD + 16 * rr + 12), __float_as_uint(a0), 0x7610);
        *(uint16_t*)pg = (uint16_t)(__float_as_uint(a1) >> 16);
        v = rdback(pc) ^ rdback(pg - (b & 1));
      }
      rdwait(sb, v);
      __syncwarp();
      if (lane == 0) flag_add(FL_F);
      STAMPIF(lane == 0, 39);
    }
  } else if (wg == 2) {
    asm volatile("setmaxnreg.dec.sync.aligned.u32 40;");
    const uint32_t e1 = __ldcg(g_epoch + b) + 1;
    if (tid < 80) {
      float c = __bfloat162float(P.c[80 * (b & 7) + tid]);
      sts16(sb + SM_SMALL + SMALL_S + 2 * tid, pack2(__fdividef(c, 1.f + __expf(-c)), 0.f));
    }
    asm volatile("barrier.cluster.wait.aligned;" ::: "memory");
    bar_sync(5, 128);
    mbar_wait(sb + 8 * (B_B + 0), 0);
    mod_box(P, sb, b, 0, tid);
    __syncwarp();
    if (lane == 0) mbar_arrive(sb + 8 * B_MB);
    STAMPIF(tid == 0, 27);
#pragma unroll 1
    for (int r = 2; r < 5; r++) {
      kv_job(P, sb, b, r, tid);
      __syncwarp();
      if (lane == 0) mbar_arrive(sb + 8 * (B_KVS + r - 2));
      if (r > 2) {
        k1_job(sb, r - 1, tid);
        __syncwarp();
        if (lane == 0) mbar_arrive(sb + 8 * (B_K + r - 3));
      }
    }
    if (lane == 0) flag_wait(FL_X, e1 * 256);
    __syncwarp();
    STAMPIF(tid == 0, 28);
#pragma unroll 1
    for (int r = 0; r < 5; r++) {
      uint4 xh[4];
#pragma unroll
      for (int n = 0; n < 4; n++) xh[n] = __ldcg((const uint4*)(g_XH + (128 * r + b) * (2 * S_)) + tid + 128 * n);
      mbar_wait(sb + 8 * (B_MF + (r >> 1)), 0);
      const uint4 md = lds128(sb + SM_SMALL + SMALL_MOD + 16 * r);
      if (r >= 2) mbar_wait(sb + 8 * (B_EWF + r - 2), 0);
      mbar_wait(sb + 8 * (B_Z + r), 0);
      const uint32_t za = sb + SM_Z + r * 4096 + 8 * tid, aa = sb + SM_EXT + (r & 1) * 4096 + 8 * tid;
#pragma unroll
      for (int n = 0; n < 4; n++) {
        uint2 z = lds64(za + 1024 * n);
        uint32_t x0 = hadd(xh[n].x, hmul(md.z, hmul(hadd(hmul(xh[n].z, md.y), md.x), z.x)));
        uint32_t x1 = hadd(xh[n].y, hmul(md.z, hmul(hadd(hmul(xh[n].w, md.y), md.x), z.y)));
        sts64(aa + 1024 * n, hmul(x0, md.w), hmul(x1, md.w));
        sts64(za + 1024 * n, x0, x1);
      }
      __syncwarp();
      if (lane == 0) mbar_arrive(sb + 8 * (B_EW + r));
      STAMPIF(tid == 0, 29 + r);
      if (r == 0) {
        k1_job(sb, 4, tid);
        __syncwarp();
        if (lane == 0) mbar_arrive(sb + 8 * (B_K + 2));
      }
      if (r == 1) {
#pragma unroll 1
        for (int cls = 1; cls < 4; cls++) {
          if (cls < 3 || b < 96) mod_box(P, sb, b, cls, tid);
          __syncwarp();
          if (lane == 0 && cls != 2) mbar_arrive(sb + 8 * (B_MB + ((cls + 1) >> 1)));
        }
      }
    }
    if (lane == 0) flag_wait(FL_F, e1 * 128);
    __syncwarp();
    STAMPIF(tid == 0, 34);
    float a[8];
    if (w < 3) {
      const int lc0 = 24 * (m & 7) + 8 * w;
      const bf16* wp = (m < 8 ? P.wg : P.wu) + (lane >> 1) * F_ + 192 * s + lc0 + 4 * (lane & 1);
      const uint32_t* cp = g_cbsb + (lane >> 1);
#pragma unroll
      for (int j = 0; j < 8; j++) a[j] = 0.f;
#pragma unroll 1
      for (int n0 = 0; n0 < 40; n0 += 5) {
        uint2 v[5]; uint32_t cf[5];
#pragma unroll
        for (int n = 0; n < 5; n++) { v[n] = __ldg((const uint2*)(wp + n * 16 * F_)); cf[n] = __ldcg(cp + 16 * n); }
        wp += 80 * F_; cp += 80;
#pragma unroll
        for (int n = 0; n < 5; n++) {
          const float k1 = blo(cf[n]), k2 = bhi(cf[n]), e0 = blo(v[n].x), e1_ = bhi(v[n].x), e2 = blo(v[n].y), e3 = bhi(v[n].y);
          a[0] += k1 * e0; a[1] += k1 * e1_; a[2] += k1 * e2; a[3] += k1 * e3;
          a[4] += k2 * e0; a[5] += k2 * e1_; a[6] += k2 * e2; a[7] += k2 * e3;
        }
      }
      bfly<8>(a, 16, lane & 16); bfly<4>(a, 8, lane & 8); bfly<2>(a, 4, lane & 4);
      const float t = a[0] + __shfl_xor_sync(0xffffffffu, a[0], 2), hi = rbf(t);
      const int lc = lc0 + 4 * (lane & 1) + ((lane >> 2) & 3), cc = lc & 63, r0 = 2 * (lane >> 4) + 2 * (lane & 2);
      uint16_t* dst = (uint16_t*)g_cimg + s * 3072 + ((m >> 3) * 3 + (lc >> 6)) * 512 + (cc & 7);
      uint16_t *d0 = dst + r0 * 64 + (((cc >> 3) ^ r0) << 3), *d1 = dst + (r0 + 1) * 64 + (((cc >> 3) ^ (r0 + 1)) << 3);
      *d0 = (uint16_t)(__float_as_uint(hi) >> 16);
      *d1 = (uint16_t)pack2(t - hi, 0.f);
      rdwait(sb, rdback(d0 - (cc & 1)) ^ rdback(d1 - (cc & 1)));
      __syncwarp();
      if (lane == 0) flag_add(FL_C + s);
      STAMPIF(tid == 0, 35);
    }
    {
      if (lane == 0) flag_wait(FL_R + 4, e1 * 128);
      __syncwarp();
      const bf16* src = g_x1T + 16 * b + 4 * (lane & 3);
      const uint2 pq = __ldcg((const uint2*)src);
      const float pv0 = blo(pq.x), pv1 = bhi(pq.x), pv2 = blo(pq.y), pv3 = bhi(pq.y);
#pragma unroll
      for (int j = 0; j < 8; j++) a[j] = 0.f;
      src += ((lane >> 2) + 8 * w) * S_;
#pragma unroll 1
      for (int n0 = 0; n0 < 20; n0 += 5) {
        uint2 v[5];
#pragma unroll
        for (int n = 0; n < 5; n++) v[n] = __ldcg((const uint2*)(src + n * 32 * S_));
        src += 160 * S_;
#pragma unroll
        for (int n = 0; n < 5; n++) {
          const float e0 = blo(v[n].x) - pv0, e1_ = bhi(v[n].x) - pv1, e2 = blo(v[n].y) - pv2, e3 = bhi(v[n].y) - pv3;
          a[0] += e0; a[1] += e1_; a[2] += e2; a[3] += e3;
          a[4] += e0 * e0; a[5] += e1_ * e1_; a[6] += e2 * e2; a[7] += e3 * e3;
        }
      }
      bfly<8>(a, 16, lane & 16); bfly<4>(a, 8, lane & 8); bfly<2>(a, 4, lane & 4);
      sts32(sb + SM_SMALL + SMALL_RED + w * 128 + (lane >> 4) * 64 + (4 * (lane & 3) + ((lane >> 2) & 3)) * 4, __float_as_uint(a[0]));
      bar_sync(5, 128);
      if (w == 3) {
        uint32_t v = 0;
        if (lane < 16) {
          float s1 = 0.f, s2 = 0.f;
#pragma unroll
          for (int j = 0; j < 4; j++) {
            s1 += __uint_as_float(lds32(sb + SM_SMALL + SMALL_RED + j * 128 + lane * 4));
            s2 += __uint_as_float(lds32(sb + SM_SMALL + SMALL_RED + j * 128 + 64 + lane * 4));
          }
          float p0 = __bfloat162float(__ldcg(g_x1T + 16 * b + lane));
          float mu = s1 * (1.f / D_), var = fmaxf(s2 * (1.f / D_) - mu * mu, 0.f);
          float sd = rbf(__fsqrt_rn(rbf(rbf(var) + 1e-5f)));
          g_stat[16 * b + lane] = make_uint4(pack2(-0.5f * (p0 + mu), -0.5f * (p0 + mu)), pack2(0.5f * sd, 0.5f * sd), 0, 0);
          v = rdback(g_stat + 16 * b + lane);
        }
        rdwait(sb, v);
        __syncwarp();
        if (lane == 0) flag_add(FL_S + m);
        STAMPIF(lane == 0, 21);
      }
    }
    {
      mbar_wait(sb + 8 * (B_HH + (w >> 1)), 0);
      const bf16* p = g_HH + (b * 6 + 3 * (w & 1)) * 4096 + (w >> 1) * 2048 + lane * 64;
      uint32_t v0 = rdback(p), v1 = rdback(p + 4096), v2 = rdback(p + 8192);
      rdwait(sb, v0 ^ v1 ^ v2);
      __syncwarp();
      if (lane == 0) flag_add(FL_H + b);
      STAMPIF(tid == 0, 50);
    }
  } else {
    asm volatile("setmaxnreg.inc.sync.aligned.u32 224;");
    const int g = lane >> 2, q = lane & 3;
    if (wg == 1) bar_arrive(1, 256);
    if (tid < 3) mbar_arrive(sb + 8 * (B_E1 + tid));
    if (tid == 3 && wg == 1) mbar_arrive(sb + 8 * (B_E1 + 5));
    uint32_t dv = *(const uint16_t*)(P.ssm_D + 128 * wg + b);
    asm volatile("barrier.cluster.wait.aligned;" ::: "memory");
    {
      const int t2 = threadIdx.x, w2 = 4 * wg + w;
      mbar_wait(sb + 8 * B_X, 0);
      STAMPIF(t2 == 0, 25);
      const uint32_t xr = ring + R_X + (t2 >> 4) * XPITCH;
      float pv = blo(lds32(xr)), s1 = 0.f, s2 = 0.f;
#pragma unroll
      for (int n = 0; n < 5; n++) {
        uint4 v = lds128(xr + 16 * ((t2 & 15) + 16 * n));
        uint32_t u[4] = {v.x, v.y, v.z, v.w};
#pragma unroll
        for (int j = 0; j < 4; j++) {
          float a = blo(u[j]) - pv, c = bhi(u[j]) - pv;
          s1 += a + c; s2 += a * a; s2 += c * c;
        }
      }
      uint32_t r[5][4];
      const uint32_t la = ring + R_X + (lane & 15) * XPITCH + (lane >> 4) * 16 + w2 * 32;
#pragma unroll
      for (int n = 0; n < 5; n++) ldsm4t(r[n], la + n * 256);
#pragma unroll
      for (int o = 1; o < 16; o <<= 1) { s1 += __shfl_xor_sync(0xffffffffu, s1, o); s2 += __shfl_xor_sync(0xffffffffu, s2, o); }
      if ((t2 & 15) == 0) {
        float mu = s1 * (1.f / D_), var = fmaxf(s2 * (1.f / D_) - mu * mu, 0.f);
        float sd = rbf(__fsqrt_rn(rbf(rbf(var) + 1e-5f)));
        sts16(sb + SM_SMALL + SMALL_XM + 2 * (t2 >> 4), pack2(pv + mu, 0.f));
        sts32(sb + SM_SMALL + SMALL_XM + 32 + 4 * (t2 >> 4), __float_as_uint(__frcp_rn(sd)));
      }
      bar_sync(6, 256);
      const uint32_t m0 = lds32(sb + SM_SMALL + SMALL_XM + 4 * q), m1 = lds32(sb + SM_SMALL + SMALL_XM + 16 + 4 * q);
      const uint2 r0 = lds64(sb + SM_SMALL + SMALL_XM + 32 + 8 * q), r1 = lds64(sb + SM_SMALL + SMALL_XM + 64 + 8 * q);
      bf16* dst = g_XH + (16 * w2 + g) * (2 * S_) + b * 32 + q * 8;
#pragma unroll
      for (int n = 0; n < 5; n++) {
#pragma unroll
        for (int j = 0; j < 2; j++) {
          uint32_t a = hsub(r[n][2 * j], m0), c = hsub(r[n][2 * j + 1], m1);
          *(uint4*)(dst + (128 * n + 8 * j) * (2 * S_)) =
              make_uint4(r[n][2 * j], r[n][2 * j + 1], pack2(blo(a) * __uint_as_float(r0.x), bhi(a) * __uint_as_float(r0.y)),
                         pack2(blo(c) * __uint_as_float(r1.x), bhi(c) * __uint_as_float(r1.y)));
        }
      }
      __syncwarp();
      const bf16* p = g_XH + (16 * w2 + (lane & 15) + 128 * (lane >> 4)) * (2 * S_) + b * 32;
      uint32_t v0 = rdback(p), v1 = rdback(p + 256 * (2 * S_)), v2 = rdback(p + (lane < 16 ? 512 : 0) * (2 * S_));
      STAMPIF(t2 == 0, 26);
      kv_job(P, sb, b, wg, tid);
      rdwait(sb, v0 ^ v1 ^ v2);
      bar_sync(3 + wg, 128);
      if (w == 0) {
        kv_signal(P, sb, b, wg, lane);
        if (lane == 0) mbar_arrive(sb + 8 * B_AUXFREE);
      }
      if (tid == 32) flag_add(FL_X);
      STAMPIF(tid == 0, 1 + wg);
      k1_job(sb, wg, tid);
      bar_sync(3 + wg, 128);
    }
    {
      const int b0 = (g >> 1) & 1, b1 = g >> 2, u = q + 4 * b0 - w;
      const uint32_t fo = 128 + (g & 1) * K1OFF + 288 * b1 + 4 * u, fo0 = fo - (u < 0 ? 32 : 0);
      const uint32_t dsel = (b1 == 0 && u == 0) ? ((g & 1) ? 0x1044 : 0x4410) : 0x4444;
      const bool wrap = b0 && q == 0;
      const int src1 = b0 ? ((lane & 20) | ((q - 1) & 3)) : (lane | 8);
#pragma unroll 1
      for (int ch = wg; ch < 5; ch += 2) {
        const uint32_t base = ring + (3 + (ch >> 1)) * 32768;
        if (ch >= 2) { mbar_wait(sb + 8 * (B_K + ch - 2), 0); mbar_wait(sb + 8 * (B_S + ch), 0); }
        const uint32_t fa = base + wg * KSZ + fo, fa0 = base + wg * KSZ + fo0;
        uint32_t af[16][4];
#pragma unroll
        for (int j = 0; j < 16; j++) {
          const int o = 64 * (j & 1) + 576 * (j >> 1);
          af[j][0] = lds32(((j & 1) ? fa : fa0) + o); af[j][1] = lds32(fa + o + 128); af[j][2] = lds32(fa + o + 32); af[j][3] = lds32(fa + o + 160);
        }
        af[0][0] = hadd(af[0][0], __byte_perm(dv, 0, dsel));
        if (ch < 3) dv = *(const uint16_t*)(P.ssm_D + 128 * (ch + 2) + b);
        mbar_wait(sb + 8 * (B_U + ch), 0);
        float acc[128];
        const uint64_t db = mkdesc(base + 2 * KSZ + wg * USZ, 32, 128, 0);
        bar_sync(1 + wg, 256);
        STAMPIF(tid == 0, 3 + ch);
        wg_fence();
        wgmma_rs_n64<0>(acc + 96, af[0], db + 192, 0);
        wgmma_rs_n192<0>(acc, af[0], db, 0);
        wgmma_rs_n64<0>(acc + 96, af[1], db + 196, 1);
        wgmma_rs_n192<0>(acc, af[1], db + 4, 1);
        wgmma_rs_n32<0>(acc + 96, af[2], db + 224, 1);
        wgmma_rs_n192<0>(acc, af[2], db + 32, 1);
        wgmma_rs_n32<0>(acc + 96, af[3], db + 228, 1);
        wgmma_rs_n192<0>(acc, af[3], db + 36, 1);
        wgmma_rs_n192<0>(acc, af[4], db + 64, 1);
        wgmma_rs_n192<0>(acc, af[5], db + 68, 1);
        wgmma_rs_n160<0>(acc, af[6], db + 96, 1);
        wgmma_rs_n160<0>(acc, af[7], db + 100, 1);
        wgmma_rs_n128<0>(acc, af[8], db + 128, 1);
        wgmma_rs_n128<0>(acc, af[9], db + 132, 1);
        wgmma_rs_n96<0>(acc, af[10], db + 160, 1);
        wgmma_rs_n96<0>(acc, af[11], db + 164, 1);
        bar_arrive(2 - wg, 256);
        wgmma_rs_n64<0>(acc, af[12], db + 192, 1);
        wgmma_rs_n64<0>(acc, af[13], db + 196, 1);
        wgmma_rs_n32<0>(acc, af[14], db + 224, 1);
        wgmma_rs_n32<0>(acc, af[15], db + 228, 1);
        wg_commit();
        wg_wait<0>();
#pragma unroll
        for (int i = 0; i < 128; i++) asm volatile("" : "+f"(acc[i])::"memory");
        bar_sync(3 + wg, 128);
        if (tid == 0) mbar_arrive(sb + 8 * (B_E1 + 3 + (ch >> 1)));
        float S0[33], T[34];
#pragma unroll
        for (int i = 0; i < 31; i++) S0[i] = acc[4 * i] + acc[4 * i + 6];
        S0[31] = acc[124]; S0[32] = 0.f;
#pragma unroll
        for (int i = 0; i < 32; i++) {
          float s1 = i < 31 ? acc[4 * i + 1] + acc[4 * i + 7] : acc[125];
          T[i] = (wrap ? S0[i + 1] : S0[i]) + __shfl_sync(0xffffffffu, s1, src1);
        }
        T[32] = 0.f; T[33] = 0.f;
        uint32_t zz[8];
#pragma unroll
        for (int mu = 0; mu < 8; mu++) {
          float y0 = (b1 ? T[4 * mu + 4] : T[4 * mu]) + __shfl_xor_sync(0xffffffffu, T[4 * mu + 2], 16);
          float y1 = (b1 ? T[4 * mu + 5] : T[4 * mu + 1]) + __shfl_xor_sync(0xffffffffu, T[4 * mu + 3], 16);
          zz[mu] = pack2(y0, y1);
        }
        sts128(sb + SM_Z + ch * 4096 + tid * 32, make_uint4(zz[0], zz[1], zz[2], zz[3]));
        sts128(sb + SM_Z + ch * 4096 + tid * 32 + 16, make_uint4(zz[4], zz[5], zz[6], zz[7]));
        __syncwarp();
        if (lane == 0) mbar_arrive(sb + 8 * (B_Z + ch));
        STAMPIF(tid == 0, 8 + ch);
      }
      if (wg == 1) bar_sync(2, 256);
    }
    uint32_t hh[48];
    {
      float ga[96], ua[96];
      const uint64_t da0 = mkdesc(ring + wg * 4096, 4096, 1024, 1), db0 = mkdesc(ring + 8192, 4096, 1024, 1);
      int st = 0, ph = 0;
#pragma unroll 1
      for (int it = 0; it < 20; it++) {
        mbar_wait(sb + 8 * (B_F1 + st), ph);
        STAMPIF(tid == 0 && it == 0, 13 + wg);
        const uint64_t da = da0 + st * 2048, db = db0 + st * 2048;
        wg_fence();
        wgmma_ss_n192<1, 1>(ga, da, db, it != 0);
        wgmma_ss_n192<1, 1>(ua, da, db + 768, it != 0);
        wgmma_ss_n192<1, 1>(ga, da + 128, db + 128, 1);
        wgmma_ss_n192<1, 1>(ua, da + 128, db + 128 + 768, 1);
        wg_commit();
        wg_wait<1>();
        if (it > 0 && tid == 0) mbar_arrive(sb + 8 * (B_E1 + (st == 0 ? 5 : st - 1)));
        if (++st == 6) { st = 0; ph ^= 1; }
      }
      mbar_wait(sb + 8 * B_EXT, 0);
      const uint64_t de = mkdesc(sb + SM_EXT, 1024, 0, 1), ds = mkdesc(sb + SM_STAT + wg * 1024, 0, 128, 0);
      wg_fence();
      wgmma_ss_n192<0, 1>(ga, ds, de, 1);
      wgmma_ss_n192<0, 1>(ua, ds, de + 192, 1);
      wg_commit();
      wg_wait<1>();
      if (tid == 0) mbar_arrive(sb + 8 * (B_E1 + 1));
      wg_wait<0>();
#pragma unroll
      for (int i = 0; i < 96; i++) asm volatile("" : "+f"(ga[i]), "+f"(ua[i])::"memory");
      STAMPIF(tid == 0, 15 + wg);
#pragma unroll
      for (int i = 0; i < 48; i++) hh[i] = pack2(ga[2 * i] * ua[2 * i], ga[2 * i + 1] * ua[2 * i + 1]);
    }
    float acc[80];
    {
      bf16* dst = g_HH + b * 6 * 4096 + (64 * wg + 16 * w + g) * 32 + ((q ^ ((g >> 1) & 3)) << 3);
#pragma unroll
      for (int k = 0; k < 6; k++) {
        *(uint4*)(dst + k * 4096) = make_uint4(hh[8 * k], hh[8 * k + 2], hh[8 * k + 4], hh[8 * k + 6]);
        *(uint4*)(dst + k * 4096 + 256) = make_uint4(hh[8 * k + 1], hh[8 * k + 3], hh[8 * k + 5], hh[8 * k + 7]);
      }
      __syncwarp();
      if (lane == 0) mbar_arrive(sb + 8 * (B_HH + wg));
      const uint64_t db0 = mkdesc(ring + 8192, 4096, 1024, 1), da0 = mkdesc(ring + wg * 4096, 16, 512, 2);
#pragma unroll
      for (int k = 0; k < 6; k++) {
        mbar_wait(sb + 8 * (B_FB + k), 0);
        const uint64_t db = db0 + ((k >> 1) + 2) * 2048 + (k & 1) * 768;
        wg_fence();
        wgmma_rs_n160<1>(acc, hh + 8 * k, db, k != 0);
        wgmma_rs_n160<1>(acc, hh + 8 * k + 4, db + 128, 1);
        wg_commit();
        wg_wait<1>();
        if (k > 0 && tid == 0) mbar_arrive(sb + 8 * (B_EB + k - 1));
      }
      STAMPIF(tid == 0, 17);
      int ka = 0, pa = 0;
#pragma unroll 1
      for (int k = 6; k < 24; k++) {
        const int sl = k < 12 ? k : k - 12;
        int gb_ = (sl >> 1) + 2; if (gb_ >= 6) gb_ -= 6;
        int ga_ = ka + 2; if (ga_ >= 6) ga_ -= 6;
        mbar_wait(sb + 8 * (B_FB + sl), k >= 12);
        mbar_wait(sb + 8 * (B_FA + ka), pa);
        const uint64_t db = db0 + gb_ * 2048 + (sl & 1) * 768, da = da0 + ga_ * 2048;
        wg_fence();
        wgmma_ss_n160<0, 1>(acc, da, db, 1);
        wgmma_ss_n160<0, 1>(acc, da + 2, db + 128, 1);
        wg_commit();
        wg_wait<1>();
        if (tid == 0) {
          mbar_arrive(sb + 8 * (B_EB + (sl == 0 ? 11 : sl - 1)));
          if (k > 6) mbar_arrive(sb + 8 * (B_EA + (ka == 0 ? 5 : ka - 1)));
        }
        if (++ka == 6) { ka = 0; pa ^= 1; }
      }
    }
    uint32_t xr[20], gbv[10];
    mbar_wait(sb + 8 * B_X1, 0);
    {
      const uint32_t la = sb + SM_Z + wg * 10240 + (8 * (lane >> 4) + (lane & 7)) * 128 + (((2 * w + ((lane >> 3) & 1)) ^ (lane & 7)) << 4);
#pragma unroll
      for (int i = 0; i < 5; i++) ldsm4t(xr + 4 * i, la + i * 2048);
#pragma unroll
      for (int i = 0; i < 10; i++) gbv[i] = lds32(sb + SM_SMALL + SMALL_GB + 16 * i + 4 * q);
    }
    float rs0 = 2.f * blo(lds32(sb + SM_STAT + (64 * wg + 16 * w + g) * 16 + 4)), rs1 = 2.f * blo(lds32(sb + SM_STAT + (64 * wg + 16 * w + g) * 16 + 132));
    rs0 = __frcp_rn(rs0 * rs0); rs1 = __frcp_rn(rs1 * rs1);
    mbar_wait(sb + 8 * B_PEER, 0);
    wg_wait<0>();
#pragma unroll
    for (int i = 0; i < 80; i++) asm volatile("" : "+f"(acc[i])::"memory");
    STAMPIF(tid == 0, 18);
    const uint32_t rbuf = ring + (2 + wg) * 32768 + 8192 + w * 5120;
    {
      const uint32_t rd = mapa(rbuf + lane * 16, (b & 1) ^ 1), rb = mapa(sb + 8 * (B_RECV + wg), (b & 1) ^ 1);
      if (b & 1) {
#pragma unroll
        for (int i = 0; i < 10; i++) st_async4(rd + i * 512, acc[4 * i], acc[4 * i + 1], acc[4 * i + 2], acc[4 * i + 3], rb);
#pragma unroll
        for (int i = 0; i < 40; i++) acc[i] = acc[40 + i];
      } else {
#pragma unroll
        for (int i = 0; i < 10; i++) st_async4(rd + i * 512, acc[40 + 4 * i], acc[41 + 4 * i], acc[42 + 4 * i], acc[43 + 4 * i], rb);
      }
    }
    mbar_wait(sb + 8 * (B_RECV + wg), 0);
    uint32_t ov[20];
#pragma unroll
    for (int i = 0; i < 10; i++) {
      uint4 v = lds128(rbuf + i * 512 + lane * 16);
      uint32_t o0 = pack2((acc[4 * i] + __uint_as_float(v.x)) * rs0, (acc[4 * i + 1] + __uint_as_float(v.y)) * rs0);
      uint32_t o1 = pack2((acc[4 * i + 2] + __uint_as_float(v.z)) * rs1, (acc[4 * i + 3] + __uint_as_float(v.w)) * rs1);
      ov[2 * i] = hadd(xr[2 * i], hmul(gbv[i], o0));
      ov[2 * i + 1] = hadd(xr[2 * i + 1], hmul(gbv[i], o1));
    }
    __syncwarp();
#pragma unroll
    for (int i = 0; i < 5; i++) stsm4(rbuf + (lane & 15) * 176 + (lane >> 4) * 16 + i * 32, ov + 4 * i);
    fence_async_s();
    __syncwarp();
    if (lane < 16) {
      int t = 2047 - (256 * (lane >> 1) + 64 * (lane & 1) + ibase(8 * m + 4 * wg + w));
      bulk_s2g(P.out + t * D_ + 80 * s, rbuf + lane * 176, 160);
      asm volatile("cp.async.bulk.commit_group;" ::: "memory");
      asm volatile("cp.async.bulk.wait_group.read 0;" ::: "memory");
    }
    if (threadIdx.x == 0) g_epoch[b] = __ldcg(g_epoch + b) + 1;
  }
}

typedef CUresult (*EncFn)(CUtensorMap*, CUtensorMapDataType, cuuint32_t, void*, const cuuint64_t*, const cuuint64_t*, const cuuint32_t*, const cuuint32_t*,
                          CUtensorMapInterleave, CUtensorMapSwizzle, CUtensorMapL2promotion, CUtensorMapFloatOOBfill);
static void mkmap(EncFn enc, CUtensorMap* m, const void* p, int rank, const cuuint64_t* dims, const cuuint64_t* strides, const cuuint32_t* box, CUtensorMapSwizzle sw) {
  cuuint32_t es[5] = {1, 1, 1, 1, 1};
  CUresult r = enc(m, CU_TENSOR_MAP_DATA_TYPE_BFLOAT16, rank, (void*)p, dims, strides, box, es, CU_TENSOR_MAP_INTERLEAVE_NONE, sw,
                   CU_TENSOR_MAP_L2_PROMOTION_L2_128B, CU_TENSOR_MAP_FLOAT_OOB_FILL_NONE);
  if (r != CUDA_SUCCESS) fprintf(stderr, "tensor map encode failed: %d\n", (int)r);
}

extern "C" void kernel_launch(void* const* d_in, const int* in_sizes, int n_in, void* d_out, int out_size) {
  void* fn = nullptr;
  cudaDriverEntryPointQueryResult qr;
  cudaGetDriverEntryPoint("cuTensorMapEncodeTiled", &fn, cudaEnableDefault, &qr);
  EncFn enc = (EncFn)fn;
  void *pAT, *pX1, *pKV;
  cudaGetSymbolAddress(&pKV, g_kvT);
  cudaGetSymbolAddress(&pAT, g_AT);
  cudaGetSymbolAddress(&pX1, g_x1T);
  Params P;
  { cuuint64_t d[] = {640, 2048}, st[] = {1280}; cuuint32_t bx[] = {64, 35}; mkmap(enc, &P.mK, d_in[1], 2, d, st, bx, CU_TENSOR_MAP_SWIZZLE_NONE); }
  { cuuint64_t d[] = {640, 2048}, st[] = {1280}; cuuint32_t bx[] = {64, 32}; mkmap(enc, &P.mV, d_in[2], 2, d, st, bx, CU_TENSOR_MAP_SWIZZLE_NONE); }
  { cuuint64_t d[] = {128, 16, 640}, st[] = {256, 4096}; cuuint32_t bx[] = {144, 16, 1}; mkmap(enc, &P.mS, d_in[4], 3, d, st, bx, CU_TENSOR_MAP_SWIZZLE_NONE); }
  { cuuint64_t d[] = {2048, 640}, st[] = {4096}; cuuint32_t bx[] = {32, 64}; mkmap(enc, &P.mKV, pKV, 2, d, st, bx, CU_TENSOR_MAP_SWIZZLE_64B); }
  { cuuint64_t d[] = {3840, 640}, st[] = {7680}; cuuint32_t bx[] = {64, 80}; mkmap(enc, &P.mWm, d_in[11], 2, d, st, bx, CU_TENSOR_MAP_SWIZZLE_NONE); }
  { cuuint64_t d[] = {64, 640, 32}, st[] = {4096, 128}; cuuint32_t bx[] = {64, 32, 2}; mkmap(enc, &P.mA, pAT, 3, d, st, bx, CU_TENSOR_MAP_SWIZZLE_128B); }
  { cuuint64_t d[] = {64, 640, 32}, st[] = {4096, 128}; cuuint32_t bx[] = {64, 80, 2}; mkmap(enc, &P.mX1, pX1, 3, d, st, bx, CU_TENSOR_MAP_SWIZZLE_128B); }
  { cuuint64_t d[] = {64, 640, 24}, st[] = {3072, 128}; cuuint32_t bx[] = {64, 32, 3};
    mkmap(enc, &P.mG, d_in[7], 3, d, st, bx, CU_TENSOR_MAP_SWIZZLE_128B); mkmap(enc, &P.mU, d_in[8], 3, d, st, bx, CU_TENSOR_MAP_SWIZZLE_128B); }
  { cuuint64_t d[] = {160, 2, 4, 192, 4}, st[] = {1280, 2560, 10240, 320}; cuuint32_t bx[] = {64, 2, 4, 4, 1}; mkmap(enc, &P.mDn, d_in[9], 5, d, st, bx, CU_TENSOR_MAP_SWIZZLE_128B); }
  { cuuint64_t d[] = {160, 2, 192, 4, 4}, st[] = {1280, 10240, 2560, 320}; cuuint32_t bx[] = {64, 2, 4, 4, 1}; mkmap(enc, &P.mDp, d_in[9], 5, d, st, bx, CU_TENSOR_MAP_SWIZZLE_128B); }
  P.x = (const bf16*)d_in[0]; P.shift_k = (const bf16*)d_in[3]; P.ssm_D = (const bf16*)d_in[5];
  P.wg = (const bf16*)d_in[7]; P.wu = (const bf16*)d_in[8]; P.c = (const bf16*)d_in[10]; P.wmod = (const bf16*)d_in[11];
  P.out = (bf16*)d_out;
  cudaFuncSetAttribute(fused_kernel, cudaFuncAttributeMaxDynamicSharedMemorySize, SM_TOTAL + DEVSM);
  cudaLaunchConfig_t cfg = {};
  cfg.gridDim = dim3(128); cfg.blockDim = dim3(512); cfg.dynamicSmemBytes = SM_TOTAL + DEVSM; cfg.stream = cudaStreamPerThread;
  cudaLaunchAttribute at[1];
  at[0].id = cudaLaunchAttributeClusterDimension; at[0].val.clusterDim.x = 2; at[0].val.clusterDim.y = 1; at[0].val.clusterDim.z = 1;
  cfg.attrs = at; cfg.numAttrs = 1;
  cudaLaunchKernelEx(&cfg, fused_kernel, P);
}
```

```cpp
#include <cuda_runtime.h>
#include <cuda.h>
#include <cuda_bf16.h>
#include <stdio.h>
#include <stdint.h>
typedef __nv_bfloat16 bf16;
#define SIG 1
__device__ __forceinline__ uint32_t smem_u32(const void* p) { return (uint32_t)__cvta_generic_to_shared(p); }
__device__ __forceinline__ void mbar_init(uint32_t bar, int cnt) { asm volatile("mbarrier.init.shared::cta.b64 [%0], %1;" ::"r"(bar), "r"(cnt) : "memory"); }
__device__ __forceinline__ void mbar_expect(uint32_t bar, int bytes) { asm volatile("mbarrier.arrive.expect_tx.shared::cta.b64 _, [%0], %1;" ::"r"(bar), "r"(bytes) : "memory"); }
__device__ __forceinline__ void mbar_arrive(uint32_t bar) { asm volatile("mbarrier.arrive.shared::cta.b64 _, [%0];" ::"r"(bar) : "memory"); }
__device__ __forceinline__ void mbar_arrive_remote(uint32_t bar) { asm volatile("mbarrier.arrive.relaxed.cluster.shared::cluster.b64 _, [%0];" ::"r"(bar) : "memory"); }
__device__ __forceinline__ uint32_t mapa(uint32_t a, uint32_t cta) { uint32_t r; asm("mapa.shared::cluster.u32 %0, %1, %2;" : "=r"(r) : "r"(a), "r"(cta)); return r; }
__device__ __forceinline__ bool mbar_try(uint32_t bar, int parity) {
  uint32_t ok;
  asm volatile("{\n.reg .pred p;\nmbarrier.try_wait.parity.shared::cta.b64 p, [%1], %2;\nselp.u32 %0, 1, 0, p;\n}" : "=r"(ok) : "r"(bar), "r"(parity) : "memory");
  return ok;
}
__device__ __forceinline__ void mbar_wait(uint32_t bar, int parity) {
#pragma unroll 1
  for (int i = 0; i < (1 << 20); i++) { if (mbar_try(bar, parity)) return; }
  __trap();
}
__device__ __forceinline__ void tma2d(uint32_t dst, const CUtensorMap* m, int c0, int c1, uint32_t bar) {
  asm volatile("cp.async.bulk.tensor.2d.shared::cluster.global.mbarrier::complete_tx::bytes [%0], [%1, {%3, %4}], [%2];" ::"r"(dst), "l"(m), "r"(bar), "r"(c0), "r"(c1) : "memory");
}
__device__ __forceinline__ void tma3d(uint32_t dst, const CUtensorMap* m, int c0, int c1, int c2, uint32_t bar) {
  asm volatile("cp.async.bulk.tensor.3d.shared::cluster.global.mbarrier::complete_tx::bytes [%0], [%1, {%3, %4, %5}], [%2];" ::"r"(dst), "l"(m), "r"(bar), "r"(c0), "r"(c1), "r"(c2) : "memory");
}
__device__ __forceinline__ void tma5d(uint32_t dst, const CUtensorMap* m, int c0, int c1, int c2, int c3, int c4, uint32_t bar) {
  asm volatile("cp.async.bulk.tensor.5d.shared::cluster.global.mbarrier::complete_tx::bytes [%0], [%1, {%3, %4, %5, %6, %7}], [%2];" ::"r"(dst), "l"(m), "r"(bar), "r"(c0), "r"(c1), "r"(c2), "r"(c3), "r"(c4) : "memory");
}
__device__ __forceinline__ void tma_store2d(const CUtensorMap* m, uint32_t src, int c0, int c1) {
  asm volatile("cp.async.bulk.tensor.2d.global.shared::cta.bulk_group [%0, {%2, %3}], [%1];" ::"l"(m), "r"(src), "r"(c0), "r"(c1) : "memory");
}
__device__ __forceinline__ void tma_store4d(const CUtensorMap* m, uint32_t src, int c0, int c1, int c2, int c3) {
  asm volatile("cp.async.bulk.tensor.4d.global.shared::cta.bulk_group [%0, {%2, %3, %4, %5}], [%1];" ::"l"(m), "r"(src), "r"(c0), "r"(c1), "r"(c2), "r"(c3) : "memory");
}
__device__ __forceinline__ void tma_prefetch2d(const CUtensorMap* m, int c0, int c1) {
  asm volatile("cp.async.bulk.prefetch.tensor.2d.L2.global [%0, {%1, %2}];" ::"l"(m), "r"(c0), "r"(c1) : "memory");
}
__device__ __forceinline__ void bulk_g2s(uint32_t dst, const void* src, int bytes, uint32_t bar) {
  asm volatile("cp.async.bulk.shared::cluster.global.mbarrier::complete_tx::bytes [%0], [%1], %2, [%3];" ::"r"(dst), "l"(src), "r"(bytes), "r"(bar) : "memory");
}
__device__ __forceinline__ void bulk_s2g(void* dst, uint32_t src, int bytes) {
  asm volatile("cp.async.bulk.global.shared::cta.bulk_group [%0], [%1], %2;" ::"l"(dst), "r"(src), "r"(bytes) : "memory");
}
__device__ __forceinline__ void st_async4(uint32_t dst, float a, float b, float c, float d, uint32_t bar) {
  asm volatile("st.async.weak.shared::cluster.mbarrier::complete_tx::bytes.v4.f32 [%0], {%1, %2, %3, %4}, [%5];" ::"r"(dst), "f"(a), "f"(b), "f"(c), "f"(d), "r"(bar) : "memory");
}
__device__ __forceinline__ void wg_fence() { asm volatile("wgmma.fence.sync.aligned;" ::: "memory"); }
__device__ __forceinline__ void wg_commit() { asm volatile("wgmma.commit_group.sync.aligned;" ::: "memory"); }
template <int N> __device__ __forceinline__ void wg_wait() { asm volatile("wgmma.wait_group.sync.aligned %0;" ::"n"(N) : "memory"); }
__device__ __forceinline__ uint64_t mkdesc(uint32_t addr, uint32_t lbo, uint32_t sbo, uint32_t swz) {
  return (uint64_t)((addr & 0x3FFFF) >> 4) | ((uint64_t)(lbo >> 4) << 16) | ((uint64_t)(sbo >> 4) << 32) | ((uint64_t)swz << 62);
}
__device__ __forceinline__ void ldsm4t(uint32_t* r, uint32_t a) {
  asm volatile("ldmatrix.sync.aligned.m8n8.x4.trans.shared.b16 {%0,%1,%2,%3}, [%4];" : "=r"(r[0]), "=r"(r[1]), "=r"(r[2]), "=r"(r[3]) : "r"(a) : "memory");
}
__device__ __forceinline__ void stsm4(uint32_t a, const uint32_t* r) {
  asm volatile("stmatrix.sync.aligned.m8n8.x4.shared.b16 [%0], {%1,%2,%3,%4};" ::"r"(a), "r"(r[0]), "r"(r[1]), "r"(r[2]), "r"(r[3]) : "memory");
}
__device__ __forceinline__ void bar_sync(int id, int n) { asm volatile("bar.sync %0, %1;" ::"r"(id), "r"(n) : "memory"); }
__device__ __forceinline__ void bar_arrive(int id, int n) { asm volatile("bar.arrive %0, %1;" ::"r"(id), "r"(n) : "memory"); }
__device__ __forceinline__ uint32_t lds32(uint32_t a) { uint32_t v; asm volatile("ld.shared.b32 %0, [%1];" : "=r"(v) : "r"(a) : "memory"); return v; }
__device__ __forceinline__ uint2 lds64(uint32_t a) { uint2 v; asm volatile("ld.shared.v2.b32 {%0,%1}, [%2];" : "=r"(v.x), "=r"(v.y) : "r"(a) : "memory"); return v; }
__device__ __forceinline__ uint4 lds128(uint32_t a) { uint4 v; asm volatile("ld.shared.v4.b32 {%0,%1,%2,%3}, [%4];" : "=r"(v.x), "=r"(v.y), "=r"(v.z), "=r"(v.w) : "r"(a) : "memory"); return v; }
__device__ __forceinline__ void sts16(uint32_t a, uint32_t v) { asm volatile("st.shared.b16 [%0], %1;" ::"r"(a), "h"((uint16_t)v) : "memory"); }
__device__ __forceinline__ void sts32(uint32_t a, uint32_t v) { asm volatile("st.shared.b32 [%0], %1;" ::"r"(a), "r"(v) : "memory"); }
__device__ __forceinline__ void sts64(uint32_t a, uint32_t x, uint32_t y) { asm volatile("st.shared.v2.b32 [%0], {%1,%2};" ::"r"(a), "r"(x), "r"(y) : "memory"); }
__device__ __forceinline__ void sts128(uint32_t a, uint4 v) { asm volatile("st.shared.v4.b32 [%0], {%1,%2,%3,%4};" ::"r"(a), "r"(v.x), "r"(v.y), "r"(v.z), "r"(v.w) : "memory"); }
template<int TB> __device__ __forceinline__ void wgmma_rs_n128(float* d, const uint32_t* a, uint64_t db, int sd) {
  asm volatile("{\n.reg .pred p;\nsetp.ne.b32 p, %69, 0;\n"
    "wgmma.mma_async.sync.aligned.m64n128k16.f32.bf16.bf16 {%0, %1, %2, %3, %4, %5, %6, %7, %8, %9, %10, %11, %12, %13, %14, %15, %16, %17, %18, %19, %20, %21, %22, %23, %24, %25, %26, %27, %28, %29, %30, %31, %32, %33, %34, %35, %36, %37, %38, %39, %40, %41, %42, %43, %44, %45, %46, %47, %48, %49, %50, %51, %52, %53, %54, %55, %56, %57, %58, %59, %60, %61, %62, %63}, {%64, %65, %66, %67}, %68, p, 1, 1, %70;\n}"
    : "+f"(d[0]), "+f"(d[1]), "+f"(d[2]), "+f"(d[3]), "+f"(d[4]), "+f"(d[5]), "+f"(d[6]), "+f"(d[7]), "+f"(d[8]), "+f"(d[9]), "+f"(d[10]), "+f"(d[11]), "+f"(d[12]), "+f"(d[13]), "+f"(d[14]), "+f"(d[15]), "+f"(d[16]), "+f"(d[17]), "+f"(d[18]), "+f"(d[19]), "+f"(d[20]), "+f"(d[21]), "+f"(d[22]), "+f"(d[23]), "+f"(d[24]), "+f"(d[25]), "+f"(d[26]), "+f"(d[27]), "+f"(d[28]), "+f"(d[29]), "+f"(d[30]), "+f"(d[31]), "+f"(d[32]), "+f"(d[33]), "+f"(d[34]), "+f"(d[35]), "+f"(d[36]), "+f"(d[37]), "+f"(d[38]), "+f"(d[39]), "+f"(d[40]), "+f"(d[41]), "+f"(d[42]), "+f"(d[43]), "+f"(d[44]), "+f"(d[45]), "+f"(d[46]), "+f"(d[47]), "+f"(d[48]), "+f"(d[49]), "+f"(d[50]), "+f"(d[51]), "+f"(d[52]), "+f"(d[53]), "+f"(d[54]), "+f"(d[55]), "+f"(d[56]), "+f"(d[57]), "+f"(d[58]), "+f"(d[59]), "+f"(d[60]), "+f"(d[61]), "+f"(d[62]), "+f"(d[63])
    : "r"(a[0]), "r"(a[1]), "r"(a[2]), "r"(a[3]), "l"(db), "r"(sd), "n"(TB));
}

template<int TB> __device__ __forceinline__ void wgmma_rs_n160(float* d, const uint32_t* a, uint64_t db, int sd) {
  asm volatile("{\n.reg .pred p;\nsetp.ne.b32 p, %85, 0;\n"
    "wgmma.mma_async.sync.aligned.m64n160k16.f32.bf16.bf16 {%0, %1, %2, %3, %4, %5, %6, %7, %8, %9, %10, %11, %12, %13, %14, %15, %16, %17, %18, %19, %20, %21, %22, %23, %24, %25, %26, %27, %28, %29, %30, %31, %32, %33, %34, %35, %36, %37, %38, %39, %40, %41, %42, %43, %44, %45, %46, %47, %48, %49, %50, %51, %52, %53, %54, %55, %56, %57, %58, %59, %60, %61, %62, %63, %64, %65, %66, %67, %68, %69, %70, %71, %72, %73, %74, %75, %76, %77, %78, %79}, {%80, %81, %82, %83}, %84, p, 1, 1, %86;\n}"
    : "+f"(d[0]), "+f"(d[1]), "+f"(d[2]), "+f"(d[3]), "+f"(d[4]), "+f"(d[5]), "+f"(d[6]), "+f"(d[7]), "+f"(d[8]), "+f"(d[9]), "+f"(d[10]), "+f"(d[11]), "+f"(d[12]), "+f"(d[13]), "+f"(d[14]), "+f"(d[15]), "+f"(d[16]), "+f"(d[17]), "+f"(d[18]), "+f"(d[19]), "+f"(d[20]), "+f"(d[21]), "+f"(d[22]), "+f"(d[23]), "+f"(d[24]), "+f"(d[25]), "+f"(d[26]), "+f"(d[27]), "+f"(d[28]), "+f"(d[29]), "+f"(d[30]), "+f"(d[31]), "+f"(d[32]), "+f"(d[33]), "+f"(d[34]), "+f"(d[35]), "+f"(d[36]), "+f"(d[37]), "+f"(d[38]), "+f"(d[39]), "+f"(d[40]), "+f"(d[41]), "+f"(d[42]), "+f"(d[43]), "+f"(d[44]), "+f"(d[45]), "+f"(d[46]), "+f"(d[47]), "+f"(d[48]), "+f"(d[49]), "+f"(d[50]), "+f"(d[51]), "+f"(d[52]), "+f"(d[53]), "+f"(d[54]), "+f"(d[55]), "+f"(d[56]), "+f"(d[57]), "+f"(d[58]), "+f"(d[59]), "+f"(d[60]), "+f"(d[61]), "+f"(d[62]), "+f"(d[63]), "+f"(d[64]), "+f"(d[65]), "+f"(d[66]), "+f"(d[67]), "+f"(d[68]), "+f"(d[69]), "+f"(d[70]), "+f"(d[71]), "+f"(d[72]), "+f"(d[73]), "+f"(d[74]), "+f"(d[75]), "+f"(d[76]), "+f"(d[77]), "+f"(d[78]), "+f"(d[79])
    : "r"(a[0]), "r"(a[1]), "r"(a[2]), "r"(a[3]), "l"(db), "r"(sd), "n"(TB));
}

template<int TB> __device__ __forceinline__ void wgmma_rs_n192(float* d, const uint32_t* a, uint64_t db, int sd) {
  asm volatile("{\n.reg .pred p;\nsetp.ne.b32 p, %101, 0;\n"
    "wgmma.mma_async.sync.aligned.m64n192k16.f32.bf16.bf16 {%0, %1, %2, %3, %4, %5, %6, %7, %8, %9, %10, %11, %12, %13, %14, %15, %16, %17, %18, %19, %20, %21, %22, %23, %24, %25, %26, %27, %28, %29, %30, %31, %32, %33, %34, %35, %36, %37, %38, %39, %40, %41, %42, %43, %44, %45, %46, %47, %48, %49, %50, %51, %52, %53, %54, %55, %56, %57, %58, %59, %60, %61, %62, %63, %64, %65, %66, %67, %68, %69, %70, %71, %72, %73, %74, %75, %76, %77, %78, %79, %80, %81, %82, %83, %84, %85, %86, %87, %88, %89, %90, %91, %92, %93, %94, %95}, {%96, %97, %98, %99}, %100, p, 1, 1, %102;\n}"
    : "+f"(d[0]), "+f"(d[1]), "+f"(d[2]), "+f"(d[3]), "+f"(d[4]), "+f"(d[5]), "+f"(d[6]), "+f"(d[7]), "+f"(d[8]), "+f"(d[9]), "+f"(d[10]), "+f"(d[11]), "+f"(d[12]), "+f"(d[13]), "+f"(d[14]), "+f"(d[15]), "+f"(d[16]), "+f"(d[17]), "+f"(d[18]), "+f"(d[19]), "+f"(d[20]), "+f"(d[21]), "+f"(d[22]), "+f"(d[23]), "+f"(d[24]), "+f"(d[25]), "+f"(d[26]), "+f"(d[27]), "+f"(d[28]), "+f"(d[29]), "+f"(d[30]), "+f"(d[31]), "+f"(d[32]), "+f"(d[33]), "+f"(d[34]), "+f"(d[35]), "+f"(d[36]), "+f"(d[37]), "+f"(d[38]), "+f"(d[39]), "+f"(d[40]), "+f"(d[41]), "+f"(d[42]), "+f"(d[43]), "+f"(d[44]), "+f"(d[45]), "+f"(d[46]), "+f"(d[47]), "+f"(d[48]), "+f"(d[49]), "+f"(d[50]), "+f"(d[51]), "+f"(d[52]), "+f"(d[53]), "+f"(d[54]), "+f"(d[55]), "+f"(d[56]), "+f"(d[57]), "+f"(d[58]), "+f"(d[59]), "+f"(d[60]), "+f"(d[61]), "+f"(d[62]), "+f"(d[63]), "+f"(d[64]), "+f"(d[65]), "+f"(d[66]), "+f"(d[67]), "+f"(d[68]), "+f"(d[69]), "+f"(d[70]), "+f"(d[71]), "+f"(d[72]), "+f"(d[73]), "+f"(d[74]), "+f"(d[75]), "+f"(d[76]), "+f"(d[77]), "+f"(d[78]), "+f"(d[79]), "+f"(d[80]), "+f"(d[81]), "+f"(d[82]), "+f"(d[83]), "+f"(d[84]), "+f"(d[85]), "+f"(d[86]), "+f"(d[87]), "+f"(d[88]), "+f"(d[89]), "+f"(d[90]), "+f"(d[91]), "+f"(d[92]), "+f"(d[93]), "+f"(d[94]), "+f"(d[95])
    : "r"(a[0]), "r"(a[1]), "r"(a[2]), "r"(a[3]), "l"(db), "r"(sd), "n"(TB));
}

template<int TB> __device__ __forceinline__ void wgmma_rs_n32(float* d, const uint32_t* a, uint64_t db, int sd) {
  asm volatile("{\n.reg .pred p;\nsetp.ne.b32 p, %21, 0;\n"
    "wgmma.mma_async.sync.aligned.m64n32k16.f32.bf16.bf16 {%0, %1, %2, %3, %4, %5, %6, %7, %8, %9, %10, %11, %12, %13, %14, %15}, {%16, %17, %18, %19}, %20, p, 1, 1, %22;\n}"
    : "+f"(d[0]), "+f"(d[1]), "+f"(d[2]), "+f"(d[3]), "+f"(d[4]), "+f"(d[5]), "+f"(d[6]), "+f"(d[7]), "+f"(d[8]), "+f"(d[9]), "+f"(d[10]), "+f"(d[11]), "+f"(d[12]), "+f"(d[13]), "+f"(d[14]), "+f"(d[15])
    : "r"(a[0]), "r"(a[1]), "r"(a[2]), "r"(a[3]), "l"(db), "r"(sd), "n"(TB));
}

template<int TB> __device__ __forceinline__ void wgmma_rs_n64(float* d, const uint32_t* a, uint64_t db, int sd) {
  asm volatile("{\n.reg .pred p;\nsetp.ne.b32 p, %37, 0;\n"
    "wgmma.mma_async.sync.aligned.m64n64k16.f32.bf16.bf16 {%0, %1, %2, %3, %4, %5, %6, %7, %8, %9, %10, %11, %12, %13, %14, %15, %16, %17, %18, %19, %20, %21, %22, %23, %24, %25, %26, %27, %28, %29, %30, %31}, {%32, %33, %34, %35}, %36, p, 1, 1, %38;\n}"
    : "+f"(d[0]), "+f"(d[1]), "+f"(d[2]), "+f"(d[3]), "+f"(d[4]), "+f"(d[5]), "+f"(d[6]), "+f"(d[7]), "+f"(d[8]), "+f"(d[9]), "+f"(d[10]), "+f"(d[11]), "+f"(d[12]), "+f"(d[13]), "+f"(d[14]), "+f"(d[15]), "+f"(d[16]), "+f"(d[17]), "+f"(d[18]), "+f"(d[19]), "+f"(d[20]), "+f"(d[21]), "+f"(d[22]), "+f"(d[23]), "+f"(d[24]), "+f"(d[25]), "+f"(d[26]), "+f"(d[27]), "+f"(d[28]), "+f"(d[29]), "+f"(d[30]), "+f"(d[31])
    : "r"(a[0]), "r"(a[1]), "r"(a[2]), "r"(a[3]), "l"(db), "r"(sd), "n"(TB));
}

template<int TB> __device__ __forceinline__ void wgmma_rs_n96(float* d, const uint32_t* a, uint64_t db, int sd) {
  asm volatile("{\n.reg .pred p;\nsetp.ne.b32 p, %53, 0;\n"
    "wgmma.mma_async.sync.aligned.m64n96k16.f32.bf16.bf16 {%0, %1, %2, %3, %4, %5, %6, %7, %8, %9, %10, %11, %12, %13, %14, %15, %16, %17, %18, %19, %20, %21, %22, %23, %24, %25, %26, %27, %28, %29, %30, %31, %32, %33, %34, %35, %36, %37, %38, %39, %40, %41, %42, %43, %44, %45, %46, %47}, {%48, %49, %50, %51}, %52, p, 1, 1, %54;\n}"
    : "+f"(d[0]), "+f"(d[1]), "+f"(d[2]), "+f"(d[3]), "+f"(d[4]), "+f"(d[5]), "+f"(d[6]), "+f"(d[7]), "+f"(d[8]), "+f"(d[9]), "+f"(d[10]), "+f"(d[11]), "+f"(d[12]), "+f"(d[13]), "+f"(d[14]), "+f"(d[15]), "+f"(d[16]), "+f"(d[17]), "+f"(d[18]), "+f"(d[19]), "+f"(d[20]), "+f"(d[21]), "+f"(d[22]), "+f"(d[23]), "+f"(d[24]), "+f"(d[25]), "+f"(d[26]), "+f"(d[27]), "+f"(d[28]), "+f"(d[29]), "+f"(d[30]), "+f"(d[31]), "+f"(d[32]), "+f"(d[33]), "+f"(d[34]), "+f"(d[35]), "+f"(d[36]), "+f"(d[37]), "+f"(d[38]), "+f"(d[39]), "+f"(d[40]), "+f"(d[41]), "+f"(d[42]), "+f"(d[43]), "+f"(d[44]), "+f"(d[45]), "+f"(d[46]), "+f"(d[47])
    : "r"(a[0]), "r"(a[1]), "r"(a[2]), "r"(a[3]), "l"(db), "r"(sd), "n"(TB));
}

template<int TA, int TB> __device__ __forceinline__ void wgmma_ss_n160(float* d, uint64_t da, uint64_t db, int sd) {
  asm volatile("{\n.reg .pred p;\nsetp.ne.b32 p, %82, 0;\n"
    "wgmma.mma_async.sync.aligned.m64n160k16.f32.bf16.bf16 {%0, %1, %2, %3, %4, %5, %6, %7, %8, %9, %10, %11, %12, %13, %14, %15, %16, %17, %18, %19, %20, %21, %22, %23, %24, %25, %26, %27, %28, %29, %30, %31, %32, %33, %34, %35, %36, %37, %38, %39, %40, %41, %42, %43, %44, %45, %46, %47, %48, %49, %50, %51, %52, %53, %54, %55, %56, %57, %58, %59, %60, %61, %62, %63, %64, %65, %66, %67, %68, %69, %70, %71, %72, %73, %74, %75, %76, %77, %78, %79}, %80, %81, p, 1, 1, %83, %84;\n}"
    : "+f"(d[0]), "+f"(d[1]), "+f"(d[2]), "+f"(d[3]), "+f"(d[4]), "+f"(d[5]), "+f"(d[6]), "+f"(d[7]), "+f"(d[8]), "+f"(d[9]), "+f"(d[10]), "+f"(d[11]), "+f"(d[12]), "+f"(d[13]), "+f"(d[14]), "+f"(d[15]), "+f"(d[16]), "+f"(d[17]), "+f"(d[18]), "+f"(d[19]), "+f"(d[20]), "+f"(d[21]), "+f"(d[22]), "+f"(d[23]), "+f"(d[24]), "+f"(d[25]), "+f"(d[26]), "+f"(d[27]), "+f"(d[28]), "+f"(d[29]), "+f"(d[30]), "+f"(d[31]), "+f"(d[32]), "+f"(d[33]), "+f"(d[34]), "+f"(d[35]), "+f"(d[36]), "+f"(d[37]), "+f"(d[38]), "+f"(d[39]), "+f"(d[40]), "+f"(d[41]), "+f"(d[42]), "+f"(d[43]), "+f"(d[44]), "+f"(d[45]), "+f"(d[46]), "+f"(d[47]), "+f"(d[48]), "+f"(d[49]), "+f"(d[50]), "+f"(d[51]), "+f"(d[52]), "+f"(d[53]), "+f"(d[54]), "+f"(d[55]), "+f"(d[56]), "+f"(d[57]), "+f"(d[58]), "+f"(d[59]), "+f"(d[60]), "+f"(d[61]), "+f"(d[62]), "+f"(d[63]), "+f"(d[64]), "+f"(d[65]), "+f"(d[66]), "+f"(d[67]), "+f"(d[68]), "+f"(d[69]), "+f"(d[70]), "+f"(d[71]), "+f"(d[72]), "+f"(d[73]), "+f"(d[74]), "+f"(d[75]), "+f"(d[76]), "+f"(d[77]), "+f"(d[78]), "+f"(d[79])
    : "l"(da), "l"(db), "r"(sd), "n"(TA), "n"(TB));
}

template<int TA, int TB> __device__ __forceinline__ void wgmma_ss_n192(float* d, uint64_t da, uint64_t db, int sd) {
  asm volatile("{\n.reg .pred p;\nsetp.ne.b32 p, %98, 0;\n"
    "wgmma.mma_async.sync.aligned.m64n192k16.f32.bf16.bf16 {%0, %1, %2, %3, %4, %5, %6, %7, %8, %9, %10, %11, %12, %13, %14, %15, %16, %17, %18, %19, %20, %21, %22, %23, %24, %25, %26, %27, %28, %29, %30, %31, %32, %33, %34, %35, %36, %37, %38, %39, %40, %41, %42, %43, %44, %45, %46, %47, %48, %49, %50, %51, %52, %53, %54, %55, %56, %57, %58, %59, %60, %61, %62, %63, %64, %65, %66, %67, %68, %69, %70, %71, %72, %73, %74, %75, %76, %77, %78, %79, %80, %81, %82, %83, %84, %85, %86, %87, %88, %89, %90, %91, %92, %93, %94, %95}, %96, %97, p, 1, 1, %99, %100;\n}"
    : "+f"(d[0]), "+f"(d[1]), "+f"(d[2]), "+f"(d[3]), "+f"(d[4]), "+f"(d[5]), "+f"(d[6]), "+f"(d[7]), "+f"(d[8]), "+f"(d[9]), "+f"(d[10]), "+f"(d[11]), "+f"(d[12]), "+f"(d[13]), "+f"(d[14]), "+f"(d[15]), "+f"(d[16]), "+f"(d[17]), "+f"(d[18]), "+f"(d[19]), "+f"(d[20]), "+f"(d[21]), "+f"(d[22]), "+f"(d[23]), "+f"(d[24]), "+f"(d[25]), "+f"(d[26]), "+f"(d[27]), "+f"(d[28]), "+f"(d[29]), "+f"(d[30]), "+f"(d[31]), "+f"(d[32]), "+f"(d[33]), "+f"(d[34]), "+f"(d[35]), "+f"(d[36]), "+f"(d[37]), "+f"(d[38]), "+f"(d[39]), "+f"(d[40]), "+f"(d[41]), "+f"(d[42]), "+f"(d[43]), "+f"(d[44]), "+f"(d[45]), "+f"(d[46]), "+f"(d[47]), "+f"(d[48]), "+f"(d[49]), "+f"(d[50]), "+f"(d[51]), "+f"(d[52]), "+f"(d[53]), "+f"(d[54]), "+f"(d[55]), "+f"(d[56]), "+f"(d[57]), "+f"(d[58]), "+f"(d[59]), "+f"(d[60]), "+f"(d[61]), "+f"(d[62]), "+f"(d[63]), "+f"(d[64]), "+f"(d[65]), "+f"(d[66]), "+f"(d[67]), "+f"(d[68]), "+f"(d[69]), "+f"(d[70]), "+f"(d[71]), "+f"(d[72]), "+f"(d[73]), "+f"(d[74]), "+f"(d[75]), "+f"(d[76]), "+f"(d[77]), "+f"(d[78]), "+f"(d[79]), "+f"(d[80]), "+f"(d[81]), "+f"(d[82]), "+f"(d[83]), "+f"(d[84]), "+f"(d[85]), "+f"(d[86]), "+f"(d[87]), "+f"(d[88]), "+f"(d[89]), "+f"(d[90]), "+f"(d[91]), "+f"(d[92]), "+f"(d[93]), "+f"(d[94]), "+f"(d[95])
    : "l"(da), "l"(db), "r"(sd), "n"(TA), "n"(TB));
}

template<int TA, int TB> __device__ __forceinline__ void wgmma_ss_n8(float* d, uint64_t da, uint64_t db, int sd) {
  asm volatile("{\n.reg .pred p;\nsetp.ne.b32 p, %6, 0;\n"
    "wgmma.mma_async.sync.aligned.m64n8k16.f32.bf16.bf16 {%0, %1, %2, %3}, %4, %5, p, 1, 1, %7, %8;\n}"
    : "+f"(d[0]), "+f"(d[1]), "+f"(d[2]), "+f"(d[3])
    : "l"(da), "l"(db), "r"(sd), "n"(TA), "n"(TB));
}

constexpr int S_ = 2048, D_ = 640, F_ = 1536;

__device__ __align__(1024) bf16 g_kvT[D_ * S_];
__device__ __align__(1024) bf16 g_XH[D_ * S_ * 2];
__device__ __align__(1024) bf16 g_x1T[D_ * S_];
__device__ __align__(1024) bf16 g_AT[D_ * S_];
__device__ __align__(1024) bf16 g_HH[S_ * F_];
__device__ __align__(1024) float g_modP[8 * 3840];
__device__ __align__(1024) bf16 g_cbsb[D_ * 2];
__device__ __align__(1024) uint4 g_stat[S_];
__device__ __align__(1024) bf16 g_cimg[8 * 6 * 512];
__device__ __align__(1024) uint32_t g_flag[256 * 8];
__device__ uint32_t g_epoch[128];
#define DEVSM 0
#define STAMP(id)
#define STAMPIF(c, id)
constexpr int FL_KV = 0, FL_X = 10, FL_R = 11, FL_S = 16, FL_C = 32, FL_M = 40, FL_F = 100, FL_H = 128;

constexpr int SM_Z = 1024, SM_EXT = 21504, SM_STAT = 27648, SM_SMALL = 29696, SM_CB = 30720, SM_RING = 34816, SM_TOTAL = SM_RING + 6 * 32768;
constexpr int SMALL_S = 0, SMALL_XM = 160, SMALL_MOD = 256, SMALL_RED = 336, SMALL_GB = 848, SMALL_DUMMY = 1008;
constexpr int JOB_SZ = 9088, R_X = 5 * 32768;
constexpr int K1OFF = 4672, KSZ = 9472, CSZ = KSZ + 4224;
enum { B_B = 0, B_X = 5, B_U = 7, B_S = 12, B_F1 = 17, B_E1 = 23, B_EB = 29, B_EA = 41, B_FB = 47, B_FA = 59, B_EXT = 65, B_X1 = 66, B_PEER = 67, B_RECV = 68,
       B_MF = 70, B_XFREE = 73, B_BOX = 74, B_CB = 78, B_ST1 = 79, B_GB = 80, B_ST0 = 81, B_Z = 82, B_KVS = 87, B_EW = 90, B_MB = 95, B_HH = 98, B_K = 100, B_ZF = 103, B_NUM = 104 };
__device__ __forceinline__ uint32_t chan_base(uint32_t sb, int ch) { return sb + SM_RING + (2 + (ch >> 1)) * 32768 + (ch & 1) * CSZ; }
__device__ __forceinline__ uint32_t box_base(uint32_t sb, int cls) {
  return sb + SM_RING + (cls == 0 ? 46080 : cls == 1 ? 4 * 32768 + 14336 : cls == 2 ? 5 * 32768 + 20480 : 5 * 32768);
}

struct Params {
  CUtensorMap mK, mV, mX, mS, mWm, mA, mG, mU, mDn, mDp, mX1, mO;
  const bf16 *shift_k, *ssm_D, *c;
};

__device__ __forceinline__ uint32_t* flagp(int id) { return g_flag + id * 8; }
__device__ __forceinline__ void flag_add(int id) { asm volatile("red.relaxed.gpu.global.add.u32 [%0], 1;" ::"l"(flagp(id)) : "memory"); }
__device__ __forceinline__ uint32_t rdback(const void* p) { uint32_t v; asm volatile("ld.relaxed.gpu.global.u32 %0, [%1];" : "=r"(v) : "l"(p) : "memory"); return v; }
__device__ __forceinline__ void rdwait(uint32_t sb, uint32_t v) { sts32(sb + SM_SMALL + SMALL_DUMMY, v); }
__device__ __forceinline__ void fence_async_s() { asm volatile("fence.proxy.async.shared::cta;" ::: "memory"); }
__device__ __forceinline__ void fence_async_g() { asm volatile("fence.proxy.async.global;" ::: "memory"); }
__device__ __forceinline__ void bulk_done() { asm volatile("cp.async.bulk.commit_group;\n\tcp.async.bulk.wait_group 0;" ::: "memory"); }
__device__ __forceinline__ void flag_wait(int id, uint32_t target) {
  const uint32_t* p = flagp(id);
#pragma unroll 1
  for (int i = 0; i < (1 << 20); i++) {
    uint32_t v;
    asm volatile("ld.relaxed.gpu.global.u32 %0, [%1];" : "=r"(v) : "l"(p) : "memory");
    if ((int)(v - target) >= 0) return;
  }
  __trap();
}
__device__ __forceinline__ int ibase(int pb) {
  int w = pb >> 5, g = (pb >> 2) & 7, q = pb & 3;
  return 128 * (g >> 2) + 8 * ((2 * q - ((g >> 1) & 1)) & 7) + 2 * w + (g & 1);
}
__device__ __forceinline__ uint32_t hmul(uint32_t a, uint32_t b) { uint32_t d; asm("mul.rn.bf16x2 %0, %1, %2;" : "=r"(d) : "r"(a), "r"(b)); return d; }
__device__ __forceinline__ uint32_t hadd(uint32_t a, uint32_t b) { uint32_t d; asm("add.rn.bf16x2 %0, %1, %2;" : "=r"(d) : "r"(a), "r"(b)); return d; }
__device__ __forceinline__ uint32_t hsub(uint32_t a, uint32_t b) { uint32_t d; asm("sub.rn.bf16x2 %0, %1, %2;" : "=r"(d) : "r"(a), "r"(b)); return d; }
__device__ __forceinline__ uint32_t pack2(float lo, float hi) { uint32_t d; asm("cvt.rn.bf16x2.f32 %0, %1, %2;" : "=r"(d) : "f"(hi), "f"(lo)); return d; }
__device__ __forceinline__ float blo(uint32_t v) { return __uint_as_float(v << 16); }
__device__ __forceinline__ float bhi(uint32_t v) { return __uint_as_float(v & 0xffff0000u); }
__device__ __forceinline__ float rbf(float v) { return blo(pack2(v, 0.f)); }
template <int N> __device__ __forceinline__ void bfly(float* v, int mask, bool up) {
#pragma unroll
  for (int i = 0; i < N / 2; i++) {
    float send = up ? v[i] : v[i + N / 2], keep = up ? v[i + N / 2] : v[i];
    v[i] = keep + __shfl_xor_sync(0xffffffffu, send, mask);
  }
}
__device__ __forceinline__ int mod_col(int idx) {
  if (idx < 40) { int v = (idx >> 1) & 3; return (v == 3 ? 4 : v) * 640 + 128 * (idx >> 3) + 64 * (idx & 1); }
  int l = idx - 40;
  return l < 10 ? 3 * 640 + 64 * l : 5 * 640 + 64 * (l - 10);
}

__device__ __forceinline__ void kv_job(uint32_t sb, int b, int r, int tid) {
  const int lp = tid & 15, ch = (tid >> 5) & 1, tc = 2 * (tid >> 6) + ((tid >> 4) & 1);
  const uint32_t base = sb + SM_RING + r * JOB_SZ, ka = base + tc * 1024 + ch * 64 + lp * 4;
  mbar_wait(sb + 8 * (B_B + r), 0);
  const uint4 sk = lds128(base + 8576 + 256 * ch + 16 * lp);
  const uint32_t s0 = __byte_perm(sk.x, sk.z, 0x5410), s1 = __byte_perm(sk.x, sk.z, 0x7632), s2 = __byte_perm(sk.y, sk.w, 0x5410), s3 = __byte_perm(sk.y, sk.w, 0x7632);
  uint32_t kk[11], o[8];
#pragma unroll
  for (int i = 0; i < 11; i++) kk[i] = lds32(ka + 128 * i);
#pragma unroll
  for (int i = 0; i < 8; i++) {
    uint32_t v = lds32(ka + 4480 + 128 * i);
    uint32_t a = hadd(hadd(hadd(hmul(kk[i], s3), hmul(kk[i + 1], s2)), hmul(kk[i + 2], s1)), hmul(kk[i + 3], s0));
    o[i] = hmul(a, v);
  }
  bf16* dst = g_kvT + (128 * r + 64 * (b & 1) + 32 * ch + 2 * lp) * S_ + 2040 - 32 * (b >> 1) - 8 * tc;
  *(uint4*)dst = make_uint4(__byte_perm(o[7], o[6], 0x5410), __byte_perm(o[5], o[4], 0x5410), __byte_perm(o[3], o[2], 0x5410), __byte_perm(o[1], o[0], 0x5410));
  *(uint4*)(dst + S_) = make_uint4(__byte_perm(o[7], o[6], 0x7632), __byte_perm(o[5], o[4], 0x7632), __byte_perm(o[3], o[2], 0x7632), __byte_perm(o[1], o[0], 0x7632));
}
__device__ __forceinline__ void kv_signal(uint32_t sb, int b, int r, int lane) {
  const bf16* p = g_kvT + (128 * r + 64 * (b & 1) + lane) * S_ + 2016 - 32 * (b >> 1);
  uint32_t v0 = rdback(p), v1 = rdback(p + 32 * S_);
  rdwait(sb, v0 ^ v1);
  __syncwarp();
  if (lane == 0) flag_add(FL_KV + 2 * r + (b & 1));
}
__device__ __forceinline__ void mod_box(uint32_t sb, int b, int cls, int tid) {
  float a[4];
  const uint64_t da = mkdesc(box_base(sb, cls), 4096, 1024, 1), db = mkdesc(sb + SM_SMALL + SMALL_S, 16, 128, 0);
  mbar_wait(sb + 8 * (B_BOX + cls), 0);
  wg_fence();
#pragma unroll
  for (int n = 0; n < 5; n++) wgmma_ss_n8<1, 0>(a, da + 128 * n, db + 2 * n, n != 0);
  wg_commit();
  wg_wait<0>();
#pragma unroll
  for (int i = 0; i < 4; i++) asm volatile("" : "+f"(a[i])::"memory");
  if ((tid & 3) == 0) {
    float* p = g_modP + (b & 7) * 3840 + mod_col(16 * cls + (b >> 3)) + 16 * (tid >> 5) + ((tid >> 2) & 7);
    p[0] = a[0]; p[8] = a[2];
  }
}
__device__ __forceinline__ uint32_t box_rdback(int b, int cls, int lane) {
  return rdback(g_modP + (b & 7) * 3840 + mod_col(16 * cls + (b >> 3)) + 32 * (lane & 1));
}
__device__ __forceinline__ float sum8(float a) {
  a += __shfl_xor_sync(0xffffffffu, a, 4);
  a += __shfl_xor_sync(0xffffffffu, a, 2);
  a += __shfl_xor_sync(0xffffffffu, a, 1);
  return rbf(a);
}
template <int NR> __device__ __forceinline__ void mod_fin(uint32_t sb, int b, int r0, uint32_t e1, int lane) {
  if (lane < 4 * NR) flag_wait(FL_M + 8 * r0 + 2 * lane + (b >> 6), e1 * 8);
  __syncwarp();
  const int v = lane >> 3;
  const float* p = g_modP + (lane & 7) * 3840 + (v == 3 ? 4 : v) * 640 + 128 * r0 + b;
  float a[NR];
#pragma unroll
  for (int n = 0; n < NR; n++) a[n] = __ldcg(p + 128 * n);
#pragma unroll
  for (int n = 0; n < NR; n++) {
    float t = sum8(a[n]);
    if (v & 1) t += 1.f;
    if ((lane & 7) == 0) sts32(sb + SM_SMALL + SMALL_MOD + 16 * (r0 + n) + 4 * v, pack2(t, t));
  }
  __syncwarp();
  if (lane == 0) mbar_arrive(sb + 8 * (B_MF + (r0 >> 1)));
}
__device__ __forceinline__ void load_kv(const Params& P, uint32_t sb, int b, int r) {
  const uint32_t bar = sb + 8 * (B_B + r), a = sb + SM_RING + r * JOB_SZ;
  mbar_expect(bar, 4480 + 4096 + 512);
  tma2d(a, &P.mK, 128 * r + 64 * (b & 1), 32 * (b >> 1) - 3, bar);
  tma2d(a + 4480, &P.mV, 128 * r + 64 * (b & 1), 32 * (b >> 1), bar);
  bulk_g2s(a + 8576, P.shift_k + (128 * r + 64 * (b & 1)) * 4, 512, bar);
}
__device__ __forceinline__ void load_x(const Params& P, uint32_t sb, int b, int h) {
  const uint32_t bar = sb + 8 * (B_X + h);
  mbar_expect(bar, 10240);
  tma5d(sb + SM_RING + R_X + h * 10240, &P.mX, 0, 0, 0, 5 * h, 191 - ibase(b), bar);
}
__device__ __forceinline__ void load_box(const Params& P, uint32_t sb, int b, int cls) {
  const uint32_t bar = sb + 8 * (B_BOX + cls);
  mbar_expect(bar, 10240);
  tma2d(box_base(sb, cls), &P.mWm, mod_col(16 * cls + (b >> 3)), 80 * (b & 7), bar);
}
__device__ __forceinline__ void load_ssm(const Params& P, uint32_t sb, int b, int r) {
  const uint32_t bar = sb + 8 * (B_S + r);
  mbar_expect(bar, 16 * 288);
  tma3d(chan_base(sb, r) + 128, &P.mS, 0, 0, 128 * r + b, bar);
}
__device__ __forceinline__ void k1_job(uint32_t sb, int r, int tid) {
  const uint32_t a0 = chan_base(sb, r) + 128 + 16 * tid + 32 * (tid >> 4);
  mbar_wait(sb + 8 * (B_S + r), 0);
#pragma unroll
  for (int n = 0; n < 2; n++) {
    const uint32_t a = a0 + 2304 * n;
    const uint4 v = lds128(a);
    const uint32_t pv = lds32(a - ((tid & 15) ? 4 : 36));
    sts128(a + K1OFF, make_uint4(__byte_perm(pv, v.x, 0x5432), __byte_perm(v.x, v.y, 0x5432), __byte_perm(v.y, v.z, 0x5432), __byte_perm(v.z, v.w, 0x5432)));
  }
}

__global__ void __launch_bounds__(512, 1) fused_kernel(const __grid_constant__ Params P) {
  extern __shared__ __align__(1024) char smem_raw[];
  const uint32_t sb = smem_u32(smem_raw), ring = sb + SM_RING;
  const int b = blockIdx.x, m = b >> 3, s = b & 7;
  {
    const int wi = __shfl_sync(0xffffffffu, threadIdx.x >> 5, 0);
    if ((threadIdx.x & 31) == 0) {
      if (wi == 12 || wi == 13) {
        mbar_init(sb + 8 * (B_B + wi - 12), 1);
        fence_async_s();
        load_kv(P, sb, b, wi - 12);
        STAMP(64 + wi - 12);
      } else if (wi == 14) {
        asm volatile("prefetch.tensormap [%0];" ::"l"(&P.mX) : "memory");
        mbar_init(sb + 8 * B_X, 1);
        mbar_init(sb + 8 * (B_X + 1), 1);
        fence_async_s();
        load_x(P, sb, b, 0);
        STAMP(66);
      } else if (wi == 15) {
#pragma unroll
        for (int i = 1; i < 10; i++) asm volatile("prefetch.tensormap [%0];" ::"l"(&P.mX + i) : "memory");
      } else {
#pragma unroll 1
        for (int i = 2 + wi; i < B_NUM; i += 12)
          if (i != B_X && i != B_X + 1) mbar_init(sb + 8 * i, i >= B_Z ? 4 : i == B_ST0 ? 5 : (i >= B_F1 && i < B_FB) ? 2 : 1);
      }
    }
  }
  if (threadIdx.x < 40) {
    int c = threadIdx.x & 7;
    sts128(chan_base(sb, threadIdx.x >> 3) + (c < 2 ? 80 + c * K1OFF : KSZ + 4096 + (c - 2) * 16), make_uint4(0, 0, 0, 0));
  }
  if (threadIdx.x < 384) fence_async_s();
  __syncthreads();
  STAMPIF(threadIdx.x == 0, 55);
  const int wg = __shfl_sync(0xffffffffu, threadIdx.x >> 7, 0);
  const int tid = threadIdx.x & 127, lane = tid & 31;
  const int w = __shfl_sync(0xffffffffu, tid >> 5, 0);

  if (wg == 3) {
    STAMPIF(tid == 0, 83);
    asm volatile("setmaxnreg.dec.sync.aligned.u32 24;");
    STAMPIF(tid == 0, 84);
    if (w == 0) {
      if (lane == 0) {
        STAMP(62);
        mbar_wait(sb + 8 * (B_B + 0), 0);
        STAMP(56);
        load_x(P, sb, b, 1);
        mbar_wait(sb + 8 * (B_B + 1), 0);
        STAMP(57);
        load_kv(P, sb, b, 2);
        mbar_wait(sb + 8 * B_X, 0);
        load_ssm(P, sb, b, 0);
        load_ssm(P, sb, b, 1);
        mbar_wait(sb + 8 * (B_X + 1), 0);
        STAMP(61);
        load_box(P, sb, b, 0);
        mbar_wait(sb + 8 * (B_B + 2), 0);
        STAMP(58);
        load_kv(P, sb, b, 3);
        mbar_wait(sb + 8 * (B_S + 1), 0);
        STAMP(67);
        load_kv(P, sb, b, 4);
        mbar_wait(sb + 8 * B_BOX, 0);
        STAMP(68);
        load_ssm(P, sb, b, 2);
        load_ssm(P, sb, b, 3);
        mbar_wait(sb + 8 * (B_B + 3), 0);
        STAMP(59);
        load_ssm(P, sb, b, 4);
        mbar_wait(sb + 8 * (B_B + 4), 0);
        STAMP(60);
        load_box(P, sb, b, 1);
        mbar_wait(sb + 8 * B_XFREE, 0);
        mbar_wait(sb + 8 * (B_KVS + 2), 0);
#pragma unroll 1
        for (int it = 0; it < 20; it++) {
          int st = it % 6;
          mbar_wait(sb + 8 * (B_E1 + st), (it / 6) & 1);
          uint32_t a = ring + st * 32768 + 8192, fb = sb + 8 * (B_F1 + st);
          mbar_expect(fb, 24576);
#pragma unroll
          for (int j = 0; j < 3; j++) {
            tma2d(a + 8192 * j, &P.mG, 192 * s + 64 * j, 32 * it, fb);
            tma2d(a + 8192 * j + 4096, &P.mU, 192 * s + 64 * j, 32 * it, fb);
          }
          if (it == 1) {
            load_box(P, sb, b, 2);
            mbar_wait(sb + 8 * (B_BOX + 1), 0);
            STAMP(69);
            if (b < 96) load_box(P, sb, b, 3);
          }
        }
#pragma unroll 1
        for (int k = 0; k < 24; k++) {
          int sl = k < 12 ? k : k - 12;
          int g1 = (sl >> 1) + 2; if (g1 >= 6) g1 -= 6;
          if (k < 12) mbar_wait(sb + 8 * (B_E1 + g1), g1 >= 2); else mbar_wait(sb + 8 * (B_EB + sl), 0);
          uint32_t a = ring + g1 * 32768 + 8192 + (sl & 1) * 12288, fb = sb + 8 * (B_FB + sl);
          int n = k / 6, kg = 4 * (6 * ((s + 2 * n) & 7) + k - 6 * n);
          mbar_expect(fb, 12288);
#pragma unroll 1
          for (int at = 0; at < 3; at++) {
            if (k < 6) tma5d(a + at * 4096, &P.mDn, 64 * at, 0, 0, kg, s >> 1, fb);
            else tma5d(a + at * 4096, &P.mDp, 64 * at, 0, kg, 0, s >> 1, fb);
          }
        }
      }
    } else if (w == 1) {
      if (lane == 0) {
        const uint32_t e1 = __ldcg(g_epoch + b) + 1;
#pragma unroll 1
        for (int r = 0; r < 5; r++) {
          flag_wait(FL_KV + 2 * r + (b >> 6), e1 * 64);
          fence_async_g();
          uint32_t bar = sb + 8 * (B_U + r);
          mbar_expect(bar, 4096);
          bulk_g2s(chan_base(sb, r) + KSZ, g_kvT + (128 * r + b) * S_, 4096, bar);
          STAMP(40 + r);
        }
#pragma unroll 1
        for (int it = 0; it < 20; it++) {
          int st = it % 6;
          if ((it & 3) == 0) { flag_wait(FL_R + (it >> 2), e1 * 128); fence_async_g(); STAMP(45 + (it >> 2)); }
          mbar_wait(sb + 8 * (B_E1 + st), (it / 6) & 1);
          uint32_t fb = sb + 8 * (B_F1 + st);
          mbar_expect(fb, 8192);
          tma3d(ring + st * 32768, &P.mA, 0, 32 * it, m * 2, fb);
        }
#pragma unroll 1
        for (int n = 1; n < 4; n++) {
          int src = 8 * m + ((s + 2 * n) & 7);
          flag_wait(FL_H + src, e1 * 4);
          fence_async_g();
          STAMP(50 + n);
#pragma unroll 1
          for (int k = 0; k < 6; k++) {
            int g1 = k + 2; if (g1 >= 6) g1 -= 6;
            if (n == 1) mbar_wait(sb + 8 * (B_E1 + g1), g1 >= 2); else mbar_wait(sb + 8 * (B_EA + k), n & 1);
            uint32_t fb = sb + 8 * (B_FA + k);
            mbar_expect(fb, 8192);
            bulk_g2s(ring + g1 * 32768, g_HH + (src * 6 + k) * 4096, 8192, fb);
          }
        }
      }
    } else if (w == 2) {
      const uint32_t e1 = __ldcg(g_epoch + b) + 1;
      if (lane == 0) {
        mbar_expect(sb + 8 * B_RECV, 20480);
        mbar_expect(sb + 8 * (B_RECV + 1), 20480);
      }
      mbar_wait(sb + 8 * B_MB, 0);
      rdwait(sb, box_rdback(b, 0, lane));
      __syncwarp();
      if (lane == 0) flag_add(FL_M + (b >> 3));
      mod_fin<2>(sb, b, 0, e1, lane);
      STAMPIF(lane == 0, 36);
      const int grp = m % 6;
#pragma unroll 1
      for (int r = 0; r < 5; r++) {
        mbar_wait(sb + 8 * (B_EW + r), 0);
        uint32_t v0 = rdback(g_AT + (128 * r + b) * S_ + 64 * lane), v1 = rdback(g_x1T + (128 * r + b) * S_ + 64 * lane);
        rdwait(sb, v0 ^ v1);
        __syncwarp();
        if (lane == 0) {
          flag_add(FL_R + r);
          if (m < 12) {
            mbar_expect(sb + 8 * B_ST0, 4096);
            tma2d(sb + SM_Z + r * 4096, (grp & 1) ? &P.mU : &P.mG, 192 * s + 64 * (grp >> 1), (m < 6 ? 0 : 320) + 32 * r, sb + 8 * B_ST0);
          }
        }
      }
      if (lane == 0) {
        if (m < 12) {
          flag_wait(FL_F, e1 * 40);
          fence_async_g();
          STAMP(34);
          mbar_expect(sb + 8 * B_CB, 1280);
          bulk_g2s(sb + SM_CB, g_cbsb + (m < 6 ? 0 : 640), 1280, sb + 8 * B_CB);
          mbar_wait(sb + 8 * B_ZF, 0);
        }
        flag_wait(FL_R + 4, e1 * 128);
        fence_async_g();
        mbar_expect(sb + 8 * B_X1, 20480);
        tma3d(sb + SM_Z, &P.mX1, 0, 80 * s, m * 2, sb + 8 * B_X1);
        flag_wait(FL_S + m, e1 * 8);
        flag_wait(FL_C + s, e1 * 48);
        fence_async_g();
        STAMP(54);
        mbar_expect(sb + 8 * B_EXT, 6144 + 2048);
        bulk_g2s(sb + SM_EXT, g_cimg + s * 3072, 6144, sb + 8 * B_EXT);
        bulk_g2s(sb + SM_STAT, g_stat + 128 * m, 2048, sb + 8 * B_EXT);
        mbar_wait(sb + 8 * (B_EB + 3), 0);
        mbar_wait(sb + 8 * (B_EB + 3), 1);
        mbar_arrive_remote(mapa(sb + 8 * B_PEER, (b & 1) ^ 1));
      }
    } else {
      const uint32_t e1 = __ldcg(g_epoch + b) + 1;
#pragma unroll 1
      for (int r = 2; r < 5; r++) {
        mbar_wait(sb + 8 * (B_KVS + r - 2), 0);
        kv_signal(sb, b, r, lane);
        STAMPIF(lane == 0, 20 + r);
      }
      mbar_wait(sb + 8 * (B_MB + 1), 0);
      if (lane == 0) mbar_arrive(sb + 8 * (B_E1 + 4));
      rdwait(sb, box_rdback(b, 1, lane));
      __syncwarp();
      if (lane == 0) flag_add(FL_M + 16 + (b >> 3));
      mbar_wait(sb + 8 * (B_MB + 2), 0);
      if (lane == 0) mbar_arrive(sb + 8 * (B_E1 + 5));
      rdwait(sb, box_rdback(b, (lane & 2) && b < 96 ? 3 : 2, lane));
      __syncwarp();
      if (lane == 0 || (lane == 1 && b < 96)) flag_add(FL_M + 32 + 16 * lane + (b >> 3));
      mod_fin<2>(sb, b, 2, e1, lane);
      STAMPIF(lane == 0, 37);
      mod_fin<1>(sb, b, 4, e1, lane);
      STAMPIF(lane == 0, 38);
      const float* p = g_modP + (lane & 7) * 3840 + 4 * (lane >> 3);
      if (b < 40) {
        if (lane < 2) flag_wait(FL_M + (lane ? 40 + (b >> 2) : 8 * (b >> 3) + 6 + ((b >> 2) & 1)), e1 * 8);
        __syncwarp();
        const float4 c0 = __ldcg((const float4*)(p + 4 * 640 + 16 * b)), c1 = __ldcg((const float4*)(p + 3 * 640 + 16 * b));
        float a[8] = {c0.x, c0.y, c0.z, c0.w, c1.x, c1.y, c1.z, c1.w};
        bfly<8>(a, 4, lane & 4); bfly<4>(a, 2, lane & 2); bfly<2>(a, 1, lane & 1);
        float t = rbf(a[0]);
        if (!(lane & 4)) t += 1.f;
        uint16_t* d = (uint16_t*)g_cbsb + 32 * b;
        d[(lane & 16) + 2 * (lane & 4) + ((lane & 8) >> 1) + (lane & 3)] = (uint16_t)pack2(t, 0.f);
        rdwait(sb, rdback(d));
        __syncwarp();
        if (lane == 0) flag_add(FL_F);
        STAMPIF(lane == 0, 39);
      }
      if (lane < 10) flag_wait(FL_M + 50 + lane, e1 * 8);
      __syncwarp();
#pragma unroll 1
      for (int n = 0; n < 5; n++) {
        const float4 c0 = __ldcg((const float4*)(p + 5 * 640 + 80 * s + 16 * n));
        float a[4] = {c0.x, c0.y, c0.z, c0.w};
        bfly<4>(a, 2, lane & 2); bfly<2>(a, 1, lane & 1);
        a[0] += __shfl_xor_sync(0xffffffffu, a[0], 4);
        sts16(sb + SM_SMALL + SMALL_GB + 32 * n + (lane & 24) + 2 * (lane & 3), pack2(a[0], 0.f));
      }
      __syncwarp();
      if (lane == 0) mbar_arrive(sb + 8 * B_GB);
    }
  } else if (wg == 2) {
    asm volatile("setmaxnreg.dec.sync.aligned.u32 40;");
    const uint32_t e1 = __ldcg(g_epoch + b) + 1;
    if (tid < 80) {
      float c = __bfloat162float(P.c[80 * (b & 7) + tid]);
      sts16(sb + SM_SMALL + SMALL_S + 2 * tid, pack2(__fdividef(c, 1.f + __expf(-c)), 0.f));
    }
    fence_async_s();
    bar_sync(5, 128);
#pragma unroll 1
    for (int r = 2; r < 5; r++) {
      kv_job(sb, b, r, tid);
      __syncwarp();
      if (lane == 0) mbar_arrive(sb + 8 * (B_KVS + r - 2));
      if (r == 2) {
        mod_box(sb, b, 0, tid);
        __syncwarp();
        if (lane == 0) mbar_arrive(sb + 8 * B_MB);
        STAMPIF(tid == 0, 27);
      }
    }
#pragma unroll 1
    for (int r = 2; r < 4; r++) {
      k1_job(sb, r, tid);
      __syncwarp();
      if (lane == 0) mbar_arrive(sb + 8 * (B_K + r - 2));
    }
    if (lane == 0) flag_wait(FL_X, e1 * 256);
    __syncwarp();
    STAMPIF(tid == 0, 28);
#pragma unroll 1
    for (int r = 0; r < 5; r++) {
      uint4 xh[4];
#pragma unroll
      for (int n = 0; n < 4; n++) xh[n] = __ldcg((const uint4*)(g_XH + (128 * r + b) * (2 * S_)) + tid + 128 * n);
      mbar_wait(sb + 8 * (B_MF + (r >> 1)), 0);
      const uint4 md = lds128(sb + SM_SMALL + SMALL_MOD + 16 * r);
      mbar_wait(sb + 8 * (B_Z + r), 0);
      const uint32_t za = sb + SM_Z + r * 4096 + 8 * tid;
      uint2 *pa = (uint2*)(g_AT + (128 * r + b) * S_) + tid, *px = (uint2*)(g_x1T + (128 * r + b) * S_) + tid;
#pragma unroll
      for (int n = 0; n < 4; n++) {
        uint2 z = lds64(za + 1024 * n);
        uint32_t x0 = hadd(xh[n].x, hmul(md.z, hmul(hadd(hmul(xh[n].z, md.y), md.x), z.x)));
        uint32_t x1 = hadd(xh[n].y, hmul(md.z, hmul(hadd(hmul(xh[n].w, md.y), md.x), z.y)));
        pa[128 * n] = make_uint2(hmul(x0, md.w), hmul(x1, md.w));
        px[128 * n] = make_uint2(x0, x1);
      }
      __syncwarp();
      if (lane == 0) mbar_arrive(sb + 8 * (B_EW + r));
      STAMPIF(tid == 0, 29 + r);
      if (r == 0) {
        k1_job(sb, 4, tid);
        __syncwarp();
        if (lane == 0) mbar_arrive(sb + 8 * (B_K + 2));
      }
      if (r == 1) {
#pragma unroll 1
        for (int cls = 1; cls < 4; cls++) {
          if (cls < 3 || b < 96) mod_box(sb, b, cls, tid);
          __syncwarp();
          if (lane == 0 && cls != 2) mbar_arrive(sb + 8 * (B_MB + ((cls + 1) >> 1)));
        }
      }
    }
    float a[8];
    if (m < 12) {
      const int grp = m % 6;
      const uint64_t da = mkdesc(sb + SM_Z, 4096, 1024, 1), db = mkdesc(sb + SM_CB, 32, 128, 0);
      mbar_wait(sb + 8 * B_CB, 0);
#pragma unroll 1
      for (int h = 0; h < 2; h++) {
        mbar_wait(sb + 8 * (h ? B_ST1 : B_ST0), 0);
        wg_fence();
#pragma unroll
        for (int n = 0; n < 10; n++) wgmma_ss_n8<1, 0>(a, da + 128 * n, db + 40 * h + 4 * n, (h | n) != 0);
        wg_commit();
        wg_wait<0>();
        if (h == 0) {
          bar_sync(5, 128);
          if (tid == 0) {
            mbar_expect(sb + 8 * B_ST1, 20480);
#pragma unroll 1
            for (int r = 0; r < 5; r++)
              tma2d(sb + SM_Z + r * 4096, (grp & 1) ? &P.mU : &P.mG, 192 * s + 64 * (grp >> 1), (m < 6 ? 160 : 480) + 32 * r, sb + 8 * B_ST1);
          }
          __syncwarp();
        }
      }
#pragma unroll
      for (int i = 0; i < 4; i++) asm volatile("" : "+f"(a[i])::"memory");
      if (lane == 0) mbar_arrive(sb + 8 * B_ZF);
      const int row = (m < 6 ? 0 : 4) + (lane & 3);
      uint16_t* dst = (uint16_t*)g_cimg + s * 3072 + grp * 512 + row * 64 + (lane >> 2);
#pragma unroll
      for (int j = 0; j < 2; j++) {
        const float c1 = __shfl_sync(0xffffffffu, a[2 * j], lane & 28), c2 = __shfl_sync(0xffffffffu, a[2 * j + 1], lane & 28);
        const float t = (lane & 2) ? c2 : c1, hi = rbf(t);
        dst[((2 * w + j) ^ row) << 3] = (uint16_t)pack2((lane & 1) ? t - hi : hi, 0.f);
      }
      rdwait(sb, rdback(dst - (lane >> 2) + (((2 * w) ^ row) << 3)));
      __syncwarp();
      if (lane == 0) flag_add(FL_C + s);
      STAMPIF(tid == 0, 35);
    }
    {
      if (lane == 0) flag_wait(FL_R + 4, e1 * 128);
      __syncwarp();
      const bf16* src = g_x1T + 16 * b + 4 * (lane & 3);
      const uint2 pq = __ldcg((const uint2*)src);
      const float pv0 = blo(pq.x), pv1 = bhi(pq.x), pv2 = blo(pq.y), pv3 = bhi(pq.y);
#pragma unroll
      for (int j = 0; j < 8; j++) a[j] = 0.f;
      src += ((lane >> 2) + 8 * w) * S_;
#pragma unroll 1
      for (int n0 = 0; n0 < 20; n0 += 5) {
        uint2 v[5];
#pragma unroll
        for (int n = 0; n < 5; n++) v[n] = __ldcg((const uint2*)(src + n * 32 * S_));
        src += 160 * S_;
#pragma unroll
        for (int n = 0; n < 5; n++) {
          const float e0 = blo(v[n].x) - pv0, e1_ = bhi(v[n].x) - pv1, e2 = blo(v[n].y) - pv2, e3 = bhi(v[n].y) - pv3;
          a[0] += e0; a[1] += e1_; a[2] += e2; a[3] += e3;
          a[4] += e0 * e0; a[5] += e1_ * e1_; a[6] += e2 * e2; a[7] += e3 * e3;
        }
      }
      bfly<8>(a, 16, lane & 16); bfly<4>(a, 8, lane & 8); bfly<2>(a, 4, lane & 4);
      sts32(sb + SM_SMALL + SMALL_RED + w * 128 + (lane >> 4) * 64 + (4 * (lane & 3) + ((lane >> 2) & 3)) * 4, __float_as_uint(a[0]));
      bar_sync(5, 128);
      if (w == 3) {
        uint32_t v = 0;
        if (lane < 16) {
          float s1 = 0.f, s2 = 0.f;
#pragma unroll
          for (int j = 0; j < 4; j++) {
            s1 += __uint_as_float(lds32(sb + SM_SMALL + SMALL_RED + j * 128 + lane * 4));
            s2 += __uint_as_float(lds32(sb + SM_SMALL + SMALL_RED + j * 128 + 64 + lane * 4));
          }
          float p0 = __bfloat162float(__ldcg(g_x1T + 16 * b + lane));
          float mu = s1 * (1.f / D_), var = fmaxf(s2 * (1.f / D_) - mu * mu, 0.f);
          float sd = rbf(__fsqrt_rn(rbf(rbf(var) + 1e-5f)));
          const uint32_t hm = pack2(-0.5f * (p0 + mu), -0.5f * (p0 + mu)), hs = pack2(0.5f * sd, 0.5f * sd);
          g_stat[16 * b + lane] = make_uint4(hm, hs, hm, hs);
          v = rdback(g_stat + 16 * b + lane);
        }
        rdwait(sb, v);
        __syncwarp();
        if (lane == 0) flag_add(FL_S + m);
        STAMPIF(lane == 0, 21);
      }
    }
    {
      mbar_wait(sb + 8 * (B_HH + (w >> 1)), 0);
      const bf16* p = g_HH + (b * 6 + 3 * (w & 1)) * 4096 + (w >> 1) * 2048 + lane * 64;
      uint32_t v0 = rdback(p), v1 = rdback(p + 4096), v2 = rdback(p + 8192);
      rdwait(sb, v0 ^ v1 ^ v2);
      __syncwarp();
      if (lane == 0) flag_add(FL_H + b);
      STAMPIF(tid == 0, 50);
    }
  } else {
    STAMPIF(threadIdx.x == 0, 81);
    asm volatile("setmaxnreg.inc.sync.aligned.u32 224;");
    STAMPIF(threadIdx.x == 0, 82);
    const int g = lane >> 2, q = lane & 3;
    if (wg == 1) bar_arrive(1, 256);
    if (tid < 2) mbar_arrive(sb + 8 * (B_E1 + tid));
    if (tid == 3 && wg == 1) mbar_arrive(sb + 8 * (B_E1 + 5));
    uint32_t dv = *(const uint16_t*)(P.ssm_D + 128 * wg + b);
    {
      const int t2 = threadIdx.x, w2 = 4 * wg + w;
      STAMPIF(t2 == 0, 20);
      kv_job(sb, b, wg, tid);
      bar_sync(3 + wg, 128);
      STAMPIF(t2 == 0, 78);
      if (w == 0) kv_signal(sb, b, wg, lane);
      STAMPIF(tid == 0, 1 + wg);
      mbar_wait(sb + 8 * B_X, 0);
      mbar_wait(sb + 8 * (B_X + 1), 0);
      STAMPIF(t2 == 0, 25);
      const uint32_t xr = ring + R_X + (15 - (t2 >> 4)) * 128;
      float pv = blo(lds32(xr)), s1 = 0.f, s2 = 0.f;
#pragma unroll
      for (int n = 0; n < 5; n++) {
        uint4 v = lds128(xr + 16 * (t2 & 7) + 2048 * ((t2 >> 3) & 1) + 4096 * n);
        uint32_t u[4] = {v.x, v.y, v.z, v.w};
#pragma unroll
        for (int j = 0; j < 4; j++) {
          float a = blo(u[j]) - pv, c = bhi(u[j]) - pv;
          s1 += a + c; s2 += a * a; s2 += c * c;
        }
      }
      uint32_t r[5][4];
      const uint32_t la = ring + R_X + wg * 2048 + (15 - (lane & 15)) * 128 + (((2 * w + (lane >> 4)) ^ (~lane & 7)) << 4);
#pragma unroll
      for (int n = 0; n < 5; n++) ldsm4t(r[n], la + n * 4096);
      STAMPIF(t2 == 0, 70);
#pragma unroll
      for (int o = 1; o < 16; o <<= 1) { s1 += __shfl_xor_sync(0xffffffffu, s1, o); s2 += __shfl_xor_sync(0xffffffffu, s2, o); }
      if ((t2 & 15) == 0) {
        float mu = s1 * (1.f / D_), var = fmaxf(s2 * (1.f / D_) - mu * mu, 0.f);
        float sd = rbf(__fsqrt_rn(rbf(rbf(var) + 1e-5f)));
        sts16(sb + SM_SMALL + SMALL_XM + 2 * (t2 >> 4), pack2(pv + mu, 0.f));
        sts32(sb + SM_SMALL + SMALL_XM + 32 + 4 * (t2 >> 4), __float_as_uint(__frcp_rn(sd)));
      }
      STAMPIF(t2 == 0, 71);
      bar_sync(6, 256);
      STAMPIF(t2 == 0, 72);
      if (t2 == 0) mbar_arrive(sb + 8 * B_XFREE);
      const uint32_t m0 = lds32(sb + SM_SMALL + SMALL_XM + 4 * q), m1 = lds32(sb + SM_SMALL + SMALL_XM + 16 + 4 * q);
      const uint2 r0 = lds64(sb + SM_SMALL + SMALL_XM + 32 + 8 * q), r1 = lds64(sb + SM_SMALL + SMALL_XM + 64 + 8 * q);
      bf16* dst = g_XH + (16 * w2 + g) * (2 * S_) + b * 32 + q * 8;
#pragma unroll
      for (int n = 0; n < 5; n++) {
#pragma unroll
        for (int j = 0; j < 2; j++) {
          uint32_t a = hsub(r[n][2 * j], m0), c = hsub(r[n][2 * j + 1], m1);
          *(uint4*)(dst + (128 * n + 8 * j) * (2 * S_)) =
              make_uint4(r[n][2 * j], r[n][2 * j + 1], pack2(blo(a) * __uint_as_float(r0.x), bhi(a) * __uint_as_float(r0.y)),
                         pack2(blo(c) * __uint_as_float(r1.x), bhi(c) * __uint_as_float(r1.y)));
        }
        STAMPIF(t2 == 0, 73 + n);
      }
      __syncwarp();
      const bf16* p = g_XH + (16 * w2 + (lane & 15) + 128 * (lane >> 4)) * (2 * S_) + b * 32;
      uint32_t v0 = rdback(p), v1 = rdback(p + 256 * (2 * S_)), v2 = rdback(p + (lane < 16 ? 512 : 0) * (2 * S_));
      STAMPIF(t2 == 0, 26);
      k1_job(sb, wg, tid);
      STAMPIF(t2 == 0, 79);
      rdwait(sb, v0 ^ v1 ^ v2);
      bar_sync(3 + wg, 128);
      if (tid == 32) flag_add(FL_X);
      STAMPIF(t2 == 0, 80);
    }
    {
      const int b0 = (g >> 1) & 1, b1 = g >> 2, u = q + 4 * b0 - w;
      const uint32_t fo = 128 + (g & 1) * K1OFF + 288 * b1 + 4 * u, fo0 = fo - (u < 0 ? 32 : 0);
      const uint32_t dsel = (b1 == 0 && u == 0) ? ((g & 1) ? 0x1044 : 0x4410) : 0x4444;
      const bool wrap = b0 && q == 0;
      const int src1 = b0 ? ((lane & 20) | ((q - 1) & 3)) : (lane | 8);
#pragma unroll 1
      for (int ch = wg; ch < 5; ch += 2) {
        const uint32_t base = chan_base(sb, ch);
        if (ch >= 2) { mbar_wait(sb + 8 * (B_K + ch - 2), 0); mbar_wait(sb + 8 * (B_S + ch), 0); }
        const uint32_t fa = base + fo, fa0 = base + fo0;
        uint32_t af[16][4];
#pragma unroll
        for (int j = 0; j < 16; j++) {
          const int o = 64 * (j & 1) + 576 * (j >> 1);
          af[j][0] = lds32(((j & 1) ? fa : fa0) + o); af[j][1] = lds32(fa + o + 128); af[j][2] = lds32(fa + o + 32); af[j][3] = lds32(fa + o + 160);
        }
        af[0][0] = hadd(af[0][0], __byte_perm(dv, 0, dsel));
        if (ch < 3) dv = *(const uint16_t*)(P.ssm_D + 128 * (ch + 2) + b);
        mbar_wait(sb + 8 * (B_U + ch), 0);
        float acc[128];
        const uint64_t db = mkdesc(base + KSZ, 32, 128, 0);
        bar_sync(1 + wg, 256);
        STAMPIF(tid == 0, 3 + ch);
        wg_fence();
        wgmma_rs_n64<0>(acc + 96, af[0], db + 192, 0);
        wgmma_rs_n192<0>(acc, af[0], db, 0);
        wgmma_rs_n64<0>(acc + 96, af[1], db + 196, 1);
        wgmma_rs_n192<0>(acc, af[1], db + 4, 1);
        wgmma_rs_n32<0>(acc + 96, af[2], db + 224, 1);
        wgmma_rs_n192<0>(acc, af[2], db + 32, 1);
        wgmma_rs_n32<0>(acc + 96, af[3], db + 228, 1);
        wgmma_rs_n192<0>(acc, af[3], db + 36, 1);
        wgmma_rs_n192<0>(acc, af[4], db + 64, 1);
        wgmma_rs_n192<0>(acc, af[5], db + 68, 1);
        wgmma_rs_n160<0>(acc, af[6], db + 96, 1);
        wgmma_rs_n160<0>(acc, af[7], db + 100, 1);
        wgmma_rs_n128<0>(acc, af[8], db + 128, 1);
        wgmma_rs_n128<0>(acc, af[9], db + 132, 1);
        wgmma_rs_n96<0>(acc, af[10], db + 160, 1);
        wgmma_rs_n96<0>(acc, af[11], db + 164, 1);
        bar_arrive(2 - wg, 256);
        wgmma_rs_n64<0>(acc, af[12], db + 192, 1);
        wgmma_rs_n64<0>(acc, af[13], db + 196, 1);
        wgmma_rs_n32<0>(acc, af[14], db + 224, 1);
        wgmma_rs_n32<0>(acc, af[15], db + 228, 1);
        wg_commit();
        wg_wait<0>();
#pragma unroll
        for (int i = 0; i < 128; i++) asm volatile("" : "+f"(acc[i])::"memory");
        bar_sync(3 + wg, 128);
        if (tid == 0) mbar_arrive(sb + 8 * (B_E1 + 2 + (ch >> 1)));
        float S0[33], T[34];
#pragma unroll
        for (int i = 0; i < 31; i++) S0[i] = acc[4 * i] + acc[4 * i + 6];
        S0[31] = acc[124]; S0[32] = 0.f;
#pragma unroll
        for (int i = 0; i < 32; i++) {
          float s1 = i < 31 ? acc[4 * i + 1] + acc[4 * i + 7] : acc[125];
          T[i] = (wrap ? S0[i + 1] : S0[i]) + __shfl_sync(0xffffffffu, s1, src1);
        }
        T[32] = 0.f; T[33] = 0.f;
        uint32_t zz[8];
#pragma unroll
        for (int mu = 0; mu < 8; mu++) {
          float y0 = (b1 ? T[4 * mu + 4] : T[4 * mu]) + __shfl_xor_sync(0xffffffffu, T[4 * mu + 2], 16);
          float y1 = (b1 ? T[4 * mu + 5] : T[4 * mu + 1]) + __shfl_xor_sync(0xffffffffu, T[4 * mu + 3], 16);
          zz[mu] = pack2(y0, y1);
        }
        sts128(sb + SM_Z + ch * 4096 + tid * 32, make_uint4(zz[0], zz[4], zz[1], zz[5]));
        sts128(sb + SM_Z + ch * 4096 + tid * 32 + 16, make_uint4(zz[2], zz[6], zz[3], zz[7]));
        __syncwarp();
        if (lane == 0) mbar_arrive(sb + 8 * (B_Z + ch));
        STAMPIF(tid == 0, 8 + ch);
      }
      if (wg == 1) bar_sync(2, 256);
    }
    uint32_t hh[48];
    {
      float ga[192];
      float* ua = ga + 96;
      const uint64_t da0 = mkdesc(ring + wg * 4096, 4096, 1024, 1), db0 = mkdesc(ring + 8192, 4096, 1024, 1);
      int st = 0, ph = 0;
#pragma unroll 1
      for (int it = 0; it < 20; it++) {
        mbar_wait(sb + 8 * (B_F1 + st), ph);
        STAMPIF(tid == 0 && it == 0, 13 + wg);
        const uint64_t da = da0 + st * 2048, db = db0 + st * 2048;
        wg_fence();
        wgmma_ss_n192<1, 1>(ga, da, db, it != 0);
        wgmma_ss_n192<1, 1>(ua, da, db + 768, it != 0);
        wgmma_ss_n192<1, 1>(ga, da + 128, db + 128, 1);
        wgmma_ss_n192<1, 1>(ua, da + 128, db + 128 + 768, 1);
        wg_commit();
        wg_wait<1>();
        if (it > 0 && tid == 0) mbar_arrive(sb + 8 * (B_E1 + (st == 0 ? 5 : st - 1)));
        if (++st == 6) { st = 0; ph ^= 1; }
      }
      mbar_wait(sb + 8 * B_EXT, 0);
      const uint64_t de = mkdesc(sb + SM_EXT, 1024, 0, 1), ds = mkdesc(sb + SM_STAT + wg * 1024, 0, 128, 0);
      wg_fence();
      wgmma_ss_n192<0, 1>(ga, ds, de, 1);
      wgmma_ss_n192<0, 1>(ua, ds, de + 192, 1);
      wg_commit();
      wg_wait<1>();
      if (tid == 0) mbar_arrive(sb + 8 * (B_E1 + 1));
      wg_wait<0>();
#pragma unroll
      for (int i = 0; i < 192; i++) asm volatile("" : "+f"(ga[i])::"memory");
      STAMPIF(tid == 0, 15 + wg);
#pragma unroll
      for (int i = 0; i < 48; i++) {
        const int j = 64 * (i >> 4) + 2 * (i & 15);
        hh[i] = pack2(ga[j] * ga[j + 32], ga[j + 1] * ga[j + 33]);
      }
    }
    float acc[80];
    {
      bf16* dst = g_HH + b * 6 * 4096 + (64 * wg + 16 * w + g) * 32 + ((q ^ ((g >> 1) & 3)) << 3);
#pragma unroll
      for (int k = 0; k < 6; k++) {
        *(uint4*)(dst + k * 4096) = make_uint4(hh[8 * k], hh[8 * k + 2], hh[8 * k + 4], hh[8 * k + 6]);
        *(uint4*)(dst + k * 4096 + 256) = make_uint4(hh[8 * k + 1], hh[8 * k + 3], hh[8 * k + 5], hh[8 * k + 7]);
      }
      __syncwarp();
      if (lane == 0) mbar_arrive(sb + 8 * (B_HH + wg));
      const uint64_t db0 = mkdesc(ring + 8192, 4096, 1024, 1), da0 = mkdesc(ring + wg * 4096, 16, 512, 2);
#pragma unroll
      for (int k = 0; k < 6; k++) {
        mbar_wait(sb + 8 * (B_FB + k), 0);
        const uint64_t db = db0 + ((k >> 1) + 2) * 2048 + (k & 1) * 768;
        wg_fence();
        wgmma_rs_n160<1>(acc, hh + 8 * k, db, k != 0);
        wgmma_rs_n160<1>(acc, hh + 8 * k + 4, db + 128, 1);
        wg_commit();
        wg_wait<1>();
        if (k > 0 && tid == 0) mbar_arrive(sb + 8 * (B_EB + k - 1));
      }
      STAMPIF(tid == 0, 17);
      int ka = 0, pa = 0;
#pragma unroll 1
      for (int k = 6; k < 24; k++) {
        const int sl = k < 12 ? k : k - 12;
        int gb_ = (sl >> 1) + 2; if (gb_ >= 6) gb_ -= 6;
        int ga_ = ka + 2; if (ga_ >= 6) ga_ -= 6;
        mbar_wait(sb + 8 * (B_FB + sl), k >= 12);
        mbar_wait(sb + 8 * (B_FA + ka), pa);
        const uint64_t db = db0 + gb_ * 2048 + (sl & 1) * 768, da = da0 + ga_ * 2048;
        wg_fence();
        wgmma_ss_n160<0, 1>(acc, da, db, 1);
        wgmma_ss_n160<0, 1>(acc, da + 2, db + 128, 1);
        wg_commit();
        wg_wait<1>();
        if (tid == 0) {
          mbar_arrive(sb + 8 * (B_EB + (sl == 0 ? 11 : sl - 1)));
          if (k > 6) mbar_arrive(sb + 8 * (B_EA + (ka == 0 ? 5 : ka - 1)));
        }
        if (++ka == 6) { ka = 0; pa ^= 1; }
      }
    }
    uint32_t xr[20], gbv[10];
    mbar_wait(sb + 8 * B_X1, 0);
    mbar_wait(sb + 8 * B_GB, 0);
    {
      const uint32_t la = sb + SM_Z + wg * 10240 + (8 * (lane >> 4) + (lane & 7)) * 128 + (((2 * w + ((lane >> 3) & 1)) ^ (lane & 7)) << 4);
#pragma unroll
      for (int i = 0; i < 5; i++) ldsm4t(xr + 4 * i, la + i * 2048);
#pragma unroll
      for (int i = 0; i < 10; i++) gbv[i] = lds32(sb + SM_SMALL + SMALL_GB + 16 * i + 4 * q);
    }
    float rs0 = 2.f * blo(lds32(sb + SM_STAT + (64 * wg + 16 * w + g) * 16 + 4)), rs1 = 2.f * blo(lds32(sb + SM_STAT + (64 * wg + 16 * w + g) * 16 + 132));
    rs0 = __frcp_rn(rs0 * rs0); rs1 = __frcp_rn(rs1 * rs1);
    mbar_wait(sb + 8 * B_PEER, 0);
    wg_wait<0>();
#pragma unroll
    for (int i = 0; i < 80; i++) asm volatile("" : "+f"(acc[i])::"memory");
    STAMPIF(tid == 0, 18);
    const uint32_t rbuf = ring + (2 + wg) * 32768 + 8192 + w * 5120;
    {
      const uint32_t rd = mapa(rbuf + lane * 16, (b & 1) ^ 1), rb = mapa(sb + 8 * (B_RECV + wg), (b & 1) ^ 1);
      if (b & 1) {
#pragma unroll
        for (int i = 0; i < 10; i++) st_async4(rd + i * 512, acc[4 * i], acc[4 * i + 1], acc[4 * i + 2], acc[4 * i + 3], rb);
#pragma unroll
        for (int i = 0; i < 40; i++) acc[i] = acc[40 + i];
      } else {
#pragma unroll
        for (int i = 0; i < 10; i++) st_async4(rd + i * 512, acc[40 + 4 * i], acc[41 + 4 * i], acc[42 + 4 * i], acc[43 + 4 * i], rb);
      }
    }
    mbar_wait(sb + 8 * (B_RECV + wg), 0);
    uint32_t ov[20];
#pragma unroll
    for (int i = 0; i < 10; i++) {
      uint4 v = lds128(rbuf + i * 512 + lane * 16);
      uint32_t o0 = pack2((acc[4 * i] + __uint_as_float(v.x)) * rs0, (acc[4 * i + 1] + __uint_as_float(v.y)) * rs0);
      uint32_t o1 = pack2((acc[4 * i + 2] + __uint_as_float(v.z)) * rs1, (acc[4 * i + 3] + __uint_as_float(v.w)) * rs1);
      ov[2 * i] = hadd(xr[2 * i], hmul(gbv[i], o0));
      ov[2 * i + 1] = hadd(xr[2 * i + 1], hmul(gbv[i], o1));
    }
    __syncwarp();
#pragma unroll
    for (int i = 0; i < 5; i++) stsm4(rbuf + (15 - (4 * (lane & 2) + 2 * ((lane >> 2) & 3) + (lane & 1))) * 160 + (lane >> 4) * 16 + i * 32, ov + 4 * i);
    fence_async_s();
    __syncwarp();
    if (lane == 0) {
      tma_store4d(&P.mO, rbuf, 80 * s, 0, 0, 191 - ibase(8 * m + 4 * wg + w));
      asm volatile("cp.async.bulk.commit_group;" ::: "memory");
      asm volatile("cp.async.bulk.wait_group.read 0;" ::: "memory");
    }
    if (threadIdx.x == 0) g_epoch[b] = __ldcg(g_epoch + b) + 1;
  }
}

typedef CUresult (*EncFn)(CUtensorMap*, CUtensorMapDataType, cuuint32_t, void*, const cuuint64_t*, const cuuint64_t*, const cuuint32_t*, const cuuint32_t*,
                          CUtensorMapInterleave, CUtensorMapSwizzle, CUtensorMapL2promotion, CUtensorMapFloatOOBfill);
static void mkmap(EncFn enc, CUtensorMap* m, const void* p, int rank, const cuuint64_t* dims, const cuuint64_t* strides, const cuuint32_t* box, CUtensorMapSwizzle sw) {
  cuuint32_t es[5] = {1, 1, 1, 1, 1};
  CUresult r = enc(m, CU_TENSOR_MAP_DATA_TYPE_BFLOAT16, rank, (void*)p, dims, strides, box, es, CU_TENSOR_MAP_INTERLEAVE_NONE, sw,
                   CU_TENSOR_MAP_L2_PROMOTION_L2_128B, CU_TENSOR_MAP_FLOAT_OOB_FILL_NONE);
  if (r != CUDA_SUCCESS) fprintf(stderr, "tensor map encode failed: %d\n", (int)r);
}

extern "C" void kernel_launch(void* const* d_in, const int* in_sizes, int n_in, void* d_out, int out_size) {
  void* fn = nullptr;
  cudaDriverEntryPointQueryResult qr;
  cudaGetDriverEntryPoint("cuTensorMapEncodeTiled", &fn, cudaEnableDefault, &qr);
  EncFn enc = (EncFn)fn;
  void *pAT, *pX1;
  cudaGetSymbolAddress(&pAT, g_AT);
  cudaGetSymbolAddress(&pX1, g_x1T);
  Params P;
  { cuuint64_t d[] = {640, 2048}, st[] = {1280}; cuuint32_t bx[] = {64, 35}; mkmap(enc, &P.mK, d_in[1], 2, d, st, bx, CU_TENSOR_MAP_SWIZZLE_NONE); }
  { cuuint64_t d[] = {640, 2048}, st[] = {1280}; cuuint32_t bx[] = {64, 32}; mkmap(enc, &P.mV, d_in[2], 2, d, st, bx, CU_TENSOR_MAP_SWIZZLE_NONE); }
  { cuuint64_t d[] = {128, 16, 640}, st[] = {256, 4096}; cuuint32_t bx[] = {144, 16, 1}; mkmap(enc, &P.mS, d_in[4], 3, d, st, bx, CU_TENSOR_MAP_SWIZZLE_NONE); }
  { cuuint64_t d[] = {3840, 640}, st[] = {7680}; cuuint32_t bx[] = {64, 80}; mkmap(enc, &P.mWm, d_in[11], 2, d, st, bx, CU_TENSOR_MAP_SWIZZLE_128B); }
  { cuuint64_t d[] = {64, 640, 32}, st[] = {4096, 128}; cuuint32_t bx[] = {64, 32, 2}; mkmap(enc, &P.mA, pAT, 3, d, st, bx, CU_TENSOR_MAP_SWIZZLE_128B); }
  { cuuint64_t d[] = {64, 640, 32}, st[] = {4096, 128}; cuuint32_t bx[] = {64, 80, 2}; mkmap(enc, &P.mX1, pX1, 3, d, st, bx, CU_TENSOR_MAP_SWIZZLE_128B); }
  { cuuint64_t d[] = {1536, 640}, st[] = {3072}; cuuint32_t bx[] = {64, 32};
    mkmap(enc, &P.mG, d_in[7], 2, d, st, bx, CU_TENSOR_MAP_SWIZZLE_128B); mkmap(enc, &P.mU, d_in[8], 2, d, st, bx, CU_TENSOR_MAP_SWIZZLE_128B); }
  { cuuint64_t d[] = {160, 2, 4, 192, 4}, st[] = {1280, 2560, 10240, 320}; cuuint32_t bx[] = {64, 2, 4, 4, 1}; mkmap(enc, &P.mDn, d_in[9], 5, d, st, bx, CU_TENSOR_MAP_SWIZZLE_128B); }
  { cuuint64_t d[] = {160, 2, 192, 4, 4}, st[] = {1280, 10240, 2560, 320}; cuuint32_t bx[] = {64, 2, 4, 4, 1}; mkmap(enc, &P.mDp, d_in[9], 5, d, st, bx, CU_TENSOR_MAP_SWIZZLE_128B); }
  { cuuint64_t d[] = {64, 2, 8, 10, 192}, st[] = {64 * 1280, 256 * 1280, 128, 1280}; cuuint32_t bx[] = {64, 2, 8, 5, 1}; mkmap(enc, &P.mX, d_in[0], 5, d, st, bx, CU_TENSOR_MAP_SWIZZLE_128B); }
  { cuuint64_t d[] = {640, 2, 8, 192}, st[] = {64 * 1280, 256 * 1280, 1280}; cuuint32_t bx[] = {80, 2, 8, 1}; mkmap(enc, &P.mO, d_out, 4, d, st, bx, CU_TENSOR_MAP_SWIZZLE_NONE); }
  P.shift_k = (const bf16*)d_in[3]; P.ssm_D = (const bf16*)d_in[5];
  P.c = (const bf16*)d_in[10];
  cudaFuncSetAttribute(fused_kernel, cudaFuncAttributeMaxDynamicSharedMemorySize, SM_TOTAL + DEVSM);
  cudaLaunchConfig_t cfg = {};
  cfg.gridDim = dim3(128); cfg.blockDim = dim3(512); cfg.dynamicSmemBytes = SM_TOTAL + DEVSM; cfg.stream = cudaStreamPerThread;
  cudaLaunchAttribute at[1];
  at[0].id = cudaLaunchAttributeClusterDimension; at[0].val.clusterDim.x = 2; at[0].val.clusterDim.y = 1; at[0].val.clusterDim.z = 1;
  cfg.attrs = at; cfg.numAttrs = 1;
  cudaLaunchKernelEx(&cfg, fused_kernel, P);
}
```

```cpp
#include <cuda_runtime.h>
#include <cuda.h>
#include <cuda_bf16.h>
#include <stdio.h>
#include <stdint.h>
typedef __nv_bfloat16 bf16;
__device__ __forceinline__ uint32_t smem_u32(const void* p) { return (uint32_t)__cvta_generic_to_shared(p); }
__device__ __forceinline__ void mbar_init(uint32_t bar, int cnt) { asm volatile("mbarrier.init.shared::cta.b64 [%0], %1;" ::"r"(bar), "r"(cnt) : "memory"); }
__device__ __forceinline__ void mbar_expect(uint32_t bar, int bytes) { asm volatile("mbarrier.arrive.expect_tx.shared::cta.b64 _, [%0], %1;" ::"r"(bar), "r"(bytes) : "memory"); }
__device__ __forceinline__ void mbar_arrive(uint32_t bar) { asm volatile("mbarrier.arrive.shared::cta.b64 _, [%0];" ::"r"(bar) : "memory"); }
__device__ __forceinline__ void mbar_arrive_remote(uint32_t bar) { asm volatile("mbarrier.arrive.relaxed.cluster.shared::cluster.b64 _, [%0];" ::"r"(bar) : "memory"); }
__device__ __forceinline__ uint32_t mapa(uint32_t a, uint32_t cta) { uint32_t r; asm("mapa.shared::cluster.u32 %0, %1, %2;" : "=r"(r) : "r"(a), "r"(cta)); return r; }
__device__ __forceinline__ bool mbar_try(uint32_t bar, int parity) {
  uint32_t ok;
  asm volatile("{\n.reg .pred p;\nmbarrier.try_wait.parity.shared::cta.b64 p, [%1], %2;\nselp.u32 %0, 1, 0, p;\n}" : "=r"(ok) : "r"(bar), "r"(parity) : "memory");
  return ok;
}
__device__ __forceinline__ void mbar_wait(uint32_t bar, int parity) {
#pragma unroll 1
  for (int i = 0; i < (1 << 20); i++) { if (mbar_try(bar, parity)) return; }
  __trap();
}
__device__ __forceinline__ void tma2d(uint32_t dst, const CUtensorMap* m, int c0, int c1, uint32_t bar) {
  asm volatile("cp.async.bulk.tensor.2d.shared::cluster.global.mbarrier::complete_tx::bytes [%0], [%1, {%3, %4}], [%2];" ::"r"(dst), "l"(m), "r"(bar), "r"(c0), "r"(c1) : "memory");
}
__device__ __forceinline__ void tma3d(uint32_t dst, const CUtensorMap* m, int c0, int c1, int c2, uint32_t bar) {
  asm volatile("cp.async.bulk.tensor.3d.shared::cluster.global.mbarrier::complete_tx::bytes [%0], [%1, {%3, %4, %5}], [%2];" ::"r"(dst), "l"(m), "r"(bar), "r"(c0), "r"(c1), "r"(c2) : "memory");
}
__device__ __forceinline__ void tma5d(uint32_t dst, const CUtensorMap* m, int c0, int c1, int c2, int c3, int c4, uint32_t bar) {
  asm volatile("cp.async.bulk.tensor.5d.shared::cluster.global.mbarrier::complete_tx::bytes [%0], [%1, {%3, %4, %5, %6, %7}], [%2];" ::"r"(dst), "l"(m), "r"(bar), "r"(c0), "r"(c1), "r"(c2), "r"(c3), "r"(c4) : "memory");
}
__device__ __forceinline__ void tma_store2d(const CUtensorMap* m, uint32_t src, int c0, int c1) {
  asm volatile("cp.async.bulk.tensor.2d.global.shared::cta.bulk_group [%0, {%2, %3}], [%1];" ::"l"(m), "r"(src), "r"(c0), "r"(c1) : "memory");
}
__device__ __forceinline__ void tma_store4d(const CUtensorMap* m, uint32_t src, int c0, int c1, int c2, int c3) {
  asm volatile("cp.async.bulk.tensor.4d.global.shared::cta.bulk_group [%0, {%2, %3, %4, %5}], [%1];" ::"l"(m), "r"(src), "r"(c0), "r"(c1), "r"(c2), "r"(c3) : "memory");
}
__device__ __forceinline__ void tma_prefetch2d(const CUtensorMap* m, int c0, int c1) {
  asm volatile("cp.async.bulk.prefetch.tensor.2d.L2.global [%0, {%1, %2}];" ::"l"(m), "r"(c0), "r"(c1) : "memory");
}
__device__ __forceinline__ void bulk_g2s(uint32_t dst, const void* src, int bytes, uint32_t bar) {
  asm volatile("cp.async.bulk.shared::cluster.global.mbarrier::complete_tx::bytes [%0], [%1], %2, [%3];" ::"r"(dst), "l"(src), "r"(bytes), "r"(bar) : "memory");
}
__device__ __forceinline__ void bulk_s2g(void* dst, uint32_t src, int bytes) {
  asm volatile("cp.async.bulk.global.shared::cta.bulk_group [%0], [%1], %2;" ::"l"(dst), "r"(src), "r"(bytes) : "memory");
}
__device__ __forceinline__ void cp16(uint32_t dst, const void* src) { asm volatile("cp.async.cg.shared.global [%0], [%1], 16;" ::"r"(dst), "l"(src) : "memory"); }
__device__ __forceinline__ void cp16z(uint32_t dst, const void* src, int n) { asm volatile("cp.async.cg.shared.global [%0], [%1], 16, %2;" ::"r"(dst), "l"(src), "r"(n) : "memory"); }
__device__ __forceinline__ void cp_arrive(uint32_t bar) { asm volatile("cp.async.mbarrier.arrive.noinc.shared::cta.b64 [%0];" ::"r"(bar) : "memory"); }
__device__ __forceinline__ void st_async4(uint32_t dst, float a, float b, float c, float d, uint32_t bar) {
  asm volatile("st.async.weak.shared::cluster.mbarrier::complete_tx::bytes.v4.f32 [%0], {%1, %2, %3, %4}, [%5];" ::"r"(dst), "f"(a), "f"(b), "f"(c), "f"(d), "r"(bar) : "memory");
}
__device__ __forceinline__ void wg_fence() { asm volatile("wgmma.fence.sync.aligned;" ::: "memory"); }
__device__ __forceinline__ void wg_commit() { asm volatile("wgmma.commit_group.sync.aligned;" ::: "memory"); }
template <int N> __device__ __forceinline__ void wg_wait() { asm volatile("wgmma.wait_group.sync.aligned %0;" ::"n"(N) : "memory"); }
__device__ __forceinline__ uint64_t mkdesc(uint32_t addr, uint32_t lbo, uint32_t sbo, uint32_t swz) {
  return (uint64_t)((addr & 0x3FFFF) >> 4) | ((uint64_t)(lbo >> 4) << 16) | ((uint64_t)(sbo >> 4) << 32) | ((uint64_t)swz << 62);
}
__device__ __forceinline__ void ldsm4t(uint32_t* r, uint32_t a) {
  asm volatile("ldmatrix.sync.aligned.m8n8.x4.trans.shared.b16 {%0,%1,%2,%3}, [%4];" : "=r"(r[0]), "=r"(r[1]), "=r"(r[2]), "=r"(r[3]) : "r"(a) : "memory");
}
__device__ __forceinline__ void stsm4(uint32_t a, const uint32_t* r) {
  asm volatile("stmatrix.sync.aligned.m8n8.x4.shared.b16 [%0], {%1,%2,%3,%4};" ::"r"(a), "r"(r[0]), "r"(r[1]), "r"(r[2]), "r"(r[3]) : "memory");
}
__device__ __forceinline__ void bar_sync(int id, int n) { asm volatile("bar.sync %0, %1;" ::"r"(id), "r"(n) : "memory"); }
__device__ __forceinline__ void bar_arrive(int id, int n) { asm volatile("bar.arrive %0, %1;" ::"r"(id), "r"(n) : "memory"); }
__device__ __forceinline__ uint32_t lds32(uint32_t a) { uint32_t v; asm volatile("ld.shared.b32 %0, [%1];" : "=r"(v) : "r"(a) : "memory"); return v; }
__device__ __forceinline__ uint2 lds64(uint32_t a) { uint2 v; asm volatile("ld.shared.v2.b32 {%0,%1}, [%2];" : "=r"(v.x), "=r"(v.y) : "r"(a) : "memory"); return v; }
__device__ __forceinline__ uint4 lds128(uint32_t a) { uint4 v; asm volatile("ld.shared.v4.b32 {%0,%1,%2,%3}, [%4];" : "=r"(v.x), "=r"(v.y), "=r"(v.z), "=r"(v.w) : "r"(a) : "memory"); return v; }
__device__ __forceinline__ void sts16(uint32_t a, uint32_t v) { asm volatile("st.shared.b16 [%0], %1;" ::"r"(a), "h"((uint16_t)v) : "memory"); }
__device__ __forceinline__ void sts32(uint32_t a, uint32_t v) { asm volatile("st.shared.b32 [%0], %1;" ::"r"(a), "r"(v) : "memory"); }
__device__ __forceinline__ void sts64(uint32_t a, uint32_t x, uint32_t y) { asm volatile("st.shared.v2.b32 [%0], {%1,%2};" ::"r"(a), "r"(x), "r"(y) : "memory"); }
__device__ __forceinline__ void sts128(uint32_t a, uint4 v) { asm volatile("st.shared.v4.b32 [%0], {%1,%2,%3,%4};" ::"r"(a), "r"(v.x), "r"(v.y), "r"(v.z), "r"(v.w) : "memory"); }
template<int TB> __device__ __forceinline__ void wgmma_rs_n128(float* d, const uint32_t* a, uint64_t db, int sd) {
  asm volatile("{\n.reg .pred p;\nsetp.ne.b32 p, %69, 0;\n"
    "wgmma.mma_async.sync.aligned.m64n128k16.f32.bf16.bf16 {%0, %1, %2, %3, %4, %5, %6, %7, %8, %9, %10, %11, %12, %13, %14, %15, %16, %17, %18, %19, %20, %21, %22, %23, %24, %25, %26, %27, %28, %29, %30, %31, %32, %33, %34, %35, %36, %37, %38, %39, %40, %41, %42, %43, %44, %45, %46, %47, %48, %49, %50, %51, %52, %53, %54, %55, %56, %57, %58, %59, %60, %61, %62, %63}, {%64, %65, %66, %67}, %68, p, 1, 1, %70;\n}"
    : "+f"(d[0]), "+f"(d[1]), "+f"(d[2]), "+f"(d[3]), "+f"(d[4]), "+f"(d[5]), "+f"(d[6]), "+f"(d[7]), "+f"(d[8]), "+f"(d[9]), "+f"(d[10]), "+f"(d[11]), "+f"(d[12]), "+f"(d[13]), "+f"(d[14]), "+f"(d[15]), "+f"(d[16]), "+f"(d[17]), "+f"(d[18]), "+f"(d[19]), "+f"(d[20]), "+f"(d[21]), "+f"(d[22]), "+f"(d[23]), "+f"(d[24]), "+f"(d[25]), "+f"(d[26]), "+f"(d[27]), "+f"(d[28]), "+f"(d[29]), "+f"(d[30]), "+f"(d[31]), "+f"(d[32]), "+f"(d[33]), "+f"(d[34]), "+f"(d[35]), "+f"(d[36]), "+f"(d[37]), "+f"(d[38]), "+f"(d[39]), "+f"(d[40]), "+f"(d[41]), "+f"(d[42]), "+f"(d[43]), "+f"(d[44]), "+f"(d[45]), "+f"(d[46]), "+f"(d[47]), "+f"(d[48]), "+f"(d[49]), "+f"(d[50]), "+f"(d[51]), "+f"(d[52]), "+f"(d[53]), "+f"(d[54]), "+f"(d[55]), "+f"(d[56]), "+f"(d[57]), "+f"(d[58]), "+f"(d[59]), "+f"(d[60]), "+f"(d[61]), "+f"(d[62]), "+f"(d[63])
    : "r"(a[0]), "r"(a[1]), "r"(a[2]), "r"(a[3]), "l"(db), "r"(sd), "n"(TB));
}

template<int TB> __device__ __forceinline__ void wgmma_rs_n160(float* d, const uint32_t* a, uint64_t db, int sd) {
  asm volatile("{\n.reg .pred p;\nsetp.ne.b32 p, %85, 0;\n"
    "wgmma.mma_async.sync.aligned.m64n160k16.f32.bf16.bf16 {%0, %1, %2, %3, %4, %5, %6, %7, %8, %9, %10, %11, %12, %13, %14, %15, %16, %17, %18, %19, %20, %21, %22, %23, %24, %25, %26, %27, %28, %29, %30, %31, %32, %33, %34, %35, %36, %37, %38, %39, %40, %41, %42, %43, %44, %45, %46, %47, %48, %49, %50, %51, %52, %53, %54, %55, %56, %57, %58, %59, %60, %61, %62, %63, %64, %65, %66, %67, %68, %69, %70, %71, %72, %73, %74, %75, %76, %77, %78, %79}, {%80, %81, %82, %83}, %84, p, 1, 1, %86;\n}"
    : "+f"(d[0]), "+f"(d[1]), "+f"(d[2]), "+f"(d[3]), "+f"(d[4]), "+f"(d[5]), "+f"(d[6]), "+f"(d[7]), "+f"(d[8]), "+f"(d[9]), "+f"(d[10]), "+f"(d[11]), "+f"(d[12]), "+f"(d[13]), "+f"(d[14]), "+f"(d[15]), "+f"(d[16]), "+f"(d[17]), "+f"(d[18]), "+f"(d[19]), "+f"(d[20]), "+f"(d[21]), "+f"(d[22]), "+f"(d[23]), "+f"(d[24]), "+f"(d[25]), "+f"(d[26]), "+f"(d[27]), "+f"(d[28]), "+f"(d[29]), "+f"(d[30]), "+f"(d[31]), "+f"(d[32]), "+f"(d[33]), "+f"(d[34]), "+f"(d[35]), "+f"(d[36]), "+f"(d[37]), "+f"(d[38]), "+f"(d[39]), "+f"(d[40]), "+f"(d[41]), "+f"(d[42]), "+f"(d[43]), "+f"(d[44]), "+f"(d[45]), "+f"(d[46]), "+f"(d[47]), "+f"(d[48]), "+f"(d[49]), "+f"(d[50]), "+f"(d[51]), "+f"(d[52]), "+f"(d[53]), "+f"(d[54]), "+f"(d[55]), "+f"(d[56]), "+f"(d[57]), "+f"(d[58]), "+f"(d[59]), "+f"(d[60]), "+f"(d[61]), "+f"(d[62]), "+f"(d[63]), "+f"(d[64]), "+f"(d[65]), "+f"(d[66]), "+f"(d[67]), "+f"(d[68]), "+f"(d[69]), "+f"(d[70]), "+f"(d[71]), "+f"(d[72]), "+f"(d[73]), "+f"(d[74]), "+f"(d[75]), "+f"(d[76]), "+f"(d[77]), "+f"(d[78]), "+f"(d[79])
    : "r"(a[0]), "r"(a[1]), "r"(a[2]), "r"(a[3]), "l"(db), "r"(sd), "n"(TB));
}

template<int TB> __device__ __forceinline__ void wgmma_rs_n192(float* d, const uint32_t* a, uint64_t db, int sd) {
  asm volatile("{\n.reg .pred p;\nsetp.ne.b32 p, %101, 0;\n"
    "wgmma.mma_async.sync.aligned.m64n192k16.f32.bf16.bf16 {%0, %1, %2, %3, %4, %5, %6, %7, %8, %9, %10, %11, %12, %13, %14, %15, %16, %17, %18, %19, %20, %21, %22, %23, %24, %25, %26, %27, %28, %29, %30, %31, %32, %33, %34, %35, %36, %37, %38, %39, %40, %41, %42, %43, %44, %45, %46, %47, %48, %49, %50, %51, %52, %53, %54, %55, %56, %57, %58, %59, %60, %61, %62, %63, %64, %65, %66, %67, %68, %69, %70, %71, %72, %73, %74, %75, %76, %77, %78, %79, %80, %81, %82, %83, %84, %85, %86, %87, %88, %89, %90, %91, %92, %93, %94, %95}, {%96, %97, %98, %99}, %100, p, 1, 1, %102;\n}"
    : "+f"(d[0]), "+f"(d[1]), "+f"(d[2]), "+f"(d[3]), "+f"(d[4]), "+f"(d[5]), "+f"(d[6]), "+f"(d[7]), "+f"(d[8]), "+f"(d[9]), "+f"(d[10]), "+f"(d[11]), "+f"(d[12]), "+f"(d[13]), "+f"(d[14]), "+f"(d[15]), "+f"(d[16]), "+f"(d[17]), "+f"(d[18]), "+f"(d[19]), "+f"(d[20]), "+f"(d[21]), "+f"(d[22]), "+f"(d[23]), "+f"(d[24]), "+f"(d[25]), "+f"(d[26]), "+f"(d[27]), "+f"(d[28]), "+f"(d[29]), "+f"(d[30]), "+f"(d[31]), "+f"(d[32]), "+f"(d[33]), "+f"(d[34]), "+f"(d[35]), "+f"(d[36]), "+f"(d[37]), "+f"(d[38]), "+f"(d[39]), "+f"(d[40]), "+f"(d[41]), "+f"(d[42]), "+f"(d[43]), "+f"(d[44]), "+f"(d[45]), "+f"(d[46]), "+f"(d[47]), "+f"(d[48]), "+f"(d[49]), "+f"(d[50]), "+f"(d[51]), "+f"(d[52]), "+f"(d[53]), "+f"(d[54]), "+f"(d[55]), "+f"(d[56]), "+f"(d[57]), "+f"(d[58]), "+f"(d[59]), "+f"(d[60]), "+f"(d[61]), "+f"(d[62]), "+f"(d[63]), "+f"(d[64]), "+f"(d[65]), "+f"(d[66]), "+f"(d[67]), "+f"(d[68]), "+f"(d[69]), "+f"(d[70]), "+f"(d[71]), "+f"(d[72]), "+f"(d[73]), "+f"(d[74]), "+f"(d[75]), "+f"(d[76]), "+f"(d[77]), "+f"(d[78]), "+f"(d[79]), "+f"(d[80]), "+f"(d[81]), "+f"(d[82]), "+f"(d[83]), "+f"(d[84]), "+f"(d[85]), "+f"(d[86]), "+f"(d[87]), "+f"(d[88]), "+f"(d[89]), "+f"(d[90]), "+f"(d[91]), "+f"(d[92]), "+f"(d[93]), "+f"(d[94]), "+f"(d[95])
    : "r"(a[0]), "r"(a[1]), "r"(a[2]), "r"(a[3]), "l"(db), "r"(sd), "n"(TB));
}

template<int TB> __device__ __forceinline__ void wgmma_rs_n32(float* d, const uint32_t* a, uint64_t db, int sd) {
  asm volatile("{\n.reg .pred p;\nsetp.ne.b32 p, %21, 0;\n"
    "wgmma.mma_async.sync.aligned.m64n32k16.f32.bf16.bf16 {%0, %1, %2, %3, %4, %5, %6, %7, %8, %9, %10, %11, %12, %13, %14, %15}, {%16, %17, %18, %19}, %20, p, 1, 1, %22;\n}"
    : "+f"(d[0]), "+f"(d[1]), "+f"(d[2]), "+f"(d[3]), "+f"(d[4]), "+f"(d[5]), "+f"(d[6]), "+f"(d[7]), "+f"(d[8]), "+f"(d[9]), "+f"(d[10]), "+f"(d[11]), "+f"(d[12]), "+f"(d[13]), "+f"(d[14]), "+f"(d[15])
    : "r"(a[0]), "r"(a[1]), "r"(a[2]), "r"(a[3]), "l"(db), "r"(sd), "n"(TB));
}

template<int TB> __device__ __forceinline__ void wgmma_rs_n64(float* d, const uint32_t* a, uint64_t db, int sd) {
  asm volatile("{\n.reg .pred p;\nsetp.ne.b32 p, %37, 0;\n"
    "wgmma.mma_async.sync.aligned.m64n64k16.f32.bf16.bf16 {%0, %1, %2, %3, %4, %5, %6, %7, %8, %9, %10, %11, %12, %13, %14, %15, %16, %17, %18, %19, %20, %21, %22, %23, %24, %25, %26, %27, %28, %29, %30, %31}, {%32, %33, %34, %35}, %36, p, 1, 1, %38;\n}"
    : "+f"(d[0]), "+f"(d[1]), "+f"(d[2]), "+f"(d[3]), "+f"(d[4]), "+f"(d[5]), "+f"(d[6]), "+f"(d[7]), "+f"(d[8]), "+f"(d[9]), "+f"(d[10]), "+f"(d[11]), "+f"(d[12]), "+f"(d[13]), "+f"(d[14]), "+f"(d[15]), "+f"(d[16]), "+f"(d[17]), "+f"(d[18]), "+f"(d[19]), "+f"(d[20]), "+f"(d[21]), "+f"(d[22]), "+f"(d[23]), "+f"(d[24]), "+f"(d[25]), "+f"(d[26]), "+f"(d[27]), "+f"(d[28]), "+f"(d[29]), "+f"(d[30]), "+f"(d[31])
    : "r"(a[0]), "r"(a[1]), "r"(a[2]), "r"(a[3]), "l"(db), "r"(sd), "n"(TB));
}

template<int TB> __device__ __forceinline__ void wgmma_rs_n96(float* d, const uint32_t* a, uint64_t db, int sd) {
  asm volatile("{\n.reg .pred p;\nsetp.ne.b32 p, %53, 0;\n"
    "wgmma.mma_async.sync.aligned.m64n96k16.f32.bf16.bf16 {%0, %1, %2, %3, %4, %5, %6, %7, %8, %9, %10, %11, %12, %13, %14, %15, %16, %17, %18, %19, %20, %21, %22, %23, %24, %25, %26, %27, %28, %29, %30, %31, %32, %33, %34, %35, %36, %37, %38, %39, %40, %41, %42, %43, %44, %45, %46, %47}, {%48, %49, %50, %51}, %52, p, 1, 1, %54;\n}"
    : "+f"(d[0]), "+f"(d[1]), "+f"(d[2]), "+f"(d[3]), "+f"(d[4]), "+f"(d[5]), "+f"(d[6]), "+f"(d[7]), "+f"(d[8]), "+f"(d[9]), "+f"(d[10]), "+f"(d[11]), "+f"(d[12]), "+f"(d[13]), "+f"(d[14]), "+f"(d[15]), "+f"(d[16]), "+f"(d[17]), "+f"(d[18]), "+f"(d[19]), "+f"(d[20]), "+f"(d[21]), "+f"(d[22]), "+f"(d[23]), "+f"(d[24]), "+f"(d[25]), "+f"(d[26]), "+f"(d[27]), "+f"(d[28]), "+f"(d[29]), "+f"(d[30]), "+f"(d[31]), "+f"(d[32]), "+f"(d[33]), "+f"(d[34]), "+f"(d[35]), "+f"(d[36]), "+f"(d[37]), "+f"(d[38]), "+f"(d[39]), "+f"(d[40]), "+f"(d[41]), "+f"(d[42]), "+f"(d[43]), "+f"(d[44]), "+f"(d[45]), "+f"(d[46]), "+f"(d[47])
    : "r"(a[0]), "r"(a[1]), "r"(a[2]), "r"(a[3]), "l"(db), "r"(sd), "n"(TB));
}

template<int TA, int TB> __device__ __forceinline__ void wgmma_ss_n160(float* d, uint64_t da, uint64_t db, int sd) {
  asm volatile("{\n.reg .pred p;\nsetp.ne.b32 p, %82, 0;\n"
    "wgmma.mma_async.sync.aligned.m64n160k16.f32.bf16.bf16 {%0, %1, %2, %3, %4, %5, %6, %7, %8, %9, %10, %11, %12, %13, %14, %15, %16, %17, %18, %19, %20, %21, %22, %23, %24, %25, %26, %27, %28, %29, %30, %31, %32, %33, %34, %35, %36, %37, %38, %39, %40, %41, %42, %43, %44, %45, %46, %47, %48, %49, %50, %51, %52, %53, %54, %55, %56, %57, %58, %59, %60, %61, %62, %63, %64, %65, %66, %67, %68, %69, %70, %71, %72, %73, %74, %75, %76, %77, %78, %79}, %80, %81, p, 1, 1, %83, %84;\n}"
    : "+f"(d[0]), "+f"(d[1]), "+f"(d[2]), "+f"(d[3]), "+f"(d[4]), "+f"(d[5]), "+f"(d[6]), "+f"(d[7]), "+f"(d[8]), "+f"(d[9]), "+f"(d[10]), "+f"(d[11]), "+f"(d[12]), "+f"(d[13]), "+f"(d[14]), "+f"(d[15]), "+f"(d[16]), "+f"(d[17]), "+f"(d[18]), "+f"(d[19]), "+f"(d[20]), "+f"(d[21]), "+f"(d[22]), "+f"(d[23]), "+f"(d[24]), "+f"(d[25]), "+f"(d[26]), "+f"(d[27]), "+f"(d[28]), "+f"(d[29]), "+f"(d[30]), "+f"(d[31]), "+f"(d[32]), "+f"(d[33]), "+f"(d[34]), "+f"(d[35]), "+f"(d[36]), "+f"(d[37]), "+f"(d[38]), "+f"(d[39]), "+f"(d[40]), "+f"(d[41]), "+f"(d[42]), "+f"(d[43]), "+f"(d[44]), "+f"(d[45]), "+f"(d[46]), "+f"(d[47]), "+f"(d[48]), "+f"(d[49]), "+f"(d[50]), "+f"(d[51]), "+f"(d[52]), "+f"(d[53]), "+f"(d[54]), "+f"(d[55]), "+f"(d[56]), "+f"(d[57]), "+f"(d[58]), "+f"(d[59]), "+f"(d[60]), "+f"(d[61]), "+f"(d[62]), "+f"(d[63]), "+f"(d[64]), "+f"(d[65]), "+f"(d[66]), "+f"(d[67]), "+f"(d[68]), "+f"(d[69]), "+f"(d[70]), "+f"(d[71]), "+f"(d[72]), "+f"(d[73]), "+f"(d[74]), "+f"(d[75]), "+f"(d[76]), "+f"(d[77]), "+f"(d[78]), "+f"(d[79])
    : "l"(da), "l"(db), "r"(sd), "n"(TA), "n"(TB));
}

template<int TA, int TB> __device__ __forceinline__ void wgmma_ss_n192(float* d, uint64_t da, uint64_t db, int sd) {
  asm volatile("{\n.reg .pred p;\nsetp.ne.b32 p, %98, 0;\n"
    "wgmma.mma_async.sync.aligned.m64n192k16.f32.bf16.bf16 {%0, %1, %2, %3, %4, %5, %6, %7, %8, %9, %10, %11, %12, %13, %14, %15, %16, %17, %18, %19, %20, %21, %22, %23, %24, %25, %26, %27, %28, %29, %30, %31, %32, %33, %34, %35, %36, %37, %38, %39, %40, %41, %42, %43, %44, %45, %46, %47, %48, %49, %50, %51, %52, %53, %54, %55, %56, %57, %58, %59, %60, %61, %62, %63, %64, %65, %66, %67, %68, %69, %70, %71, %72, %73, %74, %75, %76, %77, %78, %79, %80, %81, %82, %83, %84, %85, %86, %87, %88, %89, %90, %91, %92, %93, %94, %95}, %96, %97, p, 1, 1, %99, %100;\n}"
    : "+f"(d[0]), "+f"(d[1]), "+f"(d[2]), "+f"(d[3]), "+f"(d[4]), "+f"(d[5]), "+f"(d[6]), "+f"(d[7]), "+f"(d[8]), "+f"(d[9]), "+f"(d[10]), "+f"(d[11]), "+f"(d[12]), "+f"(d[13]), "+f"(d[14]), "+f"(d[15]), "+f"(d[16]), "+f"(d[17]), "+f"(d[18]), "+f"(d[19]), "+f"(d[20]), "+f"(d[21]), "+f"(d[22]), "+f"(d[23]), "+f"(d[24]), "+f"(d[25]), "+f"(d[26]), "+f"(d[27]), "+f"(d[28]), "+f"(d[29]), "+f"(d[30]), "+f"(d[31]), "+f"(d[32]), "+f"(d[33]), "+f"(d[34]), "+f"(d[35]), "+f"(d[36]), "+f"(d[37]), "+f"(d[38]), "+f"(d[39]), "+f"(d[40]), "+f"(d[41]), "+f"(d[42]), "+f"(d[43]), "+f"(d[44]), "+f"(d[45]), "+f"(d[46]), "+f"(d[47]), "+f"(d[48]), "+f"(d[49]), "+f"(d[50]), "+f"(d[51]), "+f"(d[52]), "+f"(d[53]), "+f"(d[54]), "+f"(d[55]), "+f"(d[56]), "+f"(d[57]), "+f"(d[58]), "+f"(d[59]), "+f"(d[60]), "+f"(d[61]), "+f"(d[62]), "+f"(d[63]), "+f"(d[64]), "+f"(d[65]), "+f"(d[66]), "+f"(d[67]), "+f"(d[68]), "+f"(d[69]), "+f"(d[70]), "+f"(d[71]), "+f"(d[72]), "+f"(d[73]), "+f"(d[74]), "+f"(d[75]), "+f"(d[76]), "+f"(d[77]), "+f"(d[78]), "+f"(d[79]), "+f"(d[80]), "+f"(d[81]), "+f"(d[82]), "+f"(d[83]), "+f"(d[84]), "+f"(d[85]), "+f"(d[86]), "+f"(d[87]), "+f"(d[88]), "+f"(d[89]), "+f"(d[90]), "+f"(d[91]), "+f"(d[92]), "+f"(d[93]), "+f"(d[94]), "+f"(d[95])
    : "l"(da), "l"(db), "r"(sd), "n"(TA), "n"(TB));
}

template<int TA, int TB> __device__ __forceinline__ void wgmma_ss_n8(float* d, uint64_t da, uint64_t db, int sd) {
  asm volatile("{\n.reg .pred p;\nsetp.ne.b32 p, %6, 0;\n"
    "wgmma.mma_async.sync.aligned.m64n8k16.f32.bf16.bf16 {%0, %1, %2, %3}, %4, %5, p, 1, 1, %7, %8;\n}"
    : "+f"(d[0]), "+f"(d[1]), "+f"(d[2]), "+f"(d[3])
    : "l"(da), "l"(db), "r"(sd), "n"(TA), "n"(TB));
}

constexpr int S_ = 2048, D_ = 640, F_ = 1536;

struct Scr {
  uint32_t flag[320 * 8];
  uint32_t epoch[256];
  bf16 cbsb[1536];
  bf16 cimg[8 * 6 * 512];
  uint4 stat[S_];
  float modP[8 * 3840];
  bf16 kvT[D_ * S_];
  bf16 x1T[D_ * S_];
  bf16 AT[D_ * S_];
  bf16 XH[D_ * S_ * 2];
  bf16 HH[S_ * F_];
};
__device__ __align__(1024) Scr g_scr;
#define DEVSM 0
#define STAMP(id)
#define STAMPIF(c, id)
constexpr int FL_KV = 0, FL_X = 80, FL_R = 82, FL_F = 87, FL_S = 88, FL_C = 104, FL_M = 112, FL_H = 172;

constexpr int SM_Z = 1024, SM_EXT = 21504, SM_STAT = 27648, SM_SMALL = 29696, SM_CB = 30720, SM_RING = 34816, SM_TOTAL = SM_RING + 6 * 32768;
constexpr int SMALL_S = 0, SMALL_XM = 160, SMALL_MOD = 256, SMALL_RED = 336, SMALL_GB = 848, SMALL_DUMMY = 1008;
constexpr int JOB_SZ = 8896, JOB_V = 4416, JOB_SK = 8640, R_X = 5 * 32768;
constexpr int K1OFF = 4672, KSZ = 9472, CSZ = KSZ + 4224;
enum { B_U = 0, B_S = 5, B_FB = 10, B_FA = 22, B_EXT = 28, B_X1 = 29, B_PEER = 30, B_RECV = 31, B_MF = 33, B_XFREE = 36, B_BOX = 38, B_CB = 42,
       B_ST1 = 43, B_GB = 44,
       B_F1 = 48, B_E1 = 54, B_EB = 60, B_EA = 72,
       B_Z = 80, B_KVS = 85, B_EW = 88, B_MB = 93, B_HH = 96, B_K = 98, B_ZF = 101,
       B_ST0 = 104, B_XS = 105, B_B = 106, B_X = 112 };
__device__ __forceinline__ uint32_t chan_base(uint32_t sb, int ch) { return sb + SM_RING + (2 + (ch >> 1)) * 32768 + (ch & 1) * CSZ; }
__device__ __forceinline__ uint32_t box_base(uint32_t sb, int cls) {
  return sb + SM_RING + (cls == 0 ? 46080 : cls == 1 ? 4 * 32768 + 14336 : cls == 2 ? 5 * 32768 + 20480 : 5 * 32768);
}

__device__ __forceinline__ uint32_t xh_base(uint32_t sb, int r) { return sb + SM_RING + (r < 2 ? R_X + 8192 * r : r < 4 ? 8192 * (r - 2) : 56320); }

struct Params { CUtensorMap mX, mS, mWm, mXH, mA, mG, mU, mDn, mDp, mX1, mO; };

__device__ __forceinline__ void flag_add(Scr* G, int id) { asm volatile("red.relaxed.gpu.global.add.u32 [%0], 1;" ::"l"(G->flag + 8 * id) : "memory"); }
__device__ __forceinline__ uint32_t rdback(const void* p) { uint32_t v; asm volatile("ld.relaxed.gpu.global.u32 %0, [%1];" : "=r"(v) : "l"(p) : "memory"); return v; }
__device__ __forceinline__ void rdwait(uint32_t sb, uint32_t v) { sts32(sb + SM_SMALL + SMALL_DUMMY, v); }
__device__ __forceinline__ void fence_async_s() { asm volatile("fence.proxy.async.shared::cta;" ::: "memory"); }
__device__ __forceinline__ void fence_async_g() { asm volatile("fence.proxy.async.global;" ::: "memory"); }
__device__ __forceinline__ void bulk_done() { asm volatile("cp.async.bulk.commit_group;\n\tcp.async.bulk.wait_group 0;" ::: "memory"); }
__device__ __forceinline__ void flag_wait(Scr* G, int id, uint32_t target) {
  const uint32_t* p = G->flag + 8 * id;
#pragma unroll 1
  for (int i = 0; i < (1 << 20); i++) {
    uint32_t v;
    asm volatile("ld.relaxed.gpu.global.u32 %0, [%1];" : "=r"(v) : "l"(p) : "memory");
    if ((int)(v - target) >= 0) return;
  }
  __trap();
}
__device__ __forceinline__ int ibase(int pb) {
  int w = pb >> 5, g = (pb >> 2) & 7, q = pb & 3;
  return 128 * (g >> 2) + 8 * ((2 * q - ((g >> 1) & 1)) & 7) + 2 * w + (g & 1);
}
__device__ __forceinline__ uint32_t hmul(uint32_t a, uint32_t b) { uint32_t d; asm("mul.rn.bf16x2 %0, %1, %2;" : "=r"(d) : "r"(a), "r"(b)); return d; }
__device__ __forceinline__ uint32_t hadd(uint32_t a, uint32_t b) { uint32_t d; asm("add.rn.bf16x2 %0, %1, %2;" : "=r"(d) : "r"(a), "r"(b)); return d; }
__device__ __forceinline__ uint32_t hsub(uint32_t a, uint32_t b) { uint32_t d; asm("sub.rn.bf16x2 %0, %1, %2;" : "=r"(d) : "r"(a), "r"(b)); return d; }
__device__ __forceinline__ uint32_t pack2(float lo, float hi) { uint32_t d; asm("cvt.rn.bf16x2.f32 %0, %1, %2;" : "=r"(d) : "f"(hi), "f"(lo)); return d; }
__device__ __forceinline__ float blo(uint32_t v) { return __uint_as_float(v << 16); }
__device__ __forceinline__ float bhi(uint32_t v) { return __uint_as_float(v & 0xffff0000u); }
__device__ __forceinline__ float rbf(float v) { return blo(pack2(v, 0.f)); }
template <int N> __device__ __forceinline__ void bfly(float* v, int mask, bool up) {
#pragma unroll
  for (int i = 0; i < N / 2; i++) {
    float send = up ? v[i] : v[i + N / 2], keep = up ? v[i + N / 2] : v[i];
    v[i] = keep + __shfl_xor_sync(0xffffffffu, send, mask);
  }
}
__device__ __forceinline__ int mod_col(int idx) {
  if (idx < 40) { int v = (idx >> 1) & 3; return (v == 3 ? 4 : v) * 640 + 128 * (idx >> 3) + 64 * (idx & 1); }
  int l = idx - 40;
  return l < 10 ? 3 * 640 + 64 * l : 5 * 640 + 64 * (l - 10);
}

__device__ __forceinline__ void kv_load(const bf16* gk, const bf16* gv, const bf16* gs, uint32_t sb, int b, int r, int tid) {
  const int row = tid >> 2, t = 64 * (b >> 2) + row, col = 128 * r + 32 * (b & 3);
  const uint32_t a = sb + SM_RING + r * JOB_SZ + row * 64 + (row >> 3) * 16 + (tid & 3) * 16;
  const int o = t * D_ + col + 8 * (tid & 3);
  cp16z(a, gk + (t < 3 ? o : o - 3 * D_), t < 3 ? 0 : 16);
  cp16(a + 2112, gk + o + 29 * D_);
  cp16(a + JOB_V, gv + o);
  cp16(a + JOB_V + 2112, gv + o + 32 * D_);
  if (tid < 12) cp16(a + 4224, gk + o + 61 * D_);
  else if (tid >= 112) cp16(sb + SM_RING + r * JOB_SZ + JOB_SK + 16 * (tid - 112), gs + 4 * col + 8 * (tid - 112));
}
__device__ __forceinline__ void kv_job(Scr* G, uint32_t sb, int b, int r, int tid) {
  const int cp = 4 * (tid >> 5) + (tid & 3), tc = (tid >> 2) & 7;
  const uint32_t base = sb + SM_RING + r * JOB_SZ, ka = base + tc * 528 + cp * 4;
  mbar_wait(sb + 8 * (B_B + r), 0);
  const uint4 sk = lds128(base + JOB_SK + 16 * cp);
  const uint32_t s0 = __byte_perm(sk.x, sk.z, 0x5410), s1 = __byte_perm(sk.x, sk.z, 0x7632), s2 = __byte_perm(sk.y, sk.w, 0x5410), s3 = __byte_perm(sk.y, sk.w, 0x7632);
  uint32_t kk[11], o[8];
#pragma unroll
  for (int i = 0; i < 11; i++) kk[i] = lds32(ka + 64 * i + 16 * (i >> 3));
#pragma unroll
  for (int i = 0; i < 8; i++) {
    uint32_t v = lds32(ka + JOB_V + 64 * i);
    uint32_t a = hadd(hadd(hadd(hmul(kk[i], s3), hmul(kk[i + 1], s2)), hmul(kk[i + 2], s1)), hmul(kk[i + 3], s0));
    o[i] = hmul(a, v);
  }
  bf16* dst = G->kvT + (128 * r + 32 * (b & 3) + 2 * cp) * S_ + 2040 - 64 * (b >> 2) - 8 * tc;
  *(uint4*)dst = make_uint4(__byte_perm(o[7], o[6], 0x5410), __byte_perm(o[5], o[4], 0x5410), __byte_perm(o[3], o[2], 0x5410), __byte_perm(o[1], o[0], 0x5410));
  *(uint4*)(dst + S_) = make_uint4(__byte_perm(o[7], o[6], 0x7632), __byte_perm(o[5], o[4], 0x7632), __byte_perm(o[3], o[2], 0x7632), __byte_perm(o[1], o[0], 0x7632));
}
__device__ __forceinline__ void kv_signal(Scr* G, uint32_t sb, int b, int r, int line, bool add) {
  rdwait(sb, rdback(G->kvT + (128 * r + 32 * (b & 3) + line) * S_ + 1984 - 64 * (b >> 2)));
  __syncwarp();
  if (add) flag_add(G, FL_KV + 16 * r + 4 * (b & 3) + (line >> 3));
}
__device__ __forceinline__ void mod_box(Scr* G, uint32_t sb, int b, int cls, int tid) {
  float a[4];
  const uint64_t da = mkdesc(box_base(sb, cls), 4096, 1024, 1), db = mkdesc(sb + SM_SMALL + SMALL_S, 16, 128, 0);
  mbar_wait(sb + 8 * (B_BOX + cls), 0);
  wg_fence();
#pragma unroll
  for (int n = 0; n < 5; n++) wgmma_ss_n8<1, 0>(a, da + 128 * n, db + 2 * n, n != 0);
  wg_commit();
  wg_wait<0>();
#pragma unroll
  for (int i = 0; i < 4; i++) asm volatile("" : "+f"(a[i])::"memory");
  if ((tid & 3) == 0) {
    float* p = G->modP + (b & 7) * 3840 + mod_col(16 * cls + (b >> 3)) + 16 * (tid >> 5) + ((tid >> 2) & 7);
    p[0] = a[0]; p[8] = a[2];
  }
}
__device__ __forceinline__ uint32_t box_rdback(Scr* G, int b, int cls, int lane) {
  return rdback(G->modP + (b & 7) * 3840 + mod_col(16 * cls + (b >> 3)) + 32 * (lane & 1));
}
__device__ __forceinline__ float sum8(float a) {
  a += __shfl_xor_sync(0xffffffffu, a, 4);
  a += __shfl_xor_sync(0xffffffffu, a, 2);
  a += __shfl_xor_sync(0xffffffffu, a, 1);
  return rbf(a);
}
template <int NR> __device__ __forceinline__ void mod_fin(Scr* G, uint32_t sb, int b, int r0, uint32_t e1, int lane) {
  if (lane < 4 * NR) flag_wait(G, FL_M + 8 * r0 + 2 * lane + (b >> 6), e1 * 8);
  __syncwarp();
  const int v = lane >> 3;
  const float* p = G->modP + (lane & 7) * 3840 + (v == 3 ? 4 : v) * 640 + 128 * r0 + b;
  float a[NR];
#pragma unroll
  for (int n = 0; n < NR; n++) a[n] = __ldcg(p + 128 * n);
#pragma unroll
  for (int n = 0; n < NR; n++) {
    float t = sum8(a[n]);
    if (v & 1) t += 1.f;
    if ((lane & 7) == 0) sts32(sb + SM_SMALL + SMALL_MOD + 16 * (r0 + n) + 4 * v, pack2(t, t));
  }
  __syncwarp();
  if (lane == 0) mbar_arrive(sb + 8 * (B_MF + (r0 >> 1)));
}
__device__ __forceinline__ void load_x(const Params& P, uint32_t sb, int b, int h) {
  const uint32_t bar = sb + 8 * (B_X + h);
  mbar_expect(bar, 10240);
  tma5d(sb + SM_RING + R_X + h * 10240, &P.mX, 0, 0, 0, 5 * h, 191 - ibase(b), bar);
}
__device__ __forceinline__ void load_box(const Params& P, uint32_t sb, int b, int cls) {
  const uint32_t bar = sb + 8 * (B_BOX + cls);
  mbar_expect(bar, 10240);
  tma2d(box_base(sb, cls), &P.mWm, mod_col(16 * cls + (b >> 3)), 80 * (b & 7), bar);
}
__device__ __forceinline__ void load_ssm(const Params& P, uint32_t sb, int b, int r) {
  const uint32_t bar = sb + 8 * (B_S + r);
  mbar_expect(bar, 16 * 288);
  tma3d(chan_base(sb, r) + 128, &P.mS, 0, 0, 128 * r + b, bar);
}
__device__ __forceinline__ void k1_job(uint32_t sb, int r, int tid) {
  const uint32_t a0 = chan_base(sb, r) + 128 + 16 * tid + 32 * (tid >> 4);
  mbar_wait(sb + 8 * (B_S + r), 0);
#pragma unroll
  for (int n = 0; n < 2; n++) {
    const uint32_t a = a0 + 2304 * n;
    const uint4 v = lds128(a);
    const uint32_t pv = lds32(a - ((tid & 15) ? 4 : 36));
    sts128(a + K1OFF, make_uint4(__byte_perm(pv, v.x, 0x5432), __byte_perm(v.x, v.y, 0x5432), __byte_perm(v.y, v.z, 0x5432), __byte_perm(v.z, v.w, 0x5432)));
  }
}

__global__ void __launch_bounds__(512, 1) fused_kernel(const bf16* __restrict__ gk, const bf16* __restrict__ gv, const bf16* __restrict__ gsk,
                                                       const bf16* __restrict__ gD, const bf16* __restrict__ gc, Scr* G, const __grid_constant__ Params P) {
  extern __shared__ __align__(1024) char smem_raw[];
  const uint32_t sb = smem_u32(smem_raw), ring = sb + SM_RING;
  const int b = blockIdx.x, m = b >> 3, s = b & 7;
  const int wg = __shfl_sync(0xffffffffu, threadIdx.x >> 7, 0);
  const int tid = threadIdx.x & 127, lane = tid & 31;
  const int w = __shfl_sync(0xffffffffu, tid >> 5, 0);
  uint32_t e1 = 0, cin = 0;
  if (wg < 2) {
    kv_load(gk, gv, gsk, sb, b, wg, tid);
  } else {
    if (wg == 2) {
      if (tid < 40) {
        int c = tid & 7;
        sts128(chan_base(sb, tid >> 3) + (c < 2 ? 80 + c * K1OFF : KSZ + 4096 + (c - 2) * 16), make_uint4(0, 0, 0, 0));
      }
    }
    if (lane == 0) {
      const int j = 4 * (3 - wg) + w - 1;
      if (j < 3) asm volatile("prefetch.tensormap [%0];" ::"l"(&P.mS + j) : "memory");
      if (j < 0) {
        mbar_init(sb + 8 * B_X, 1);
        mbar_init(sb + 8 * (B_X + 1), 1);
        fence_async_s();
        load_x(P, sb, b, 0);
      } else {
        const int c = j < 3 ? 1 : j < 5 ? 2 : 4;
#pragma unroll
        for (int i = 0; i < 16; i++) mbar_init(sb + 128 * j + 8 * i, i < 8 || j < 6 ? c : i == 8 ? 5 : i == 9 ? 8 : 128);
      }
    }
    fence_async_s();
    e1 = rdback(G->epoch + b);
    if (wg == 2 && tid < 80) cin = *(const uint16_t*)(gc + 80 * (b & 7) + tid);
  }
  __syncthreads();
  STAMPIF(threadIdx.x == 0, 55);

  if (wg == 3) {
    asm volatile("setmaxnreg.dec.sync.aligned.u32 24;");
    if (w < 2) {
     if (w == 0) {
      if (lane == 0) {
        STAMP(62);
        mbar_wait(sb + 8 * (B_B + 0), 0);
        STAMP(56);
        load_x(P, sb, b, 1);
        mbar_wait(sb + 8 * (B_B + 1), 0);
        STAMP(57);
        load_ssm(P, sb, b, 0);
        load_ssm(P, sb, b, 1);
        mbar_wait(sb + 8 * (B_X + 1), 0);
        STAMP(61);
        load_box(P, sb, b, 0);
        mbar_wait(sb + 8 * (B_B + 2), 0);
        STAMP(58);
        load_ssm(P, sb, b, 2);
        load_ssm(P, sb, b, 3);
        mbar_wait(sb + 8 * (B_B + 3), 0);
        STAMP(59);
        load_ssm(P, sb, b, 4);
        load_box(P, sb, b, 1);
        mbar_wait(sb + 8 * (B_B + 4), 0);
        STAMP(60);
        load_box(P, sb, b, 2);
        mbar_wait(sb + 8 * (B_BOX + 1), 0);
        STAMP(69);
        mbar_wait(sb + 8 * B_XFREE, 0);
        if (b < 96) load_box(P, sb, b, 3);
        mbar_wait(sb + 8 * (B_XFREE + 1), 0);
        mbar_wait(sb + 8 * (B_KVS + 2), 0);
        STAMP(70);
#pragma unroll 1
        for (int it = 0; it < 20; it++) {
          int st = it % 6;
          mbar_wait(sb + 8 * (B_E1 + st), (it / 6) & 1);
          uint32_t a = ring + st * 32768 + 8192, fb = sb + 8 * (B_F1 + st);
          mbar_expect(fb, 24576);
#pragma unroll
          for (int j = 0; j < 3; j++) {
            tma2d(a + 8192 * j, &P.mG, 192 * s + 64 * j, 32 * it, fb);
            tma2d(a + 8192 * j + 4096, &P.mU, 192 * s + 64 * j, 32 * it, fb);
          }
        }
#pragma unroll 1
        for (int k = 0; k < 24; k++) {
          int sl = k < 12 ? k : k - 12;
          int g1 = (sl >> 1) + 2; if (g1 >= 6) g1 -= 6;
          if (k < 12) mbar_wait(sb + 8 * (B_E1 + g1), g1 >= 2); else mbar_wait(sb + 8 * (B_EB + sl), 0);
          uint32_t a = ring + g1 * 32768 + 8192 + (sl & 1) * 12288, fb = sb + 8 * (B_FB + sl);
          int n = k / 6, kg = 4 * (6 * ((s + 2 * n) & 7) + k - 6 * n);
          mbar_expect(fb, 12288);
#pragma unroll 1
          for (int at = 0; at < 3; at++) {
            if (k < 6) tma5d(a + at * 4096, &P.mDn, 64 * at, 0, 0, kg, s >> 1, fb);
            else tma5d(a + at * 4096, &P.mDp, 64 * at, 0, kg, 0, s >> 1, fb);
          }
        }
      }
     } else {
      if (lane == 0) {
#pragma unroll
        for (int i = 4; i < 11; i++) asm volatile("prefetch.tensormap [%0];" ::"l"(&P.mX + i) : "memory");
        asm volatile("add.u32 %0, %0, 1;" : "+r"(e1));
#pragma unroll 1
        for (int r = 0; r < 5; r++) {
          flag_wait(G, FL_KV + 16 * r + (b >> 3), e1 * 32);
          fence_async_g();
          uint32_t bar = sb + 8 * (B_U + r);
          mbar_expect(bar, 4096);
          bulk_g2s(chan_base(sb, r) + KSZ, G->kvT + (128 * r + b) * S_, 4096, bar);
          STAMP(40 + r);
          if (r == 1) {
            mbar_wait(sb + 8 * B_XS, 0);
            mbar_wait(bar, 0);
            tma_store2d(&P.mXH, xh_base(sb, 0), 32 * b, 0);
          }
          if (r == 3) tma_store2d(&P.mXH, xh_base(sb, 4), 32 * b, 512);
          if (r >= 1 && r < 4) tma_store2d(&P.mXH, r == 1 ? xh_base(sb, 1) : ring + 8192 * (r - 2), 32 * b, 128 * r);
          if (r == 1 || r == 4) {
            bulk_done();
            flag_add(G, FL_X + (r >> 2));
            mbar_arrive(sb + 8 * (B_XFREE + (r >> 2)));
            STAMP(71 + (r >> 2));
          }
        }
#pragma unroll 1
        for (int it = 0; it < 20; it++) {
          int st = it % 6;
          if ((it & 3) == 0) { flag_wait(G, FL_R + (it >> 2), e1 * 128); fence_async_g(); STAMP(45 + (it >> 2)); }
          mbar_wait(sb + 8 * (B_E1 + st), (it / 6) & 1);
          uint32_t fb = sb + 8 * (B_F1 + st);
          mbar_expect(fb, 8192);
          tma3d(ring + st * 32768, &P.mA, 0, 32 * it, m * 2, fb);
        }
#pragma unroll 1
        for (int n = 1; n < 4; n++) {
          int src = 8 * m + ((s + 2 * n) & 7);
          flag_wait(G, FL_H + src, e1 * 4);
          fence_async_g();
          STAMP(50 + n);
#pragma unroll 1
          for (int k = 0; k < 6; k++) {
            int g1 = k + 2; if (g1 >= 6) g1 -= 6;
            if (n == 1) mbar_wait(sb + 8 * (B_E1 + g1), g1 >= 2); else mbar_wait(sb + 8 * (B_EA + k), n & 1);
            uint32_t fb = sb + 8 * (B_FA + k);
            mbar_expect(fb, 8192);
            bulk_g2s(ring + g1 * 32768, G->HH + (src * 6 + k) * 4096, 8192, fb);
          }
        }
        G->epoch[b] = e1;
      }
     }
    } else if (w == 2) {
      if (lane == 0) {
        mbar_expect(sb + 8 * B_RECV, 20480);
        mbar_expect(sb + 8 * (B_RECV + 1), 20480);
      }
      asm volatile("add.u32 %0, %0, 1;" : "+r"(e1));
      mbar_wait(sb + 8 * B_MB, 0);
      rdwait(sb, box_rdback(G, b, 0, lane));
      __syncwarp();
      if (lane == 0) flag_add(G, FL_M + (b >> 3));
      mod_fin<2>(G, sb, b, 0, e1, lane);
      STAMPIF(lane == 0, 36);
      const int grp = m % 6;
#pragma unroll 1
      for (int r = 0; r < 5; r++) {
        mbar_wait(sb + 8 * (B_EW + r), 0);
        uint32_t v0 = rdback(G->AT + (128 * r + b) * S_ + 64 * lane), v1 = rdback(G->x1T + (128 * r + b) * S_ + 64 * lane);
        rdwait(sb, v0 ^ v1);
        __syncwarp();
        if (lane == 0) {
          flag_add(G, FL_R + r);
          if (m < 12) {
            mbar_expect(sb + 8 * B_ST0, 4096);
            tma2d(sb + SM_Z + r * 4096, (grp & 1) ? &P.mU : &P.mG, 192 * s + 64 * (grp >> 1), (m < 6 ? 0 : 320) + 32 * r, sb + 8 * B_ST0);
          }
        }
      }
      if (lane == 0) {
        if (m < 12) {
          flag_wait(G, FL_F, e1 * 40);
          fence_async_g();
          STAMP(34);
          mbar_expect(sb + 8 * B_CB, 1280);
          bulk_g2s(sb + SM_CB, G->cbsb + (m < 6 ? 0 : 640), 1280, sb + 8 * B_CB);
          mbar_wait(sb + 8 * B_ZF, 0);
        }
        flag_wait(G, FL_R + 4, e1 * 128);
        fence_async_g();
        mbar_expect(sb + 8 * B_X1, 20480);
        tma3d(sb + SM_Z, &P.mX1, 0, 80 * s, m * 2, sb + 8 * B_X1);
        flag_wait(G, FL_S + m, e1 * 8);
        flag_wait(G, FL_C + s, e1 * 48);
        fence_async_g();
        STAMP(54);
        mbar_expect(sb + 8 * B_EXT, 6144 + 2048);
        bulk_g2s(sb + SM_EXT, G->cimg + s * 3072, 6144, sb + 8 * B_EXT);
        bulk_g2s(sb + SM_STAT, G->stat + 128 * m, 2048, sb + 8 * B_EXT);
        mbar_wait(sb + 8 * (B_EB + 3), 0);
        mbar_wait(sb + 8 * (B_EB + 3), 1);
        mbar_arrive_remote(mapa(sb + 8 * B_PEER, (b & 1) ^ 1));
      }
    } else {
      asm volatile("add.u32 %0, %0, 1;" : "+r"(e1));
#pragma unroll 1
      for (int r = 2; r < 5; r++) {
        mbar_wait(sb + 8 * (B_KVS + r - 2), 0);
        kv_signal(G, sb, b, r, lane, (lane & 7) == 0);
        STAMPIF(lane == 0, 20 + r);
      }
      mbar_wait(sb + 8 * (B_MB + 1), 0);
      if (lane == 0) mbar_arrive(sb + 8 * (B_E1 + 4));
      rdwait(sb, box_rdback(G, b, 1, lane));
      __syncwarp();
      if (lane == 0) flag_add(G, FL_M + 16 + (b >> 3));
      mbar_wait(sb + 8 * (B_MB + 2), 0);
      if (lane == 0) mbar_arrive(sb + 8 * (B_E1 + 5));
      rdwait(sb, box_rdback(G, b, (lane & 2) && b < 96 ? 3 : 2, lane));
      __syncwarp();
      if (lane == 0 || (lane == 1 && b < 96)) flag_add(G, FL_M + 32 + 16 * lane + (b >> 3));
      STAMPIF(lane == 0, 73);
      mod_fin<2>(G, sb, b, 2, e1, lane);
      STAMPIF(lane == 0, 37);
      mod_fin<1>(G, sb, b, 4, e1, lane);
      STAMPIF(lane == 0, 38);
      const float* p = G->modP + (lane & 7) * 3840 + 4 * (lane >> 3);
      if (b < 40) {
        if (lane < 2) flag_wait(G, FL_M + (lane ? 40 + (b >> 2) : 8 * (b >> 3) + 6 + ((b >> 2) & 1)), e1 * 8);
        __syncwarp();
        const float4 c0 = __ldcg((const float4*)(p + 4 * 640 + 16 * b)), c1 = __ldcg((const float4*)(p + 3 * 640 + 16 * b));
        float a[8] = {c0.x, c0.y, c0.z, c0.w, c1.x, c1.y, c1.z, c1.w};
        bfly<8>(a, 4, lane & 4); bfly<4>(a, 2, lane & 2); bfly<2>(a, 1, lane & 1);
        float t = rbf(a[0]);
        if (!(lane & 4)) t += 1.f;
        uint16_t* d = (uint16_t*)G->cbsb + 32 * b;
        d[(lane & 16) + 2 * (lane & 4) + ((lane & 8) >> 1) + (lane & 3)] = (uint16_t)pack2(t, 0.f);
        rdwait(sb, rdback(d));
        __syncwarp();
        if (lane == 0) flag_add(G, FL_F);
        STAMPIF(lane == 0, 39);
      }
      if (lane < 10) flag_wait(G, FL_M + 50 + lane, e1 * 8);
      __syncwarp();
#pragma unroll 1
      for (int n = 0; n < 5; n++) {
        const float4 c0 = __ldcg((const float4*)(p + 5 * 640 + 80 * s + 16 * n));
        float a[4] = {c0.x, c0.y, c0.z, c0.w};
        bfly<4>(a, 2, lane & 2); bfly<2>(a, 1, lane & 1);
        a[0] += __shfl_xor_sync(0xffffffffu, a[0], 4);
        sts16(sb + SM_SMALL + SMALL_GB + 32 * n + (lane & 24) + 2 * (lane & 3), pack2(a[0], 0.f));
      }
      __syncwarp();
      if (lane == 0) mbar_arrive(sb + 8 * B_GB);
    }
  } else if (wg == 2) {
    asm volatile("setmaxnreg.dec.sync.aligned.u32 40;");
    asm volatile("add.u32 %0, %0, 1;" : "+r"(e1));
    if (tid < 80) {
      float c = blo(cin);
      sts16(sb + SM_SMALL + SMALL_S + 2 * tid, pack2(__fdividef(c, 1.f + __expf(-c)), 0.f));
    }
    fence_async_s();
    bar_sync(5, 128);
#pragma unroll 1
    for (int r = 2; r < 5; r++) {
      if (r < 4) mbar_wait(sb + 8 * (r == 2 ? B_X : B_S + 1), 0);
      else {
        kv_job(G, sb, b, 2, tid);
        __syncwarp();
        if (lane == 0) mbar_arrive(sb + 8 * B_KVS);
        mbar_wait(sb + 8 * B_BOX, 0);
        STAMPIF(tid == 0, 68);
      }
      kv_load(gk, gv, gsk, sb, b, r, tid);
      cp_arrive(sb + 8 * (B_B + r));
    }
    mod_box(G, sb, b, 0, tid);
    __syncwarp();
    if (lane == 0) mbar_arrive(sb + 8 * B_MB);
    STAMPIF(tid == 0, 27);
#pragma unroll 1
    for (int r = 3; r < 5; r++) {
      kv_job(G, sb, b, r, tid);
      __syncwarp();
      if (lane == 0) mbar_arrive(sb + 8 * (B_KVS + r - 2));
#pragma unroll 1
      for (int j = 2 * r - 4; j <= r; j++) {
        k1_job(sb, j, tid);
        __syncwarp();
        if (lane == 0) mbar_arrive(sb + 8 * (B_K + j - 2));
      }
    }
    STAMPIF(tid == 0, 74);
#pragma unroll 1
    for (int r = 0; r < 5; r++) {
      if (lane == 0 && !(r & 5)) flag_wait(G, FL_X + (r >> 1), e1 * 128);
      __syncwarp();
      STAMPIF(tid == 0 && r == 0, 28);
      uint4 xh[4];
#pragma unroll
      for (int n = 0; n < 4; n++) xh[n] = __ldcg((const uint4*)(G->XH + (128 * r + b) * (2 * S_)) + tid + 128 * n);
      mbar_wait(sb + 8 * (B_MF + (r >> 1)), 0);
      const uint4 md = lds128(sb + SM_SMALL + SMALL_MOD + 16 * r);
      mbar_wait(sb + 8 * (B_Z + r), 0);
      const uint32_t za = sb + SM_Z + r * 4096 + 8 * tid;
      uint2 *pa = (uint2*)(G->AT + (128 * r + b) * S_) + tid, *px = (uint2*)(G->x1T + (128 * r + b) * S_) + tid;
#pragma unroll
      for (int n = 0; n < 4; n++) {
        uint2 z = lds64(za + 1024 * n);
        uint32_t x0 = hadd(xh[n].x, hmul(md.z, hmul(hadd(hmul(xh[n].z, md.y), md.x), z.x)));
        uint32_t x1 = hadd(xh[n].y, hmul(md.z, hmul(hadd(hmul(xh[n].w, md.y), md.x), z.y)));
        pa[128 * n] = make_uint2(hmul(x0, md.w), hmul(x1, md.w));
        px[128 * n] = make_uint2(x0, x1);
      }
      __syncwarp();
      if (lane == 0) mbar_arrive(sb + 8 * (B_EW + r));
      STAMPIF(tid == 0, 29 + r);
      if (r < 2) {
#pragma unroll 1
        for (int cls = r + 1; cls <= 2 * r + 1; cls++)
          if (cls < 3 || b < 96) mod_box(G, sb, b, cls, tid);
        __syncwarp();
        if (lane == 0) mbar_arrive(sb + 8 * (B_MB + r + 1));
      }
    }
    float a[8];
    if (m < 12) {
      const int grp = m % 6;
      const uint64_t da = mkdesc(sb + SM_Z, 4096, 1024, 1), db = mkdesc(sb + SM_CB, 32, 128, 0);
      mbar_wait(sb + 8 * B_CB, 0);
#pragma unroll 1
      for (int h = 0; h < 2; h++) {
        mbar_wait(sb + 8 * (h ? B_ST1 : B_ST0), 0);
        wg_fence();
#pragma unroll
        for (int n = 0; n < 10; n++) wgmma_ss_n8<1, 0>(a, da + 128 * n, db + 40 * h + 4 * n, (h | n) != 0);
        wg_commit();
        wg_wait<0>();
        if (h == 0) {
          bar_sync(5, 128);
          if (tid == 0) {
            mbar_expect(sb + 8 * B_ST1, 20480);
#pragma unroll 1
            for (int r = 0; r < 5; r++)
              tma2d(sb + SM_Z + r * 4096, (grp & 1) ? &P.mU : &P.mG, 192 * s + 64 * (grp >> 1), (m < 6 ? 160 : 480) + 32 * r, sb + 8 * B_ST1);
          }
          __syncwarp();
        }
      }
#pragma unroll
      for (int i = 0; i < 4; i++) asm volatile("" : "+f"(a[i])::"memory");
      if (lane == 0) mbar_arrive(sb + 8 * B_ZF);
      const int row = (m < 6 ? 0 : 4) + (lane & 3);
      uint16_t* dst = (uint16_t*)G->cimg + s * 3072 + grp * 512 + row * 64 + (lane >> 2);
#pragma unroll
      for (int j = 0; j < 2; j++) {
        const float c1 = __shfl_sync(0xffffffffu, a[2 * j], lane & 28), c2 = __shfl_sync(0xffffffffu, a[2 * j + 1], lane & 28);
        const float t = (lane & 2) ? c2 : c1, hi = rbf(t);
        dst[((2 * w + j) ^ row) << 3] = (uint16_t)pack2((lane & 1) ? t - hi : hi, 0.f);
      }
      rdwait(sb, rdback(dst - (lane >> 2) + (((2 * w) ^ row) << 3)));
      __syncwarp();
      if (lane == 0) flag_add(G, FL_C + s);
      STAMPIF(tid == 0, 35);
    }
    {
      if (lane == 0) flag_wait(G, FL_R + 4, e1 * 128);
      __syncwarp();
      const bf16* src = G->x1T + 16 * b + 4 * (lane & 3);
      const uint2 pq = __ldcg((const uint2*)src);
      const float pv0 = blo(pq.x), pv1 = bhi(pq.x), pv2 = blo(pq.y), pv3 = bhi(pq.y);
#pragma unroll
      for (int j = 0; j < 8; j++) a[j] = 0.f;
      src += ((lane >> 2) + 8 * w) * S_;
#pragma unroll 1
      for (int n0 = 0; n0 < 20; n0 += 5) {
        uint2 v[5];
#pragma unroll
        for (int n = 0; n < 5; n++) v[n] = __ldcg((const uint2*)(src + n * 32 * S_));
        src += 160 * S_;
#pragma unroll
        for (int n = 0; n < 5; n++) {
          const float e0 = blo(v[n].x) - pv0, e1_ = bhi(v[n].x) - pv1, e2 = blo(v[n].y) - pv2, e3 = bhi(v[n].y) - pv3;
          a[0] += e0; a[1] += e1_; a[2] += e2; a[3] += e3;
          a[4] += e0 * e0; a[5] += e1_ * e1_; a[6] += e2 * e2; a[7] += e3 * e3;
        }
      }
      bfly<8>(a, 16, lane & 16); bfly<4>(a, 8, lane & 8); bfly<2>(a, 4, lane & 4);
      sts32(sb + SM_SMALL + SMALL_RED + w * 128 + (lane >> 4) * 64 + (4 * (lane & 3) + ((lane >> 2) & 3)) * 4, __float_as_uint(a[0]));
      bar_sync(5, 128);
      if (w == 3) {
        uint32_t v = 0;
        if (lane < 16) {
          float s1 = 0.f, s2 = 0.f;
#pragma unroll
          for (int j = 0; j < 4; j++) {
            s1 += __uint_as_float(lds32(sb + SM_SMALL + SMALL_RED + j * 128 + lane * 4));
            s2 += __uint_as_float(lds32(sb + SM_SMALL + SMALL_RED + j * 128 + 64 + lane * 4));
          }
          float p0 = __bfloat162float(__ldcg(G->x1T + 16 * b + lane));
          float mu = s1 * (1.f / D_), var = fmaxf(s2 * (1.f / D_) - mu * mu, 0.f);
          float sd = rbf(__fsqrt_rn(rbf(rbf(var) + 1e-5f)));
          const uint32_t hm = pack2(-0.5f * (p0 + mu), -0.5f * (p0 + mu)), hs = pack2(0.5f * sd, 0.5f * sd);
          G->stat[16 * b + lane] = make_uint4(hm, hs, hm, hs);
          v = rdback(G->stat + 16 * b + lane);
        }
        rdwait(sb, v);
        __syncwarp();
        if (lane == 0) flag_add(G, FL_S + m);
        STAMPIF(lane == 0, 21);
      }
    }
    {
      mbar_wait(sb + 8 * (B_HH + (w >> 1)), 0);
      const bf16* p = G->HH + (b * 6 + 3 * (w & 1)) * 4096 + (w >> 1) * 2048 + lane * 64;
      uint32_t v0 = rdback(p), v1 = rdback(p + 4096), v2 = rdback(p + 8192);
      rdwait(sb, v0 ^ v1 ^ v2);
      __syncwarp();
      if (lane == 0) flag_add(G, FL_H + b);
      STAMPIF(tid == 0, 50);
    }
  } else {
    cp_arrive(sb + 8 * (B_B + wg));
    asm volatile("setmaxnreg.inc.sync.aligned.u32 224;");
    STAMPIF(threadIdx.x == 0, 82);
    const int g = lane >> 2, q = lane & 3;
    if (wg == 1) bar_arrive(1, 256);
    if (tid < 2) mbar_arrive(sb + 8 * (B_E1 + tid));
    if (tid == 3 && wg == 1) mbar_arrive(sb + 8 * (B_E1 + 5));
    uint32_t dv = *(const uint16_t*)(gD + 128 * wg + b);
    {
      const int t2 = threadIdx.x, w2 = 4 * wg + w;
      STAMPIF(t2 == 0, 20);
      kv_job(G, sb, b, wg, tid);
      __syncwarp();
      STAMPIF(t2 == 0, 78);
      kv_signal(G, sb, b, wg, 8 * w + (lane & 7), lane == 0);
      STAMPIF(tid == 0, 1 + wg);
      mbar_wait(sb + 8 * B_X, 0);
      mbar_wait(sb + 8 * (B_X + 1), 0);
      STAMPIF(t2 == 0, 25);
      const uint32_t xr = ring + R_X + (15 - (t2 >> 4)) * 128;
      float pv = blo(lds32(xr)), s1 = 0.f, s2 = 0.f;
#pragma unroll
      for (int n = 0; n < 5; n++) {
        uint4 v = lds128(xr + 16 * (t2 & 7) + 2048 * ((t2 >> 3) & 1) + 4096 * n);
        uint32_t u[4] = {v.x, v.y, v.z, v.w};
#pragma unroll
        for (int j = 0; j < 4; j++) {
          float a = blo(u[j]) - pv, c = bhi(u[j]) - pv;
          s1 += a + c; s2 += a * a; s2 += c * c;
        }
      }
      uint32_t r[5][4];
      const uint32_t la = ring + R_X + wg * 2048 + (15 - (lane & 15)) * 128 + (((2 * w + (lane >> 4)) ^ (~lane & 7)) << 4);
#pragma unroll
      for (int n = 0; n < 5; n++) ldsm4t(r[n], la + n * 4096);
#pragma unroll
      for (int o = 1; o < 16; o <<= 1) { s1 += __shfl_xor_sync(0xffffffffu, s1, o); s2 += __shfl_xor_sync(0xffffffffu, s2, o); }
      if ((t2 & 15) == 0) {
        float mu = s1 * (1.f / D_), var = fmaxf(s2 * (1.f / D_) - mu * mu, 0.f);
        float sd = rbf(__fsqrt_rn(rbf(rbf(var) + 1e-5f)));
        sts16(sb + SM_SMALL + SMALL_XM + 2 * (t2 >> 4), pack2(pv + mu, 0.f));
        sts32(sb + SM_SMALL + SMALL_XM + 32 + 4 * (t2 >> 4), __float_as_uint(__frcp_rn(sd)));
      }
      bar_sync(6, 256);
      STAMPIF(t2 == 0, 75);
      const uint32_t m0 = lds32(sb + SM_SMALL + SMALL_XM + 4 * q), m1 = lds32(sb + SM_SMALL + SMALL_XM + 16 + 4 * q);
      const uint2 r0 = lds64(sb + SM_SMALL + SMALL_XM + 32 + 8 * q), r1 = lds64(sb + SM_SMALL + SMALL_XM + 64 + 8 * q);
#pragma unroll
      for (int n = 0; n < 5; n++) {
#pragma unroll
        for (int j = 0; j < 2; j++) {
          uint32_t a = hsub(r[n][2 * j], m0), c = hsub(r[n][2 * j + 1], m1);
          sts128(xh_base(sb, n) + 1024 * w2 + 512 * j + 16 * lane,
                 make_uint4(r[n][2 * j], r[n][2 * j + 1], pack2(blo(a) * __uint_as_float(r0.x), bhi(a) * __uint_as_float(r0.y)),
                            pack2(blo(c) * __uint_as_float(r1.x), bhi(c) * __uint_as_float(r1.y))));
        }
      }
      fence_async_s();
      __syncwarp();
      if (lane == 0) mbar_arrive(sb + 8 * B_XS);
      STAMPIF(t2 == 0, 26);
      k1_job(sb, wg, tid);
      bar_sync(3 + wg, 128);
      STAMPIF(t2 == 0, 79);
    }
    {
      const int b0 = (g >> 1) & 1, b1 = g >> 2, u = q + 4 * b0 - w;
      const uint32_t fo = 128 + (g & 1) * K1OFF + 288 * b1 + 4 * u, fo0 = fo - (u < 0 ? 32 : 0);
      const uint32_t dsel = (b1 == 0 && u == 0) ? ((g & 1) ? 0x1044 : 0x4410) : 0x4444;
      const bool wrap = b0 && q == 0;
      const int src1 = b0 ? ((lane & 20) | ((q - 1) & 3)) : (lane | 8);
#pragma unroll 1
      for (int ch = wg; ch < 5; ch += 2) {
        const uint32_t base = chan_base(sb, ch);
        if (ch >= 2) { mbar_wait(sb + 8 * (B_K + ch - 2), 0); mbar_wait(sb + 8 * (B_S + ch), 0); }
        const uint32_t fa = base + fo, fa0 = base + fo0;
        uint32_t af[16][4];
#pragma unroll
        for (int j = 0; j < 16; j++) {
          const int o = 64 * (j & 1) + 576 * (j >> 1);
          af[j][0] = lds32(((j & 1) ? fa : fa0) + o); af[j][1] = lds32(fa + o + 128); af[j][2] = lds32(fa + o + 32); af[j][3] = lds32(fa + o + 160);
        }
        af[0][0] = hadd(af[0][0], __byte_perm(dv, 0, dsel));
        if (ch < 3) dv = *(const uint16_t*)(gD + 128 * (ch + 2) + b);
        mbar_wait(sb + 8 * (B_U + ch), 0);
        float acc[128];
        const uint64_t db = mkdesc(base + KSZ, 32, 128, 0);
        bar_sync(1 + wg, 256);
        STAMPIF(tid == 0, 3 + ch);
        wg_fence();
        wgmma_rs_n64<0>(acc + 96, af[0], db + 192, 0);
        wgmma_rs_n192<0>(acc, af[0], db, 0);
        wgmma_rs_n64<0>(acc + 96, af[1], db + 196, 1);
        wgmma_rs_n192<0>(acc, af[1], db + 4, 1);
        wgmma_rs_n32<0>(acc + 96, af[2], db + 224, 1);
        wgmma_rs_n192<0>(acc, af[2], db + 32, 1);
        wgmma_rs_n32<0>(acc + 96, af[3], db + 228, 1);
        wgmma_rs_n192<0>(acc, af[3], db + 36, 1);
        wgmma_rs_n192<0>(acc, af[4], db + 64, 1);
        wgmma_rs_n192<0>(acc, af[5], db + 68, 1);
        wgmma_rs_n160<0>(acc, af[6], db + 96, 1);
        wgmma_rs_n160<0>(acc, af[7], db + 100, 1);
        wgmma_rs_n128<0>(acc, af[8], db + 128, 1);
        wgmma_rs_n128<0>(acc, af[9], db + 132, 1);
        wgmma_rs_n96<0>(acc, af[10], db + 160, 1);
        wgmma_rs_n96<0>(acc, af[11], db + 164, 1);
        bar_arrive(2 - wg, 256);
        wgmma_rs_n64<0>(acc, af[12], db + 192, 1);
        wgmma_rs_n64<0>(acc, af[13], db + 196, 1);
        wgmma_rs_n32<0>(acc, af[14], db + 224, 1);
        wgmma_rs_n32<0>(acc, af[15], db + 228, 1);
        wg_commit();
        wg_wait<0>();
#pragma unroll
        for (int i = 0; i < 128; i++) asm volatile("" : "+f"(acc[i])::"memory");
        bar_sync(3 + wg, 128);
        if (tid == 0) mbar_arrive(sb + 8 * (B_E1 + 2 + (ch >> 1)));
        float S0[33], T[34];
#pragma unroll
        for (int i = 0; i < 31; i++) S0[i] = acc[4 * i] + acc[4 * i + 6];
        S0[31] = acc[124]; S0[32] = 0.f;
#pragma unroll
        for (int i = 0; i < 32; i++) {
          float s1 = i < 31 ? acc[4 * i + 1] + acc[4 * i + 7] : acc[125];
          T[i] = (wrap ? S0[i + 1] : S0[i]) + __shfl_sync(0xffffffffu, s1, src1);
        }
        T[32] = 0.f; T[33] = 0.f;
        uint32_t zz[8];
#pragma unroll
        for (int mu = 0; mu < 8; mu++) {
          float y0 = (b1 ? T[4 * mu + 4] : T[4 * mu]) + __shfl_xor_sync(0xffffffffu, T[4 * mu + 2], 16);
          float y1 = (b1 ? T[4 * mu + 5] : T[4 * mu + 1]) + __shfl_xor_sync(0xffffffffu, T[4 * mu + 3], 16);
          zz[mu] = pack2(y0, y1);
        }
        sts128(sb + SM_Z + ch * 4096 + tid * 32, make_uint4(zz[0], zz[4], zz[1], zz[5]));
        sts128(sb + SM_Z + ch * 4096 + tid * 32 + 16, make_uint4(zz[2], zz[6], zz[3], zz[7]));
        __syncwarp();
        if (lane == 0) mbar_arrive(sb + 8 * (B_Z + ch));
        STAMPIF(tid == 0, 8 + ch);
      }
      if (wg == 1) bar_sync(2, 256);
    }
    uint32_t hh[48];
    {
      float ga[192];
      float* ua = ga + 96;
      const uint64_t da0 = mkdesc(ring + wg * 4096, 4096, 1024, 1), db0 = mkdesc(ring + 8192, 4096, 1024, 1);
      int st = 0, ph = 0;
#pragma unroll 1
      for (int it = 0; it < 20; it++) {
        mbar_wait(sb + 8 * (B_F1 + st), ph);
        STAMPIF(tid == 0 && it == 0, 13 + wg);
        const uint64_t da = da0 + st * 2048, db = db0 + st * 2048;
        wg_fence();
        wgmma_ss_n192<1, 1>(ga, da, db, it != 0);
        wgmma_ss_n192<1, 1>(ua, da, db + 768, it != 0);
        wgmma_ss_n192<1, 1>(ga, da + 128, db + 128, 1);
        wgmma_ss_n192<1, 1>(ua, da + 128, db + 128 + 768, 1);
        wg_commit();
        wg_wait<1>();
        if (it > 0 && tid == 0) mbar_arrive(sb + 8 * (B_E1 + (st == 0 ? 5 : st - 1)));
        if (++st == 6) { st = 0; ph ^= 1; }
      }
      mbar_wait(sb + 8 * B_EXT, 0);
      const uint64_t de = mkdesc(sb + SM_EXT, 1024, 0, 1), ds = mkdesc(sb + SM_STAT + wg * 1024, 0, 128, 0);
      wg_fence();
      wgmma_ss_n192<0, 1>(ga, ds, de, 1);
      wgmma_ss_n192<0, 1>(ua, ds, de + 192, 1);
      wg_commit();
      wg_wait<1>();
      if (tid == 0) mbar_arrive(sb + 8 * (B_E1 + 1));
      wg_wait<0>();
#pragma unroll
      for (int i = 0; i < 192; i++) asm volatile("" : "+f"(ga[i])::"memory");
      STAMPIF(tid == 0, 15 + wg);
#pragma unroll
      for (int i = 0; i < 48; i++) {
        const int j = 64 * (i >> 4) + 2 * (i & 15);
        hh[i] = pack2(ga[j] * ga[j + 32], ga[j + 1] * ga[j + 33]);
      }
    }
    float acc[80];
    {
      bf16* dst = G->HH + b * 6 * 4096 + (64 * wg + 16 * w + g) * 32 + ((q ^ ((g >> 1) & 3)) << 3);
#pragma unroll
      for (int k = 0; k < 6; k++) {
        *(uint4*)(dst + k * 4096) = make_uint4(hh[8 * k], hh[8 * k + 2], hh[8 * k + 4], hh[8 * k + 6]);
        *(uint4*)(dst + k * 4096 + 256) = make_uint4(hh[8 * k + 1], hh[8 * k + 3], hh[8 * k + 5], hh[8 * k + 7]);
      }
      __syncwarp();
      if (lane == 0) mbar_arrive(sb + 8 * (B_HH + wg));
      const uint64_t db0 = mkdesc(ring + 8192, 4096, 1024, 1), da0 = mkdesc(ring + wg * 4096, 16, 512, 2);
#pragma unroll
      for (int k = 0; k < 6; k++) {
        mbar_wait(sb + 8 * (B_FB + k), 0);
        const uint64_t db = db0 + ((k >> 1) + 2) * 2048 + (k & 1) * 768;
        wg_fence();
        wgmma_rs_n160<1>(acc, hh + 8 * k, db, k != 0);
        wgmma_rs_n160<1>(acc, hh + 8 * k + 4, db + 128, 1);
        wg_commit();
        wg_wait<1>();
        if (k > 0 && tid == 0) mbar_arrive(sb + 8 * (B_EB + k - 1));
      }
      STAMPIF(tid == 0, 17);
      int ka = 0, pa = 0;
#pragma unroll 1
      for (int k = 6; k < 24; k++) {
        const int sl = k < 12 ? k : k - 12;
        int gb_ = (sl >> 1) + 2; if (gb_ >= 6) gb_ -= 6;
        int ga_ = ka + 2; if (ga_ >= 6) ga_ -= 6;
        mbar_wait(sb + 8 * (B_FB + sl), k >= 12);
        mbar_wait(sb + 8 * (B_FA + ka), pa);
        const uint64_t db = db0 + gb_ * 2048 + (sl & 1) * 768, da = da0 + ga_ * 2048;
        wg_fence();
        wgmma_ss_n160<0, 1>(acc, da, db, 1);
        wgmma_ss_n160<0, 1>(acc, da + 2, db + 128, 1);
        wg_commit();
        wg_wait<1>();
        if (tid == 0) {
          mbar_arrive(sb + 8 * (B_EB + (sl == 0 ? 11 : sl - 1)));
          if (k > 6) mbar_arrive(sb + 8 * (B_EA + (ka == 0 ? 5 : ka - 1)));
        }
        if (++ka == 6) { ka = 0; pa ^= 1; }
      }
    }
    uint32_t xr[20], gbv[10];
    mbar_wait(sb + 8 * B_X1, 0);
    mbar_wait(sb + 8 * B_GB, 0);
    {
      const uint32_t la = sb + SM_Z + wg * 10240 + (8 * (lane >> 4) + (lane & 7)) * 128 + (((2 * w + ((lane >> 3) & 1)) ^ (lane & 7)) << 4);
#pragma unroll
      for (int i = 0; i < 5; i++) ldsm4t(xr + 4 * i, la + i * 2048);
#pragma unroll
      for (int i = 0; i < 10; i++) gbv[i] = lds32(sb + SM_SMALL + SMALL_GB + 16 * i + 4 * q);
    }
    float rs0 = 2.f * blo(lds32(sb + SM_STAT + (64 * wg + 16 * w + g) * 16 + 4)), rs1 = 2.f * blo(lds32(sb + SM_STAT + (64 * wg + 16 * w + g) * 16 + 132));
    rs0 = __frcp_rn(rs0 * rs0); rs1 = __frcp_rn(rs1 * rs1);
    mbar_wait(sb + 8 * B_PEER, 0);
    wg_wait<0>();
#pragma unroll
    for (int i = 0; i < 80; i++) asm volatile("" : "+f"(acc[i])::"memory");
    STAMPIF(tid == 0, 18);
    const uint32_t rbuf = ring + (2 + wg) * 32768 + 8192 + w * 5120;
    {
      const uint32_t rd = mapa(rbuf + lane * 16, (b & 1) ^ 1), rb = mapa(sb + 8 * (B_RECV + wg), (b & 1) ^ 1);
      if (b & 1) {
#pragma unroll
        for (int i = 0; i < 10; i++) st_async4(rd + i * 512, acc[4 * i], acc[4 * i + 1], acc[4 * i + 2], acc[4 * i + 3], rb);
#pragma unroll
        for (int i = 0; i < 40; i++) acc[i] = acc[40 + i];
      } else {
#pragma unroll
        for (int i = 0; i < 10; i++) st_async4(rd + i * 512, acc[40 + 4 * i], acc[41 + 4 * i], acc[42 + 4 * i], acc[43 + 4 * i], rb);
      }
    }
    mbar_wait(sb + 8 * (B_RECV + wg), 0);
    uint32_t ov[20];
#pragma unroll
    for (int i = 0; i < 10; i++) {
      uint4 v = lds128(rbuf + i * 512 + lane * 16);
      uint32_t o0 = pack2((acc[4 * i] + __uint_as_float(v.x)) * rs0, (acc[4 * i + 1] + __uint_as_float(v.y)) * rs0);
      uint32_t o1 = pack2((acc[4 * i + 2] + __uint_as_float(v.z)) * rs1, (acc[4 * i + 3] + __uint_as_float(v.w)) * rs1);
      ov[2 * i] = hadd(xr[2 * i], hmul(gbv[i], o0));
      ov[2 * i + 1] = hadd(xr[2 * i + 1], hmul(gbv[i], o1));
    }
    __syncwarp();
#pragma unroll
    for (int i = 0; i < 5; i++) stsm4(rbuf + (15 - (4 * (lane & 2) + 2 * ((lane >> 2) & 3) + (lane & 1))) * 160 + (lane >> 4) * 16 + i * 32, ov + 4 * i);
    fence_async_s();
    __syncwarp();
    if (lane == 0) {
      tma_store4d(&P.mO, rbuf, 80 * s, 0, 0, 191 - ibase(8 * m + 4 * wg + w));
      asm volatile("cp.async.bulk.commit_group;" ::: "memory");
      asm volatile("cp.async.bulk.wait_group.read 0;" ::: "memory");
    }
  }
}

typedef CUresult (*EncFn)(CUtensorMap*, CUtensorMapDataType, cuuint32_t, void*, const cuuint64_t*, const cuuint64_t*, const cuuint32_t*, const cuuint32_t*,
                          CUtensorMapInterleave, CUtensorMapSwizzle, CUtensorMapL2promotion, CUtensorMapFloatOOBfill);
static void mkmap(EncFn enc, CUtensorMap* m, const void* p, int rank, const cuuint64_t* dims, const cuuint64_t* strides, const cuuint32_t* box, CUtensorMapSwizzle sw) {
  cuuint32_t es[5] = {1, 1, 1, 1, 1};
  CUresult r = enc(m, CU_TENSOR_MAP_DATA_TYPE_BFLOAT16, rank, (void*)p, dims, strides, box, es, CU_TENSOR_MAP_INTERLEAVE_NONE, sw,
                   CU_TENSOR_MAP_L2_PROMOTION_L2_128B, CU_TENSOR_MAP_FLOAT_OOB_FILL_NONE);
  if (r != CUDA_SUCCESS) fprintf(stderr, "tensor map encode failed: %d\n", (int)r);
}

extern "C" void kernel_launch(void* const* d_in, const int* in_sizes, int n_in, void* d_out, int out_size) {
  void* fn = nullptr;
  cudaDriverEntryPointQueryResult qr;
  cudaGetDriverEntryPoint("cuTensorMapEncodeTiled", &fn, cudaEnableDefault, &qr);
  EncFn enc = (EncFn)fn;
  Scr* G;
  cudaGetSymbolAddress((void**)&G, g_scr);
  void *pAT = G->AT, *pX1 = G->x1T;
  Params P;
  { cuuint64_t d[] = {4096, 640}, st[] = {8192}; cuuint32_t bx[] = {32, 128}; mkmap(enc, &P.mXH, G->XH, 2, d, st, bx, CU_TENSOR_MAP_SWIZZLE_NONE); }
  { cuuint64_t d[] = {128, 16, 640}, st[] = {256, 4096}; cuuint32_t bx[] = {144, 16, 1}; mkmap(enc, &P.mS, d_in[4], 3, d, st, bx, CU_TENSOR_MAP_SWIZZLE_NONE); }
  { cuuint64_t d[] = {3840, 640}, st[] = {7680}; cuuint32_t bx[] = {64, 80}; mkmap(enc, &P.mWm, d_in[11], 2, d, st, bx, CU_TENSOR_MAP_SWIZZLE_128B); }
  { cuuint64_t d[] = {64, 640, 32}, st[] = {4096, 128}; cuuint32_t bx[] = {64, 32, 2}; mkmap(enc, &P.mA, pAT, 3, d, st, bx, CU_TENSOR_MAP_SWIZZLE_128B); }
  { cuuint64_t d[] = {64, 640, 32}, st[] = {4096, 128}; cuuint32_t bx[] = {64, 80, 2}; mkmap(enc, &P.mX1, pX1, 3, d, st, bx, CU_TENSOR_MAP_SWIZZLE_128B); }
  { cuuint64_t d[] = {1536, 640}, st[] = {3072}; cuuint32_t bx[] = {64, 32};
    mkmap(enc, &P.mG, d_in[7], 2, d, st, bx, CU_TENSOR_MAP_SWIZZLE_128B); mkmap(enc, &P.mU, d_in[8], 2, d, st, bx, CU_TENSOR_MAP_SWIZZLE_128B); }
  { cuuint64_t d[] = {160, 2, 4, 192, 4}, st[] = {1280, 2560, 10240, 320}; cuuint32_t bx[] = {64, 2, 4, 4, 1}; mkmap(enc, &P.mDn, d_in[9], 5, d, st, bx, CU_TENSOR_MAP_SWIZZLE_128B); }
  { cuuint64_t d[] = {160, 2, 192, 4, 4}, st[] = {1280, 10240, 2560, 320}; cuuint32_t bx[] = {64, 2, 4, 4, 1}; mkmap(enc, &P.mDp, d_in[9], 5, d, st, bx, CU_TENSOR_MAP_SWIZZLE_128B); }
  { cuuint64_t d[] = {64, 2, 8, 10, 192}, st[] = {64 * 1280, 256 * 1280, 128, 1280}; cuuint32_t bx[] = {64, 2, 8, 5, 1}; mkmap(enc, &P.mX, d_in[0], 5, d, st, bx, CU_TENSOR_MAP_SWIZZLE_128B); }
  { cuuint64_t d[] = {640, 2, 8, 192}, st[] = {64 * 1280, 256 * 1280, 1280}; cuuint32_t bx[] = {80, 2, 8, 1}; mkmap(enc, &P.mO, d_out, 4, d, st, bx, CU_TENSOR_MAP_SWIZZLE_NONE); }
  cudaFuncSetAttribute(fused_kernel, cudaFuncAttributeMaxDynamicSharedMemorySize, SM_TOTAL + DEVSM);
  cudaLaunchConfig_t cfg = {};
  cfg.gridDim = dim3(128); cfg.blockDim = dim3(512); cfg.dynamicSmemBytes = SM_TOTAL + DEVSM; cfg.stream = cudaStreamPerThread;
  cudaLaunchAttribute at[1];
  at[0].id = cudaLaunchAttributeClusterDimension; at[0].val.clusterDim.x = 2; at[0].val.clusterDim.y = 1; at[0].val.clusterDim.z = 1;
  cfg.attrs = at; cfg.numAttrs = 1;
  cudaLaunchKernelEx(&cfg, fused_kernel, (const bf16*)d_in[1], (const bf16*)d_in[2], (const bf16*)d_in[3], (const bf16*)d_in[5], (const bf16*)d_in[10], G, P);
}
```

```cpp
#include <cuda_runtime.h>
#include <cuda.h>
#include <cuda_bf16.h>
#include <stdio.h>
#include <stdint.h>
typedef __nv_bfloat16 bf16;
__device__ __forceinline__ uint32_t smem_u32(const void* p) { return (uint32_t)__cvta_generic_to_shared(p); }
__device__ __forceinline__ void mbar_init(uint32_t bar, int cnt) { asm volatile("mbarrier.init.shared::cta.b64 [%0], %1;" ::"r"(bar), "r"(cnt) : "memory"); }
__device__ __forceinline__ void mbar_expect(uint32_t bar, int bytes) { asm volatile("mbarrier.arrive.expect_tx.shared::cta.b64 _, [%0], %1;" ::"r"(bar), "r"(bytes) : "memory"); }
__device__ __forceinline__ void mbar_arrive(uint32_t bar) { asm volatile("mbarrier.arrive.shared::cta.b64 _, [%0];" ::"r"(bar) : "memory"); }
__device__ __forceinline__ void mbar_arrive_remote(uint32_t bar) { asm volatile("mbarrier.arrive.relaxed.cluster.shared::cluster.b64 _, [%0];" ::"r"(bar) : "memory"); }
__device__ __forceinline__ uint32_t mapa(uint32_t a, uint32_t cta) { uint32_t r; asm("mapa.shared::cluster.u32 %0, %1, %2;" : "=r"(r) : "r"(a), "r"(cta)); return r; }
__device__ __forceinline__ bool mbar_try(uint32_t bar, int parity) {
  uint32_t ok;
  asm volatile("{\n.reg .pred p;\nmbarrier.try_wait.parity.shared::cta.b64 p, [%1], %2;\nselp.u32 %0, 1, 0, p;\n}" : "=r"(ok) : "r"(bar), "r"(parity) : "memory");
  return ok;
}
__device__ __forceinline__ void mbar_wait(uint32_t bar, int parity) {
#pragma unroll 1
  for (int i = 0; i < (1 << 20); i++) { if (mbar_try(bar, parity)) return; }
  __trap();
}
__device__ __forceinline__ void tma2d(uint32_t dst, const CUtensorMap* m, int c0, int c1, uint32_t bar) {
  asm volatile("cp.async.bulk.tensor.2d.shared::cluster.global.mbarrier::complete_tx::bytes [%0], [%1, {%3, %4}], [%2];" ::"r"(dst), "l"(m), "r"(bar), "r"(c0), "r"(c1) : "memory");
}
__device__ __forceinline__ void tma3d(uint32_t dst, const CUtensorMap* m, int c0, int c1, int c2, uint32_t bar) {
  asm volatile("cp.async.bulk.tensor.3d.shared::cluster.global.mbarrier::complete_tx::bytes [%0], [%1, {%3, %4, %5}], [%2];" ::"r"(dst), "l"(m), "r"(bar), "r"(c0), "r"(c1), "r"(c2) : "memory");
}
__device__ __forceinline__ void tma5d(uint32_t dst, const CUtensorMap* m, int c0, int c1, int c2, int c3, int c4, uint32_t bar) {
  asm volatile("cp.async.bulk.tensor.5d.shared::cluster.global.mbarrier::complete_tx::bytes [%0], [%1, {%3, %4, %5, %6, %7}], [%2];" ::"r"(dst), "l"(m), "r"(bar), "r"(c0), "r"(c1), "r"(c2), "r"(c3), "r"(c4) : "memory");
}
__device__ __forceinline__ void tma_store2d(const CUtensorMap* m, uint32_t src, int c0, int c1) {
  asm volatile("cp.async.bulk.tensor.2d.global.shared::cta.bulk_group [%0, {%2, %3}], [%1];" ::"l"(m), "r"(src), "r"(c0), "r"(c1) : "memory");
}
__device__ __forceinline__ void tma_store4d(const CUtensorMap* m, uint32_t src, int c0, int c1, int c2, int c3) {
  asm volatile("cp.async.bulk.tensor.4d.global.shared::cta.bulk_group [%0, {%2, %3, %4, %5}], [%1];" ::"l"(m), "r"(src), "r"(c0), "r"(c1), "r"(c2), "r"(c3) : "memory");
}
__device__ __forceinline__ void tma_prefetch2d(const CUtensorMap* m, int c0, int c1) {
  asm volatile("cp.async.bulk.prefetch.tensor.2d.L2.global [%0, {%1, %2}];" ::"l"(m), "r"(c0), "r"(c1) : "memory");
}
__device__ __forceinline__ void bulk_g2s(uint32_t dst, const void* src, int bytes, uint32_t bar) {
  asm volatile("cp.async.bulk.shared::cluster.global.mbarrier::complete_tx::bytes [%0], [%1], %2, [%3];" ::"r"(dst), "l"(src), "r"(bytes), "r"(bar) : "memory");
}
__device__ __forceinline__ void bulk_s2g(void* dst, uint32_t src, int bytes) {
  asm volatile("cp.async.bulk.global.shared::cta.bulk_group [%0], [%1], %2;" ::"l"(dst), "r"(src), "r"(bytes) : "memory");
}
__device__ __forceinline__ void cp16(uint32_t dst, const void* src) { asm volatile("cp.async.cg.shared.global [%0], [%1], 16;" ::"r"(dst), "l"(src) : "memory"); }
__device__ __forceinline__ void cp16z(uint32_t dst, const void* src, int n) { asm volatile("cp.async.cg.shared.global [%0], [%1], 16, %2;" ::"r"(dst), "l"(src), "r"(n) : "memory"); }
__device__ __forceinline__ void cp_arrive(uint32_t bar) { asm volatile("cp.async.mbarrier.arrive.noinc.shared::cta.b64 [%0];" ::"r"(bar) : "memory"); }
__device__ __forceinline__ void st_async4(uint32_t dst, float a, float b, float c, float d, uint32_t bar) {
  asm volatile("st.async.weak.shared::cluster.mbarrier::complete_tx::bytes.v4.f32 [%0], {%1, %2, %3, %4}, [%5];" ::"r"(dst), "f"(a), "f"(b), "f"(c), "f"(d), "r"(bar) : "memory");
}
__device__ __forceinline__ void wg_fence() { asm volatile("wgmma.fence.sync.aligned;" ::: "memory"); }
__device__ __forceinline__ void wg_commit() { asm volatile("wgmma.commit_group.sync.aligned;" ::: "memory"); }
template <int N> __device__ __forceinline__ void wg_wait() { asm volatile("wgmma.wait_group.sync.aligned %0;" ::"n"(N) : "memory"); }
__device__ __forceinline__ uint64_t mkdesc(uint32_t addr, uint32_t lbo, uint32_t sbo, uint32_t swz) {
  return (uint64_t)((addr & 0x3FFFF) >> 4) | ((uint64_t)(lbo >> 4) << 16) | ((uint64_t)(sbo >> 4) << 32) | ((uint64_t)swz << 62);
}
__device__ __forceinline__ void ldsm4t(uint32_t* r, uint32_t a) {
  asm volatile("ldmatrix.sync.aligned.m8n8.x4.trans.shared.b16 {%0,%1,%2,%3}, [%4];" : "=r"(r[0]), "=r"(r[1]), "=r"(r[2]), "=r"(r[3]) : "r"(a) : "memory");
}
__device__ __forceinline__ void stsm4(uint32_t a, const uint32_t* r) {
  asm volatile("stmatrix.sync.aligned.m8n8.x4.shared.b16 [%0], {%1,%2,%3,%4};" ::"r"(a), "r"(r[0]), "r"(r[1]), "r"(r[2]), "r"(r[3]) : "memory");
}
__device__ __forceinline__ void bar_sync(int id, int n) { asm volatile("bar.sync %0, %1;" ::"r"(id), "r"(n) : "memory"); }
__device__ __forceinline__ void bar_arrive(int id, int n) { asm volatile("bar.arrive %0, %1;" ::"r"(id), "r"(n) : "memory"); }
__device__ __forceinline__ uint32_t lds32(uint32_t a) { uint32_t v; asm volatile("ld.shared.b32 %0, [%1];" : "=r"(v) : "r"(a) : "memory"); return v; }
__device__ __forceinline__ uint2 lds64(uint32_t a) { uint2 v; asm volatile("ld.shared.v2.b32 {%0,%1}, [%2];" : "=r"(v.x), "=r"(v.y) : "r"(a) : "memory"); return v; }
__device__ __forceinline__ uint4 lds128(uint32_t a) { uint4 v; asm volatile("ld.shared.v4.b32 {%0,%1,%2,%3}, [%4];" : "=r"(v.x), "=r"(v.y), "=r"(v.z), "=r"(v.w) : "r"(a) : "memory"); return v; }
__device__ __forceinline__ void sts16(uint32_t a, uint32_t v) { asm volatile("st.shared.b16 [%0], %1;" ::"r"(a), "h"((uint16_t)v) : "memory"); }
__device__ __forceinline__ void sts32(uint32_t a, uint32_t v) { asm volatile("st.shared.b32 [%0], %1;" ::"r"(a), "r"(v) : "memory"); }
__device__ __forceinline__ void sts64(uint32_t a, uint32_t x, uint32_t y) { asm volatile("st.shared.v2.b32 [%0], {%1,%2};" ::"r"(a), "r"(x), "r"(y) : "memory"); }
__device__ __forceinline__ void sts128(uint32_t a, uint4 v) { asm volatile("st.shared.v4.b32 [%0], {%1,%2,%3,%4};" ::"r"(a), "r"(v.x), "r"(v.y), "r"(v.z), "r"(v.w) : "memory"); }
template<int TB> __device__ __forceinline__ void wgmma_rs_n128(float* d, const uint32_t* a, uint64_t db, int sd) {
  asm volatile("{\n.reg .pred p;\nsetp.ne.b32 p, %69, 0;\n"
    "wgmma.mma_async.sync.aligned.m64n128k16.f32.bf16.bf16 {%0, %1, %2, %3, %4, %5, %6, %7, %8, %9, %10, %11, %12, %13, %14, %15, %16, %17, %18, %19, %20, %21, %22, %23, %24, %25, %26, %27, %28, %29, %30, %31, %32, %33, %34, %35, %36, %37, %38, %39, %40, %41, %42, %43, %44, %45, %46, %47, %48, %49, %50, %51, %52, %53, %54, %55, %56, %57, %58, %59, %60, %61, %62, %63}, {%64, %65, %66, %67}, %68, p, 1, 1, %70;\n}"
    : "+f"(d[0]), "+f"(d[1]), "+f"(d[2]), "+f"(d[3]), "+f"(d[4]), "+f"(d[5]), "+f"(d[6]), "+f"(d[7]), "+f"(d[8]), "+f"(d[9]), "+f"(d[10]), "+f"(d[11]), "+f"(d[12]), "+f"(d[13]), "+f"(d[14]), "+f"(d[15]), "+f"(d[16]), "+f"(d[17]), "+f"(d[18]), "+f"(d[19]), "+f"(d[20]), "+f"(d[21]), "+f"(d[22]), "+f"(d[23]), "+f"(d[24]), "+f"(d[25]), "+f"(d[26]), "+f"(d[27]), "+f"(d[28]), "+f"(d[29]), "+f"(d[30]), "+f"(d[31]), "+f"(d[32]), "+f"(d[33]), "+f"(d[34]), "+f"(d[35]), "+f"(d[36]), "+f"(d[37]), "+f"(d[38]), "+f"(d[39]), "+f"(d[40]), "+f"(d[41]), "+f"(d[42]), "+f"(d[43]), "+f"(d[44]), "+f"(d[45]), "+f"(d[46]), "+f"(d[47]), "+f"(d[48]), "+f"(d[49]), "+f"(d[50]), "+f"(d[51]), "+f"(d[52]), "+f"(d[53]), "+f"(d[54]), "+f"(d[55]), "+f"(d[56]), "+f"(d[57]), "+f"(d[58]), "+f"(d[59]), "+f"(d[60]), "+f"(d[61]), "+f"(d[62]), "+f"(d[63])
    : "r"(a[0]), "r"(a[1]), "r"(a[2]), "r"(a[3]), "l"(db), "r"(sd), "n"(TB));
}

template<int TB> __device__ __forceinline__ void wgmma_rs_n160(float* d, const uint32_t* a, uint64_t db, int sd) {
  asm volatile("{\n.reg .pred p;\nsetp.ne.b32 p, %85, 0;\n"
    "wgmma.mma_async.sync.aligned.m64n160k16.f32.bf16.bf16 {%0, %1, %2, %3, %4, %5, %6, %7, %8, %9, %10, %11, %12, %13, %14, %15, %16, %17, %18, %19, %20, %21, %22, %23, %24, %25, %26, %27, %28, %29, %30, %31, %32, %33, %34, %35, %36, %37, %38, %39, %40, %41, %42, %43, %44, %45, %46, %47, %48, %49, %50, %51, %52, %53, %54, %55, %56, %57, %58, %59, %60, %61, %62, %63, %64, %65, %66, %67, %68, %69, %70, %71, %72, %73, %74, %75, %76, %77, %78, %79}, {%80, %81, %82, %83}, %84, p, 1, 1, %86;\n}"
    : "+f"(d[0]), "+f"(d[1]), "+f"(d[2]), "+f"(d[3]), "+f"(d[4]), "+f"(d[5]), "+f"(d[6]), "+f"(d[7]), "+f"(d[8]), "+f"(d[9]), "+f"(d[10]), "+f"(d[11]), "+f"(d[12]), "+f"(d[13]), "+f"(d[14]), "+f"(d[15]), "+f"(d[16]), "+f"(d[17]), "+f"(d[18]), "+f"(d[19]), "+f"(d[20]), "+f"(d[21]), "+f"(d[22]), "+f"(d[23]), "+f"(d[24]), "+f"(d[25]), "+f"(d[26]), "+f"(d[27]), "+f"(d[28]), "+f"(d[29]), "+f"(d[30]), "+f"(d[31]), "+f"(d[32]), "+f"(d[33]), "+f"(d[34]), "+f"(d[35]), "+f"(d[36]), "+f"(d[37]), "+f"(d[38]), "+f"(d[39]), "+f"(d[40]), "+f"(d[41]), "+f"(d[42]), "+f"(d[43]), "+f"(d[44]), "+f"(d[45]), "+f"(d[46]), "+f"(d[47]), "+f"(d[48]), "+f"(d[49]), "+f"(d[50]), "+f"(d[51]), "+f"(d[52]), "+f"(d[53]), "+f"(d[54]), "+f"(d[55]), "+f"(d[56]), "+f"(d[57]), "+f"(d[58]), "+f"(d[59]), "+f"(d[60]), "+f"(d[61]), "+f"(d[62]), "+f"(d[63]), "+f"(d[64]), "+f"(d[65]), "+f"(d[66]), "+f"(d[67]), "+f"(d[68]), "+f"(d[69]), "+f"(d[70]), "+f"(d[71]), "+f"(d[72]), "+f"(d[73]), "+f"(d[74]), "+f"(d[75]), "+f"(d[76]), "+f"(d[77]), "+f"(d[78]), "+f"(d[79])
    : "r"(a[0]), "r"(a[1]), "r"(a[2]), "r"(a[3]), "l"(db), "r"(sd), "n"(TB));
}

template<int TB> __device__ __forceinline__ void wgmma_rs_n192(float* d, const uint32_t* a, uint64_t db, int sd) {
  asm volatile("{\n.reg .pred p;\nsetp.ne.b32 p, %101, 0;\n"
    "wgmma.mma_async.sync.aligned.m64n192k16.f32.bf16.bf16 {%0, %1, %2, %3, %4, %5, %6, %7, %8, %9, %10, %11, %12, %13, %14, %15, %16, %17, %18, %19, %20, %21, %22, %23, %24, %25, %26, %27, %28, %29, %30, %31, %32, %33, %34, %35, %36, %37, %38, %39, %40, %41, %42, %43, %44, %45, %46, %47, %48, %49, %50, %51, %52, %53, %54, %55, %56, %57, %58, %59, %60, %61, %62, %63, %64, %65, %66, %67, %68, %69, %70, %71, %72, %73, %74, %75, %76, %77, %78, %79, %80, %81, %82, %83, %84, %85, %86, %87, %88, %89, %90, %91, %92, %93, %94, %95}, {%96, %97, %98, %99}, %100, p, 1, 1, %102;\n}"
    : "+f"(d[0]), "+f"(d[1]), "+f"(d[2]), "+f"(d[3]), "+f"(d[4]), "+f"(d[5]), "+f"(d[6]), "+f"(d[7]), "+f"(d[8]), "+f"(d[9]), "+f"(d[10]), "+f"(d[11]), "+f"(d[12]), "+f"(d[13]), "+f"(d[14]), "+f"(d[15]), "+f"(d[16]), "+f"(d[17]), "+f"(d[18]), "+f"(d[19]), "+f"(d[20]), "+f"(d[21]), "+f"(d[22]), "+f"(d[23]), "+f"(d[24]), "+f"(d[25]), "+f"(d[26]), "+f"(d[27]), "+f"(d[28]), "+f"(d[29]), "+f"(d[30]), "+f"(d[31]), "+f"(d[32]), "+f"(d[33]), "+f"(d[34]), "+f"(d[35]), "+f"(d[36]), "+f"(d[37]), "+f"(d[38]), "+f"(d[39]), "+f"(d[40]), "+f"(d[41]), "+f"(d[42]), "+f"(d[43]), "+f"(d[44]), "+f"(d[45]), "+f"(d[46]), "+f"(d[47]), "+f"(d[48]), "+f"(d[49]), "+f"(d[50]), "+f"(d[51]), "+f"(d[52]), "+f"(d[53]), "+f"(d[54]), "+f"(d[55]), "+f"(d[56]), "+f"(d[57]), "+f"(d[58]), "+f"(d[59]), "+f"(d[60]), "+f"(d[61]), "+f"(d[62]), "+f"(d[63]), "+f"(d[64]), "+f"(d[65]), "+f"(d[66]), "+f"(d[67]), "+f"(d[68]), "+f"(d[69]), "+f"(d[70]), "+f"(d[71]), "+f"(d[72]), "+f"(d[73]), "+f"(d[74]), "+f"(d[75]), "+f"(d[76]), "+f"(d[77]), "+f"(d[78]), "+f"(d[79]), "+f"(d[80]), "+f"(d[81]), "+f"(d[82]), "+f"(d[83]), "+f"(d[84]), "+f"(d[85]), "+f"(d[86]), "+f"(d[87]), "+f"(d[88]), "+f"(d[89]), "+f"(d[90]), "+f"(d[91]), "+f"(d[92]), "+f"(d[93]), "+f"(d[94]), "+f"(d[95])
    : "r"(a[0]), "r"(a[1]), "r"(a[2]), "r"(a[3]), "l"(db), "r"(sd), "n"(TB));
}

template<int TB> __device__ __forceinline__ void wgmma_rs_n32(float* d, const uint32_t* a, uint64_t db, int sd) {
  asm volatile("{\n.reg .pred p;\nsetp.ne.b32 p, %21, 0;\n"
    "wgmma.mma_async.sync.aligned.m64n32k16.f32.bf16.bf16 {%0, %1, %2, %3, %4, %5, %6, %7, %8, %9, %10, %11, %12, %13, %14, %15}, {%16, %17, %18, %19}, %20, p, 1, 1, %22;\n}"
    : "+f"(d[0]), "+f"(d[1]), "+f"(d[2]), "+f"(d[3]), "+f"(d[4]), "+f"(d[5]), "+f"(d[6]), "+f"(d[7]), "+f"(d[8]), "+f"(d[9]), "+f"(d[10]), "+f"(d[11]), "+f"(d[12]), "+f"(d[13]), "+f"(d[14]), "+f"(d[15])
    : "r"(a[0]), "r"(a[1]), "r"(a[2]), "r"(a[3]), "l"(db), "r"(sd), "n"(TB));
}

template<int TB> __device__ __forceinline__ void wgmma_rs_n64(float* d, const uint32_t* a, uint64_t db, int sd) {
  asm volatile("{\n.reg .pred p;\nsetp.ne.b32 p, %37, 0;\n"
    "wgmma.mma_async.sync.aligned.m64n64k16.f32.bf16.bf16 {%0, %1, %2, %3, %4, %5, %6, %7, %8, %9, %10, %11, %12, %13, %14, %15, %16, %17, %18, %19, %20, %21, %22, %23, %24, %25, %26, %27, %28, %29, %30, %31}, {%32, %33, %34, %35}, %36, p, 1, 1, %38;\n}"
    : "+f"(d[0]), "+f"(d[1]), "+f"(d[2]), "+f"(d[3]), "+f"(d[4]), "+f"(d[5]), "+f"(d[6]), "+f"(d[7]), "+f"(d[8]), "+f"(d[9]), "+f"(d[10]), "+f"(d[11]), "+f"(d[12]), "+f"(d[13]), "+f"(d[14]), "+f"(d[15]), "+f"(d[16]), "+f"(d[17]), "+f"(d[18]), "+f"(d[19]), "+f"(d[20]), "+f"(d[21]), "+f"(d[22]), "+f"(d[23]), "+f"(d[24]), "+f"(d[25]), "+f"(d[26]), "+f"(d[27]), "+f"(d[28]), "+f"(d[29]), "+f"(d[30]), "+f"(d[31])
    : "r"(a[0]), "r"(a[1]), "r"(a[2]), "r"(a[3]), "l"(db), "r"(sd), "n"(TB));
}

template<int TB> __device__ __forceinline__ void wgmma_rs_n96(float* d, const uint32_t* a, uint64_t db, int sd) {
  asm volatile("{\n.reg .pred p;\nsetp.ne.b32 p, %53, 0;\n"
    "wgmma.mma_async.sync.aligned.m64n96k16.f32.bf16.bf16 {%0, %1, %2, %3, %4, %5, %6, %7, %8, %9, %10, %11, %12, %13, %14, %15, %16, %17, %18, %19, %20, %21, %22, %23, %24, %25, %26, %27, %28, %29, %30, %31, %32, %33, %34, %35, %36, %37, %38, %39, %40, %41, %42, %43, %44, %45, %46, %47}, {%48, %49, %50, %51}, %52, p, 1, 1, %54;\n}"
    : "+f"(d[0]), "+f"(d[1]), "+f"(d[2]), "+f"(d[3]), "+f"(d[4]), "+f"(d[5]), "+f"(d[6]), "+f"(d[7]), "+f"(d[8]), "+f"(d[9]), "+f"(d[10]), "+f"(d[11]), "+f"(d[12]), "+f"(d[13]), "+f"(d[14]), "+f"(d[15]), "+f"(d[16]), "+f"(d[17]), "+f"(d[18]), "+f"(d[19]), "+f"(d[20]), "+f"(d[21]), "+f"(d[22]), "+f"(d[23]), "+f"(d[24]), "+f"(d[25]), "+f"(d[26]), "+f"(d[27]), "+f"(d[28]), "+f"(d[29]), "+f"(d[30]), "+f"(d[31]), "+f"(d[32]), "+f"(d[33]), "+f"(d[34]), "+f"(d[35]), "+f"(d[36]), "+f"(d[37]), "+f"(d[38]), "+f"(d[39]), "+f"(d[40]), "+f"(d[41]), "+f"(d[42]), "+f"(d[43]), "+f"(d[44]), "+f"(d[45]), "+f"(d[46]), "+f"(d[47])
    : "r"(a[0]), "r"(a[1]), "r"(a[2]), "r"(a[3]), "l"(db), "r"(sd), "n"(TB));
}

template<int TA, int TB> __device__ __forceinline__ void wgmma_ss_n160(float* d, uint64_t da, uint64_t db, int sd) {
  asm volatile("{\n.reg .pred p;\nsetp.ne.b32 p, %82, 0;\n"
    "wgmma.mma_async.sync.aligned.m64n160k16.f32.bf16.bf16 {%0, %1, %2, %3, %4, %5, %6, %7, %8, %9, %10, %11, %12, %13, %14, %15, %16, %17, %18, %19, %20, %21, %22, %23, %24, %25, %26, %27, %28, %29, %30, %31, %32, %33, %34, %35, %36, %37, %38, %39, %40, %41, %42, %43, %44, %45, %46, %47, %48, %49, %50, %51, %52, %53, %54, %55, %56, %57, %58, %59, %60, %61, %62, %63, %64, %65, %66, %67, %68, %69, %70, %71, %72, %73, %74, %75, %76, %77, %78, %79}, %80, %81, p, 1, 1, %83, %84;\n}"
    : "+f"(d[0]), "+f"(d[1]), "+f"(d[2]), "+f"(d[3]), "+f"(d[4]), "+f"(d[5]), "+f"(d[6]), "+f"(d[7]), "+f"(d[8]), "+f"(d[9]), "+f"(d[10]), "+f"(d[11]), "+f"(d[12]), "+f"(d[13]), "+f"(d[14]), "+f"(d[15]), "+f"(d[16]), "+f"(d[17]), "+f"(d[18]), "+f"(d[19]), "+f"(d[20]), "+f"(d[21]), "+f"(d[22]), "+f"(d[23]), "+f"(d[24]), "+f"(d[25]), "+f"(d[26]), "+f"(d[27]), "+f"(d[28]), "+f"(d[29]), "+f"(d[30]), "+f"(d[31]), "+f"(d[32]), "+f"(d[33]), "+f"(d[34]), "+f"(d[35]), "+f"(d[36]), "+f"(d[37]), "+f"(d[38]), "+f"(d[39]), "+f"(d[40]), "+f"(d[41]), "+f"(d[42]), "+f"(d[43]), "+f"(d[44]), "+f"(d[45]), "+f"(d[46]), "+f"(d[47]), "+f"(d[48]), "+f"(d[49]), "+f"(d[50]), "+f"(d[51]), "+f"(d[52]), "+f"(d[53]), "+f"(d[54]), "+f"(d[55]), "+f"(d[56]), "+f"(d[57]), "+f"(d[58]), "+f"(d[59]), "+f"(d[60]), "+f"(d[61]), "+f"(d[62]), "+f"(d[63]), "+f"(d[64]), "+f"(d[65]), "+f"(d[66]), "+f"(d[67]), "+f"(d[68]), "+f"(d[69]), "+f"(d[70]), "+f"(d[71]), "+f"(d[72]), "+f"(d[73]), "+f"(d[74]), "+f"(d[75]), "+f"(d[76]), "+f"(d[77]), "+f"(d[78]), "+f"(d[79])
    : "l"(da), "l"(db), "r"(sd), "n"(TA), "n"(TB));
}

template<int TA, int TB> __device__ __forceinline__ void wgmma_ss_n192(float* d, uint64_t da, uint64_t db, int sd) {
  asm volatile("{\n.reg .pred p;\nsetp.ne.b32 p, %98, 0;\n"
    "wgmma.mma_async.sync.aligned.m64n192k16.f32.bf16.bf16 {%0, %1, %2, %3, %4, %5, %6, %7, %8, %9, %10, %11, %12, %13, %14, %15, %16, %17, %18, %19, %20, %21, %22, %23, %24, %25, %26, %27, %28, %29, %30, %31, %32, %33, %34, %35, %36, %37, %38, %39, %40, %41, %42, %43, %44, %45, %46, %47, %48, %49, %50, %51, %52, %53, %54, %55, %56, %57, %58, %59, %60, %61, %62, %63, %64, %65, %66, %67, %68, %69, %70, %71, %72, %73, %74, %75, %76, %77, %78, %79, %80, %81, %82, %83, %84, %85, %86, %87, %88, %89, %90, %91, %92, %93, %94, %95}, %96, %97, p, 1, 1, %99, %100;\n}"
    : "+f"(d[0]), "+f"(d[1]), "+f"(d[2]), "+f"(d[3]), "+f"(d[4]), "+f"(d[5]), "+f"(d[6]), "+f"(d[7]), "+f"(d[8]), "+f"(d[9]), "+f"(d[10]), "+f"(d[11]), "+f"(d[12]), "+f"(d[13]), "+f"(d[14]), "+f"(d[15]), "+f"(d[16]), "+f"(d[17]), "+f"(d[18]), "+f"(d[19]), "+f"(d[20]), "+f"(d[21]), "+f"(d[22]), "+f"(d[23]), "+f"(d[24]), "+f"(d[25]), "+f"(d[26]), "+f"(d[27]), "+f"(d[28]), "+f"(d[29]), "+f"(d[30]), "+f"(d[31]), "+f"(d[32]), "+f"(d[33]), "+f"(d[34]), "+f"(d[35]), "+f"(d[36]), "+f"(d[37]), "+f"(d[38]), "+f"(d[39]), "+f"(d[40]), "+f"(d[41]), "+f"(d[42]), "+f"(d[43]), "+f"(d[44]), "+f"(d[45]), "+f"(d[46]), "+f"(d[47]), "+f"(d[48]), "+f"(d[49]), "+f"(d[50]), "+f"(d[51]), "+f"(d[52]), "+f"(d[53]), "+f"(d[54]), "+f"(d[55]), "+f"(d[56]), "+f"(d[57]), "+f"(d[58]), "+f"(d[59]), "+f"(d[60]), "+f"(d[61]), "+f"(d[62]), "+f"(d[63]), "+f"(d[64]), "+f"(d[65]), "+f"(d[66]), "+f"(d[67]), "+f"(d[68]), "+f"(d[69]), "+f"(d[70]), "+f"(d[71]), "+f"(d[72]), "+f"(d[73]), "+f"(d[74]), "+f"(d[75]), "+f"(d[76]), "+f"(d[77]), "+f"(d[78]), "+f"(d[79]), "+f"(d[80]), "+f"(d[81]), "+f"(d[82]), "+f"(d[83]), "+f"(d[84]), "+f"(d[85]), "+f"(d[86]), "+f"(d[87]), "+f"(d[88]), "+f"(d[89]), "+f"(d[90]), "+f"(d[91]), "+f"(d[92]), "+f"(d[93]), "+f"(d[94]), "+f"(d[95])
    : "l"(da), "l"(db), "r"(sd), "n"(TA), "n"(TB));
}

template<int TA, int TB> __device__ __forceinline__ void wgmma_ss_n8(float* d, uint64_t da, uint64_t db, int sd) {
  asm volatile("{\n.reg .pred p;\nsetp.ne.b32 p, %6, 0;\n"
    "wgmma.mma_async.sync.aligned.m64n8k16.f32.bf16.bf16 {%0, %1, %2, %3}, %4, %5, p, 1, 1, %7, %8;\n}"
    : "+f"(d[0]), "+f"(d[1]), "+f"(d[2]), "+f"(d[3])
    : "l"(da), "l"(db), "r"(sd), "n"(TA), "n"(TB));
}

constexpr int S_ = 2048, D_ = 640, F_ = 1536;

struct Scr {
  uint32_t flag[320 * 8];
  uint32_t epoch[256];
  uint2 cbsb[640];
  bf16 cimg[8 * 6 * 512];
  uint4 stat[S_];
  uint2 modP[8 * 3840];
  bf16 kvT[D_ * S_];
  bf16 x1T[D_ * S_];
  bf16 AT[D_ * S_];
  bf16 ln1[2 * S_];
  bf16 xT[D_ * S_];
  bf16 HH[S_ * F_];
};
__device__ __align__(1024) Scr g_scr;
#define DEVSM 0
#define STAMP(id)
#define STAMPIF(c, id)
constexpr int FL_KV = 0, FL_R = 80, FL_S = 88, FL_C = 104, FL_X = 112, FL_H = 172;

constexpr int SM_Z = 1024, SM_EXT = 21504, SM_STAT = 27648, SM_SMALL = 29696, SM_CB = 30720, SM_RING = 34816, SM_TOTAL = SM_RING + 6 * 32768;
constexpr int SMALL_S = 0, SMALL_XM = 160, SMALL_MOD = 256, SMALL_RED = 336, SMALL_GB = 848, SMALL_DUMMY = 1008;
constexpr int JOB_SZ = 8896, JOB_V = 4416, JOB_SK = 8640, R_X = 5 * 32768;
constexpr int K1OFF = 4672, KSZ = 9472, CSZ = KSZ + 4224;
enum { B_U = 0, B_S = 5, B_FB = 10, B_FA = 22, B_EXT = 28, B_X1 = 29, B_PEER = 30, B_RECV = 31, B_MF = 33, B_XFREE = 36, B_XS0 = 37, B_BOX = 38, B_ST0 = 42,
       B_ST1 = 43, B_GB = 44, B_XC = 45,
       B_F1 = 48, B_E1 = 54, B_EB = 60, B_EA = 72,
       B_Z = 80, B_KVS = 85, B_EW = 88, B_MB = 93, B_HH = 96, B_K = 98, B_ZF = 101,
       B_XS = 105, B_B = 106, B_X = 112 };
__device__ __forceinline__ uint32_t chan_base(uint32_t sb, int ch) { return sb + SM_RING + (2 + (ch >> 1)) * 32768 + (ch & 1) * CSZ; }
__device__ __forceinline__ uint32_t box_base(uint32_t sb, int cls) {
  return sb + SM_RING + (cls == 0 ? 46080 : cls == 1 ? 4 * 32768 + 14336 : cls == 2 ? 5 * 32768 + 22528 : 5 * 32768);
}

constexpr int XS_LN = SM_RING + 56320 + 8192;
__device__ __forceinline__ uint32_t xs_base(uint32_t sb, int r) { return sb + SM_RING + (r < 2 ? 56320 : R_X + 2048) + 4096 * r; }
__device__ __forceinline__ uint32_t xc_base(uint32_t sb, int r) { return sb + (r < 2 ? SM_RING + 4 * 32768 + 24576 + 4096 * r : r == 2 ? SM_CB : SM_Z + 4096 * (r - 3)); }

struct Params { CUtensorMap mX, mS, mWm, mXc, mA, mG, mU, mDn, mDp, mX1, mO; };

__device__ __forceinline__ void flag_add(Scr* G, int id) { asm volatile("red.relaxed.gpu.global.add.u32 [%0], 1;" ::"l"(G->flag + 8 * id) : "memory"); }
__device__ __forceinline__ uint32_t rdback(const void* p) { uint32_t v; asm volatile("ld.relaxed.gpu.global.u32 %0, [%1];" : "=r"(v) : "l"(p) : "memory"); return v; }
__device__ __forceinline__ void st_tag(uint2* p, uint32_t v, uint32_t t) { asm volatile("st.relaxed.gpu.global.v2.u32 [%0], {%1, %2};" ::"l"(p), "r"(v), "r"(t) : "memory"); }
__device__ __forceinline__ uint2 ld_tag(const uint2* p) { uint2 v; asm volatile("ld.relaxed.gpu.global.v2.u32 {%0, %1}, [%2];" : "=r"(v.x), "=r"(v.y) : "l"(p) : "memory"); return v; }
__device__ __forceinline__ uint4 ld_tag2(const uint2* p) {
  uint4 v;
  asm volatile("ld.relaxed.gpu.global.v4.u32 {%0, %1, %2, %3}, [%4];" : "=r"(v.x), "=r"(v.y), "=r"(v.z), "=r"(v.w) : "l"(p) : "memory");
  return v;
}
__device__ __forceinline__ void rdwait(uint32_t sb, uint32_t v) { sts32(sb + SM_SMALL + SMALL_DUMMY, v); }
__device__ __forceinline__ void fence_async_s() { asm volatile("fence.proxy.async.shared::cta;" ::: "memory"); }
__device__ __forceinline__ void fence_async_g() { asm volatile("fence.proxy.async.global;" ::: "memory"); }
__device__ __forceinline__ void bulk_done() { asm volatile("cp.async.bulk.commit_group;\n\tcp.async.bulk.wait_group 0;" ::: "memory"); }
__device__ __forceinline__ void flag_wait(Scr* G, int id, uint32_t target) {
  const uint32_t* p = G->flag + 8 * id;
#pragma unroll 1
  for (int i = 0; i < (1 << 20); i++) {
    uint32_t v;
    asm volatile("ld.relaxed.gpu.global.u32 %0, [%1];" : "=r"(v) : "l"(p) : "memory");
    if ((int)(v - target) >= 0) return;
  }
  __trap();
}
__device__ __forceinline__ int ibase(int pb) {
  int w = pb >> 5, g = (pb >> 2) & 7, q = pb & 3;
  return 128 * (g >> 2) + 8 * ((2 * q - ((g >> 1) & 1)) & 7) + 2 * w + (g & 1);
}
__device__ __forceinline__ uint32_t hmul(uint32_t a, uint32_t b) { uint32_t d; asm("mul.rn.bf16x2 %0, %1, %2;" : "=r"(d) : "r"(a), "r"(b)); return d; }
__device__ __forceinline__ uint32_t hadd(uint32_t a, uint32_t b) { uint32_t d; asm("add.rn.bf16x2 %0, %1, %2;" : "=r"(d) : "r"(a), "r"(b)); return d; }
__device__ __forceinline__ uint32_t hsub(uint32_t a, uint32_t b) { uint32_t d; asm("sub.rn.bf16x2 %0, %1, %2;" : "=r"(d) : "r"(a), "r"(b)); return d; }
__device__ __forceinline__ uint32_t pack2(float lo, float hi) { uint32_t d; asm("cvt.rn.bf16x2.f32 %0, %1, %2;" : "=r"(d) : "f"(hi), "f"(lo)); return d; }
__device__ __forceinline__ float blo(uint32_t v) { return __uint_as_float(v << 16); }
__device__ __forceinline__ float bhi(uint32_t v) { return __uint_as_float(v & 0xffff0000u); }
__device__ __forceinline__ float rcp(float v) { float r; asm("rcp.approx.ftz.f32 %0, %1;" : "=f"(r) : "f"(v)); return r; }
__device__ __forceinline__ float rbf(float v) { return blo(pack2(v, 0.f)); }
template <int N> __device__ __forceinline__ void bfly(float* v, int mask, bool up) {
#pragma unroll
  for (int i = 0; i < N / 2; i++) {
    float send = up ? v[i] : v[i + N / 2], keep = up ? v[i + N / 2] : v[i];
    v[i] = keep + __shfl_xor_sync(0xffffffffu, send, mask);
  }
}
__device__ __forceinline__ int mod_col(int idx) {
  if (idx < 40) { int v = (idx >> 1) & 3; return (v == 3 ? 4 : v) * 640 + 128 * (idx >> 3) + 64 * (idx & 1); }
  int l = idx - 40;
  return l < 10 ? 3 * 640 + 64 * l : 5 * 640 + 64 * (l - 10);
}

__device__ __forceinline__ void kv_load(const bf16* gk, const bf16* gv, const bf16* gs, uint32_t sb, int b, int r, int tid) {
  const int row = tid >> 2, t = 64 * (b >> 2) + row, col = 128 * r + 32 * (b & 3);
  const uint32_t a = sb + SM_RING + r * JOB_SZ + row * 64 + (row >> 3) * 16 + (tid & 3) * 16;
  const int o = t * D_ + col + 8 * (tid & 3);
  cp16z(a, gk + (t < 3 ? o : o - 3 * D_), t < 3 ? 0 : 16);
  cp16(a + 2112, gk + o + 29 * D_);
  cp16(a + JOB_V, gv + o);
  cp16(a + JOB_V + 2112, gv + o + 32 * D_);
  if (tid < 12) cp16(a + 4224, gk + o + 61 * D_);
  else if (tid >= 112) cp16(sb + SM_RING + r * JOB_SZ + JOB_SK + 16 * (tid - 112), gs + 4 * col + 8 * (tid - 112));
}
__device__ __forceinline__ void kv_load_w(const bf16* gk, const bf16* gv, const bf16* gs, uint32_t sb, int b, int r, int lane) {
  const int t = 64 * (b >> 2) + (lane >> 2), col = 128 * r + 32 * (b & 3);
  const uint32_t a = sb + SM_RING + r * JOB_SZ + lane * 16;
  const int o = t * D_ + col + 8 * (lane & 3);
  cp16z(a, gk + (t < 3 ? o : o - 3 * D_), t < 3 ? 0 : 16);
#pragma unroll
  for (int i = 1; i < 8; i++) cp16(a + 528 * i, gk + o + (8 * i - 3) * D_);
  if (lane < 12) cp16(a + 4224, gk + o + 61 * D_);
  else if (lane >= 16) cp16(a + JOB_SK - 256, gs + 4 * col + 8 * (lane - 16));
#pragma unroll
  for (int i = 0; i < 8; i++) cp16(a + JOB_V + 528 * i, gv + o + 8 * i * D_);
  cp_arrive(sb + 8 * (B_B + r));
}
__device__ __forceinline__ void kv_job(Scr* G, uint32_t sb, int b, int r, int tid) {
  const int cp = 4 * (tid >> 5) + (tid & 3), tc = (tid >> 2) & 7;
  const uint32_t base = sb + SM_RING + r * JOB_SZ, ka = base + tc * 528 + cp * 4;
  mbar_wait(sb + 8 * (B_B + r), 0);
  const uint4 sk = lds128(base + JOB_SK + 16 * cp);
  const uint32_t s0 = __byte_perm(sk.x, sk.z, 0x5410), s1 = __byte_perm(sk.x, sk.z, 0x7632), s2 = __byte_perm(sk.y, sk.w, 0x5410), s3 = __byte_perm(sk.y, sk.w, 0x7632);
  uint32_t kk[11], o[8];
#pragma unroll
  for (int i = 0; i < 11; i++) kk[i] = lds32(ka + 64 * i + 16 * (i >> 3));
#pragma unroll
  for (int i = 0; i < 8; i++) {
    uint32_t v = lds32(ka + JOB_V + 64 * i);
    uint32_t a = hadd(hadd(hadd(hmul(kk[i], s3), hmul(kk[i + 1], s2)), hmul(kk[i + 2], s1)), hmul(kk[i + 3], s0));
    o[i] = hmul(a, v);
  }
  bf16* dst = G->kvT + (128 * r + 32 * (b & 3) + 2 * cp) * S_ + 2040 - 64 * (b >> 2) - 8 * tc;
  *(uint4*)dst = make_uint4(__byte_perm(o[7], o[6], 0x5410), __byte_perm(o[5], o[4], 0x5410), __byte_perm(o[3], o[2], 0x5410), __byte_perm(o[1], o[0], 0x5410));
  *(uint4*)(dst + S_) = make_uint4(__byte_perm(o[7], o[6], 0x7632), __byte_perm(o[5], o[4], 0x7632), __byte_perm(o[3], o[2], 0x7632), __byte_perm(o[1], o[0], 0x7632));
}
__device__ __forceinline__ void kv_signal(Scr* G, uint32_t sb, int b, int r, int line, bool add) {
  rdwait(sb, rdback(G->kvT + (128 * r + 32 * (b & 3) + line) * S_ + 1984 - 64 * (b >> 2)));
  __syncwarp();
  if (add) flag_add(G, FL_KV + 16 * r + 4 * (b & 3) + (line >> 3));
}
__device__ __forceinline__ void mod_box(Scr* G, uint32_t sb, int b, int cls, uint32_t e1, int tid) {
  float a[4];
  const uint64_t da = mkdesc(box_base(sb, cls), 4096, 1024, 1), db = mkdesc(sb + SM_SMALL + SMALL_S, 16, 128, 0);
  mbar_wait(sb + 8 * (B_BOX + cls), 0);
  wg_fence();
#pragma unroll
  for (int n = 0; n < 5; n++) wgmma_ss_n8<1, 0>(a, da + 128 * n, db + 2 * n, n != 0);
  wg_commit();
  wg_wait<0>();
#pragma unroll
  for (int i = 0; i < 4; i++) asm volatile("" : "+f"(a[i])::"memory");
  if ((tid & 3) == 0) {
    uint2* p = G->modP + (b & 7) * 3840 + mod_col(16 * cls + (b >> 3)) + 16 * (tid >> 5) + ((tid >> 2) & 7);
    st_tag(p, __float_as_uint(a[0]), e1);
    st_tag(p + 8, __float_as_uint(a[2]), e1);
  }
}
__device__ __forceinline__ float sum8(float a) {
  a += __shfl_xor_sync(0xffffffffu, a, 4);
  a += __shfl_xor_sync(0xffffffffu, a, 2);
  a += __shfl_xor_sync(0xffffffffu, a, 1);
  return rbf(a);
}
__device__ __forceinline__ void mod_poll(const uint2* p, int o, uint32_t e1, float& r0, float& r1) {
  uint2 a, c;
#pragma unroll 1
  for (int i = 0;; i++) {
    a = ld_tag(p); c = ld_tag(p + o);
    if (__all_sync(0xffffffffu, a.y == e1 && c.y == e1)) break;
    if (i > (1 << 20)) __trap();
  }
  r0 = sum8(__uint_as_float(a.x)); r1 = sum8(__uint_as_float(c.x));
}
__device__ __forceinline__ float mod_fin(Scr* G, uint32_t sb, int b, int r0, uint32_t e1, int lane) {
  const int v = lane >> 3, c = (v == 3 ? 4 : v) * 640 + 128 * r0;
  float t0, t1;
  mod_poll(G->modP + (lane & 7) * 3840 + c + b, r0 < 4 ? 128 : 3 * 640 + 128 * v - c, e1, t0, t1);
  const float o = (v & 1) ? 1.f : 0.f;
  if ((lane & 7) == 0) {
    sts32(sb + SM_SMALL + SMALL_MOD + 16 * r0 + 4 * v, pack2(t0 + o, t0 + o));
    if (r0 < 4) sts32(sb + SM_SMALL + SMALL_MOD + 16 * r0 + 16 + 4 * v, pack2(t1 + o, t1 + o));
  }
  __syncwarp();
  if (lane == 0) mbar_arrive(sb + 8 * (B_MF + (r0 >> 1)));
  return t1;
}
__device__ __forceinline__ void load_x(const Params& P, uint32_t sb, int b, int h) {
  const uint32_t bar = sb + 8 * (B_X + h);
  mbar_expect(bar, 10240);
  tma5d(sb + SM_RING + R_X + h * 10240, &P.mX, 0, 0, 0, 5 * h, 191 - ibase(b), bar);
}
__device__ __forceinline__ void load_box(const Params& P, uint32_t sb, int b, int cls) {
  const uint32_t bar = sb + 8 * (B_BOX + cls);
  mbar_expect(bar, 10240);
  tma2d(box_base(sb, cls), &P.mWm, mod_col(16 * cls + (b >> 3)), 80 * (b & 7), bar);
}
__device__ __forceinline__ void load_ssm(const Params& P, uint32_t sb, int b, int r) {
  const uint32_t bar = sb + 8 * (B_S + r);
  mbar_expect(bar, 16 * 288);
  tma3d(chan_base(sb, r) + 128, &P.mS, 0, 0, 128 * r + b, bar);
}
__device__ __forceinline__ void k1_job(uint32_t sb, int r, int tid) {
  const uint32_t a0 = chan_base(sb, r) + 128 + 16 * tid + 32 * (tid >> 4);
  mbar_wait(sb + 8 * (B_S + r), 0);
#pragma unroll
  for (int n = 0; n < 2; n++) {
    const uint32_t a = a0 + 2304 * n;
    const uint4 v = lds128(a);
    const uint32_t pv = lds32(a - ((tid & 15) ? 4 : 36));
    sts128(a + K1OFF, make_uint4(__byte_perm(pv, v.x, 0x5432), __byte_perm(v.x, v.y, 0x5432), __byte_perm(v.y, v.z, 0x5432), __byte_perm(v.z, v.w, 0x5432)));
  }
}

__device__ __forceinline__ void load_hh(Scr* G, uint32_t sb, int b, int n, uint32_t e1) {
  const int src = (b & ~7) + ((b + 2 * n) & 7);
  flag_wait(G, FL_H + src, e1 * 4);
  fence_async_g();
  STAMP(50 + n);
#pragma unroll 1
  for (int k = 0; k < 6; k++) {
    int g1 = k + 2; if (g1 >= 6) g1 -= 6;
    if (n == 1) mbar_wait(sb + 8 * (B_E1 + g1), g1 >= 2);
    else { mbar_wait(sb + 8 * (B_EA + k), 0); if (n == 3) mbar_wait(sb + 8 * (B_EA + k), 1); }
    uint32_t fb = sb + 8 * (B_FA + k);
    mbar_expect(fb, 8192);
    bulk_g2s(sb + SM_RING + g1 * 32768, G->HH + (src * 6 + k) * 4096, 8192, fb);
  }
}
__device__ __forceinline__ void load_strip(const Params& P, uint32_t sb, int b, int h) {
  const int m = b >> 3, grp = m < 6 ? m : m - 6;
  mbar_expect(sb + 8 * (B_ST0 + h), 20480);
#pragma unroll 1
  for (int r = 0; r < 5; r++)
    tma2d(sb + SM_Z + r * 4096, (grp & 1) ? &P.mU : &P.mG, 192 * (b & 7) + 64 * (grp >> 1), (m < 6 ? 0 : 320) + 160 * h + 32 * r, sb + 8 * (B_ST0 + h));
}
__device__ __forceinline__ void strip(float* a, uint32_t sb, int h) {
  const uint64_t da = mkdesc(sb + SM_Z, 4096, 1024, 1), db = mkdesc(sb + SM_CB, 32, 128, 0);
  mbar_wait(sb + 8 * (h ? B_ST1 : B_ST0), 0);
  wg_fence();
#pragma unroll
  for (int n = 0; n < 10; n++) wgmma_ss_n8<1, 0>(a, da + 128 * n, db + 40 * h + 4 * n, (h | n) != 0);
  wg_commit();
  wg_wait<0>();
#pragma unroll
  for (int i = 0; i < 4; i++) asm volatile("" : "+f"(a[i])::"memory");
}
__device__ __forceinline__ void l2_prefetch(const void* p, int bytes) { asm volatile("cp.async.bulk.prefetch.L2.global [%0], %1;" ::"l"(p), "r"(bytes) : "memory"); }
__device__ __forceinline__ int role(int bx) {
  const int c = bx >> 1, d = c - 36, q = (d * 37) >> 8, k = d - 7 * q;
  const int rank = c < 4 ? 12 + c : c < 36 ? ((c - 4) & 7) * 8 + ((c - 4) >> 3) : (k ? k + 1 : 0) * 8 + 4 + q;
  return 8 * (rank & 15) + 2 * (rank >> 4) + (bx & 1);
}
#define PD 3
#define PACE(a3, a2) (PD == 3 ? (a3) : (a2))

__global__ void __launch_bounds__(512, 1) fused_kernel(const bf16* __restrict__ gk, const bf16* __restrict__ gv, const bf16* __restrict__ gsk,
                                                       const bf16* __restrict__ gD, const bf16* __restrict__ gc, Scr* G, const bf16* gWg, const bf16* gWu,
                                                       const bf16* gWd, const __grid_constant__ Params P) {
  extern __shared__ __align__(1024) char smem_raw[];
  const uint32_t sb = smem_u32(smem_raw), ring = sb + SM_RING;
  const int b = role(blockIdx.x), m = b >> 3, s = b & 7;
  const int wg = __shfl_sync(0xffffffffu, threadIdx.x >> 7, 0);
  const int tid = threadIdx.x & 127, lane = tid & 31;
  const int w = __shfl_sync(0xffffffffu, tid >> 5, 0);
  if (wg < 2) {
    kv_load(gk, gv, gsk, sb, b, wg, tid);
  } else {
    if (wg == 2) {
      if (tid < 40) {
        int c = tid & 7;
        sts128(chan_base(sb, tid >> 3) + (c < 2 ? 80 + c * K1OFF : KSZ + 4096 + (c - 2) * 16), make_uint4(0, 0, 0, 0));
      }
    }
    if (lane == 0) {
      const int j = 4 * (3 - wg) + w - 1;
      if (j < 2) asm volatile("prefetch.tensormap [%0];" ::"l"(&P.mS + j) : "memory");
      if (j < 0) {
        mbar_init(sb + 8 * B_X, 1);
        mbar_init(sb + 8 * (B_X + 1), 1);
        fence_async_s();
        load_x(P, sb, b, 0);
      } else {
        const int c = j < 3 ? 1 : j < 5 ? 2 : 4;
#pragma unroll
        for (int i = 0; i < 16; i++) mbar_init(sb + 128 * j + 8 * i, i < 8 || j < 6 ? c : i == 8 ? 5 : i == 9 ? 8 : i < 12 ? 128 : 32);
      }
    }
    fence_async_s();
  }
  __syncthreads();
  STAMPIF(threadIdx.x == 0, 55);

  if (wg == 3) {
    asm volatile("setmaxnreg.dec.sync.aligned.u32 24;");
    if (w < 2) {
     if (w == 0) {
      STAMPIF(lane == 0, 62);
      mbar_wait(sb + 8 * (B_B + PACE(0, 1)), 0);
      STAMPIF(lane == 0, 56);
      if (lane == 0) load_x(P, sb, b, 1);
      mbar_wait(sb + 8 * PACE(B_B + 1, B_X), 0);
      STAMPIF(lane == 0, 57);
      kv_load_w(gk, gv, gsk, sb, b, 2, lane);
      mbar_wait(sb + 8 * PACE(B_X, B_X + 1), 0);
      if (lane == 0) { load_ssm(P, sb, b, 0); load_ssm(P, sb, b, 1); }
      mbar_wait(sb + 8 * PACE(B_X + 1, B_B + 2), 0);
      STAMPIF(lane == 0, 61);
      kv_load_w(gk, gv, gsk, sb, b, 3, lane);
      mbar_wait(sb + 8 * PACE(B_B + 2, B_S + 1), 0);
      STAMPIF(lane == 0, 58);
      if (lane == 0) load_box(P, sb, b, 0);
      mbar_wait(sb + 8 * PACE(B_S + 1, B_B + 3), 0);
      kv_load_w(gk, gv, gsk, sb, b, 4, lane);
      if (lane == 0) {
        mbar_wait(sb + 8 * PACE(B_B + 3, B_BOX), 0);
        STAMP(59);
        load_ssm(P, sb, b, 2);
        load_ssm(P, sb, b, 3);
        mbar_wait(sb + 8 * PACE(B_BOX, B_B + 4), 0);
        load_ssm(P, sb, b, 4);
        l2_prefetch(gWg + b * F_, 2 * F_);
        l2_prefetch(gWu + b * F_, 2 * F_);
        mbar_wait(sb + 8 * PACE(B_B + 4, B_S + 3), 0);
        STAMP(60);
        load_box(P, sb, b, 1);
        mbar_wait(sb + 8 * B_XFREE, 0);
        mbar_wait(sb + 8 * (B_KVS + 2), 0);
        STAMP(70);
#pragma unroll 1
        for (int it = 0; it < 20; it++) {
          int st = it % 6;
          if (it == 2 || (it == 3 && b < 96)) {
            mbar_wait(sb + 8 * (B_BOX + it - 1), 0);
            STAMPIF(it == 2, 69);
            load_box(P, sb, b, it);
          }
          mbar_wait(sb + 8 * (B_E1 + st), (it / 6) & 1);
          uint32_t a = ring + st * 32768 + 8192, fb = sb + 8 * (B_F1 + st);
          mbar_expect(fb, 24576);
#pragma unroll
          for (int j = 0; j < 3; j++) {
            tma2d(a + 8192 * j, &P.mG, 192 * s + 64 * j, 32 * it, fb);
            tma2d(a + 8192 * j + 4096, &P.mU, 192 * s + 64 * j, 32 * it, fb);
          }
          if (it >= 3 && it < 7) {
            l2_prefetch(gWg + (128 * it - 256 + b) * F_, 2 * F_);
            l2_prefetch(gWu + (128 * it - 256 + b) * F_, 2 * F_);
          }
          if (it >= 7 && it < 10) l2_prefetch(gWd + (512 * it - 3584 + 4 * b) * D_, 8 * D_);
        }
#pragma unroll 1
        for (int k = 0; k < 24; k++) {
          int sl = k < 12 ? k : k - 12;
          int g1 = (sl >> 1) + 2; if (g1 >= 6) g1 -= 6;
          if (k < 12) mbar_wait(sb + 8 * (B_E1 + g1), g1 >= 2);
          else if (k < 21) mbar_wait(sb + 8 * (B_EB + (k < 18 ? sl : sl + 3)), 0);
          else mbar_wait(sb + 8 * (B_EB + k - 21), 1);
          uint32_t a = ring + g1 * 32768 + 8192 + (sl & 1) * 12288, fb = sb + 8 * (B_FB + sl);
          int n = k / 6, kg = 4 * (6 * ((s + 2 * n) & 7) + k - 6 * n);
          mbar_expect(fb, 12288);
#pragma unroll 1
          for (int at = 0; at < 3; at++) {
            if (k < 6) tma5d(a + at * 4096, &P.mDn, 64 * at, 0, 0, kg, s >> 1, fb);
            else tma5d(a + at * 4096, &P.mDp, 64 * at, 0, kg, 0, s >> 1, fb);
          }
        }
      }
     } else {
      const uint32_t e1 = rdback(G->epoch + b) + 1;
      if (lane >= 3 && lane < 11) asm volatile("prefetch.tensormap [%0];" ::"l"(&P.mX + lane) : "memory");
      {
        bool pend = lane < 7;
        const uint32_t* fp = G->flag + 8 * (lane < 5 ? FL_KV + 16 * lane + (b >> 3) : FL_X + lane - 5);
#pragma unroll 1
        for (int i = 0; __any_sync(0xffffffffu, pend); i++) {
          if (pend && (int)(rdback(fp) - e1 * (lane < 5 ? 32 : 128)) >= 0) {
            pend = false;
            fence_async_g();
            if (lane < 5) {
              mbar_expect(sb + 8 * (B_U + lane), 4096);
              bulk_g2s(chan_base(sb, lane) + KSZ, G->kvT + (128 * lane + b) * S_, 4096, sb + 8 * (B_U + lane));
              STAMP(40 + lane);
            } else {
              const uint32_t bar = sb + 8 * (B_XC - 5 + lane);
              mbar_expect(bar, lane == 5 ? 12288 : 4096);
              tma2d(xc_base(sb, 0) + 4096 * (lane - 5), &P.mXc, 16 * (128 * (lane - 5) + b), 0, bar);
              if (lane == 5) bulk_g2s(sb + SM_EXT, G->ln1, 8192, bar);
              STAMP(78 + lane);
            }
          }
          if (i > (1 << 20)) __trap();
        }
      }
      if (lane == 0) {
#pragma unroll 1
        for (int it = 0; it < 20; it++) {
          int st = it % 6;
          if ((it & 3) == 0) { flag_wait(G, FL_R + (it >> 2), e1 * 128); fence_async_g(); STAMP(45 + (it >> 2)); }
          mbar_wait(sb + 8 * (B_E1 + st), (it / 6) & 1);
          uint32_t fb = sb + 8 * (B_F1 + st);
          mbar_expect(fb, 8192);
          tma3d(ring + st * 32768, &P.mA, 0, 32 * it, m * 2, fb);
        }
        load_hh(G, sb, b, 1, e1);
        load_hh(G, sb, b, 3, e1);
        G->epoch[b] = e1;
      }
     }
    } else if (w == 2) {
      const uint32_t e1 = rdback(G->epoch + b) + 1;
      if (lane == 0) {
        mbar_expect(sb + 8 * B_RECV, 20480);
        mbar_expect(sb + 8 * (B_RECV + 1), 20480);
      }
      mbar_wait(sb + 8 * B_XS0, 0);
      bf16* xo = G->xT + b * 10240;
#pragma unroll 1
      for (int r = 0; r < 2; r++) {
        if (lane == 0) bulk_s2g(xo + 2048 * r, xs_base(sb, 0) + 4096 * r, 4096);
        else if (lane < 3 && r == 0) bulk_s2g(G->ln1 + (lane - 1) * S_ + 16 * b, sb + XS_LN + 32 * (lane - 1), 32);
        bulk_done();
        __syncwarp();
        uint32_t v0 = rdback(xo + 2048 * r + 64 * lane), v1 = rdback(G->ln1 + (lane & 1) * S_ + 16 * b);
        rdwait(sb, v0 ^ v1);
        __syncwarp();
        if (lane == 0) flag_add(G, FL_X + r);
        STAMPIF(lane == 0, 71 + r);
      }
      if (lane == 0) mbar_arrive(sb + 8 * B_XFREE);
      mod_fin(G, sb, b, 0, e1, lane);
      STAMPIF(lane == 0, 36);
#pragma unroll 1
      for (int r = 0; r < 5; r++) {
        mbar_wait(sb + 8 * (B_EW + r), 0);
        rdwait(sb, rdback(G->AT + (128 * r + b) * S_ + 64 * lane));
        __syncwarp();
        if (lane == 0) {
          flag_add(G, FL_R + r);
          bulk_s2g(G->x1T + (128 * r + b) * S_, sb + SM_Z + 4096 * r, 4096);
        }
        if (r == 0) {
          mbar_wait(sb + 8 * B_XS, 0);
          if (lane == 0) bulk_s2g(xo + 4096, xs_base(sb, 2), 12288);
          bulk_done();
          __syncwarp();
          uint32_t v0 = rdback(xo + 4096 + 64 * lane), v1 = rdback(xo + 6144 + 64 * lane), v2 = rdback(xo + 8192 + 64 * lane);
          rdwait(sb, v0 ^ v1 ^ v2);
          __syncwarp();
          if (lane == 0) { flag_add(G, FL_X + 2); mbar_arrive(sb + 8 * (B_E1 + 5)); }
          STAMPIF(lane == 0, 85);
        }
        if (r == 1 && lane == 0) {
          bulk_done();
          flag_wait(G, FL_X + 2, e1 * 128);
          fence_async_g();
          mbar_expect(sb + 8 * (B_XC + 2), 12288);
#pragma unroll
          for (int j = 2; j < 5; j++) tma2d(xc_base(sb, j), &P.mXc, 16 * (128 * j + b), 0, sb + 8 * (B_XC + 2));
          STAMP(86);
        }
        __syncwarp();
      }
      bulk_done();
      if (lane == 0 && m < 12) load_strip(P, sb, b, 0);
      __syncwarp();
      {
        uint32_t v = 0;
#pragma unroll
        for (int r = 0; r < 5; r++) v ^= rdback(G->x1T + (128 * r + b) * S_ + 64 * lane);
        rdwait(sb, v);
        __syncwarp();
      }
      if (lane == 0) {
        flag_add(G, FL_R + 5);
        if (m < 12) mbar_wait(sb + 8 * B_ZF, 0);
        flag_wait(G, FL_R + 5, e1 * 128);
        fence_async_g();
        mbar_expect(sb + 8 * B_X1, 20480);
        tma3d(sb + SM_Z, &P.mX1, 0, 80 * s, m * 2, sb + 8 * B_X1);
        flag_wait(G, FL_S + m, e1 * 8);
        flag_wait(G, FL_C + s, e1 * 48);
        fence_async_g();
        STAMP(54);
        mbar_expect(sb + 8 * B_EXT, 6144 + 2048);
        bulk_g2s(sb + SM_EXT, G->cimg + s * 3072, 6144, sb + 8 * B_EXT);
        bulk_g2s(sb + SM_STAT, G->stat + 128 * m, 2048, sb + 8 * B_EXT);
        mbar_wait(sb + 8 * (B_EB + 3), 0);
        mbar_wait(sb + 8 * (B_EB + 3), 1);
        mbar_arrive_remote(mapa(sb + 8 * B_PEER, (b & 1) ^ 1));
      }
    } else {
      const uint32_t e1 = rdback(G->epoch + b) + 1;
#pragma unroll 1
      for (int r = 2; r < 5; r++) {
        mbar_wait(sb + 8 * (B_KVS + r - 2), 0);
        kv_signal(G, sb, b, r, lane, (lane & 7) == 0);
        STAMPIF(lane == 0, 20 + r);
      }
      mod_fin(G, sb, b, 2, e1, lane);
      STAMPIF(lane == 0, 37);
      float t0 = mod_fin(G, sb, b, 4, e1, lane), t1, t2;
      STAMPIF(lane == 0, 38);
      const uint2* p = G->modP + (lane & 7) * 3840;
      mod_poll(p + 3 * 640 + 512 + b, 0, e1, t1, t2);
      mbar_wait(sb + 8 * B_MF, 0);
      if ((lane & 7) == 0 || lane == 1) {
        const int r = lane == 1 ? 4 : lane >> 3;
        st_tag(G->cbsb + 128 * r + b, __byte_perm(lds32(sb + SM_SMALL + SMALL_MOD + 16 * r + 12), __float_as_uint(lane == 1 ? t1 : t0), 0x7610), e1);
      }
      STAMPIF(lane == 0, 39);
#pragma unroll 1
      for (int n = 0; n < 10; n++) {
        mod_poll(p + 5 * 640 + 80 * s + 8 * n + 2 * (lane >> 3), 1, e1, t1, t2);
        if ((lane & 7) == 0) sts32(sb + SM_SMALL + SMALL_GB + 16 * n + (lane >> 1), pack2(t1, t2));
      }
      __syncwarp();
      if (lane == 0) {
        mbar_arrive(sb + 8 * B_GB);
        mbar_wait(sb + 8 * B_HH, 0);
        load_hh(G, sb, b, 2, e1);
      }
    }
  } else if (wg == 2) {
    asm volatile("setmaxnreg.dec.sync.aligned.u32 40;");
    const uint32_t e1 = rdback(G->epoch + b) + 1;
    if (tid < 80) {
      float c = blo(*(const uint16_t*)(gc + 80 * (b & 7) + tid));
      sts16(sb + SM_SMALL + SMALL_S + 2 * tid, pack2(__fdividef(c, 1.f + __expf(-c)), 0.f));
    }
    fence_async_s();
    bar_sync(5, 128);
#pragma unroll 1
    for (int r = 2; r < 5; r++) {
      if (r == 4) { mod_box(G, sb, b, 0, e1, tid); STAMPIF(tid == 0, 27); }
      kv_job(G, sb, b, r, tid);
      __syncwarp();
      if (lane == 0) mbar_arrive(sb + 8 * (B_KVS + r - 2));
    }
#pragma unroll 1
    for (int j = 2; j < 4; j++) {
      k1_job(sb, j, tid);
      __syncwarp();
      if (lane == 0) mbar_arrive(sb + 8 * (B_K + j - 2));
    }
    STAMPIF(tid == 0, 74);
#pragma unroll 1
    for (int r = 0; r < 5; r++) {
      if (r < 3) mbar_wait(sb + 8 * (B_XC + r), 0);
      STAMPIF(tid == 0 && r == 0, 28);
      uint32_t xv[8], hv[8];
#pragma unroll
      for (int n = 0; n < 2; n++) {
        const uint4 x4 = lds128(xc_base(sb, r) + 16 * tid + 2048 * n), m4 = lds128(sb + SM_EXT + 16 * tid + 2048 * n), s4 = lds128(sb + SM_EXT + 4096 + 16 * tid + 2048 * n);
        const uint32_t x_[4] = {x4.x, x4.y, x4.z, x4.w}, m_[4] = {m4.x, m4.y, m4.z, m4.w}, s_[4] = {s4.x, s4.y, s4.z, s4.w};
#pragma unroll
        for (int j = 0; j < 4; j++) {
          const uint32_t d = hsub(x_[j], m_[j]);
          xv[4 * n + j] = x_[j];
          hv[4 * n + j] = pack2(blo(d) * rcp(blo(s_[j])), bhi(d) * rcp(bhi(s_[j])));
        }
      }
      mbar_wait(sb + 8 * (B_MF + (r >> 1)), 0);
      const uint4 md = lds128(sb + SM_SMALL + SMALL_MOD + 16 * r);
      mbar_wait(sb + 8 * (B_Z + r), 0);
      const uint32_t za = sb + SM_Z + r * 4096 + 16 * tid;
      uint4* pa = (uint4*)(G->AT + (128 * r + b) * S_) + tid;
#pragma unroll
      for (int n = 0; n < 2; n++) {
        const uint4 z4 = lds128(za + 2048 * n);
        const uint32_t z_[4] = {z4.x, z4.y, z4.z, z4.w};
        uint32_t o[4];
#pragma unroll
        for (int j = 0; j < 4; j++) o[j] = hadd(xv[4 * n + j], hmul(md.z, hmul(hadd(hmul(hv[4 * n + j], md.y), md.x), z_[j])));
        pa[128 * n] = make_uint4(hmul(o[0], md.w), hmul(o[1], md.w), hmul(o[2], md.w), hmul(o[3], md.w));
        sts128(za + 2048 * n, make_uint4(o[0], o[1], o[2], o[3]));
      }
      fence_async_s();
      __syncwarp();
      if (lane == 0) mbar_arrive(sb + 8 * (B_EW + r));
      STAMPIF(tid == 0, 29 + r);
      if (r == 0) {
        k1_job(sb, 4, tid);
        __syncwarp();
        if (lane == 0) mbar_arrive(sb + 8 * (B_K + 2));
      }
      if (r == 1) {
        bar_sync(5, 128);
        if (tid == 0) mbar_arrive(sb + 8 * (B_E1 + 4));
      }
      if (r < 2) {
#pragma unroll 1
        for (int cls = r + 1; cls <= 2 * r + 1; cls++)
          if (cls < 3 || b < 96) mod_box(G, sb, b, cls, e1, tid);
        STAMPIF(tid == 0, 73 + 3 * r);
      }
      if (r == 1) {
        bar_sync(5, 128);
        if (tid == 0) mbar_arrive(sb + 8 * (B_E1 + 5));
      }
    }
    float ca[4];
    const int grp = m % 6;
    if (m < 12) {
      if (tid < 80) {
        const uint2* p = G->cbsb + (m < 6 ? 0 : 320) + 4 * tid;
        uint4 a, c;
#pragma unroll 1
        for (int i = 0;; i++) {
          a = ld_tag2(p); c = ld_tag2(p + 2);
          if (a.y == e1 && a.w == e1 && c.y == e1 && c.w == e1) break;
          if (i > (1 << 20)) __trap();
        }
        const uint32_t d = sb + SM_CB + 32 * (tid >> 1) + 8 * (tid & 1);
        sts64(d, __byte_perm(a.x, a.z, 0x5410), __byte_perm(c.x, c.z, 0x5410));
        sts64(d + 16, __byte_perm(a.x, a.z, 0x7632), __byte_perm(c.x, c.z, 0x7632));
      }
      fence_async_s();
      bar_sync(5, 128);
      STAMPIF(tid == 0, 34);
      strip(ca, sb, 0);
      bar_sync(5, 128);
      if (tid == 0) load_strip(P, sb, b, 1);
      __syncwarp();
      STAMPIF(tid == 0, 77);
    }
    {
      if (lane == 0) flag_wait(G, FL_R + 5, e1 * 128);
      STAMPIF(tid == 0, 87);
      __syncwarp();
      const bf16* src = G->x1T + 16 * b + 4 * (lane & 3);
      const uint2 pq = __ldcg((const uint2*)src);
      const float pv0 = blo(pq.x), pv1 = bhi(pq.x), pv2 = blo(pq.y), pv3 = bhi(pq.y);
      float a[8];
#pragma unroll
      for (int j = 0; j < 8; j++) a[j] = 0.f;
      src += ((lane >> 2) + 8 * w) * S_;
#pragma unroll 1
      for (int n0 = 0; n0 < 20; n0 += 5) {
        uint2 v[5];
#pragma unroll
        for (int n = 0; n < 5; n++) v[n] = __ldcg((const uint2*)(src + n * 32 * S_));
        src += 160 * S_;
#pragma unroll
        for (int n = 0; n < 5; n++) {
          const float e0 = blo(v[n].x) - pv0, e1_ = bhi(v[n].x) - pv1, e2 = blo(v[n].y) - pv2, e3 = bhi(v[n].y) - pv3;
          a[0] += e0; a[1] += e1_; a[2] += e2; a[3] += e3;
          a[4] += e0 * e0; a[5] += e1_ * e1_; a[6] += e2 * e2; a[7] += e3 * e3;
        }
      }
      bfly<8>(a, 16, lane & 16); bfly<4>(a, 8, lane & 8); bfly<2>(a, 4, lane & 4);
      sts32(sb + SM_SMALL + SMALL_RED + w * 128 + (lane >> 4) * 64 + (4 * (lane & 3) + ((lane >> 2) & 3)) * 4, __float_as_uint(a[0]));
      bar_sync(5, 128);
      if (w == 3) {
        uint32_t v = 0;
        if (lane < 16) {
          float s1 = 0.f, s2 = 0.f;
#pragma unroll
          for (int j = 0; j < 4; j++) {
            s1 += __uint_as_float(lds32(sb + SM_SMALL + SMALL_RED + j * 128 + lane * 4));
            s2 += __uint_as_float(lds32(sb + SM_SMALL + SMALL_RED + j * 128 + 64 + lane * 4));
          }
          float p0 = __bfloat162float(__ldcg(G->x1T + 16 * b + lane));
          float mu = s1 * (1.f / D_), var = fmaxf(s2 * (1.f / D_) - mu * mu, 0.f);
          float sd = rbf(__fsqrt_rn(rbf(rbf(var) + 1e-5f)));
          const uint32_t hm = pack2(-0.5f * (p0 + mu), -0.5f * (p0 + mu)), hs = pack2(0.5f * sd, 0.5f * sd);
          G->stat[16 * b + lane] = make_uint4(hm, hs, hm, hs);
          v = rdback(G->stat + 16 * b + lane);
        }
        rdwait(sb, v);
        __syncwarp();
        if (lane == 0) flag_add(G, FL_S + m);
        STAMPIF(lane == 0, 21);
      }
    }
    if (m < 12) {
      strip(ca, sb, 1);
      if (lane == 0) mbar_arrive(sb + 8 * B_ZF);
      const int row = (m < 6 ? 0 : 4) + (lane & 3);
      uint16_t* dst = (uint16_t*)G->cimg + s * 3072 + grp * 512 + row * 64 + (lane >> 2);
#pragma unroll
      for (int j = 0; j < 2; j++) {
        const float c1 = __shfl_sync(0xffffffffu, ca[2 * j], lane & 28), c2 = __shfl_sync(0xffffffffu, ca[2 * j + 1], lane & 28);
        const float t = (lane & 2) ? c2 : c1, hi = rbf(t);
        dst[((2 * w + j) ^ row) << 3] = (uint16_t)pack2((lane & 1) ? t - hi : hi, 0.f);
      }
      rdwait(sb, rdback(dst - (lane >> 2) + (((2 * w) ^ row) << 3)));
      __syncwarp();
      if (lane == 0) flag_add(G, FL_C + s);
      STAMPIF(tid == 0, 35);
    }
    {
      mbar_wait(sb + 8 * (B_HH + (w >> 1)), 0);
      const bf16* p = G->HH + (b * 6 + 3 * (w & 1)) * 4096 + (w >> 1) * 2048 + lane * 64;
      uint32_t v0 = rdback(p), v1 = rdback(p + 4096), v2 = rdback(p + 8192);
      rdwait(sb, v0 ^ v1 ^ v2);
      __syncwarp();
      if (lane == 0) flag_add(G, FL_H + b);
      STAMPIF(tid == 0, 50);
    }
  } else {
    cp_arrive(sb + 8 * (B_B + wg));
    asm volatile("setmaxnreg.inc.sync.aligned.u32 224;");
    STAMPIF(threadIdx.x == 0, 82);
    const int g = lane >> 2, q = lane & 3;
    if (wg == 1) bar_arrive(1, 256);
    if (tid < 2) mbar_arrive(sb + 8 * (B_E1 + tid));
    uint32_t dv = *(const uint16_t*)(gD + 128 * wg + b);
    {
      const int t2 = threadIdx.x, w2 = 4 * wg + w;
      STAMPIF(t2 == 0, 20);
      kv_job(G, sb, b, wg, tid);
      __syncwarp();
      STAMPIF(t2 == 0, 78);
      kv_signal(G, sb, b, wg, 8 * w + (lane & 7), lane == 0);
      STAMPIF(tid == 0, 1 + wg);
      mbar_wait(sb + 8 * B_X, 0);
      mbar_wait(sb + 8 * (B_X + 1), 0);
      STAMPIF(t2 == 0, 25);
      const uint32_t xr = ring + R_X + (15 - (t2 >> 4)) * 128;
      float pv = blo(lds32(xr)), s1 = 0.f, s2 = 0.f;
#pragma unroll
      for (int n = 0; n < 5; n++) {
        uint4 v = lds128(xr + 16 * (t2 & 7) + 2048 * ((t2 >> 3) & 1) + 4096 * n);
        uint32_t u[4] = {v.x, v.y, v.z, v.w};
#pragma unroll
        for (int j = 0; j < 4; j++) {
          float a = blo(u[j]) - pv, c = bhi(u[j]) - pv;
          s1 += a + c; s2 += a * a; s2 += c * c;
        }
      }
      uint32_t r[5][4];
      const uint32_t la = ring + R_X + wg * 2048 + (15 - (lane & 15)) * 128 + (((2 * w + (lane >> 4)) ^ (~lane & 7)) << 4);
#pragma unroll
      for (int n = 0; n < 5; n++) ldsm4t(r[n], la + n * 4096);
#pragma unroll
      for (int n = 0; n < 4; n++) sts64(xs_base(sb, n >> 1) + 512 * w2 + 256 * (n & 1) + 8 * lane, r[n >> 1][2 * (n & 1)], r[n >> 1][2 * (n & 1) + 1]);
#pragma unroll
      for (int o = 1; o < 16; o <<= 1) { s1 += __shfl_xor_sync(0xffffffffu, s1, o); s2 += __shfl_xor_sync(0xffffffffu, s2, o); }
      if ((t2 & 15) == 0) {
        float mu = s1 * (1.f / D_), var = fmaxf(s2 * (1.f / D_) - mu * mu, 0.f);
        const uint32_t a = sb + XS_LN + 8 * w + 4 * wg + (lane >> 3);
        sts16(a, pack2(pv + mu, 0.f));
        sts16(a + 32, pack2(__fsqrt_rn(rbf(rbf(var) + 1e-5f)), 0.f));
      }
      fence_async_s();
      bar_sync(6, 256);
      if (t2 == 0) mbar_arrive(sb + 8 * B_XS0);
      STAMPIF(t2 == 0, 75);
#pragma unroll
      for (int n = 4; n < 10; n++) sts64(xs_base(sb, n >> 1) + 512 * w2 + 256 * (n & 1) + 8 * lane, r[n >> 1][2 * (n & 1)], r[n >> 1][2 * (n & 1) + 1]);
      fence_async_s();
      __syncwarp();
      if (lane == 0) mbar_arrive(sb + 8 * B_XS);
      STAMPIF(t2 == 0, 26);
      k1_job(sb, wg, tid);
      bar_sync(3 + wg, 128);
      STAMPIF(t2 == 0, 79);
    }
    {
      const int b0 = (g >> 1) & 1, b1 = g >> 2, u = q + 4 * b0 - w;
      const uint32_t fo = 128 + (g & 1) * K1OFF + 288 * b1 + 4 * u, fo0 = fo - (u < 0 ? 32 : 0);
      const uint32_t dsel = (b1 == 0 && u == 0) ? ((g & 1) ? 0x1044 : 0x4410) : 0x4444;
      const bool wrap = b0 && q == 0;
      const int src1 = b0 ? ((lane & 20) | ((q - 1) & 3)) : (lane | 8);
#pragma unroll 1
      for (int ch = wg; ch < 5; ch += 2) {
        const uint32_t base = chan_base(sb, ch);
        if (ch >= 2) { mbar_wait(sb + 8 * (B_K + ch - 2), 0); mbar_wait(sb + 8 * (B_S + ch), 0); }
        const uint32_t fa = base + fo, fa0 = base + fo0;
        uint32_t af[16][4];
#pragma unroll
        for (int j = 0; j < 16; j++) {
          const int o = 64 * (j & 1) + 576 * (j >> 1);
          af[j][0] = lds32(((j & 1) ? fa : fa0) + o); af[j][1] = lds32(fa + o + 128); af[j][2] = lds32(fa + o + 32); af[j][3] = lds32(fa + o + 160);
        }
        af[0][0] = hadd(af[0][0], __byte_perm(dv, 0, dsel));
        if (ch < 3) dv = *(const uint16_t*)(gD + 128 * (ch + 2) + b);
        mbar_wait(sb + 8 * (B_U + ch), 0);
        float acc[128];
        const uint64_t db = mkdesc(base + KSZ, 32, 128, 0);
        bar_sync(1 + wg, 256);
        STAMPIF(tid == 0, 3 + ch);
        wg_fence();
        wgmma_rs_n64<0>(acc + 96, af[0], db + 192, 0);
        wgmma_rs_n192<0>(acc, af[0], db, 0);
        wgmma_rs_n64<0>(acc + 96, af[1], db + 196, 1);
        wgmma_rs_n192<0>(acc, af[1], db + 4, 1);
        wgmma_rs_n32<0>(acc + 96, af[2], db + 224, 1);
        wgmma_rs_n192<0>(acc, af[2], db + 32, 1);
        wgmma_rs_n32<0>(acc + 96, af[3], db + 228, 1);
        wgmma_rs_n192<0>(acc, af[3], db + 36, 1);
        wgmma_rs_n192<0>(acc, af[4], db + 64, 1);
        wgmma_rs_n192<0>(acc, af[5], db + 68, 1);
        wgmma_rs_n160<0>(acc, af[6], db + 96, 1);
        wgmma_rs_n160<0>(acc, af[7], db + 100, 1);
        wgmma_rs_n128<0>(acc, af[8], db + 128, 1);
        wgmma_rs_n128<0>(acc, af[9], db + 132, 1);
        wgmma_rs_n96<0>(acc, af[10], db + 160, 1);
        wgmma_rs_n96<0>(acc, af[11], db + 164, 1);
        bar_arrive(2 - wg, 256);
        wgmma_rs_n64<0>(acc, af[12], db + 192, 1);
        wgmma_rs_n64<0>(acc, af[13], db + 196, 1);
        wgmma_rs_n32<0>(acc, af[14], db + 224, 1);
        wgmma_rs_n32<0>(acc, af[15], db + 228, 1);
        wg_commit();
        wg_wait<0>();
#pragma unroll
        for (int i = 0; i < 128; i++) asm volatile("" : "+f"(acc[i])::"memory");
        bar_sync(3 + wg, 128);
        if (tid == 0) mbar_arrive(sb + 8 * (B_E1 + 2 + (ch >> 1)));
        float S0[33], T[34];
#pragma unroll
        for (int i = 0; i < 31; i++) S0[i] = acc[4 * i] + acc[4 * i + 6];
        S0[31] = acc[124]; S0[32] = 0.f;
#pragma unroll
        for (int i = 0; i < 32; i++) {
          float s1 = i < 31 ? acc[4 * i + 1] + acc[4 * i + 7] : acc[125];
          T[i] = (wrap ? S0[i + 1] : S0[i]) + __shfl_sync(0xffffffffu, s1, src1);
        }
        T[32] = 0.f; T[33] = 0.f;
        uint32_t zz[8];
#pragma unroll
        for (int mu = 0; mu < 8; mu++) {
          float y0 = (b1 ? T[4 * mu + 4] : T[4 * mu]) + __shfl_xor_sync(0xffffffffu, T[4 * mu + 2], 16);
          float y1 = (b1 ? T[4 * mu + 5] : T[4 * mu + 1]) + __shfl_xor_sync(0xffffffffu, T[4 * mu + 3], 16);
          zz[mu] = pack2(y0, y1);
        }
        sts128(sb + SM_Z + ch * 4096 + tid * 32, make_uint4(zz[0], zz[4], zz[1], zz[5]));
        sts128(sb + SM_Z + ch * 4096 + tid * 32 + 16, make_uint4(zz[2], zz[6], zz[3], zz[7]));
        __syncwarp();
        if (lane == 0) mbar_arrive(sb + 8 * (B_Z + ch));
        STAMPIF(tid == 0, 8 + ch);
      }
      if (wg == 1) bar_sync(2, 256);
    }
    uint32_t hh[48];
    {
      float ga[192];
      float* ua = ga + 96;
      const uint64_t da0 = mkdesc(ring + wg * 4096, 4096, 1024, 1), db0 = mkdesc(ring + 8192, 4096, 1024, 1);
      int st = 0, ph = 0;
#pragma unroll 1
      for (int it = 0; it < 20; it++) {
        mbar_wait(sb + 8 * (B_F1 + st), ph);
        STAMPIF(tid == 0 && it == 0, 13 + wg);
        const uint64_t da = da0 + st * 2048, db = db0 + st * 2048;
        wg_fence();
        wgmma_ss_n192<1, 1>(ga, da, db, it != 0);
        wgmma_ss_n192<1, 1>(ua, da, db + 768, it != 0);
        wgmma_ss_n192<1, 1>(ga, da + 128, db + 128, 1);
        wgmma_ss_n192<1, 1>(ua, da + 128, db + 128 + 768, 1);
        wg_commit();
        wg_wait<1>();
        if (it > 0 && tid == 0) mbar_arrive(sb + 8 * (B_E1 + (st == 0 ? 5 : st - 1)));
        if (++st == 6) { st = 0; ph ^= 1; }
      }
      mbar_wait(sb + 8 * B_EXT, 0);
      const uint64_t de = mkdesc(sb + SM_EXT, 1024, 0, 1), ds = mkdesc(sb + SM_STAT + wg * 1024, 0, 128, 0);
      wg_fence();
      wgmma_ss_n192<0, 1>(ga, ds, de, 1);
      wgmma_ss_n192<0, 1>(ua, ds, de + 192, 1);
      wg_commit();
      wg_wait<1>();
      if (tid == 0) mbar_arrive(sb + 8 * (B_E1 + 1));
      wg_wait<0>();
#pragma unroll
      for (int i = 0; i < 192; i++) asm volatile("" : "+f"(ga[i])::"memory");
      STAMPIF(tid == 0, 15 + wg);
#pragma unroll
      for (int i = 0; i < 48; i++) {
        const int j = 64 * (i >> 4) + 2 * (i & 15);
        hh[i] = pack2(ga[j] * ga[j + 32], ga[j + 1] * ga[j + 33]);
      }
    }
    float acc[80];
    {
      bf16* dst = G->HH + b * 6 * 4096 + (64 * wg + 16 * w + g) * 32 + ((q ^ ((g >> 1) & 3)) << 3);
      const uint64_t db0 = mkdesc(ring + 8192, 4096, 1024, 1), da0 = mkdesc(ring + wg * 4096, 16, 512, 2);
#pragma unroll
      for (int k = 0; k < 6; k++) {
        mbar_wait(sb + 8 * (B_FB + k), 0);
        const uint64_t db = db0 + ((k >> 1) + 2) * 2048 + (k & 1) * 768;
        wg_fence();
        wgmma_rs_n160<1>(acc, hh + 8 * k, db, k != 0);
        wgmma_rs_n160<1>(acc, hh + 8 * k + 4, db + 128, 1);
        wg_commit();
        if (k < 3) {
#pragma unroll
          for (int j = 2 * k; j < 2 * k + 2; j++) {
            *(uint4*)(dst + j * 4096) = make_uint4(hh[8 * j], hh[8 * j + 2], hh[8 * j + 4], hh[8 * j + 6]);
            *(uint4*)(dst + j * 4096 + 256) = make_uint4(hh[8 * j + 1], hh[8 * j + 3], hh[8 * j + 5], hh[8 * j + 7]);
          }
          if (k == 2) {
            __syncwarp();
            if (lane == 0) mbar_arrive(sb + 8 * (B_HH + wg));
            STAMPIF(tid == 0, 81);
          }
        }
        wg_wait<1>();
        if (k > 0 && tid == 0) mbar_arrive(sb + 8 * (B_EB + k - 1));
      }
      STAMPIF(tid == 0, 17);
      int ka = 0, pa = 0;
#pragma unroll 1
      for (int k = 6; k < 24; k++) {
        const int sl = k < 12 ? k : k - 12;
        int gb_ = (sl >> 1) + 2; if (gb_ >= 6) gb_ -= 6;
        int ga_ = ka + 2; if (ga_ >= 6) ga_ -= 6;
        mbar_wait(sb + 8 * (B_FB + sl), k >= 12);
        mbar_wait(sb + 8 * (B_FA + ka), pa);
        const uint64_t db = db0 + gb_ * 2048 + (sl & 1) * 768, da = da0 + ga_ * 2048;
        wg_fence();
        wgmma_ss_n160<0, 1>(acc, da, db, 1);
        wgmma_ss_n160<0, 1>(acc, da + 2, db + 128, 1);
        wg_commit();
        wg_wait<1>();
        if (tid == 0) {
          mbar_arrive(sb + 8 * (B_EB + (sl == 0 ? 11 : sl - 1)));
          if (k > 6) mbar_arrive(sb + 8 * (B_EA + (ka == 0 ? 5 : ka - 1)));
        }
        if (++ka == 6) { ka = 0; pa ^= 1; }
      }
    }
    uint32_t xr[20], gbv[10];
    mbar_wait(sb + 8 * B_X1, 0);
    mbar_wait(sb + 8 * B_GB, 0);
    {
      const uint32_t la = sb + SM_Z + wg * 10240 + (8 * (lane >> 4) + (lane & 7)) * 128 + (((2 * w + ((lane >> 3) & 1)) ^ (lane & 7)) << 4);
#pragma unroll
      for (int i = 0; i < 5; i++) ldsm4t(xr + 4 * i, la + i * 2048);
#pragma unroll
      for (int i = 0; i < 10; i++) gbv[i] = lds32(sb + SM_SMALL + SMALL_GB + 16 * i + 4 * q);
    }
    float rs0 = 2.f * blo(lds32(sb + SM_STAT + (64 * wg + 16 * w + g) * 16 + 4)), rs1 = 2.f * blo(lds32(sb + SM_STAT + (64 * wg + 16 * w + g) * 16 + 132));
    rs0 = __frcp_rn(rs0 * rs0); rs1 = __frcp_rn(rs1 * rs1);
    mbar_wait(sb + 8 * B_PEER, 0);
    wg_wait<0>();
#pragma unroll
    for (int i = 0; i < 80; i++) asm volatile("" : "+f"(acc[i])::"memory");
    STAMPIF(tid == 0, 18);
    const uint32_t rbuf = ring + (2 + wg) * 32768 + 8192 + w * 5120;
    {
      const uint32_t rd = mapa(rbuf + lane * 16, (b & 1) ^ 1), rb = mapa(sb + 8 * (B_RECV + wg), (b & 1) ^ 1);
      if (b & 1) {
#pragma unroll
        for (int i = 0; i < 10; i++) st_async4(rd + i * 512, acc[4 * i], acc[4 * i + 1], acc[4 * i + 2], acc[4 * i + 3], rb);
#pragma unroll
        for (int i = 0; i < 40; i++) acc[i] = acc[40 + i];
      } else {
#pragma unroll
        for (int i = 0; i < 10; i++) st_async4(rd + i * 512, acc[40 + 4 * i], acc[41 + 4 * i], acc[42 + 4 * i], acc[43 + 4 * i], rb);
      }
    }
    mbar_wait(sb + 8 * (B_RECV + wg), 0);
    uint32_t ov[20];
#pragma unroll
    for (int i = 0; i < 10; i++) {
      uint4 v = lds128(rbuf + i * 512 + lane * 16);
      uint32_t o0 = pack2((acc[4 * i] + __uint_as_float(v.x)) * rs0, (acc[4 * i + 1] + __uint_as_float(v.y)) * rs0);
      uint32_t o1 = pack2((acc[4 * i + 2] + __uint_as_float(v.z)) * rs1, (acc[4 * i + 3] + __uint_as_float(v.w)) * rs1);
      ov[2 * i] = hadd(xr[2 * i], hmul(gbv[i], o0));
      ov[2 * i + 1] = hadd(xr[2 * i + 1], hmul(gbv[i], o1));
    }
    __syncwarp();
#pragma unroll
    for (int i = 0; i < 5; i++) stsm4(rbuf + (15 - (4 * (lane & 2) + 2 * ((lane >> 2) & 3) + (lane & 1))) * 160 + (lane >> 4) * 16 + i * 32, ov + 4 * i);
    fence_async_s();
    __syncwarp();
    if (lane == 0) {
      tma_store4d(&P.mO, rbuf, 80 * s, 0, 0, 191 - ibase(8 * m + 4 * wg + w));
      asm volatile("cp.async.bulk.commit_group;" ::: "memory");
      asm volatile("cp.async.bulk.wait_group.read 0;" ::: "memory");
    }
  }
}

typedef CUresult (*EncFn)(CUtensorMap*, CUtensorMapDataType, cuuint32_t, void*, const cuuint64_t*, const cuuint64_t*, const cuuint32_t*, const cuuint32_t*,
                          CUtensorMapInterleave, CUtensorMapSwizzle, CUtensorMapL2promotion, CUtensorMapFloatOOBfill);
static void mkmap(EncFn enc, CUtensorMap* m, const void* p, int rank, const cuuint64_t* dims, const cuuint64_t* strides, const cuuint32_t* box, CUtensorMapSwizzle sw) {
  cuuint32_t es[5] = {1, 1, 1, 1, 1};
  CUresult r = enc(m, CU_TENSOR_MAP_DATA_TYPE_BFLOAT16, rank, (void*)p, dims, strides, box, es, CU_TENSOR_MAP_INTERLEAVE_NONE, sw,
                   CU_TENSOR_MAP_L2_PROMOTION_L2_128B, CU_TENSOR_MAP_FLOAT_OOB_FILL_NONE);
  if (r != CUDA_SUCCESS) fprintf(stderr, "tensor map encode failed: %d\n", (int)r);
}

extern "C" void kernel_launch(void* const* d_in, const int* in_sizes, int n_in, void* d_out, int out_size) {
  void* fn = nullptr;
  cudaDriverEntryPointQueryResult qr;
  cudaGetDriverEntryPoint("cuTensorMapEncodeTiled", &fn, cudaEnableDefault, &qr);
  EncFn enc = (EncFn)fn;
  Scr* G;
  cudaGetSymbolAddress((void**)&G, g_scr);
  void *pAT = G->AT, *pX1 = G->x1T;
  Params P;
  { cuuint64_t d[] = {10240, 128}, st[] = {20480}; cuuint32_t bx[] = {16, 128}; mkmap(enc, &P.mXc, G->xT, 2, d, st, bx, CU_TENSOR_MAP_SWIZZLE_NONE); }
  { cuuint64_t d[] = {128, 16, 640}, st[] = {256, 4096}; cuuint32_t bx[] = {144, 16, 1}; mkmap(enc, &P.mS, d_in[4], 3, d, st, bx, CU_TENSOR_MAP_SWIZZLE_NONE); }
  { cuuint64_t d[] = {3840, 640}, st[] = {7680}; cuuint32_t bx[] = {64, 80}; mkmap(enc, &P.mWm, d_in[11], 2, d, st, bx, CU_TENSOR_MAP_SWIZZLE_128B); }
  { cuuint64_t d[] = {64, 640, 32}, st[] = {4096, 128}; cuuint32_t bx[] = {64, 32, 2}; mkmap(enc, &P.mA, pAT, 3, d, st, bx, CU_TENSOR_MAP_SWIZZLE_128B); }
  { cuuint64_t d[] = {64, 640, 32}, st[] = {4096, 128}; cuuint32_t bx[] = {64, 80, 2}; mkmap(enc, &P.mX1, pX1, 3, d, st, bx, CU_TENSOR_MAP_SWIZZLE_128B); }
  { cuuint64_t d[] = {1536, 640}, st[] = {3072}; cuuint32_t bx[] = {64, 32};
    mkmap(enc, &P.mG, d_in[7], 2, d, st, bx, CU_TENSOR_MAP_SWIZZLE_128B); mkmap(enc, &P.mU, d_in[8], 2, d, st, bx, CU_TENSOR_MAP_SWIZZLE_128B); }
  { cuuint64_t d[] = {160, 2, 4, 192, 4}, st[] = {1280, 2560, 10240, 320}; cuuint32_t bx[] = {64, 2, 4, 4, 1}; mkmap(enc, &P.mDn, d_in[9], 5, d, st, bx, CU_TENSOR_MAP_SWIZZLE_128B); }
  { cuuint64_t d[] = {160, 2, 192, 4, 4}, st[] = {1280, 10240, 2560, 320}; cuuint32_t bx[] = {64, 2, 4, 4, 1}; mkmap(enc, &P.mDp, d_in[9], 5, d, st, bx, CU_TENSOR_MAP_SWIZZLE_128B); }
  { cuuint64_t d[] = {64, 2, 8, 10, 192}, st[] = {64 * 1280, 256 * 1280, 128, 1280}; cuuint32_t bx[] = {64, 2, 8, 5, 1}; mkmap(enc, &P.mX, d_in[0], 5, d, st, bx, CU_TENSOR_MAP_SWIZZLE_128B); }
  { cuuint64_t d[] = {640, 2, 8, 192}, st[] = {64 * 1280, 256 * 1280, 1280}; cuuint32_t bx[] = {80, 2, 8, 1}; mkmap(enc, &P.mO, d_out, 4, d, st, bx, CU_TENSOR_MAP_SWIZZLE_NONE); }
  cudaFuncSetAttribute(fused_kernel, cudaFuncAttributeMaxDynamicSharedMemorySize, SM_TOTAL + DEVSM);
  cudaLaunchConfig_t cfg = {};
  cfg.gridDim = dim3(128); cfg.blockDim = dim3(512); cfg.dynamicSmemBytes = SM_TOTAL + DEVSM; cfg.stream = cudaStreamPerThread;
  cudaLaunchAttribute at[1];
  at[0].id = cudaLaunchAttributeClusterDimension; at[0].val.clusterDim.x = 2; at[0].val.clusterDim.y = 1; at[0].val.clusterDim.z = 1;
  cfg.attrs = at; cfg.numAttrs = 1;
  cudaLaunchKernelEx(&cfg, fused_kernel, (const bf16*)d_in[1], (const bf16*)d_in[2], (const bf16*)d_in[3], (const bf16*)d_in[5], (const bf16*)d_in[10], G,
                     (const bf16*)d_in[7], (const bf16*)d_in[8], (const bf16*)d_in[9], P);
}
```

```cpp
#include <cuda_runtime.h>
#include <cuda.h>
#include <cuda_bf16.h>
#include <stdio.h>
#include <stdint.h>
typedef __nv_bfloat16 bf16;
__device__ __forceinline__ uint32_t smem_u32(const void* p) { return (uint32_t)__cvta_generic_to_shared(p); }
__device__ __forceinline__ void mbar_init(uint32_t bar, int cnt) { asm volatile("mbarrier.init.shared::cta.b64 [%0], %1;" ::"r"(bar), "r"(cnt) : "memory"); }
__device__ __forceinline__ void mbar_expect(uint32_t bar, int bytes) { asm volatile("mbarrier.arrive.expect_tx.shared::cta.b64 _, [%0], %1;" ::"r"(bar), "r"(bytes) : "memory"); }
__device__ __forceinline__ void mbar_arrive(uint32_t bar) { asm volatile("mbarrier.arrive.shared::cta.b64 _, [%0];" ::"r"(bar) : "memory"); }
__device__ __forceinline__ void mbar_arrive_remote(uint32_t bar) { asm volatile("mbarrier.arrive.relaxed.cluster.shared::cluster.b64 _, [%0];" ::"r"(bar) : "memory"); }
__device__ __forceinline__ uint32_t mapa(uint32_t a, uint32_t cta) { uint32_t r; asm("mapa.shared::cluster.u32 %0, %1, %2;" : "=r"(r) : "r"(a), "r"(cta)); return r; }
__device__ __forceinline__ bool mbar_try(uint32_t bar, int parity) {
  uint32_t ok;
  asm volatile("{\n.reg .pred p;\nmbarrier.try_wait.parity.shared::cta.b64 p, [%1], %2;\nselp.u32 %0, 1, 0, p;\n}" : "=r"(ok) : "r"(bar), "r"(parity) : "memory");
  return ok;
}
__device__ __forceinline__ void mbar_wait(uint32_t bar, int parity) {
#pragma unroll 1
  for (int i = 0; i < (1 << 20); i++) { if (mbar_try(bar, parity)) return; }
  __trap();
}
__device__ __forceinline__ bool elect() {
  uint32_t p;
  asm volatile("{\n.reg .pred P;\nelect.sync _|P, 0xffffffff;\nselp.u32 %0, 1, 0, P;\n}" : "=r"(p));
  return p;
}
__device__ __forceinline__ void tma2d(uint32_t dst, const CUtensorMap* m, int c0, int c1, uint32_t bar) {
  asm volatile("cp.async.bulk.tensor.2d.shared::cluster.global.mbarrier::complete_tx::bytes [%0], [%1, {%3, %4}], [%2];" ::"r"(dst), "l"(m), "r"(bar), "r"(c0), "r"(c1) : "memory");
}
__device__ __forceinline__ void tma3d(uint32_t dst, const CUtensorMap* m, int c0, int c1, int c2, uint32_t bar) {
  asm volatile("cp.async.bulk.tensor.3d.shared::cluster.global.mbarrier::complete_tx::bytes [%0], [%1, {%3, %4, %5}], [%2];" ::"r"(dst), "l"(m), "r"(bar), "r"(c0), "r"(c1), "r"(c2) : "memory");
}
__device__ __forceinline__ void tma5d(uint32_t dst, const CUtensorMap* m, int c0, int c1, int c2, int c3, int c4, uint32_t bar) {
  asm volatile("cp.async.bulk.tensor.5d.shared::cluster.global.mbarrier::complete_tx::bytes [%0], [%1, {%3, %4, %5, %6, %7}], [%2];" ::"r"(dst), "l"(m), "r"(bar), "r"(c0), "r"(c1), "r"(c2), "r"(c3), "r"(c4) : "memory");
}
__device__ __forceinline__ void tma_store2d(const CUtensorMap* m, uint32_t src, int c0, int c1) {
  asm volatile("cp.async.bulk.tensor.2d.global.shared::cta.bulk_group [%0, {%2, %3}], [%1];" ::"l"(m), "r"(src), "r"(c0), "r"(c1) : "memory");
}
__device__ __forceinline__ void tma_store4d(const CUtensorMap* m, uint32_t src, int c0, int c1, int c2, int c3) {
  asm volatile("cp.async.bulk.tensor.4d.global.shared::cta.bulk_group [%0, {%2, %3, %4, %5}], [%1];" ::"l"(m), "r"(src), "r"(c0), "r"(c1), "r"(c2), "r"(c3) : "memory");
}
__device__ __forceinline__ void tma_prefetch2d(const CUtensorMap* m, int c0, int c1) {
  asm volatile("cp.async.bulk.prefetch.tensor.2d.L2.global [%0, {%1, %2}];" ::"l"(m), "r"(c0), "r"(c1) : "memory");
}
__device__ __forceinline__ void bulk_g2s(uint32_t dst, const void* src, int bytes, uint32_t bar) {
  asm volatile("cp.async.bulk.shared::cluster.global.mbarrier::complete_tx::bytes [%0], [%1], %2, [%3];" ::"r"(dst), "l"(src), "r"(bytes), "r"(bar) : "memory");
}
__device__ __forceinline__ void bulk_s2g(void* dst, uint32_t src, int bytes) {
  asm volatile("cp.async.bulk.global.shared::cta.bulk_group [%0], [%1], %2;" ::"l"(dst), "r"(src), "r"(bytes) : "memory");
}
__device__ __forceinline__ void cp16(uint32_t dst, const void* src) { asm volatile("cp.async.cg.shared.global [%0], [%1], 16;" ::"r"(dst), "l"(src) : "memory"); }
__device__ __forceinline__ void cp16z(uint32_t dst, const void* src, int n) { asm volatile("cp.async.cg.shared.global [%0], [%1], 16, %2;" ::"r"(dst), "l"(src), "r"(n) : "memory"); }
__device__ __forceinline__ void cp_arrive(uint32_t bar) { asm volatile("cp.async.mbarrier.arrive.noinc.shared::cta.b64 [%0];" ::"r"(bar) : "memory"); }
__device__ __forceinline__ void st_async4(uint32_t dst, const uint32_t* v, uint32_t bar) {
  asm volatile("st.async.weak.shared::cluster.mbarrier::complete_tx::bytes.v4.b32 [%0], {%1, %2, %3, %4}, [%5];" ::"r"(dst), "r"(v[0]), "r"(v[1]), "r"(v[2]), "r"(v[3]), "r"(bar) : "memory");
}
__device__ __forceinline__ void wg_fence() { asm volatile("wgmma.fence.sync.aligned;" ::: "memory"); }
__device__ __forceinline__ void wg_commit() { asm volatile("wgmma.commit_group.sync.aligned;" ::: "memory"); }
template <int N> __device__ __forceinline__ void wg_wait() { asm volatile("wgmma.wait_group.sync.aligned %0;" ::"n"(N) : "memory"); }
__device__ __forceinline__ uint64_t mkdesc(uint32_t addr, uint32_t lbo, uint32_t sbo, uint32_t swz) {
  return (uint64_t)((addr & 0x3FFFF) >> 4) | ((uint64_t)(lbo >> 4) << 16) | ((uint64_t)(sbo >> 4) << 32) | ((uint64_t)swz << 62);
}
__device__ __forceinline__ void ldsm4t(uint32_t* r, uint32_t a) {
  asm volatile("ldmatrix.sync.aligned.m8n8.x4.trans.shared.b16 {%0,%1,%2,%3}, [%4];" : "=r"(r[0]), "=r"(r[1]), "=r"(r[2]), "=r"(r[3]) : "r"(a) : "memory");
}
__device__ __forceinline__ void stsm4(uint32_t a, const uint32_t* r) {
  asm volatile("stmatrix.sync.aligned.m8n8.x4.shared.b16 [%0], {%1,%2,%3,%4};" ::"r"(a), "r"(r[0]), "r"(r[1]), "r"(r[2]), "r"(r[3]) : "memory");
}
__device__ __forceinline__ void bar_sync(int id, int n) { asm volatile("bar.sync %0, %1;" ::"r"(id), "r"(n) : "memory"); }
__device__ __forceinline__ void bar_arrive(int id, int n) { asm volatile("bar.arrive %0, %1;" ::"r"(id), "r"(n) : "memory"); }
__device__ __forceinline__ uint32_t lds32(uint32_t a) { uint32_t v; asm volatile("ld.shared.b32 %0, [%1];" : "=r"(v) : "r"(a) : "memory"); return v; }
__device__ __forceinline__ uint2 lds64(uint32_t a) { uint2 v; asm volatile("ld.shared.v2.b32 {%0,%1}, [%2];" : "=r"(v.x), "=r"(v.y) : "r"(a) : "memory"); return v; }
__device__ __forceinline__ uint4 lds128(uint32_t a) { uint4 v; asm volatile("ld.shared.v4.b32 {%0,%1,%2,%3}, [%4];" : "=r"(v.x), "=r"(v.y), "=r"(v.z), "=r"(v.w) : "r"(a) : "memory"); return v; }
__device__ __forceinline__ void sts16(uint32_t a, uint32_t v) { asm volatile("st.shared.b16 [%0], %1;" ::"r"(a), "h"((uint16_t)v) : "memory"); }
__device__ __forceinline__ void sts32(uint32_t a, uint32_t v) { asm volatile("st.shared.b32 [%0], %1;" ::"r"(a), "r"(v) : "memory"); }
__device__ __forceinline__ void sts64(uint32_t a, uint32_t x, uint32_t y) { asm volatile("st.shared.v2.b32 [%0], {%1,%2};" ::"r"(a), "r"(x), "r"(y) : "memory"); }
__device__ __forceinline__ void sts128(uint32_t a, uint4 v) { asm volatile("st.shared.v4.b32 [%0], {%1,%2,%3,%4};" ::"r"(a), "r"(v.x), "r"(v.y), "r"(v.z), "r"(v.w) : "memory"); }
template<int TB> __device__ __forceinline__ void wgmma_rs_n128(float* d, const uint32_t* a, uint64_t db, int sd) {
  asm volatile("{\n.reg .pred p;\nsetp.ne.b32 p, %69, 0;\n"
    "wgmma.mma_async.sync.aligned.m64n128k16.f32.bf16.bf16 {%0, %1, %2, %3, %4, %5, %6, %7, %8, %9, %10, %11, %12, %13, %14, %15, %16, %17, %18, %19, %20, %21, %22, %23, %24, %25, %26, %27, %28, %29, %30, %31, %32, %33, %34, %35, %36, %37, %38, %39, %40, %41, %42, %43, %44, %45, %46, %47, %48, %49, %50, %51, %52, %53, %54, %55, %56, %57, %58, %59, %60, %61, %62, %63}, {%64, %65, %66, %67}, %68, p, 1, 1, %70;\n}"
    : "+f"(d[0]), "+f"(d[1]), "+f"(d[2]), "+f"(d[3]), "+f"(d[4]), "+f"(d[5]), "+f"(d[6]), "+f"(d[7]), "+f"(d[8]), "+f"(d[9]), "+f"(d[10]), "+f"(d[11]), "+f"(d[12]), "+f"(d[13]), "+f"(d[14]), "+f"(d[15]), "+f"(d[16]), "+f"(d[17]), "+f"(d[18]), "+f"(d[19]), "+f"(d[20]), "+f"(d[21]), "+f"(d[22]), "+f"(d[23]), "+f"(d[24]), "+f"(d[25]), "+f"(d[26]), "+f"(d[27]), "+f"(d[28]), "+f"(d[29]), "+f"(d[30]), "+f"(d[31]), "+f"(d[32]), "+f"(d[33]), "+f"(d[34]), "+f"(d[35]), "+f"(d[36]), "+f"(d[37]), "+f"(d[38]), "+f"(d[39]), "+f"(d[40]), "+f"(d[41]), "+f"(d[42]), "+f"(d[43]), "+f"(d[44]), "+f"(d[45]), "+f"(d[46]), "+f"(d[47]), "+f"(d[48]), "+f"(d[49]), "+f"(d[50]), "+f"(d[51]), "+f"(d[52]), "+f"(d[53]), "+f"(d[54]), "+f"(d[55]), "+f"(d[56]), "+f"(d[57]), "+f"(d[58]), "+f"(d[59]), "+f"(d[60]), "+f"(d[61]), "+f"(d[62]), "+f"(d[63])
    : "r"(a[0]), "r"(a[1]), "r"(a[2]), "r"(a[3]), "l"(db), "r"(sd), "n"(TB));
}

template<int TB> __device__ __forceinline__ void wgmma_rs_n160(float* d, const uint32_t* a, uint64_t db, int sd) {
  asm volatile("{\n.reg .pred p;\nsetp.ne.b32 p, %85, 0;\n"
    "wgmma.mma_async.sync.aligned.m64n160k16.f32.bf16.bf16 {%0, %1, %2, %3, %4, %5, %6, %7, %8, %9, %10, %11, %12, %13, %14, %15, %16, %17, %18, %19, %20, %21, %22, %23, %24, %25, %26, %27, %28, %29, %30, %31, %32, %33, %34, %35, %36, %37, %38, %39, %40, %41, %42, %43, %44, %45, %46, %47, %48, %49, %50, %51, %52, %53, %54, %55, %56, %57, %58, %59, %60, %61, %62, %63, %64, %65, %66, %67, %68, %69, %70, %71, %72, %73, %74, %75, %76, %77, %78, %79}, {%80, %81, %82, %83}, %84, p, 1, 1, %86;\n}"
    : "+f"(d[0]), "+f"(d[1]), "+f"(d[2]), "+f"(d[3]), "+f"(d[4]), "+f"(d[5]), "+f"(d[6]), "+f"(d[7]), "+f"(d[8]), "+f"(d[9]), "+f"(d[10]), "+f"(d[11]), "+f"(d[12]), "+f"(d[13]), "+f"(d[14]), "+f"(d[15]), "+f"(d[16]), "+f"(d[17]), "+f"(d[18]), "+f"(d[19]), "+f"(d[20]), "+f"(d[21]), "+f"(d[22]), "+f"(d[23]), "+f"(d[24]), "+f"(d[25]), "+f"(d[26]), "+f"(d[27]), "+f"(d[28]), "+f"(d[29]), "+f"(d[30]), "+f"(d[31]), "+f"(d[32]), "+f"(d[33]), "+f"(d[34]), "+f"(d[35]), "+f"(d[36]), "+f"(d[37]), "+f"(d[38]), "+f"(d[39]), "+f"(d[40]), "+f"(d[41]), "+f"(d[42]), "+f"(d[43]), "+f"(d[44]), "+f"(d[45]), "+f"(d[46]), "+f"(d[47]), "+f"(d[48]), "+f"(d[49]), "+f"(d[50]), "+f"(d[51]), "+f"(d[52]), "+f"(d[53]), "+f"(d[54]), "+f"(d[55]), "+f"(d[56]), "+f"(d[57]), "+f"(d[58]), "+f"(d[59]), "+f"(d[60]), "+f"(d[61]), "+f"(d[62]), "+f"(d[63]), "+f"(d[64]), "+f"(d[65]), "+f"(d[66]), "+f"(d[67]), "+f"(d[68]), "+f"(d[69]), "+f"(d[70]), "+f"(d[71]), "+f"(d[72]), "+f"(d[73]), "+f"(d[74]), "+f"(d[75]), "+f"(d[76]), "+f"(d[77]), "+f"(d[78]), "+f"(d[79])
    : "r"(a[0]), "r"(a[1]), "r"(a[2]), "r"(a[3]), "l"(db), "r"(sd), "n"(TB));
}

template<int TB> __device__ __forceinline__ void wgmma_rs_n192(float* d, const uint32_t* a, uint64_t db, int sd) {
  asm volatile("{\n.reg .pred p;\nsetp.ne.b32 p, %101, 0;\n"
    "wgmma.mma_async.sync.aligned.m64n192k16.f32.bf16.bf16 {%0, %1, %2, %3, %4, %5, %6, %7, %8, %9, %10, %11, %12, %13, %14, %15, %16, %17, %18, %19, %20, %21, %22, %23, %24, %25, %26, %27, %28, %29, %30, %31, %32, %33, %34, %35, %36, %37, %38, %39, %40, %41, %42, %43, %44, %45, %46, %47, %48, %49, %50, %51, %52, %53, %54, %55, %56, %57, %58, %59, %60, %61, %62, %63, %64, %65, %66, %67, %68, %69, %70, %71, %72, %73, %74, %75, %76, %77, %78, %79, %80, %81, %82, %83, %84, %85, %86, %87, %88, %89, %90, %91, %92, %93, %94, %95}, {%96, %97, %98, %99}, %100, p, 1, 1, %102;\n}"
    : "+f"(d[0]), "+f"(d[1]), "+f"(d[2]), "+f"(d[3]), "+f"(d[4]), "+f"(d[5]), "+f"(d[6]), "+f"(d[7]), "+f"(d[8]), "+f"(d[9]), "+f"(d[10]), "+f"(d[11]), "+f"(d[12]), "+f"(d[13]), "+f"(d[14]), "+f"(d[15]), "+f"(d[16]), "+f"(d[17]), "+f"(d[18]), "+f"(d[19]), "+f"(d[20]), "+f"(d[21]), "+f"(d[22]), "+f"(d[23]), "+f"(d[24]), "+f"(d[25]), "+f"(d[26]), "+f"(d[27]), "+f"(d[28]), "+f"(d[29]), "+f"(d[30]), "+f"(d[31]), "+f"(d[32]), "+f"(d[33]), "+f"(d[34]), "+f"(d[35]), "+f"(d[36]), "+f"(d[37]), "+f"(d[38]), "+f"(d[39]), "+f"(d[40]), "+f"(d[41]), "+f"(d[42]), "+f"(d[43]), "+f"(d[44]), "+f"(d[45]), "+f"(d[46]), "+f"(d[47]), "+f"(d[48]), "+f"(d[49]), "+f"(d[50]), "+f"(d[51]), "+f"(d[52]), "+f"(d[53]), "+f"(d[54]), "+f"(d[55]), "+f"(d[56]), "+f"(d[57]), "+f"(d[58]), "+f"(d[59]), "+f"(d[60]), "+f"(d[61]), "+f"(d[62]), "+f"(d[63]), "+f"(d[64]), "+f"(d[65]), "+f"(d[66]), "+f"(d[67]), "+f"(d[68]), "+f"(d[69]), "+f"(d[70]), "+f"(d[71]), "+f"(d[72]), "+f"(d[73]), "+f"(d[74]), "+f"(d[75]), "+f"(d[76]), "+f"(d[77]), "+f"(d[78]), "+f"(d[79]), "+f"(d[80]), "+f"(d[81]), "+f"(d[82]), "+f"(d[83]), "+f"(d[84]), "+f"(d[85]), "+f"(d[86]), "+f"(d[87]), "+f"(d[88]), "+f"(d[89]), "+f"(d[90]), "+f"(d[91]), "+f"(d[92]), "+f"(d[93]), "+f"(d[94]), "+f"(d[95])
    : "r"(a[0]), "r"(a[1]), "r"(a[2]), "r"(a[3]), "l"(db), "r"(sd), "n"(TB));
}

template<int TB> __device__ __forceinline__ void wgmma_rs_n32(float* d, const uint32_t* a, uint64_t db, int sd) {
  asm volatile("{\n.reg .pred p;\nsetp.ne.b32 p, %21, 0;\n"
    "wgmma.mma_async.sync.aligned.m64n32k16.f32.bf16.bf16 {%0, %1, %2, %3, %4, %5, %6, %7, %8, %9, %10, %11, %12, %13, %14, %15}, {%16, %17, %18, %19}, %20, p, 1, 1, %22;\n}"
    : "+f"(d[0]), "+f"(d[1]), "+f"(d[2]), "+f"(d[3]), "+f"(d[4]), "+f"(d[5]), "+f"(d[6]), "+f"(d[7]), "+f"(d[8]), "+f"(d[9]), "+f"(d[10]), "+f"(d[11]), "+f"(d[12]), "+f"(d[13]), "+f"(d[14]), "+f"(d[15])
    : "r"(a[0]), "r"(a[1]), "r"(a[2]), "r"(a[3]), "l"(db), "r"(sd), "n"(TB));
}

template<int TB> __device__ __forceinline__ void wgmma_rs_n64(float* d, const uint32_t* a, uint64_t db, int sd) {
  asm volatile("{\n.reg .pred p;\nsetp.ne.b32 p, %37, 0;\n"
    "wgmma.mma_async.sync.aligned.m64n64k16.f32.bf16.bf16 {%0, %1, %2, %3, %4, %5, %6, %7, %8, %9, %10, %11, %12, %13, %14, %15, %16, %17, %18, %19, %20, %21, %22, %23, %24, %25, %26, %27, %28, %29, %30, %31}, {%32, %33, %34, %35}, %36, p, 1, 1, %38;\n}"
    : "+f"(d[0]), "+f"(d[1]), "+f"(d[2]), "+f"(d[3]), "+f"(d[4]), "+f"(d[5]), "+f"(d[6]), "+f"(d[7]), "+f"(d[8]), "+f"(d[9]), "+f"(d[10]), "+f"(d[11]), "+f"(d[12]), "+f"(d[13]), "+f"(d[14]), "+f"(d[15]), "+f"(d[16]), "+f"(d[17]), "+f"(d[18]), "+f"(d[19]), "+f"(d[20]), "+f"(d[21]), "+f"(d[22]), "+f"(d[23]), "+f"(d[24]), "+f"(d[25]), "+f"(d[26]), "+f"(d[27]), "+f"(d[28]), "+f"(d[29]), "+f"(d[30]), "+f"(d[31])
    : "r"(a[0]), "r"(a[1]), "r"(a[2]), "r"(a[3]), "l"(db), "r"(sd), "n"(TB));
}

template<int TB> __device__ __forceinline__ void wgmma_rs_n80(float* d, const uint32_t* a, uint64_t db, int sd) {
  asm volatile("{\n.reg .pred p;\nsetp.ne.b32 p, %45, 0;\n"
    "wgmma.mma_async.sync.aligned.m64n80k16.f32.bf16.bf16 {%0, %1, %2, %3, %4, %5, %6, %7, %8, %9, %10, %11, %12, %13, %14, %15, %16, %17, %18, %19, %20, %21, %22, %23, %24, %25, %26, %27, %28, %29, %30, %31, %32, %33, %34, %35, %36, %37, %38, %39}, {%40, %41, %42, %43}, %44, p, 1, 1, %46;\n}"
    : "+f"(d[0]), "+f"(d[1]), "+f"(d[2]), "+f"(d[3]), "+f"(d[4]), "+f"(d[5]), "+f"(d[6]), "+f"(d[7]), "+f"(d[8]), "+f"(d[9]), "+f"(d[10]), "+f"(d[11]), "+f"(d[12]), "+f"(d[13]), "+f"(d[14]), "+f"(d[15]), "+f"(d[16]), "+f"(d[17]), "+f"(d[18]), "+f"(d[19]), "+f"(d[20]), "+f"(d[21]), "+f"(d[22]), "+f"(d[23]), "+f"(d[24]), "+f"(d[25]), "+f"(d[26]), "+f"(d[27]), "+f"(d[28]), "+f"(d[29]), "+f"(d[30]), "+f"(d[31]), "+f"(d[32]), "+f"(d[33]), "+f"(d[34]), "+f"(d[35]), "+f"(d[36]), "+f"(d[37]), "+f"(d[38]), "+f"(d[39])
    : "r"(a[0]), "r"(a[1]), "r"(a[2]), "r"(a[3]), "l"(db), "r"(sd), "n"(TB));
}

template<int TB> __device__ __forceinline__ void wgmma_rs_n96(float* d, const uint32_t* a, uint64_t db, int sd) {
  asm volatile("{\n.reg .pred p;\nsetp.ne.b32 p, %53, 0;\n"
    "wgmma.mma_async.sync.aligned.m64n96k16.f32.bf16.bf16 {%0, %1, %2, %3, %4, %5, %6, %7, %8, %9, %10, %11, %12, %13, %14, %15, %16, %17, %18, %19, %20, %21, %22, %23, %24, %25, %26, %27, %28, %29, %30, %31, %32, %33, %34, %35, %36, %37, %38, %39, %40, %41, %42, %43, %44, %45, %46, %47}, {%48, %49, %50, %51}, %52, p, 1, 1, %54;\n}"
    : "+f"(d[0]), "+f"(d[1]), "+f"(d[2]), "+f"(d[3]), "+f"(d[4]), "+f"(d[5]), "+f"(d[6]), "+f"(d[7]), "+f"(d[8]), "+f"(d[9]), "+f"(d[10]), "+f"(d[11]), "+f"(d[12]), "+f"(d[13]), "+f"(d[14]), "+f"(d[15]), "+f"(d[16]), "+f"(d[17]), "+f"(d[18]), "+f"(d[19]), "+f"(d[20]), "+f"(d[21]), "+f"(d[22]), "+f"(d[23]), "+f"(d[24]), "+f"(d[25]), "+f"(d[26]), "+f"(d[27]), "+f"(d[28]), "+f"(d[29]), "+f"(d[30]), "+f"(d[31]), "+f"(d[32]), "+f"(d[33]), "+f"(d[34]), "+f"(d[35]), "+f"(d[36]), "+f"(d[37]), "+f"(d[38]), "+f"(d[39]), "+f"(d[40]), "+f"(d[41]), "+f"(d[42]), "+f"(d[43]), "+f"(d[44]), "+f"(d[45]), "+f"(d[46]), "+f"(d[47])
    : "r"(a[0]), "r"(a[1]), "r"(a[2]), "r"(a[3]), "l"(db), "r"(sd), "n"(TB));
}

template<int TA, int TB> __device__ __forceinline__ void wgmma_ss_n192(float* d, uint64_t da, uint64_t db, int sd) {
  asm volatile("{\n.reg .pred p;\nsetp.ne.b32 p, %98, 0;\n"
    "wgmma.mma_async.sync.aligned.m64n192k16.f32.bf16.bf16 {%0, %1, %2, %3, %4, %5, %6, %7, %8, %9, %10, %11, %12, %13, %14, %15, %16, %17, %18, %19, %20, %21, %22, %23, %24, %25, %26, %27, %28, %29, %30, %31, %32, %33, %34, %35, %36, %37, %38, %39, %40, %41, %42, %43, %44, %45, %46, %47, %48, %49, %50, %51, %52, %53, %54, %55, %56, %57, %58, %59, %60, %61, %62, %63, %64, %65, %66, %67, %68, %69, %70, %71, %72, %73, %74, %75, %76, %77, %78, %79, %80, %81, %82, %83, %84, %85, %86, %87, %88, %89, %90, %91, %92, %93, %94, %95}, %96, %97, p, 1, 1, %99, %100;\n}"
    : "+f"(d[0]), "+f"(d[1]), "+f"(d[2]), "+f"(d[3]), "+f"(d[4]), "+f"(d[5]), "+f"(d[6]), "+f"(d[7]), "+f"(d[8]), "+f"(d[9]), "+f"(d[10]), "+f"(d[11]), "+f"(d[12]), "+f"(d[13]), "+f"(d[14]), "+f"(d[15]), "+f"(d[16]), "+f"(d[17]), "+f"(d[18]), "+f"(d[19]), "+f"(d[20]), "+f"(d[21]), "+f"(d[22]), "+f"(d[23]), "+f"(d[24]), "+f"(d[25]), "+f"(d[26]), "+f"(d[27]), "+f"(d[28]), "+f"(d[29]), "+f"(d[30]), "+f"(d[31]), "+f"(d[32]), "+f"(d[33]), "+f"(d[34]), "+f"(d[35]), "+f"(d[36]), "+f"(d[37]), "+f"(d[38]), "+f"(d[39]), "+f"(d[40]), "+f"(d[41]), "+f"(d[42]), "+f"(d[43]), "+f"(d[44]), "+f"(d[45]), "+f"(d[46]), "+f"(d[47]), "+f"(d[48]), "+f"(d[49]), "+f"(d[50]), "+f"(d[51]), "+f"(d[52]), "+f"(d[53]), "+f"(d[54]), "+f"(d[55]), "+f"(d[56]), "+f"(d[57]), "+f"(d[58]), "+f"(d[59]), "+f"(d[60]), "+f"(d[61]), "+f"(d[62]), "+f"(d[63]), "+f"(d[64]), "+f"(d[65]), "+f"(d[66]), "+f"(d[67]), "+f"(d[68]), "+f"(d[69]), "+f"(d[70]), "+f"(d[71]), "+f"(d[72]), "+f"(d[73]), "+f"(d[74]), "+f"(d[75]), "+f"(d[76]), "+f"(d[77]), "+f"(d[78]), "+f"(d[79]), "+f"(d[80]), "+f"(d[81]), "+f"(d[82]), "+f"(d[83]), "+f"(d[84]), "+f"(d[85]), "+f"(d[86]), "+f"(d[87]), "+f"(d[88]), "+f"(d[89]), "+f"(d[90]), "+f"(d[91]), "+f"(d[92]), "+f"(d[93]), "+f"(d[94]), "+f"(d[95])
    : "l"(da), "l"(db), "r"(sd), "n"(TA), "n"(TB));
}

template<int TA, int TB> __device__ __forceinline__ void wgmma_ss_n8(float* d, uint64_t da, uint64_t db, int sd) {
  asm volatile("{\n.reg .pred p;\nsetp.ne.b32 p, %6, 0;\n"
    "wgmma.mma_async.sync.aligned.m64n8k16.f32.bf16.bf16 {%0, %1, %2, %3}, %4, %5, p, 1, 1, %7, %8;\n}"
    : "+f"(d[0]), "+f"(d[1]), "+f"(d[2]), "+f"(d[3])
    : "l"(da), "l"(db), "r"(sd), "n"(TA), "n"(TB));
}

constexpr int S_ = 2048, D_ = 640, F_ = 1536;

struct Scr {
  uint32_t flag[320 * 8];
  uint32_t epoch[256];
  uint2 cbsb[640];
  bf16 cimg[8 * 6 * 512];
  uint2 st2[8 * S_];
  uint2 modP[8 * 3840];
  bf16 kvT[D_ * S_];
  bf16 x1T[D_ * S_];
  bf16 AT[D_ * S_];
  bf16 ln1[3 * S_];
  bf16 xT[D_ * S_];
  uint4 PP[128 * 3 * 1280];
};
__device__ __align__(1024) Scr g_scr;
__device__ __forceinline__ uint32_t clk() { uint32_t c; asm volatile("mov.u32 %0, %%clock;" : "=r"(c) :: "memory"); return c; }
#define DEVSM 0
#define STAMP(id)
#define STAMPIF(c, id)
constexpr int FL_KV = 0, FL_R = 80, FL_C = 104, FL_X = 112;

constexpr int SM_Z = 1024, SM_EXT = 21504, SM_STAT = 27648, SM_SMALL = 29696, SM_CB = 30720, SM_RING = 34816, SM_TOTAL = SM_RING + 6 * 32768;
constexpr int SMALL_S = 0, SMALL_MOD = 256, SMALL_PV = 512, SMALL_GB = 848, SMALL_DUMMY = 1008, SMALL_E = 1012;
constexpr int JOB_SZ = 8896, JOB_V = 4416, JOB_SK = 8640, R_X = 5 * 32768;
constexpr int K1OFF = 4672, KSZ = 9472, CSZ = KSZ + 4224;
enum { B_U = 0, B_S = 5, B_FB = 10, B_PEER = 20, B_RECV = 24, B_EXT = 28, B_X1 = 29, B_MF = 33, B_XFREE = 36, B_XS0 = 37, B_BOX = 38, B_ST0 = 42,
       B_ST1 = 43, B_GB = 44, B_XC = 45,
       B_F1 = 48, B_E1 = 54, B_EB = 60,
       B_Z = 80, B_K = 85, B_EW = 88, B_ST2 = 94, B_KVS = 98,
       B_XS = 105, B_B = 106, B_X = 112 };
__device__ __forceinline__ uint32_t chan_base(uint32_t sb, int ch) { return sb + SM_RING + (2 + (ch >> 1)) * 32768 + (ch & 1) * CSZ; }
__device__ __forceinline__ uint32_t box_base(uint32_t sb, int cls) {
  return sb + SM_RING + (cls == 0 ? 46080 : cls == 1 ? 4 * 32768 + 14336 : cls == 2 ? 5 * 32768 + 22528 : 5 * 32768);
}

constexpr int XS_LN = SM_RING + 56320 + 8192;
__device__ __forceinline__ uint32_t xs_base(uint32_t sb, int r) { return sb + SM_RING + (r < 2 ? 56320 : R_X + 2048) + 4096 * r; }
__device__ __forceinline__ uint32_t xc_base(uint32_t sb, int r) { return sb + SM_RING + (r < 2 ? 4 * 32768 + 24576 : R_X + 2048) + 4096 * r; }

struct Params { CUtensorMap mX, mS, mWm, mXc, mA, mG, mU, mD, mX1, mO, mO2; };

__device__ __forceinline__ void flag_add(Scr* G, int id) { asm volatile("red.relaxed.gpu.global.add.u32 [%0], 1;" ::"l"(G->flag + 8 * id) : "memory"); }
__device__ __forceinline__ uint32_t rdback(const void* p) { uint32_t v; asm volatile("ld.relaxed.gpu.global.u32 %0, [%1];" : "=r"(v) : "l"(p) : "memory"); return v; }
__device__ __forceinline__ void st_tag(uint2* p, uint32_t v, uint32_t t) { asm volatile("st.relaxed.gpu.global.v2.u32 [%0], {%1, %2};" ::"l"(p), "r"(v), "r"(t) : "memory"); }
__device__ __forceinline__ uint2 ld_tag(const uint2* p) { uint2 v; asm volatile("ld.relaxed.gpu.global.v2.u32 {%0, %1}, [%2];" : "=r"(v.x), "=r"(v.y) : "l"(p) : "memory"); return v; }
__device__ __forceinline__ uint4 ld_tag2(const uint2* p) {
  uint4 v;
  asm volatile("ld.relaxed.gpu.global.v4.u32 {%0, %1, %2, %3}, [%4];" : "=r"(v.x), "=r"(v.y), "=r"(v.z), "=r"(v.w) : "l"(p) : "memory");
  return v;
}
__device__ __forceinline__ void rdwait(uint32_t sb, uint32_t v) { sts32(sb + SM_SMALL + SMALL_DUMMY, v); }
__device__ __forceinline__ void fence_async_s() { asm volatile("fence.proxy.async.shared::cta;" ::: "memory"); }
__device__ __forceinline__ void fence_async_g() { asm volatile("fence.proxy.async.global;" ::: "memory"); }
__device__ __forceinline__ void bulk_done() { asm volatile("cp.async.bulk.commit_group;\n\tcp.async.bulk.wait_group 0;" ::: "memory"); }
__device__ __forceinline__ void flag_wait(Scr* G, int id, uint32_t target) {
  const uint32_t* p = G->flag + 8 * id;
#pragma unroll 1
  for (int i = 0; i < (1 << 20); i++) {
    uint32_t v;
    asm volatile("ld.relaxed.gpu.global.u32 %0, [%1];" : "=r"(v) : "l"(p) : "memory");
    if ((int)(v - target) >= 0) return;
  }
  __trap();
}
__device__ __forceinline__ int ibase(int pb) {
  int w = pb >> 5, g = (pb >> 2) & 7, q = pb & 3;
  return 128 * (g >> 2) + 8 * ((2 * q - ((g >> 1) & 1)) & 7) + 2 * w + (g & 1);
}
__device__ __forceinline__ uint32_t hmul(uint32_t a, uint32_t b) { uint32_t d; asm("mul.rn.bf16x2 %0, %1, %2;" : "=r"(d) : "r"(a), "r"(b)); return d; }
__device__ __forceinline__ uint32_t hadd(uint32_t a, uint32_t b) { uint32_t d; asm("add.rn.bf16x2 %0, %1, %2;" : "=r"(d) : "r"(a), "r"(b)); return d; }
__device__ __forceinline__ uint32_t hsub(uint32_t a, uint32_t b) { uint32_t d; asm("sub.rn.bf16x2 %0, %1, %2;" : "=r"(d) : "r"(a), "r"(b)); return d; }
__device__ __forceinline__ uint32_t hfma(uint32_t a, uint32_t b, uint32_t c) { uint32_t d; asm("fma.rn.bf16x2 %0, %1, %2, %3;" : "=r"(d) : "r"(a), "r"(b), "r"(c)); return d; }
__device__ __forceinline__ uint32_t pack2(float lo, float hi) { uint32_t d; asm("cvt.rn.bf16x2.f32 %0, %1, %2;" : "=r"(d) : "f"(hi), "f"(lo)); return d; }
__device__ __forceinline__ float blo(uint32_t v) { return __uint_as_float(v << 16); }
__device__ __forceinline__ float bhi(uint32_t v) { return __uint_as_float(v & 0xffff0000u); }
__device__ __forceinline__ float rbf(float v) { return blo(pack2(v, 0.f)); }
template <int N> __device__ __forceinline__ void bfly(float* v, int mask, bool up) {
#pragma unroll
  for (int i = 0; i < N / 2; i++) {
    float send = up ? v[i] : v[i + N / 2], keep = up ? v[i + N / 2] : v[i];
    v[i] = keep + __shfl_xor_sync(0xffffffffu, send, mask);
  }
}
__device__ __forceinline__ int mod_col(int idx) {
  if (idx < 40) { int v = (idx >> 1) & 3; return (v == 3 ? 4 : v) * 640 + 128 * (idx >> 3) + 64 * (idx & 1); }
  int l = idx - 40;
  return l < 10 ? 3 * 640 + 64 * l : 5 * 640 + 64 * (l - 10);
}

__device__ __forceinline__ void kv_load(const bf16* gk, const bf16* gv, const bf16* gs, uint32_t sb, int b, int r, int tid) {
  const int row = tid >> 2, t = 64 * (b >> 2) + row, col = 128 * r + 32 * (b & 3);
  const uint32_t a = sb + SM_RING + r * JOB_SZ + row * 64 + (row >> 3) * 16 + (tid & 3) * 16;
  const int o = t * D_ + col + 8 * (tid & 3);
  cp16z(a, gk + (t < 3 ? o : o - 3 * D_), t < 3 ? 0 : 16);
  cp16(a + 2112, gk + o + 29 * D_);
  cp16(a + JOB_V, gv + o);
  cp16(a + JOB_V + 2112, gv + o + 32 * D_);
  if (tid < 12) cp16(a + 4224, gk + o + 61 * D_);
  else if (tid >= 112) cp16(sb + SM_RING + r * JOB_SZ + JOB_SK + 16 * (tid - 112), gs + 4 * col + 8 * (tid - 112));
}
__device__ __forceinline__ void kv_load_w(const bf16* gk, const bf16* gv, const bf16* gs, uint32_t sb, int b, int r, int lane) {
  const int t = 64 * (b >> 2) + (lane >> 2), col = 128 * r + 32 * (b & 3);
  const uint32_t a = sb + SM_RING + r * JOB_SZ + lane * 16;
  const int o = t * D_ + col + 8 * (lane & 3);
  cp16z(a, gk + (t < 3 ? o : o - 3 * D_), t < 3 ? 0 : 16);
#pragma unroll
  for (int i = 1; i < 8; i++) cp16(a + 528 * i, gk + o + (8 * i - 3) * D_);
  if (lane < 12) cp16(a + 4224, gk + o + 61 * D_);
  else if (lane >= 16) cp16(a + JOB_SK - 256, gs + 4 * col + 8 * (lane - 16));
#pragma unroll
  for (int i = 0; i < 8; i++) cp16(a + JOB_V + 528 * i, gv + o + 8 * i * D_);
  cp_arrive(sb + 8 * (B_B + r));
}
__device__ __forceinline__ void kv_job(Scr* G, uint32_t sb, int b, int r, int tid) {
  const int cp = 4 * (tid >> 5) + (tid & 3), tc = (tid >> 2) & 7;
  const uint32_t base = sb + SM_RING + r * JOB_SZ, ka = base + tc * 528 + cp * 4;
  mbar_wait(sb + 8 * (B_B + r), 0);
  STAMPIF(tid == 0, 56 + r);
  const uint4 sk = lds128(base + JOB_SK + 16 * cp);
  const uint32_t s0 = __byte_perm(sk.x, sk.z, 0x5410), s1 = __byte_perm(sk.x, sk.z, 0x7632), s2 = __byte_perm(sk.y, sk.w, 0x5410), s3 = __byte_perm(sk.y, sk.w, 0x7632);
  uint32_t kk[11], o[8];
#pragma unroll
  for (int i = 0; i < 11; i++) kk[i] = lds32(ka + 64 * i + 16 * (i >> 3));
#pragma unroll
  for (int i = 0; i < 8; i++) {
    uint32_t v = lds32(ka + JOB_V + 64 * i);
    uint32_t a = hadd(hadd(hadd(hmul(kk[i], s3), hmul(kk[i + 1], s2)), hmul(kk[i + 2], s1)), hmul(kk[i + 3], s0));
    o[i] = hmul(a, v);
  }
  bf16* dst = G->kvT + (128 * r + 32 * (b & 3) + 2 * cp) * S_ + 2040 - 64 * (b >> 2) - 8 * tc;
  *(uint4*)dst = make_uint4(__byte_perm(o[7], o[6], 0x5410), __byte_perm(o[5], o[4], 0x5410), __byte_perm(o[3], o[2], 0x5410), __byte_perm(o[1], o[0], 0x5410));
  *(uint4*)(dst + S_) = make_uint4(__byte_perm(o[7], o[6], 0x7632), __byte_perm(o[5], o[4], 0x7632), __byte_perm(o[3], o[2], 0x7632), __byte_perm(o[1], o[0], 0x7632));
}
__device__ __forceinline__ void kv_signal(Scr* G, uint32_t sb, int b, int r, int line, bool add) {
  rdwait(sb, rdback(G->kvT + (128 * r + 32 * (b & 3) + line) * S_ + 1984 - 64 * (b >> 2)));
  __syncwarp();
  if (add) flag_add(G, FL_KV + 16 * r + 4 * (b & 3) + (line >> 3));
}
__device__ __forceinline__ void mod_box(Scr* G, uint32_t sb, int b, int cls, uint32_t e1, int tid) {
  float a[4];
  const uint64_t da = mkdesc(box_base(sb, cls), 4096, 1024, 1), db = mkdesc(sb + SM_SMALL + SMALL_S, 16, 128, 0);
  mbar_wait(sb + 8 * (B_BOX + cls), 0);
  wg_fence();
#pragma unroll
  for (int n = 0; n < 5; n++) wgmma_ss_n8<1, 0>(a, da + 128 * n, db + 2 * n, n != 0);
  wg_commit();
  wg_wait<0>();
#pragma unroll
  for (int i = 0; i < 4; i++) asm volatile("" : "+f"(a[i])::"memory");
  if ((tid & 3) == 0) {
    uint2* p = G->modP + (b & 7) * 3840 + mod_col(16 * cls + (b >> 3)) + 16 * (tid >> 5) + ((tid >> 2) & 7);
    st_tag(p, __float_as_uint(a[0]), e1);
    st_tag(p + 8, __float_as_uint(a[2]), e1);
  }
}
__device__ __forceinline__ float sum8(float a) {
  a += __shfl_xor_sync(0xffffffffu, a, 4);
  a += __shfl_xor_sync(0xffffffffu, a, 2);
  a += __shfl_xor_sync(0xffffffffu, a, 1);
  return rbf(a);
}
__device__ __forceinline__ void mod_poll(const uint2* p, int o, uint32_t e1, float& r0, float& r1) {
  uint2 a, c;
#pragma unroll 1
  for (int i = 0;; i++) {
    a = ld_tag(p); c = ld_tag(p + o);
    if (__all_sync(0xffffffffu, a.y == e1 && c.y == e1)) break;
    if (i > (1 << 20)) __trap();
  }
  r0 = sum8(__uint_as_float(a.x)); r1 = sum8(__uint_as_float(c.x));
}
__device__ __forceinline__ float mod_fin(Scr* G, uint32_t sb, int b, int r0, uint32_t e1, int lane) {
  const int v = lane >> 3, c = (v == 3 ? 4 : v) * 640 + 128 * r0;
  float t0, t1;
  mod_poll(G->modP + (lane & 7) * 3840 + c + b, r0 < 4 ? 128 : 3 * 640 + 128 * v - c, e1, t0, t1);
  const float o = (v & 1) ? 1.f : 0.f;
  if ((lane & 7) == 0) {
    sts32(sb + SM_SMALL + SMALL_MOD + 16 * r0 + 4 * v, pack2(t0 + o, t0 + o));
    if (r0 < 4) sts32(sb + SM_SMALL + SMALL_MOD + 16 * r0 + 16 + 4 * v, pack2(t1 + o, t1 + o));
  }
  __syncwarp();
  if (lane == 0) mbar_arrive(sb + 8 * (B_MF + (r0 >> 1)));
  return t1;
}
__device__ __forceinline__ void load_x(const Params& P, uint32_t sb, int b, int h) {
  const uint32_t bar = sb + 8 * (B_X + h);
  mbar_expect(bar, 10240);
  tma5d(sb + SM_RING + R_X + h * 10240, &P.mX, 0, 0, 0, 5 * h, 191 - ibase(b), bar);
}
__device__ __forceinline__ void load_box(const Params& P, uint32_t sb, int b, int cls) {
  const uint32_t bar = sb + 8 * (B_BOX + cls);
  mbar_expect(bar, 10240);
  tma2d(box_base(sb, cls), &P.mWm, mod_col(16 * cls + (b >> 3)), 80 * (b & 7), bar);
}
__device__ __forceinline__ void load_ssm(const Params& P, uint32_t sb, int b, int r) {
  const uint32_t bar = sb + 8 * (B_S + r);
  mbar_expect(bar, 16 * 288);
  tma3d(chan_base(sb, r) + 128, &P.mS, 0, 0, 128 * r + b, bar);
}
__device__ __forceinline__ void k1_job(uint32_t sb, int r, int tid) {
  const uint32_t a0 = chan_base(sb, r) + 128 + 16 * tid + 32 * (tid >> 4);
  mbar_wait(sb + 8 * (B_S + r), 0);
#pragma unroll
  for (int n = 0; n < 2; n++) {
    const uint32_t a = a0 + 2304 * n;
    const uint4 v = lds128(a);
    const uint32_t pv = lds32(a - ((tid & 15) ? 4 : 36));
    sts128(a + K1OFF, make_uint4(__byte_perm(pv, v.x, 0x5432), __byte_perm(v.x, v.y, 0x5432), __byte_perm(v.y, v.z, 0x5432), __byte_perm(v.z, v.w, 0x5432)));
  }
}

__device__ __forceinline__ void pp_send(uint4* p, const float* a, uint32_t tag) {
#pragma unroll
  for (int i = 0; i < 5; i++)
    p[256 * i] = make_uint4(pack2(a[8 * i], a[8 * i + 1]), pack2(a[8 * i + 2], a[8 * i + 3]), pack2(a[8 * i + 4], a[8 * i + 5]), (pack2(a[8 * i + 6], a[8 * i + 7]) & ~1u) | tag);
}
__device__ __forceinline__ void pp_load(uint4* f, const uint4* p) {
#pragma unroll
  for (int i = 0; i < 5; i++) f[i] = ld_tag2((const uint2*)(p + 256 * i));
}
__device__ __forceinline__ void pp_wait(uint4* f, const uint4* p, uint32_t tag) {
  asm volatile("{\n.reg .pred p;\n.reg .b32 t, n;\nmov.b32 n, 0;\n"
               "L0:\nxor.b32 t, %3, %21;\nlop3.b32 t, t, %7, %21, 0xf6;\nlop3.b32 t, t, %11, %21, 0xf6;\nlop3.b32 t, t, %15, %21, 0xf6;\nlop3.b32 t, t, %19, %21, 0xf6;\n"
               "and.b32 t, t, 1;\nsetp.ne.b32 p, t, 0;\nvote.sync.any.pred p, p, 0xffffffff;\n@!p bra.uni L1;\n"
               "ld.relaxed.gpu.global.v4.u32 {%0, %1, %2, %3}, [%20];\nld.relaxed.gpu.global.v4.u32 {%4, %5, %6, %7}, [%20+4096];\n"
               "ld.relaxed.gpu.global.v4.u32 {%8, %9, %10, %11}, [%20+8192];\nld.relaxed.gpu.global.v4.u32 {%12, %13, %14, %15}, [%20+12288];\n"
               "ld.relaxed.gpu.global.v4.u32 {%16, %17, %18, %19}, [%20+16384];\n"
               "add.u32 n, n, 1;\nsetp.lt.u32 p, n, 1000000;\n@p bra.uni L0;\ntrap;\nL1:\n}"
               : "+r"(f[0].x), "+r"(f[0].y), "+r"(f[0].z), "+r"(f[0].w), "+r"(f[1].x), "+r"(f[1].y), "+r"(f[1].z), "+r"(f[1].w), "+r"(f[2].x), "+r"(f[2].y),
                 "+r"(f[2].z), "+r"(f[2].w), "+r"(f[3].x), "+r"(f[3].y), "+r"(f[3].z), "+r"(f[3].w), "+r"(f[4].x), "+r"(f[4].y), "+r"(f[4].z), "+r"(f[4].w)
               : "l"(p), "r"(tag) : "memory");
}
__device__ __forceinline__ void pp_add(float* a, const uint4* f, const uint4* e, bool first) {
#pragma unroll
  for (int i = 0; i < 5; i++) {
    const uint32_t v[4] = {f[i].x, f[i].y, f[i].z, f[i].w}, u[4] = {e[i].x, e[i].y, e[i].z, e[i].w};
#pragma unroll
    for (int j = 0; j < 8; j++) a[8 * i + j] = ((j & 1) ? bhi(v[j >> 1]) : blo(v[j >> 1])) + (!first ? a[8 * i + j] : (j & 1) ? bhi(u[j >> 1]) : blo(u[j >> 1]));
  }
}
__device__ __forceinline__ int out_col(int s, int n) { return 320 * (s & 1) + (n < 4 ? 32 * (s & 6) + 16 * n : 256 + 8 * (s & 6)); }
__device__ __forceinline__ void l2_prefetch(const void* p, int bytes) { asm volatile("cp.async.bulk.prefetch.L2.global [%0], %1;" ::"l"(p), "r"(bytes) : "memory"); }
__device__ __forceinline__ void pf_line(const void* p) { asm volatile("prefetch.global.L2 [%0];" ::"l"(p) : "memory"); }
__device__ __forceinline__ int role(int bx) {
  const int c = bx >> 1, d = c - 36, q = (d * 37) >> 8, k = d - 7 * q;
  const int rank = c < 4 ? 12 + c : c < 36 ? ((c - 4) & 7) * 8 + ((c - 4) >> 3) : (k ? k + 1 : 0) * 8 + 4 + q;
  return 8 * (rank & 15) + 2 * (rank >> 4) + (bx & 1);
}
enum { K_KV, K_SSM, K_BOX, K_PW, K_PD, K_PKV, K_PSSM, K_PBOX, K_W, K_X, K_END = 15 };
#define E(t, bar, kind, r) ((t) << 16 | (bar) << 8 | (kind) << 4 | (r))
#define SCHED E(0, 255, K_KV, 1), E(0, B_B + 0, K_X, 1), E(0, B_B + 1, K_KV, 2), E(0, B_X + 0, K_SSM, 0), E(0, 255, K_SSM, 1), E(0, B_X + 1, K_KV, 3), \
              E(0, B_B + 2, K_BOX, 0), E(0, B_S + 1, K_KV, 4), E(0, B_B + 3, K_SSM, 2), E(0, 255, K_SSM, 3), E(0, B_BOX + 0, K_SSM, 4), E(0, 255, K_PW, 0), \
              E(0, B_B + 4, K_BOX, 1), E(0, B_BOX + 1, K_BOX, 2), E(0, B_BOX + 2, K_BOX, 3), E(0, 255, K_W, 0), E(0, 255, K_W, 1), E(0, 255, K_W, 2), \
              E(0, 255, K_PW, 1), E(0, 255, K_W, 3), E(0, 255, K_PW, 2), E(0, 255, K_W, 4), E(0, 255, K_PW, 3), E(0, 255, K_W, 5), \
              E(0, 255, K_PW, 4), E(0, 255, K_W, 6), E(0, 255, K_W, 7), E(0, 255, K_W, 8), E(0, 255, K_W, 9), E(0, 255, K_W, 10), \
              E(0, 255, K_W, 11), E(0, 255, K_PD, 0), E(0, 255, K_W, 12), E(0, 255, K_PD, 1), E(0, 255, K_W, 13), E(0, 255, K_PD, 2)
#define XPF 0
#define XBOTH 0
#define PL1 12
#define PL2 14
#define SJ(h) (3 * (h))
constexpr uint32_t kSched[] = {SCHED, E(0, 255, K_END, 0)};
struct In { const bf16 *k, *v, *sk, *Wg, *Wu, *Wd, *ss; };
__device__ __forceinline__ void load_w(const Params& P, uint32_t sb, int s, int it) {
  const int st = it % 5;
  mbar_wait(sb + 8 * (B_E1 + st), (it / 5) & 1);
  const uint32_t a = sb + SM_RING + st * 32768 + 8192, fb = sb + 8 * (B_F1 + st);
  mbar_expect(fb, 24576);
#pragma unroll
  for (int j = 0; j < 3; j++) {
    tma2d(a + 8192 * j, &P.mG, 192 * s + 64 * j, 32 * it, fb);
    tma2d(a + 8192 * j + 4096, &P.mU, 192 * s + 64 * j, 32 * it, fb);
  }
}

template <int I> __device__ __forceinline__ int sched_run(const Params& P, const In& in, uint32_t sb, int b, int lane, uint32_t t_0) {
  constexpr uint32_t e = kSched[I];
  constexpr int kind = (e >> 4) & 15, r = e & 15, bar = (e >> 8) & 255;
  if constexpr (kind == K_END) return 0;
  else {
    if constexpr ((e >> 16) != 0) while (clk() - t_0 < (e >> 16));
    if (bar != 255 && (bar != B_BOX + 3 || b < 96)) mbar_wait(sb + 8 * bar, 0);
    if (kind == K_KV) kv_load_w(in.k, in.v, in.sk, sb, b, r, lane);
    else if (kind == K_PKV) {
      const bf16* kvp = (lane < 16 ? in.k : in.v) + (16 * b + (lane & 15)) * D_ + 128 * r;
      pf_line(kvp); pf_line(kvp + 64);
    } else {
      if (elect()) {
        if (kind == K_X) load_x(P, sb, b, 1);
        if (kind == K_SSM) load_ssm(P, sb, b, r);
        if (kind == K_BOX && (r < 3 || b < 96)) {
          if (r == 3) mbar_wait(sb + 8 * B_XFREE, 0);
          load_box(P, sb, b, r);
        }
        if (kind == K_PW) { l2_prefetch(in.Wg + (128 * r + b) * F_, 2 * F_); l2_prefetch(in.Wu + (128 * r + b) * F_, 2 * F_); }
        if (kind == K_PD) l2_prefetch(in.Wd + (512 * r + 4 * b) * D_, 8 * D_);
        if (kind == K_PSSM) l2_prefetch(in.ss + (128 * r + b) * S_, 4096);
        if (kind == K_PBOX && (r < 3 || b < 96)) tma_prefetch2d(&P.mWm, mod_col(16 * r + (b >> 3)), 80 * (b & 7));
        if (kind == K_W) {
          if (r == 0) { mbar_wait(sb + 8 * B_XFREE, 0); mbar_wait(sb + 8 * (B_KVS + 3), 0); STAMP(70); }
          load_w(P, sb, b & 7, r);
        }
      }
      __syncwarp();
    }
    return sched_run<I + 1>(P, in, sb, b, lane, t_0) + (kind == K_W);
  }
}

__global__ void __launch_bounds__(512, 1) fused_kernel(const bf16* __restrict__ gk, const bf16* __restrict__ gv, const bf16* __restrict__ gsk,
                                                       const bf16* __restrict__ gD, const bf16* __restrict__ gc, Scr* G, const bf16* gWg, const bf16* gWu,
                                                       const bf16* gWd, const bf16* gx, const bf16* gss, const __grid_constant__ Params P) {
  extern __shared__ __align__(1024) char smem_raw[];
  const uint32_t sb = smem_u32(smem_raw), ring = sb + SM_RING;
  const int b = role(blockIdx.x), m = b >> 3, s = b & 7;
  const uint32_t t_0 = clk();
  const int wg = __shfl_sync(0xffffffffu, threadIdx.x >> 7, 0);
  const int tid = threadIdx.x & 127, lane = tid & 31;
  const int w = __shfl_sync(0xffffffffu, tid >> 5, 0);
  if (wg < 2) {
    if (threadIdx.x < 128) kv_load(gk, gv, gsk, sb, b, 0, tid);
    else if (tid < XPF) {
      const bf16* p = gx + (191 - ibase(b) + 64 * (tid & 1) + 256 * ((tid >> 1) & 7)) * D_ + 128 * (tid >> 4);
      pf_line(p); pf_line(p + 64);
    }
  } else {
    if (wg == 2) {
      if (tid < 40) {
        int c = tid & 7;
        sts128(chan_base(sb, tid >> 3) + (c < 2 ? 80 + c * K1OFF : KSZ + 4096 + (c - 2) * 16), make_uint4(0, 0, 0, 0));
      }
    }
    if (elect()) {
      const int j = 4 * (3 - wg) + w - 1;
      if (j < 2) asm volatile("prefetch.tensormap [%0];" ::"l"(&P.mS + j) : "memory");
      if (j < 0) {
        mbar_init(sb + 8 * B_X, 1);
        mbar_init(sb + 8 * (B_X + 1), 1);
        fence_async_s();
        load_x(P, sb, b, 0);
        if (XBOTH) load_x(P, sb, b, 1);
      } else {
        const int c = j < 3 ? 1 : j < 5 ? 2 : 4;
#pragma unroll
        for (int i = 0; i < 16; i++) mbar_init(sb + 128 * j + 8 * i, i < 8 || j < 6 ? c : i == 8 ? 5 : i == 9 ? 8 : i == 10 ? 128 : 32);
      }
    }
    fence_async_s();
  }
  __syncthreads();
  STAMPIF(threadIdx.x == 0, 55);

  if (wg == 3) {
    asm volatile("setmaxnreg.dec.sync.aligned.u32 24;");
    if (w < 2) {
     if (w == 0) {
      STAMPIF(lane == 0, 62);
      int it = sched_run<0>(P, In{gk, gv, gsk, gWg, gWu, gWd, gss}, sb, b, lane, __shfl_sync(0xffffffffu, t_0, 0));
      if (elect()) {
        STAMP(69);
#pragma unroll 1
        for (; it < 20; it++) load_w(P, sb, s, it);
#pragma unroll
        for (int k = 0; k < 10; k++) {
          const int st = k == 0 ? 5 : (k - 1) % 5, pe = k < 6 ? k / 3 : k & 1, d = k < 6 ? 2 - (k & 1) : k >> 1;
          mbar_wait(sb + 8 * (k < 6 ? B_E1 + st : B_EB + st), 0);
          mbar_expect(sb + 8 * (B_FB + k), 24576);
          tma2d(ring + st * 32768 + 8192, &P.mD, 320 * (s & 1) + (st > 3 ? 256 : 32 * ((s + 2 * d) & 6)), 192 * (s ^ pe), sb + 8 * (B_FB + k));
        }
      }
     } else {
      const uint32_t e1 = rdback(G->epoch + b) + 1;
      if (lane >= 3 && lane < 11) asm volatile("prefetch.tensormap [%0];" ::"l"(&P.mX + lane) : "memory");
      {
        uint32_t pend = 127;
        const uint32_t* fp = G->flag + 8 * (lane < 5 ? FL_KV + 16 * lane + (b >> 3) : FL_X + lane - 5);
#pragma unroll 1
        for (int i = 0; pend; i++) {
          uint32_t rdy = __ballot_sync(0xffffffffu, ((pend >> lane) & 1) && (int)(rdback(fp) - e1 * (lane < 5 ? 32 : 128)) >= 0);
          pend ^= rdy;
          if (rdy && elect()) {
            fence_async_g();
#pragma unroll 1
            for (uint32_t t = rdy & 31; t; t &= t - 1) {
              const int r = __ffs(t) - 1;
              mbar_expect(sb + 8 * (B_U + r), 4096);
              bulk_g2s(chan_base(sb, r) + KSZ, G->kvT + (128 * r + b) * S_, 4096, sb + 8 * (B_U + r));
              STAMP(40 + r);
            }
            if (rdy & 32) {
              mbar_expect(sb + 8 * B_XC, 16384);
              tma2d(xc_base(sb, 0), &P.mXc, 16 * b, 0, sb + 8 * B_XC);
              bulk_g2s(sb + SM_EXT, G->ln1, 8192, sb + 8 * B_XC);
              bulk_g2s(sb + SM_CB, G->ln1 + 2 * S_, 4096, sb + 8 * B_XC);
              STAMP(83);
            }
            if (rdy & 64) {
              mbar_expect(sb + 8 * (B_XC + 1), 4096);
              tma2d(xc_base(sb, 1), &P.mXc, 16 * (128 + b), 0, sb + 8 * (B_XC + 1));
              mbar_expect(sb + 8 * (B_XC + 2), 12288);
#pragma unroll
              for (int j = 2; j < 5; j++) tma2d(xc_base(sb, j), &P.mXc, 16 * (128 * j + b), 0, sb + 8 * (B_XC + 2));
              STAMP(84);
            }
          }
          __syncwarp();
          if (i > (1 << 20)) __trap();
        }
      }
      if (elect()) {
#pragma unroll 1
        for (int it = 0; it < 20; it++) {
          int st = it % 5;
          if ((it & 3) == 0) { flag_wait(G, FL_R + (it >> 2), e1 * 128); fence_async_g(); STAMP(45 + (it >> 2)); }
          mbar_wait(sb + 8 * (B_E1 + st), (it / 5) & 1);
          uint32_t fb = sb + 8 * (B_F1 + st);
          mbar_expect(fb, 8192);
          tma3d(ring + st * 32768, &P.mA, 0, 32 * it, m * 2, fb);
        }
        G->epoch[b] = e1;
      }
     }
    } else if (w == 2) {
      const uint32_t e1 = rdback(G->epoch + b) + 1;
      if (lane < 4) mbar_expect(sb + 8 * (B_RECV + lane), 12288);
      mbar_wait(sb + 8 * B_XS0, 0);
      bf16* xo = G->xT + b * 10240;
      {
        if (elect()) {
          bulk_s2g(xo, xs_base(sb, 0), 4096);
#pragma unroll
          for (int j = 0; j < 3; j++) bulk_s2g(G->ln1 + j * S_ + 16 * b, sb + XS_LN + 32 * j, 32);
          bulk_done();
        }
        __syncwarp();
        uint32_t v0 = rdback(xo + 64 * lane), v1 = rdback(G->ln1 + (lane % 3) * S_ + 16 * b);
        mbar_wait(sb + 8 * B_XS, 0);
        rdwait(sb, v0 ^ v1);
        __syncwarp();
        if (lane == 0) flag_add(G, FL_X);
        STAMPIF(lane == 0, 71);
        if (elect()) {
          bulk_s2g(xo + 2048, xs_base(sb, 1), 4096);
          bulk_s2g(xo + 4096, xs_base(sb, 2), 12288);
          bulk_done();
          mbar_arrive(sb + 8 * B_XFREE);
        }
        __syncwarp();
        v0 = rdback(xo + 2048 + 64 * lane); v1 = rdback(xo + 4096 + 64 * lane);
        uint32_t v2 = rdback(xo + 6144 + 64 * lane), v3 = rdback(xo + 8192 + 64 * lane);
        rdwait(sb, v0 ^ v1 ^ v2 ^ v3);
        __syncwarp();
        if (lane == 0) flag_add(G, FL_X + 1);
        STAMPIF(lane == 0, 72);
      }
      mod_fin(G, sb, b, 0, e1, lane);
      STAMPIF(lane == 0, 36);
#pragma unroll 1
      for (int r = 0; r < 5; r++) {
        mbar_wait(sb + 8 * (B_EW + r), 0);
        rdwait(sb, rdback(G->AT + (128 * r + b) * S_ + 64 * lane));
        __syncwarp();
        if (elect()) {
          flag_add(G, FL_R + r);
          STAMP(90 + r);
          fence_async_s();
          bulk_s2g(G->x1T + (128 * r + b) * S_, sb + SM_Z + 4096 * r, 4096);
        }
      }
      bulk_done();
      STAMPIF(lane == 0, 95);
      __syncwarp();
      {
        uint32_t v = 0;
#pragma unroll
        for (int r = 0; r < 5; r++) v ^= rdback(G->x1T + (128 * r + b) * S_ + 64 * lane);
        rdwait(sb, v);
        __syncwarp();
      }
      if (elect()) {
        flag_add(G, FL_R + 5);
        STAMP(96);
        flag_wait(G, FL_R + 5, e1 * 128);
        fence_async_g();
        mbar_expect(sb + 8 * B_X1, 20480);
#pragma unroll
        for (int n = 0; n < 5; n++) tma3d(sb + SM_Z + 4096 * n, &P.mX1, 0, out_col(s, n), m * 2, sb + 8 * B_X1);
        STAMP(86);
        flag_wait(G, FL_C + s, e1 * 48);
        fence_async_g();
        STAMP(54);
        mbar_expect(sb + 8 * B_EXT, 6144);
        bulk_g2s(sb + SM_EXT, G->cimg + s * 3072, 6144, sb + 8 * B_EXT);
      }
    } else {
      const uint32_t e1 = rdback(G->epoch + b) + 1;
#pragma unroll 1
      for (int j = 0; j < 4; j++) {
        mbar_wait(sb + 8 * (B_KVS + j), 0);
        kv_signal(G, sb, b, j ? j + 1 : 0, lane, (lane & 7) == 0);
        STAMPIF(lane == 0, j ? 21 + j : 1);
      }
      mod_fin(G, sb, b, 2, e1, lane);
      STAMPIF(lane == 0, 37);
      float t0 = mod_fin(G, sb, b, 4, e1, lane), t1, t2;
      STAMPIF(lane == 0, 38);
      const uint2* p = G->modP + (lane & 7) * 3840;
      mod_poll(p + 3 * 640 + 512 + b, 0, e1, t1, t2);
      mbar_wait(sb + 8 * B_MF, 0);
      if ((lane & 7) == 0 || lane == 1) {
        const int r = lane == 1 ? 4 : lane >> 3;
        st_tag(G->cbsb + 128 * r + b, __byte_perm(lds32(sb + SM_SMALL + SMALL_MOD + 16 * r + 12), __float_as_uint(lane == 1 ? t1 : t0), 0x7610), e1);
      }
      STAMPIF(lane == 0, 39);
#pragma unroll 1
      for (int n = 0; n < 10; n++) {
        mod_poll(p + 5 * 640 + out_col(s, n >> 1) + 8 * (n & 1) + 2 * (lane >> 3), 1, e1, t1, t2);
        if ((lane & 7) == 0) sts32(sb + SM_SMALL + SMALL_GB + 16 * n + (lane >> 1), pack2(t1, t2));
      }
      __syncwarp();
      if (lane == 0) mbar_arrive(sb + 8 * B_GB);
    }
  } else if (wg == 2) {
    asm volatile("setmaxnreg.dec.sync.aligned.u32 40;");
    const uint32_t e1 = rdback(G->epoch + b) + 1;
    if (tid == 0) sts32(sb + SM_SMALL + SMALL_E, e1);
    if (tid < 80) {
      float c = blo(*(const uint16_t*)(gc + 80 * (b & 7) + tid));
      sts16(sb + SM_SMALL + SMALL_S + 2 * tid, pack2(__fdividef(c, 1.f + __expf(-c)), 0.f));
    }
    fence_async_s();
    bar_sync(5, 128);
#pragma unroll 1
    for (int r = 2; r < 5; r++) {
      if (r == 3) { mod_box(G, sb, b, 0, e1, tid); STAMPIF(tid == 0, 27); }
      kv_job(G, sb, b, r, tid);
      __syncwarp();
      if (lane == 0) mbar_arrive(sb + 8 * (B_KVS + r - 1));
    }
#pragma unroll 1
    for (int j = 2; j < 5; j++) {
      k1_job(sb, j, tid);
      __syncwarp();
      if (lane == 0) mbar_arrive(sb + 8 * (B_K + j - 2));
    }
    STAMPIF(tid == 0, 74);
#pragma unroll 1
    for (int r = 0; r < 5; r++) {
      if (r < 3) mbar_wait(sb + 8 * (B_XC + r), 0);
      STAMPIF(tid == 0 && r == 0, 28);
      uint32_t xv[8], hv[8];
#pragma unroll
      for (int n = 0; n < 2; n++) {
        const uint4 x4 = lds128(xc_base(sb, r) + 16 * tid + 2048 * n), m4 = lds128(sb + SM_EXT + 16 * tid + 2048 * n), s4 = lds128(sb + SM_EXT + 4096 + 16 * tid + 2048 * n);
        const uint4 l4 = lds128(sb + SM_CB + 16 * tid + 2048 * n);
        const uint32_t x_[4] = {x4.x, x4.y, x4.z, x4.w}, m_[4] = {m4.x, m4.y, m4.z, m4.w}, s_[4] = {s4.x, s4.y, s4.z, s4.w}, l_[4] = {l4.x, l4.y, l4.z, l4.w};
        if (16 * m == (tid & 112) + 128 * n) sts128(sb + SM_SMALL + SMALL_PV + 16 * (tid & 15), m4);
#pragma unroll
        for (int j = 0; j < 4; j++) {
          const uint32_t d = hsub(x_[j], m_[j]);
          xv[4 * n + j] = x_[j];
          hv[4 * n + j] = hfma(d, s_[j], hmul(d, l_[j]));
        }
      }
      mbar_wait(sb + 8 * (B_MF + (r >> 1)), 0);
      const uint4 md = lds128(sb + SM_SMALL + SMALL_MOD + 16 * r);
      mbar_wait(sb + 8 * (B_Z + r), 0);
      const uint32_t za = sb + SM_Z + r * 4096 + 16 * tid;
      uint4* pa = (uint4*)(G->AT + (128 * r + b) * S_) + tid;
#pragma unroll
      for (int n = 0; n < 2; n++) {
        const uint4 z4 = lds128(za + 2048 * n);
        const uint32_t z_[4] = {z4.x, z4.y, z4.z, z4.w};
        uint32_t o[4];
#pragma unroll
        for (int j = 0; j < 4; j++) o[j] = hadd(xv[4 * n + j], hmul(md.z, hmul(hadd(hmul(hv[4 * n + j], md.y), md.x), z_[j])));
        pa[128 * n] = make_uint4(hmul(o[0], md.w), hmul(o[1], md.w), hmul(o[2], md.w), hmul(o[3], md.w));
        sts128(za + 2048 * n, make_uint4(o[0], o[1], o[2], o[3]));
      }
      __syncwarp();
      if (lane == 0) mbar_arrive(sb + 8 * (B_EW + r));
      STAMPIF(tid == 0, 29 + r);
      if (r == 1) {
        bar_sync(5, 128);
        if (tid == 0) mbar_arrive(sb + 8 * (B_E1 + 4));
      }
      if (r < 2) {
#pragma unroll 1
        for (int cls = r + 1; cls <= 2 * r + 1; cls++)
          if (cls < 3 || b < 96) mod_box(G, sb, b, cls, e1, tid);
        STAMPIF(tid == 0, 73 + 3 * r);
      }
    }
    bar_sync(5, 128);
    STAMPIF(tid == 0, 88);
    float ca[4];
    const int grp = m % 6;
    if (m < 12) {
      if (w == 3 && elect()) {
        mbar_expect(sb + 8 * B_ST0, 40960);
#pragma unroll 1
        for (int c = 0; c < 10; c++)
          tma2d((c < 2 ? sb + SM_EXT : ring + R_X - 8192) + 4096 * c, (grp & 1) ? &P.mU : &P.mG, 192 * s + 64 * (grp >> 1), (m < 6 ? 0 : 320) + 32 * c, sb + 8 * B_ST0);
      }
      if (tid < 80) {
        const uint2* p = G->cbsb + (m < 6 ? 0 : 320) + 4 * tid;
        uint4 a, c;
#pragma unroll 1
        for (int i = 0;; i++) {
          a = ld_tag2(p); c = ld_tag2(p + 2);
          if (a.y == e1 && a.w == e1 && c.y == e1 && c.w == e1) break;
          if (i > (1 << 20)) __trap();
        }
        STAMPIF(tid == 0, 89);
        const uint32_t d = sb + SM_CB + 32 * (tid >> 1) + 8 * (tid & 1);
        sts64(d, __byte_perm(a.x, a.z, 0x5410), __byte_perm(c.x, c.z, 0x5410));
        sts64(d + 16, __byte_perm(a.x, a.z, 0x7632), __byte_perm(c.x, c.z, 0x7632));
      }
      fence_async_s();
      bar_sync(5, 128);
      STAMPIF(tid == 0, 34);
      const uint64_t da = mkdesc(sb + SM_EXT, 4096, 1024, 1), db = mkdesc(sb + SM_CB, 32, 128, 0);
      mbar_wait(sb + 8 * B_ST0, 0);
      STAMPIF(tid == 0, 97);
      wg_fence();
#pragma unroll
      for (int n = 0; n < 20; n++) wgmma_ss_n8<1, 0>(ca, da + 128 * n + (n < 4 ? 0 : (SM_RING + R_X - 8192 - SM_EXT) / 16), db + 4 * n, n != 0);
      wg_commit();
      wg_wait<0>();
#pragma unroll
      for (int i = 0; i < 4; i++) asm volatile("" : "+f"(ca[i])::"memory");
      STAMPIF(tid == 0, 77);
      const int row = (m < 6 ? 0 : 4) + (lane & 3);
      uint16_t* dst = (uint16_t*)G->cimg + s * 3072 + grp * 512 + row * 64 + (lane >> 2);
#pragma unroll
      for (int j = 0; j < 2; j++) {
        const float c1 = __shfl_sync(0xffffffffu, ca[2 * j], lane & 28), c2 = __shfl_sync(0xffffffffu, ca[2 * j + 1], lane & 28);
        const float t = (lane & 2) ? c2 : c1, hi = rbf(t);
        dst[((2 * w + j) ^ row) << 3] = (uint16_t)pack2((lane & 1) ? t - hi : hi, 0.f);
      }
      rdwait(sb, rdback(dst - (lane >> 2) + (((2 * w) ^ row) << 3)));
      __syncwarp();
      if (lane == 0) flag_add(G, FL_C + s);
      STAMPIF(tid == 0, 35);
    }
    {
      const int j = 4 * ((lane >> 2) & 1) + (lane >> 3), row = 32 * w + 8 * (lane & 3) + (lane >> 2);
      bar_sync(5, 128);
      if (tid < 2) mbar_arrive(sb + 8 * (B_E1 + 5));
      const uint4 m4 = lds128(sb + SM_SMALL + SMALL_PV + 64 * w + 16 * (lane & 3));
      const uint32_t m_[4] = {m4.x, m4.y, m4.z, m4.w};
      float a[16];
#pragma unroll
      for (int i = 0; i < 16; i++) a[i] = 0.f;
      const uint32_t xa = sb + SM_Z + (w >> 1) * 2048 + 128 * j + (((4 * (w & 1) + (lane & 3)) ^ j) << 4);
      mbar_wait(sb + 8 * B_X1, 0);
      STAMPIF(tid == 0, 85);
#pragma unroll 2
      for (int n = 0; n < 10; n++) {
        const uint4 x4 = lds128(xa + 1024 * (n & 1) + 2048 * (n & 14));
        const uint32_t x_[4] = {x4.x, x4.y, x4.z, x4.w};
#pragma unroll
        for (int i = 0; i < 4; i++) {
          const float d0 = blo(x_[i]) - blo(m_[i]), d1 = bhi(x_[i]) - bhi(m_[i]);
          a[4 * i] += d0; a[4 * i + 1] += d0 * d0; a[4 * i + 2] += d1; a[4 * i + 3] += d1 * d1;
        }
      }
      bfly<16>(a, 16, lane & 16); bfly<8>(a, 8, lane & 8); bfly<4>(a, 4, lane & 4);
      uint2* p = G->st2 + 1024 * m + row;
      st_tag(p + 128 * s, __float_as_uint(a[0]), (__float_as_uint(a[1]) & ~15u) | (e1 & 15));
      STAMPIF(tid == 0, 87);
      float s1, s2;
#pragma unroll 1
      for (int i = 0;; i++) {
        uint32_t t = 0;
        s1 = 0.f; s2 = 0.f;
#pragma unroll
        for (int n = 0; n < 8; n++) { const uint2 v = ld_tag(p + 128 * n); s1 += __uint_as_float(v.x); s2 += __uint_as_float(v.y); t |= v.y ^ e1; }
        if (!(t & 15)) break;
        if (i > (1 << 20)) __trap();
      }
      const float pv = blo(lds32(sb + SM_SMALL + SMALL_PV + 4 * (row >> 1)) >> (16 * (row & 1)));
      const float mu = s1 * (1.f / D_), var = fmaxf(s2 * (1.f / D_) - mu * mu, 0.f);
      const float sd = rbf(__fsqrt_rn(rbf(rbf(var) + 1e-5f)));
      const uint32_t hm = pack2(-0.5f * (pv + mu), -0.5f * (pv + mu)), hs = pack2(0.5f * sd, 0.5f * sd);
      sts128(sb + SM_STAT + 16 * row, make_uint4(hm, hs, hm, hs));
      fence_async_s();
      __syncwarp();
      if (lane == 0) mbar_arrive(sb + 8 * B_ST2);
      STAMPIF(tid == 0, 21);
    }
  } else {
    if (wg == 0) cp_arrive(sb + 8 * B_B);
    asm volatile("setmaxnreg.inc.sync.aligned.u32 224;");
    STAMPIF(threadIdx.x == 0, 82);
    const int g = lane >> 2, q = lane & 3;
    if (wg == 1) bar_arrive(1, 256);
    uint32_t dv = *(const uint16_t*)(gD + 128 * wg + b);
    {
      const int t2 = threadIdx.x, w2 = 4 * wg + w;
      STAMPIF(t2 == 0, 20);
      if (wg == 0) {
        kv_job(G, sb, b, 0, tid);
        __syncwarp();
        if (lane == 0) mbar_arrive(sb + 8 * B_KVS);
        STAMPIF(t2 == 0, 78);
      }
      mbar_wait(sb + 8 * B_X, 0);
      mbar_wait(sb + 8 * (B_X + 1), 0);
      STAMPIF(t2 == 0, 25);
      const uint32_t xr = ring + R_X + (15 - (t2 >> 4)) * 128;
      float pv = blo(lds32(xr)), s1 = 0.f, s2 = 0.f;
#pragma unroll
      for (int n = 0; n < 5; n++) {
        uint4 v = lds128(xr + 16 * (t2 & 7) + 2048 * ((t2 >> 3) & 1) + 4096 * n);
        uint32_t u[4] = {v.x, v.y, v.z, v.w};
#pragma unroll
        for (int j = 0; j < 4; j++) {
          float a = blo(u[j]) - pv, c = bhi(u[j]) - pv;
          s1 += a + c; s2 += a * a; s2 += c * c;
        }
      }
      uint32_t r[5][4];
      const uint32_t la = ring + R_X + wg * 2048 + (15 - (lane & 15)) * 128 + (((2 * w + (lane >> 4)) ^ (~lane & 7)) << 4);
#pragma unroll
      for (int n = 0; n < 5; n++) ldsm4t(r[n], la + n * 4096);
#pragma unroll
      for (int n = 0; n < 4; n++) sts64(xs_base(sb, n >> 1) + 512 * w2 + 256 * (n & 1) + 8 * lane, r[n >> 1][2 * (n & 1)], r[n >> 1][2 * (n & 1) + 1]);
#pragma unroll
      for (int o = 1; o < 16; o <<= 1) { s1 += __shfl_xor_sync(0xffffffffu, s1, o); s2 += __shfl_xor_sync(0xffffffffu, s2, o); }
      if ((t2 & 15) == 0) {
        float mu = s1 * (1.f / D_), var = fmaxf(s2 * (1.f / D_) - mu * mu, 0.f);
        const uint32_t a = sb + XS_LN + 8 * w + 4 * wg + (lane >> 3);
        sts16(a, pack2(pv + mu, 0.f));
        const float rs = __frcp_rn(rbf(__fsqrt_rn(rbf(rbf(var) + 1e-5f))));
        sts16(a + 32, pack2(rs, 0.f));
        sts16(a + 64, pack2(rs - rbf(rs), 0.f));
      }
      fence_async_s();
      bar_sync(6, 256);
      if (t2 == 0) mbar_arrive(sb + 8 * B_XS0);
      STAMPIF(t2 == 0, 75);
#pragma unroll
      for (int n = 4; n < 10; n++) sts64(xs_base(sb, n >> 1) + 512 * w2 + 256 * (n & 1) + 8 * lane, r[n >> 1][2 * (n & 1)], r[n >> 1][2 * (n & 1) + 1]);
      fence_async_s();
      __syncwarp();
      if (lane == 0) mbar_arrive(sb + 8 * B_XS);
      STAMPIF(t2 == 0, 26);
      if (wg == 1) {
        kv_job(G, sb, b, 1, tid);
        __syncwarp();
        kv_signal(G, sb, b, 1, 8 * w + (lane & 7), lane == 0);
        STAMPIF(tid == 0, 2);
      }
      k1_job(sb, wg, tid);
      bar_sync(3 + wg, 128);
      if (tid < 2) mbar_arrive(sb + 8 * (B_E1 + tid));
      STAMPIF(t2 == 0, 79);
    }
    {
      const int b0 = (g >> 1) & 1, b1 = g >> 2, u = q + 4 * b0 - w;
      const uint32_t fo = 128 + (g & 1) * K1OFF + 288 * b1 + 4 * u, fo0 = fo - (u < 0 ? 32 : 0);
      const uint32_t dsel = (b1 == 0 && u == 0) ? ((g & 1) ? 0x1044 : 0x4410) : 0x4444;
      const bool wrap = b0 && q == 0;
      const int src1 = b0 ? ((lane & 20) | ((q - 1) & 3)) : (lane | 8);
#pragma unroll 1
      for (int ch = wg; ch < 5; ch += 2) {
        const uint32_t base = chan_base(sb, ch);
        if (ch >= 2) { mbar_wait(sb + 8 * (B_K + ch - 2), 0); mbar_wait(sb + 8 * (B_S + ch), 0); }
        const uint32_t fa = base + fo, fa0 = base + fo0;
        uint32_t af[16][4];
#pragma unroll
        for (int j = 0; j < 16; j++) {
          const int o = 64 * (j & 1) + 576 * (j >> 1);
          af[j][0] = lds32(((j & 1) ? fa : fa0) + o); af[j][1] = lds32(fa + o + 128); af[j][2] = lds32(fa + o + 32); af[j][3] = lds32(fa + o + 160);
        }
        af[0][0] = hadd(af[0][0], __byte_perm(dv, 0, dsel));
        if (ch < 3) dv = *(const uint16_t*)(gD + 128 * (ch + 2) + b);
        mbar_wait(sb + 8 * (B_U + ch), 0);
        float acc[128];
        const uint64_t db = mkdesc(base + KSZ, 32, 128, 0);
        bar_sync(1 + wg, 256);
        STAMPIF(tid == 0, 3 + ch);
        wg_fence();
        wgmma_rs_n64<0>(acc + 96, af[0], db + 192, 0);
        wgmma_rs_n192<0>(acc, af[0], db, 0);
        wgmma_rs_n64<0>(acc + 96, af[1], db + 196, 1);
        wgmma_rs_n192<0>(acc, af[1], db + 4, 1);
        wgmma_rs_n32<0>(acc + 96, af[2], db + 224, 1);
        wgmma_rs_n192<0>(acc, af[2], db + 32, 1);
        wgmma_rs_n32<0>(acc + 96, af[3], db + 228, 1);
        wgmma_rs_n192<0>(acc, af[3], db + 36, 1);
        wgmma_rs_n192<0>(acc, af[4], db + 64, 1);
        wgmma_rs_n192<0>(acc, af[5], db + 68, 1);
        wgmma_rs_n160<0>(acc, af[6], db + 96, 1);
        wgmma_rs_n160<0>(acc, af[7], db + 100, 1);
        wgmma_rs_n128<0>(acc, af[8], db + 128, 1);
        wgmma_rs_n128<0>(acc, af[9], db + 132, 1);
        wgmma_rs_n96<0>(acc, af[10], db + 160, 1);
        wgmma_rs_n96<0>(acc, af[11], db + 164, 1);
        bar_arrive(2 - wg, 256);
        wgmma_rs_n64<0>(acc, af[12], db + 192, 1);
        wgmma_rs_n64<0>(acc, af[13], db + 196, 1);
        wgmma_rs_n32<0>(acc, af[14], db + 224, 1);
        wgmma_rs_n32<0>(acc, af[15], db + 228, 1);
        wg_commit();
        wg_wait<0>();
#pragma unroll
        for (int i = 0; i < 128; i++) asm volatile("" : "+f"(acc[i])::"memory");
        bar_sync(3 + wg, 128);
        if (tid == 0) mbar_arrive(sb + 8 * (B_E1 + 2 + (ch >> 1)));
        float S0[33], T[34];
#pragma unroll
        for (int i = 0; i < 31; i++) S0[i] = acc[4 * i] + acc[4 * i + 6];
        S0[31] = acc[124]; S0[32] = 0.f;
#pragma unroll
        for (int i = 0; i < 32; i++) {
          float s1 = i < 31 ? acc[4 * i + 1] + acc[4 * i + 7] : acc[125];
          T[i] = (wrap ? S0[i + 1] : S0[i]) + __shfl_sync(0xffffffffu, s1, src1);
        }
        T[32] = 0.f; T[33] = 0.f;
        uint32_t zz[8];
#pragma unroll
        for (int mu = 0; mu < 8; mu++) {
          float y0 = (b1 ? T[4 * mu + 4] : T[4 * mu]) + __shfl_xor_sync(0xffffffffu, T[4 * mu + 2], 16);
          float y1 = (b1 ? T[4 * mu + 5] : T[4 * mu + 1]) + __shfl_xor_sync(0xffffffffu, T[4 * mu + 3], 16);
          zz[mu] = pack2(y0, y1);
        }
        sts128(sb + SM_Z + ch * 4096 + tid * 32, make_uint4(zz[0], zz[4], zz[1], zz[5]));
        sts128(sb + SM_Z + ch * 4096 + tid * 32 + 16, make_uint4(zz[2], zz[6], zz[3], zz[7]));
        __syncwarp();
        if (lane == 0) mbar_arrive(sb + 8 * (B_Z + ch));
        STAMPIF(tid == 0, 8 + ch);
      }
      if (wg == 1) bar_sync(2, 256);
    }
    uint32_t hh[96];
    {
      float ga[192];
      float* ua = ga + 96;
      const uint64_t da0 = mkdesc(ring + wg * 4096, 4096, 1024, 1), db0 = mkdesc(ring + 8192, 4096, 1024, 1);
      int st = 0, ph = 0;
#pragma unroll 1
      for (int it = 0; it < 20; it++) {
        mbar_wait(sb + 8 * (B_F1 + st), ph);
        STAMPIF(tid == 0 && it == 0, 13 + wg);
        STAMPIF(threadIdx.x == 0, 100 + it);
        const uint64_t da = da0 + st * 2048, db = db0 + st * 2048;
        wg_fence();
        wgmma_ss_n192<1, 1>(ga, da, db, it != 0);
        wgmma_ss_n192<1, 1>(ua, da, db + 768, it != 0);
        wgmma_ss_n192<1, 1>(ga, da + 128, db + 128, 1);
        wgmma_ss_n192<1, 1>(ua, da + 128, db + 128 + 768, 1);
        wg_commit();
        wg_wait<1>();
        if (it > 0 && tid == 0) mbar_arrive(sb + 8 * (B_E1 + (st == 0 ? 4 : st - 1)));
        if (++st == 5) { st = 0; ph ^= 1; }
      }
      STAMPIF(threadIdx.x == 0, 61);
      if (tid == 0) {
        mbar_wait(sb + 8 * (B_E1 + 5), 0);
        mbar_arrive_remote(mapa(sb + 8 * (B_PEER + 2 * wg), (b & 1) ^ 1));
      }
      mbar_wait(sb + 8 * B_EXT, 0);
      mbar_wait(sb + 8 * B_ST2, 0);
      const uint64_t de = mkdesc(sb + SM_EXT, 1024, 0, 1), ds = mkdesc(sb + SM_STAT + wg * 1024, 0, 128, 0);
      wg_fence();
      wgmma_ss_n192<0, 1>(ga, ds, de, 1);
      wgmma_ss_n192<0, 1>(ua, ds, de + 192, 1);
      wg_commit();
      wg_wait<1>();
      if (tid == 0) {
        mbar_arrive(sb + 8 * (B_E1 + 4));
        mbar_arrive_remote(mapa(sb + 8 * (B_PEER + 2 * wg + 1), (b & 1) ^ 1));
      }
      wg_wait<0>();
#pragma unroll
      for (int i = 0; i < 192; i++) asm volatile("" : "+f"(ga[i])::"memory");
      STAMPIF(tid == 0, 15 + wg);
#pragma unroll
      for (int i = 0; i < 48; i++) {
        const int j = 64 * (i >> 4) + 2 * (i & 15);
        hh[i] = pack2(ga[j] * ga[j + 32], ga[j + 1] * ga[j + 33]);
        asm volatile("" : "+r"(hh[i])::"memory");
      }
    }
    float acc[80];
    uint4 pf[15];
    const uint32_t tag = lds32(sb + SM_SMALL + SMALL_E) & 1;
    uint4* const pp[3] = {G->PP + threadIdx.x, G->PP + 128 * 1280 + threadIdx.x, G->PP + 256 * 1280 + threadIdx.x};
    {
      const uint32_t la = ring + wg * 4096 + tid * 16, ra = mapa(la, (b & 1) ^ 1), rb = mapa(sb + 8 * (B_RECV + 2 * wg), (b & 1) ^ 1);
#pragma unroll
      for (int h = 0; h < 16; h++) {
        const int gr = h >> 1, pe = gr < 4 ? gr >> 1 : gr & 1, ac = gr < 4 ? gr & 1 : gr / 6, d = gr < 4 ? ac + 1 : ac + 3;
        if (h == 0) mbar_wait(sb + 8 * B_FB, 0);
        if (h == 4) mbar_wait(sb + 8 * (B_FB + 5), 0);
        if (!(h & 1)) mbar_wait(sb + 8 * (B_FB + gr + (gr < 4 ? 1 : 2)), 0);
        if (gr == 2) {
          mbar_wait(sb + 8 * (B_RECV + 2 * wg + (h & 1)), 0);
#pragma unroll
          for (int j = 6 * (h & 1); j < 6 * (h & 1) + 6; j++) {
            const uint4 v = lds128(la + (j < 2 ? 5 : (j >> 1) - 1) * 32768 + (j & 1) * 2048);
            hh[48 + 4 * j] = v.x; hh[49 + 4 * j] = v.y; hh[50 + 4 * j] = v.z; hh[51 + 4 * j] = v.w;
          }
        }
        STAMPIF(threadIdx.x == 0 && h % 4 == 0, 121 + h / 4);
        const uint64_t db = mkdesc(ring + (gr & 3) * 32768 + 8192, (5 - pe - (gr & 3)) * 32768 + 16 * ((s + 2 * d) & 6), 1024, 1);
        wg_fence();
#pragma unroll
        for (int j = 6 * (h & 1); j < 6 * (h & 1) + 6; j++) wgmma_rs_n80<1>(acc + 40 * ac, hh + 48 * pe + 4 * j, db + 128 * j, pe || j);
        wg_commit();
        if (h < 4) {
#pragma unroll
          for (int j = SJ(h); j < SJ(h + 1); j++) {
            if (j == 0 || j == 10) mbar_wait(sb + 8 * (B_PEER + 2 * wg + j / 10), 0);
            st_async4(ra + (j < 2 ? 5 : (j >> 1) - 1) * 32768 + (j & 1) * 2048, hh + 4 * j, rb + 8 * (j / 6));
          }
          STAMPIF(tid == 0 && h == 3, 81);
        }
        if (h == 2 || h == 4 || h == 6 || h == 8 || h == 12) {
          wg_wait<1>();
          if (h < 12 && tid == 0) mbar_arrive(sb + 8 * (B_EB + gr - 1));
          if (h >= 6) {
            const int i = h == 6 ? 1 : h == 8 ? 2 : 3;
            float* a = acc + 40 * (1 - ac);
#pragma unroll
            for (int j = 0; j < 40; j++) asm volatile("" : "+f"(a[j])::"memory");
            pp_send(pp[i - 1] + ((b & ~6) + ((b + 2 * i) & 6)) * 1280, a, tag);
            STAMPIF(threadIdx.x == 0, 50 + i);
          }
        }
        if (h == 5) bar_sync(3 + wg, 128);
        if (h == PL1) pp_load(pf, pp[0] + b * 1280);
        if (h == PL2) pp_load(pf + 5, pp[1] + b * 1280);
        if (h == 14) wg_wait<1>();
      }
    }
    STAMPIF(tid == 0, 17);
    uint32_t xr[20], gbv[10];
    mbar_wait(sb + 8 * B_X1, 0);
    mbar_wait(sb + 8 * B_GB, 0);
    float rs0 = 2.f * blo(lds32(sb + SM_STAT + (64 * wg + 16 * w + g) * 16 + 4)), rs1 = 2.f * blo(lds32(sb + SM_STAT + (64 * wg + 16 * w + g) * 16 + 132));
    {
      const uint32_t la = sb + SM_Z + wg * 2048 + (8 * (lane >> 4) + (lane & 7)) * 128 + (((2 * w + ((lane >> 3) & 1)) ^ (lane & 7)) << 4);
#pragma unroll
      for (int i = 0; i < 5; i++) ldsm4t(xr + 4 * i, la + i * 4096);
#pragma unroll
      for (int i = 0; i < 10; i++) gbv[i] = lds32(sb + SM_SMALL + SMALL_GB + 16 * i + 4 * q);
    }
    rs0 = __frcp_rn(rs0 * rs0); rs1 = __frcp_rn(rs1 * rs1);
#pragma unroll
    for (int i = 0; i < 3; i++) {
      pp_wait(pf + 5 * i, pp[i] + b * 1280, tag);
      if (i == 1) pp_load(pf + 10, pp[2] + b * 1280);
      STAMPIF(threadIdx.x == 0 && i < 2, 98 + i);
      if (i) pp_add(acc, pf + 5 * i, pf, i == 1);
#pragma unroll
      for (int j = 0; j < 40 && i == 1; j++) asm volatile("" : "+f"(acc[j])::"memory");
    }
#pragma unroll
    for (int i = 0; i < 40; i++) { acc[i] *= (i & 2) ? rs1 : rs0; asm volatile("" : "+f"(acc[i])::"memory"); }
    STAMPIF(threadIdx.x == 0, 125);
    wg_wait<0>();
    float* a = acc + 40;
#pragma unroll
    for (int i = 0; i < 40; i++) asm volatile("" : "+f"(a[i])::"memory");
    STAMPIF(tid == 0, 18);
    uint32_t ov[20];
#pragma unroll
    for (int i = 0; i < 10; i++) {
      ov[2 * i] = hadd(xr[2 * i], hmul(gbv[i], pack2(a[4 * i] * rs0 + acc[4 * i], a[4 * i + 1] * rs0 + acc[4 * i + 1])));
      ov[2 * i + 1] = hadd(xr[2 * i + 1], hmul(gbv[i], pack2(a[4 * i + 2] * rs1 + acc[4 * i + 2], a[4 * i + 3] * rs1 + acc[4 * i + 3])));
    }
    const uint32_t obuf = ring + w * 32768 + wg * 4096;
    const int orow = 15 - (4 * (lane & 2) + 2 * ((lane >> 2) & 3) + (lane & 1));
#pragma unroll
    for (int i = 0; i < 4; i++) stsm4(obuf + orow * 128 + (((lane >> 4) + 2 * i) ^ (orow & 7)) * 16, ov + 4 * i);
    stsm4(obuf + 2048 + orow * 32 + (lane >> 4) * 16, ov + 16);
    fence_async_s();
    __syncwarp();
    if (elect()) {
      const int t = 191 - ibase(8 * m + 4 * wg + w);
      tma_store4d(&P.mO, obuf, out_col(s, 0), 0, 0, t);
      tma_store4d(&P.mO2, obuf + 2048, out_col(s, 4), 0, 0, t);
      asm volatile("cp.async.bulk.commit_group;" ::: "memory");
      asm volatile("cp.async.bulk.wait_group.read 0;" ::: "memory");
    }
  }
}

typedef CUresult (*EncFn)(CUtensorMap*, CUtensorMapDataType, cuuint32_t, void*, const cuuint64_t*, const cuuint64_t*, const cuuint32_t*, const cuuint32_t*,
                          CUtensorMapInterleave, CUtensorMapSwizzle, CUtensorMapL2promotion, CUtensorMapFloatOOBfill);
static void mkmap(EncFn enc, CUtensorMap* m, const void* p, int rank, const cuuint64_t* dims, const cuuint64_t* strides, const cuuint32_t* box, CUtensorMapSwizzle sw) {
  cuuint32_t es[5] = {1, 1, 1, 1, 1};
  CUresult r = enc(m, CU_TENSOR_MAP_DATA_TYPE_BFLOAT16, rank, (void*)p, dims, strides, box, es, CU_TENSOR_MAP_INTERLEAVE_NONE, sw,
                   CU_TENSOR_MAP_L2_PROMOTION_L2_128B, CU_TENSOR_MAP_FLOAT_OOB_FILL_NONE);
  if (r != CUDA_SUCCESS) fprintf(stderr, "tensor map encode failed: %d\n", (int)r);
}

extern "C" void kernel_launch(void* const* d_in, const int* in_sizes, int n_in, void* d_out, int out_size) {
  void* fn = nullptr;
  cudaDriverEntryPointQueryResult qr;
  cudaGetDriverEntryPoint("cuTensorMapEncodeTiled", &fn, cudaEnableDefault, &qr);
  EncFn enc = (EncFn)fn;
  Scr* G;
  cudaGetSymbolAddress((void**)&G, g_scr);
  void *pAT = G->AT, *pX1 = G->x1T;
  Params P;
  { cuuint64_t d[] = {10240, 128}, st[] = {20480}; cuuint32_t bx[] = {16, 128}; mkmap(enc, &P.mXc, G->xT, 2, d, st, bx, CU_TENSOR_MAP_SWIZZLE_NONE); }
  { cuuint64_t d[] = {128, 16, 640}, st[] = {256, 4096}; cuuint32_t bx[] = {144, 16, 1}; mkmap(enc, &P.mS, d_in[4], 3, d, st, bx, CU_TENSOR_MAP_SWIZZLE_NONE); }
  { cuuint64_t d[] = {3840, 640}, st[] = {7680}; cuuint32_t bx[] = {64, 80}; mkmap(enc, &P.mWm, d_in[11], 2, d, st, bx, CU_TENSOR_MAP_SWIZZLE_128B); }
  { cuuint64_t d[] = {64, 640, 32}, st[] = {4096, 128}; cuuint32_t bx[] = {64, 32, 2}; mkmap(enc, &P.mA, pAT, 3, d, st, bx, CU_TENSOR_MAP_SWIZZLE_128B); }
  { cuuint64_t d[] = {64, 640, 32}, st[] = {4096, 128}; cuuint32_t bx[] = {64, 16, 2}; mkmap(enc, &P.mX1, pX1, 3, d, st, bx, CU_TENSOR_MAP_SWIZZLE_128B); }
  { cuuint64_t d[] = {1536, 640}, st[] = {3072}; cuuint32_t bx[] = {64, 32};
    mkmap(enc, &P.mG, d_in[7], 2, d, st, bx, CU_TENSOR_MAP_SWIZZLE_128B); mkmap(enc, &P.mU, d_in[8], 2, d, st, bx, CU_TENSOR_MAP_SWIZZLE_128B); }
  { cuuint64_t d[] = {640, 1536}, st[] = {1280}; cuuint32_t bx[] = {64, 192}; mkmap(enc, &P.mD, d_in[9], 2, d, st, bx, CU_TENSOR_MAP_SWIZZLE_128B); }
  { cuuint64_t d[] = {64, 2, 8, 10, 192}, st[] = {64 * 1280, 256 * 1280, 128, 1280}; cuuint32_t bx[] = {64, 2, 8, 5, 1}; mkmap(enc, &P.mX, d_in[0], 5, d, st, bx, CU_TENSOR_MAP_SWIZZLE_128B); }
  { cuuint64_t d[] = {640, 2, 8, 192}, st[] = {64 * 1280, 256 * 1280, 1280}; cuuint32_t bx[] = {64, 2, 8, 1}, bx2[] = {16, 2, 8, 1};
    mkmap(enc, &P.mO, d_out, 4, d, st, bx, CU_TENSOR_MAP_SWIZZLE_128B); mkmap(enc, &P.mO2, d_out, 4, d, st, bx2, CU_TENSOR_MAP_SWIZZLE_NONE); }
  cudaFuncSetAttribute(fused_kernel, cudaFuncAttributeMaxDynamicSharedMemorySize, SM_TOTAL + DEVSM);
  cudaLaunchConfig_t cfg = {};
  cfg.gridDim = dim3(128); cfg.blockDim = dim3(512); cfg.dynamicSmemBytes = SM_TOTAL + DEVSM; cfg.stream = cudaStreamPerThread;
  cudaLaunchAttribute at[1];
  at[0].id = cudaLaunchAttributeClusterDimension; at[0].val.clusterDim.x = 2; at[0].val.clusterDim.y = 1; at[0].val.clusterDim.z = 1;
  cfg.attrs = at; cfg.numAttrs = 1;
  cudaLaunchKernelEx(&cfg, fused_kernel, (const bf16*)d_in[1], (const bf16*)d_in[2], (const bf16*)d_in[3], (const bf16*)d_in[5], (const bf16*)d_in[10], G,
                     (const bf16*)d_in[7], (const bf16*)d_in[8], (const bf16*)d_in[9], (const bf16*)d_in[0], (const bf16*)d_in[4], P);
}
```

```cpp
#include <cuda_runtime.h>
#include <cuda.h>
#include <cuda_bf16.h>
#include <stdio.h>
#include <stdint.h>
typedef __nv_bfloat16 bf16;
__device__ __forceinline__ uint32_t smem_u32(const void* p) { return (uint32_t)__cvta_generic_to_shared(p); }
__device__ __forceinline__ void mbar_init(uint32_t bar, int cnt) { asm volatile("mbarrier.init.shared::cta.b64 [%0], %1;" ::"r"(bar), "r"(cnt) : "memory"); }
__device__ __forceinline__ void mbar_expect(uint32_t bar, int bytes) { asm volatile("mbarrier.arrive.expect_tx.shared::cta.b64 _, [%0], %1;" ::"r"(bar), "r"(bytes) : "memory"); }
__device__ __forceinline__ void mbar_arrive(uint32_t bar) { asm volatile("mbarrier.arrive.shared::cta.b64 _, [%0];" ::"r"(bar) : "memory"); }
__device__ __forceinline__ void mbar_arrive_remote(uint32_t bar) { asm volatile("mbarrier.arrive.relaxed.cluster.shared::cluster.b64 _, [%0];" ::"r"(bar) : "memory"); }
__device__ __forceinline__ uint32_t mapa(uint32_t a, uint32_t cta) { uint32_t r; asm("mapa.shared::cluster.u32 %0, %1, %2;" : "=r"(r) : "r"(a), "r"(cta)); return r; }
__device__ __forceinline__ bool mbar_try(uint32_t bar, int parity) {
  uint32_t ok;
  asm volatile("{\n.reg .pred p;\nmbarrier.try_wait.parity.shared::cta.b64 p, [%1], %2;\nselp.u32 %0, 1, 0, p;\n}" : "=r"(ok) : "r"(bar), "r"(parity) : "memory");
  return ok;
}
__device__ __forceinline__ void mbar_wait(uint32_t bar, int parity) {
#pragma unroll 1
  for (int i = 0; i < (1 << 20); i++) { if (mbar_try(bar, parity)) return; }
  __trap();
}
__device__ __forceinline__ bool elect() {
  uint32_t p;
  asm volatile("{\n.reg .pred P;\nelect.sync _|P, 0xffffffff;\nselp.u32 %0, 1, 0, P;\n}" : "=r"(p));
  return p;
}
__device__ __forceinline__ void tma2d(uint32_t dst, const CUtensorMap* m, int c0, int c1, uint32_t bar) {
  asm volatile("cp.async.bulk.tensor.2d.shared::cluster.global.mbarrier::complete_tx::bytes [%0], [%1, {%3, %4}], [%2];" ::"r"(dst), "l"(m), "r"(bar), "r"(c0), "r"(c1) : "memory");
}
__device__ __forceinline__ void tma3d(uint32_t dst, const CUtensorMap* m, int c0, int c1, int c2, uint32_t bar) {
  asm volatile("cp.async.bulk.tensor.3d.shared::cluster.global.mbarrier::complete_tx::bytes [%0], [%1, {%3, %4, %5}], [%2];" ::"r"(dst), "l"(m), "r"(bar), "r"(c0), "r"(c1), "r"(c2) : "memory");
}
__device__ __forceinline__ void tma5d(uint32_t dst, const CUtensorMap* m, int c0, int c1, int c2, int c3, int c4, uint32_t bar) {
  asm volatile("cp.async.bulk.tensor.5d.shared::cluster.global.mbarrier::complete_tx::bytes [%0], [%1, {%3, %4, %5, %6, %7}], [%2];" ::"r"(dst), "l"(m), "r"(bar), "r"(c0), "r"(c1), "r"(c2), "r"(c3), "r"(c4) : "memory");
}
__device__ __forceinline__ void tma_store2d(const CUtensorMap* m, uint32_t src, int c0, int c1) {
  asm volatile("cp.async.bulk.tensor.2d.global.shared::cta.bulk_group [%0, {%2, %3}], [%1];" ::"l"(m), "r"(src), "r"(c0), "r"(c1) : "memory");
}
__device__ __forceinline__ void tma_store4d(const CUtensorMap* m, uint32_t src, int c0, int c1, int c2, int c3) {
  asm volatile("cp.async.bulk.tensor.4d.global.shared::cta.bulk_group [%0, {%2, %3, %4, %5}], [%1];" ::"l"(m), "r"(src), "r"(c0), "r"(c1), "r"(c2), "r"(c3) : "memory");
}
__device__ __forceinline__ void tma_prefetch2d(const CUtensorMap* m, int c0, int c1) {
  asm volatile("cp.async.bulk.prefetch.tensor.2d.L2.global [%0, {%1, %2}];" ::"l"(m), "r"(c0), "r"(c1) : "memory");
}
__device__ __forceinline__ void bulk_g2s(uint32_t dst, const void* src, int bytes, uint32_t bar) {
  asm volatile("cp.async.bulk.shared::cluster.global.mbarrier::complete_tx::bytes [%0], [%1], %2, [%3];" ::"r"(dst), "l"(src), "r"(bytes), "r"(bar) : "memory");
}
__device__ __forceinline__ void bulk_s2g(void* dst, uint32_t src, int bytes) {
  asm volatile("cp.async.bulk.global.shared::cta.bulk_group [%0], [%1], %2;" ::"l"(dst), "r"(src), "r"(bytes) : "memory");
}
__device__ __forceinline__ void cp16(uint32_t dst, const void* src) { asm volatile("cp.async.cg.shared.global [%0], [%1], 16;" ::"r"(dst), "l"(src) : "memory"); }
__device__ __forceinline__ void cp16z(uint32_t dst, const void* src, int n) { asm volatile("cp.async.cg.shared.global [%0], [%1], 16, %2;" ::"r"(dst), "l"(src), "r"(n) : "memory"); }
__device__ __forceinline__ void cp_arrive(uint32_t bar) { asm volatile("cp.async.mbarrier.arrive.noinc.shared::cta.b64 [%0];" ::"r"(bar) : "memory"); }
__device__ __forceinline__ void st_async4(uint32_t dst, const uint32_t* v, uint32_t bar) {
  asm volatile("st.async.weak.shared::cluster.mbarrier::complete_tx::bytes.v4.b32 [%0], {%1, %2, %3, %4}, [%5];" ::"r"(dst), "r"(v[0]), "r"(v[1]), "r"(v[2]), "r"(v[3]), "r"(bar) : "memory");
}
__device__ __forceinline__ void wg_fence() { asm volatile("wgmma.fence.sync.aligned;" ::: "memory"); }
__device__ __forceinline__ void wg_commit() { asm volatile("wgmma.commit_group.sync.aligned;" ::: "memory"); }
template <int N> __device__ __forceinline__ void wg_wait() { asm volatile("wgmma.wait_group.sync.aligned %0;" ::"n"(N) : "memory"); }
__device__ __forceinline__ uint64_t mkdesc(uint32_t addr, uint32_t lbo, uint32_t sbo, uint32_t swz) {
  return (uint64_t)((addr & 0x3FFFF) >> 4) | ((uint64_t)(lbo >> 4) << 16) | ((uint64_t)(sbo >> 4) << 32) | ((uint64_t)swz << 62);
}
__device__ __forceinline__ void ldsm4t(uint32_t* r, uint32_t a) {
  asm volatile("ldmatrix.sync.aligned.m8n8.x4.trans.shared.b16 {%0,%1,%2,%3}, [%4];" : "=r"(r[0]), "=r"(r[1]), "=r"(r[2]), "=r"(r[3]) : "r"(a) : "memory");
}
__device__ __forceinline__ void stsm4(uint32_t a, const uint32_t* r) {
  asm volatile("stmatrix.sync.aligned.m8n8.x4.shared.b16 [%0], {%1,%2,%3,%4};" ::"r"(a), "r"(r[0]), "r"(r[1]), "r"(r[2]), "r"(r[3]) : "memory");
}
__device__ __forceinline__ void bar_sync(int id, int n) { asm volatile("bar.sync %0, %1;" ::"r"(id), "r"(n) : "memory"); }
__device__ __forceinline__ void bar_arrive(int id, int n) { asm volatile("bar.arrive %0, %1;" ::"r"(id), "r"(n) : "memory"); }
__device__ __forceinline__ uint32_t lds32(uint32_t a) { uint32_t v; asm volatile("ld.shared.b32 %0, [%1];" : "=r"(v) : "r"(a) : "memory"); return v; }
__device__ __forceinline__ uint2 lds64(uint32_t a) { uint2 v; asm volatile("ld.shared.v2.b32 {%0,%1}, [%2];" : "=r"(v.x), "=r"(v.y) : "r"(a) : "memory"); return v; }
__device__ __forceinline__ uint4 lds128(uint32_t a) { uint4 v; asm volatile("ld.shared.v4.b32 {%0,%1,%2,%3}, [%4];" : "=r"(v.x), "=r"(v.y), "=r"(v.z), "=r"(v.w) : "r"(a) : "memory"); return v; }
__device__ __forceinline__ void sts16(uint32_t a, uint32_t v) { asm volatile("st.shared.b16 [%0], %1;" ::"r"(a), "h"((uint16_t)v) : "memory"); }
__device__ __forceinline__ void sts32(uint32_t a, uint32_t v) { asm volatile("st.shared.b32 [%0], %1;" ::"r"(a), "r"(v) : "memory"); }
__device__ __forceinline__ void sts64(uint32_t a, uint32_t x, uint32_t y) { asm volatile("st.shared.v2.b32 [%0], {%1,%2};" ::"r"(a), "r"(x), "r"(y) : "memory"); }
__device__ __forceinline__ void sts128(uint32_t a, uint4 v) { asm volatile("st.shared.v4.b32 [%0], {%1,%2,%3,%4};" ::"r"(a), "r"(v.x), "r"(v.y), "r"(v.z), "r"(v.w) : "memory"); }
template<int TB> __device__ __forceinline__ void wgmma_rs_n128(float* d, const uint32_t* a, uint64_t db, int sd) {
  asm volatile("{\n.reg .pred p;\nsetp.ne.b32 p, %69, 0;\n"
    "wgmma.mma_async.sync.aligned.m64n128k16.f32.bf16.bf16 {%0, %1, %2, %3, %4, %5, %6, %7, %8, %9, %10, %11, %12, %13, %14, %15, %16, %17, %18, %19, %20, %21, %22, %23, %24, %25, %26, %27, %28, %29, %30, %31, %32, %33, %34, %35, %36, %37, %38, %39, %40, %41, %42, %43, %44, %45, %46, %47, %48, %49, %50, %51, %52, %53, %54, %55, %56, %57, %58, %59, %60, %61, %62, %63}, {%64, %65, %66, %67}, %68, p, 1, 1, %70;\n}"
    : "+f"(d[0]), "+f"(d[1]), "+f"(d[2]), "+f"(d[3]), "+f"(d[4]), "+f"(d[5]), "+f"(d[6]), "+f"(d[7]), "+f"(d[8]), "+f"(d[9]), "+f"(d[10]), "+f"(d[11]), "+f"(d[12]), "+f"(d[13]), "+f"(d[14]), "+f"(d[15]), "+f"(d[16]), "+f"(d[17]), "+f"(d[18]), "+f"(d[19]), "+f"(d[20]), "+f"(d[21]), "+f"(d[22]), "+f"(d[23]), "+f"(d[24]), "+f"(d[25]), "+f"(d[26]), "+f"(d[27]), "+f"(d[28]), "+f"(d[29]), "+f"(d[30]), "+f"(d[31]), "+f"(d[32]), "+f"(d[33]), "+f"(d[34]), "+f"(d[35]), "+f"(d[36]), "+f"(d[37]), "+f"(d[38]), "+f"(d[39]), "+f"(d[40]), "+f"(d[41]), "+f"(d[42]), "+f"(d[43]), "+f"(d[44]), "+f"(d[45]), "+f"(d[46]), "+f"(d[47]), "+f"(d[48]), "+f"(d[49]), "+f"(d[50]), "+f"(d[51]), "+f"(d[52]), "+f"(d[53]), "+f"(d[54]), "+f"(d[55]), "+f"(d[56]), "+f"(d[57]), "+f"(d[58]), "+f"(d[59]), "+f"(d[60]), "+f"(d[61]), "+f"(d[62]), "+f"(d[63])
    : "r"(a[0]), "r"(a[1]), "r"(a[2]), "r"(a[3]), "l"(db), "r"(sd), "n"(TB));
}

template<int TB> __device__ __forceinline__ void wgmma_rs_n160(float* d, const uint32_t* a, uint64_t db, int sd) {
  asm volatile("{\n.reg .pred p;\nsetp.ne.b32 p, %85, 0;\n"
    "wgmma.mma_async.sync.aligned.m64n160k16.f32.bf16.bf16 {%0, %1, %2, %3, %4, %5, %6, %7, %8, %9, %10, %11, %12, %13, %14, %15, %16, %17, %18, %19, %20, %21, %22, %23, %24, %25, %26, %27, %28, %29, %30, %31, %32, %33, %34, %35, %36, %37, %38, %39, %40, %41, %42, %43, %44, %45, %46, %47, %48, %49, %50, %51, %52, %53, %54, %55, %56, %57, %58, %59, %60, %61, %62, %63, %64, %65, %66, %67, %68, %69, %70, %71, %72, %73, %74, %75, %76, %77, %78, %79}, {%80, %81, %82, %83}, %84, p, 1, 1, %86;\n}"
    : "+f"(d[0]), "+f"(d[1]), "+f"(d[2]), "+f"(d[3]), "+f"(d[4]), "+f"(d[5]), "+f"(d[6]), "+f"(d[7]), "+f"(d[8]), "+f"(d[9]), "+f"(d[10]), "+f"(d[11]), "+f"(d[12]), "+f"(d[13]), "+f"(d[14]), "+f"(d[15]), "+f"(d[16]), "+f"(d[17]), "+f"(d[18]), "+f"(d[19]), "+f"(d[20]), "+f"(d[21]), "+f"(d[22]), "+f"(d[23]), "+f"(d[24]), "+f"(d[25]), "+f"(d[26]), "+f"(d[27]), "+f"(d[28]), "+f"(d[29]), "+f"(d[30]), "+f"(d[31]), "+f"(d[32]), "+f"(d[33]), "+f"(d[34]), "+f"(d[35]), "+f"(d[36]), "+f"(d[37]), "+f"(d[38]), "+f"(d[39]), "+f"(d[40]), "+f"(d[41]), "+f"(d[42]), "+f"(d[43]), "+f"(d[44]), "+f"(d[45]), "+f"(d[46]), "+f"(d[47]), "+f"(d[48]), "+f"(d[49]), "+f"(d[50]), "+f"(d[51]), "+f"(d[52]), "+f"(d[53]), "+f"(d[54]), "+f"(d[55]), "+f"(d[56]), "+f"(d[57]), "+f"(d[58]), "+f"(d[59]), "+f"(d[60]), "+f"(d[61]), "+f"(d[62]), "+f"(d[63]), "+f"(d[64]), "+f"(d[65]), "+f"(d[66]), "+f"(d[67]), "+f"(d[68]), "+f"(d[69]), "+f"(d[70]), "+f"(d[71]), "+f"(d[72]), "+f"(d[73]), "+f"(d[74]), "+f"(d[75]), "+f"(d[76]), "+f"(d[77]), "+f"(d[78]), "+f"(d[79])
    : "r"(a[0]), "r"(a[1]), "r"(a[2]), "r"(a[3]), "l"(db), "r"(sd), "n"(TB));
}

template<int TB> __device__ __forceinline__ void wgmma_rs_n192(float* d, const uint32_t* a, uint64_t db, int sd) {
  asm volatile("{\n.reg .pred p;\nsetp.ne.b32 p, %101, 0;\n"
    "wgmma.mma_async.sync.aligned.m64n192k16.f32.bf16.bf16 {%0, %1, %2, %3, %4, %5, %6, %7, %8, %9, %10, %11, %12, %13, %14, %15, %16, %17, %18, %19, %20, %21, %22, %23, %24, %25, %26, %27, %28, %29, %30, %31, %32, %33, %34, %35, %36, %37, %38, %39, %40, %41, %42, %43, %44, %45, %46, %47, %48, %49, %50, %51, %52, %53, %54, %55, %56, %57, %58, %59, %60, %61, %62, %63, %64, %65, %66, %67, %68, %69, %70, %71, %72, %73, %74, %75, %76, %77, %78, %79, %80, %81, %82, %83, %84, %85, %86, %87, %88, %89, %90, %91, %92, %93, %94, %95}, {%96, %97, %98, %99}, %100, p, 1, 1, %102;\n}"
    : "+f"(d[0]), "+f"(d[1]), "+f"(d[2]), "+f"(d[3]), "+f"(d[4]), "+f"(d[5]), "+f"(d[6]), "+f"(d[7]), "+f"(d[8]), "+f"(d[9]), "+f"(d[10]), "+f"(d[11]), "+f"(d[12]), "+f"(d[13]), "+f"(d[14]), "+f"(d[15]), "+f"(d[16]), "+f"(d[17]), "+f"(d[18]), "+f"(d[19]), "+f"(d[20]), "+f"(d[21]), "+f"(d[22]), "+f"(d[23]), "+f"(d[24]), "+f"(d[25]), "+f"(d[26]), "+f"(d[27]), "+f"(d[28]), "+f"(d[29]), "+f"(d[30]), "+f"(d[31]), "+f"(d[32]), "+f"(d[33]), "+f"(d[34]), "+f"(d[35]), "+f"(d[36]), "+f"(d[37]), "+f"(d[38]), "+f"(d[39]), "+f"(d[40]), "+f"(d[41]), "+f"(d[42]), "+f"(d[43]), "+f"(d[44]), "+f"(d[45]), "+f"(d[46]), "+f"(d[47]), "+f"(d[48]), "+f"(d[49]), "+f"(d[50]), "+f"(d[51]), "+f"(d[52]), "+f"(d[53]), "+f"(d[54]), "+f"(d[55]), "+f"(d[56]), "+f"(d[57]), "+f"(d[58]), "+f"(d[59]), "+f"(d[60]), "+f"(d[61]), "+f"(d[62]), "+f"(d[63]), "+f"(d[64]), "+f"(d[65]), "+f"(d[66]), "+f"(d[67]), "+f"(d[68]), "+f"(d[69]), "+f"(d[70]), "+f"(d[71]), "+f"(d[72]), "+f"(d[73]), "+f"(d[74]), "+f"(d[75]), "+f"(d[76]), "+f"(d[77]), "+f"(d[78]), "+f"(d[79]), "+f"(d[80]), "+f"(d[81]), "+f"(d[82]), "+f"(d[83]), "+f"(d[84]), "+f"(d[85]), "+f"(d[86]), "+f"(d[87]), "+f"(d[88]), "+f"(d[89]), "+f"(d[90]), "+f"(d[91]), "+f"(d[92]), "+f"(d[93]), "+f"(d[94]), "+f"(d[95])
    : "r"(a[0]), "r"(a[1]), "r"(a[2]), "r"(a[3]), "l"(db), "r"(sd), "n"(TB));
}

template<int TB> __device__ __forceinline__ void wgmma_rs_n32(float* d, const uint32_t* a, uint64_t db, int sd) {
  asm volatile("{\n.reg .pred p;\nsetp.ne.b32 p, %21, 0;\n"
    "wgmma.mma_async.sync.aligned.m64n32k16.f32.bf16.bf16 {%0, %1, %2, %3, %4, %5, %6, %7, %8, %9, %10, %11, %12, %13, %14, %15}, {%16, %17, %18, %19}, %20, p, 1, 1, %22;\n}"
    : "+f"(d[0]), "+f"(d[1]), "+f"(d[2]), "+f"(d[3]), "+f"(d[4]), "+f"(d[5]), "+f"(d[6]), "+f"(d[7]), "+f"(d[8]), "+f"(d[9]), "+f"(d[10]), "+f"(d[11]), "+f"(d[12]), "+f"(d[13]), "+f"(d[14]), "+f"(d[15])
    : "r"(a[0]), "r"(a[1]), "r"(a[2]), "r"(a[3]), "l"(db), "r"(sd), "n"(TB));
}

template<int TB> __device__ __forceinline__ void wgmma_rs_n64(float* d, const uint32_t* a, uint64_t db, int sd) {
  asm volatile("{\n.reg .pred p;\nsetp.ne.b32 p, %37, 0;\n"
    "wgmma.mma_async.sync.aligned.m64n64k16.f32.bf16.bf16 {%0, %1, %2, %3, %4, %5, %6, %7, %8, %9, %10, %11, %12, %13, %14, %15, %16, %17, %18, %19, %20, %21, %22, %23, %24, %25, %26, %27, %28, %29, %30, %31}, {%32, %33, %34, %35}, %36, p, 1, 1, %38;\n}"
    : "+f"(d[0]), "+f"(d[1]), "+f"(d[2]), "+f"(d[3]), "+f"(d[4]), "+f"(d[5]), "+f"(d[6]), "+f"(d[7]), "+f"(d[8]), "+f"(d[9]), "+f"(d[10]), "+f"(d[11]), "+f"(d[12]), "+f"(d[13]), "+f"(d[14]), "+f"(d[15]), "+f"(d[16]), "+f"(d[17]), "+f"(d[18]), "+f"(d[19]), "+f"(d[20]), "+f"(d[21]), "+f"(d[22]), "+f"(d[23]), "+f"(d[24]), "+f"(d[25]), "+f"(d[26]), "+f"(d[27]), "+f"(d[28]), "+f"(d[29]), "+f"(d[30]), "+f"(d[31])
    : "r"(a[0]), "r"(a[1]), "r"(a[2]), "r"(a[3]), "l"(db), "r"(sd), "n"(TB));
}

template<int TB> __device__ __forceinline__ void wgmma_rs_n80(float* d, const uint32_t* a, uint64_t db, int sd) {
  asm volatile("{\n.reg .pred p;\nsetp.ne.b32 p, %45, 0;\n"
    "wgmma.mma_async.sync.aligned.m64n80k16.f32.bf16.bf16 {%0, %1, %2, %3, %4, %5, %6, %7, %8, %9, %10, %11, %12, %13, %14, %15, %16, %17, %18, %19, %20, %21, %22, %23, %24, %25, %26, %27, %28, %29, %30, %31, %32, %33, %34, %35, %36, %37, %38, %39}, {%40, %41, %42, %43}, %44, p, 1, 1, %46;\n}"
    : "+f"(d[0]), "+f"(d[1]), "+f"(d[2]), "+f"(d[3]), "+f"(d[4]), "+f"(d[5]), "+f"(d[6]), "+f"(d[7]), "+f"(d[8]), "+f"(d[9]), "+f"(d[10]), "+f"(d[11]), "+f"(d[12]), "+f"(d[13]), "+f"(d[14]), "+f"(d[15]), "+f"(d[16]), "+f"(d[17]), "+f"(d[18]), "+f"(d[19]), "+f"(d[20]), "+f"(d[21]), "+f"(d[22]), "+f"(d[23]), "+f"(d[24]), "+f"(d[25]), "+f"(d[26]), "+f"(d[27]), "+f"(d[28]), "+f"(d[29]), "+f"(d[30]), "+f"(d[31]), "+f"(d[32]), "+f"(d[33]), "+f"(d[34]), "+f"(d[35]), "+f"(d[36]), "+f"(d[37]), "+f"(d[38]), "+f"(d[39])
    : "r"(a[0]), "r"(a[1]), "r"(a[2]), "r"(a[3]), "l"(db), "r"(sd), "n"(TB));
}

template<int TB> __device__ __forceinline__ void wgmma_rs_n96(float* d, const uint32_t* a, uint64_t db, int sd) {
  asm volatile("{\n.reg .pred p;\nsetp.ne.b32 p, %53, 0;\n"
    "wgmma.mma_async.sync.aligned.m64n96k16.f32.bf16.bf16 {%0, %1, %2, %3, %4, %5, %6, %7, %8, %9, %10, %11, %12, %13, %14, %15, %16, %17, %18, %19, %20, %21, %22, %23, %24, %25, %26, %27, %28, %29, %30, %31, %32, %33, %34, %35, %36, %37, %38, %39, %40, %41, %42, %43, %44, %45, %46, %47}, {%48, %49, %50, %51}, %52, p, 1, 1, %54;\n}"
    : "+f"(d[0]), "+f"(d[1]), "+f"(d[2]), "+f"(d[3]), "+f"(d[4]), "+f"(d[5]), "+f"(d[6]), "+f"(d[7]), "+f"(d[8]), "+f"(d[9]), "+f"(d[10]), "+f"(d[11]), "+f"(d[12]), "+f"(d[13]), "+f"(d[14]), "+f"(d[15]), "+f"(d[16]), "+f"(d[17]), "+f"(d[18]), "+f"(d[19]), "+f"(d[20]), "+f"(d[21]), "+f"(d[22]), "+f"(d[23]), "+f"(d[24]), "+f"(d[25]), "+f"(d[26]), "+f"(d[27]), "+f"(d[28]), "+f"(d[29]), "+f"(d[30]), "+f"(d[31]), "+f"(d[32]), "+f"(d[33]), "+f"(d[34]), "+f"(d[35]), "+f"(d[36]), "+f"(d[37]), "+f"(d[38]), "+f"(d[39]), "+f"(d[40]), "+f"(d[41]), "+f"(d[42]), "+f"(d[43]), "+f"(d[44]), "+f"(d[45]), "+f"(d[46]), "+f"(d[47])
    : "r"(a[0]), "r"(a[1]), "r"(a[2]), "r"(a[3]), "l"(db), "r"(sd), "n"(TB));
}

template<int TA, int TB> __device__ __forceinline__ void wgmma_ss_n192(float* d, uint64_t da, uint64_t db, int sd) {
  asm volatile("{\n.reg .pred p;\nsetp.ne.b32 p, %98, 0;\n"
    "wgmma.mma_async.sync.aligned.m64n192k16.f32.bf16.bf16 {%0, %1, %2, %3, %4, %5, %6, %7, %8, %9, %10, %11, %12, %13, %14, %15, %16, %17, %18, %19, %20, %21, %22, %23, %24, %25, %26, %27, %28, %29, %30, %31, %32, %33, %34, %35, %36, %37, %38, %39, %40, %41, %42, %43, %44, %45, %46, %47, %48, %49, %50, %51, %52, %53, %54, %55, %56, %57, %58, %59, %60, %61, %62, %63, %64, %65, %66, %67, %68, %69, %70, %71, %72, %73, %74, %75, %76, %77, %78, %79, %80, %81, %82, %83, %84, %85, %86, %87, %88, %89, %90, %91, %92, %93, %94, %95}, %96, %97, p, 1, 1, %99, %100;\n}"
    : "+f"(d[0]), "+f"(d[1]), "+f"(d[2]), "+f"(d[3]), "+f"(d[4]), "+f"(d[5]), "+f"(d[6]), "+f"(d[7]), "+f"(d[8]), "+f"(d[9]), "+f"(d[10]), "+f"(d[11]), "+f"(d[12]), "+f"(d[13]), "+f"(d[14]), "+f"(d[15]), "+f"(d[16]), "+f"(d[17]), "+f"(d[18]), "+f"(d[19]), "+f"(d[20]), "+f"(d[21]), "+f"(d[22]), "+f"(d[23]), "+f"(d[24]), "+f"(d[25]), "+f"(d[26]), "+f"(d[27]), "+f"(d[28]), "+f"(d[29]), "+f"(d[30]), "+f"(d[31]), "+f"(d[32]), "+f"(d[33]), "+f"(d[34]), "+f"(d[35]), "+f"(d[36]), "+f"(d[37]), "+f"(d[38]), "+f"(d[39]), "+f"(d[40]), "+f"(d[41]), "+f"(d[42]), "+f"(d[43]), "+f"(d[44]), "+f"(d[45]), "+f"(d[46]), "+f"(d[47]), "+f"(d[48]), "+f"(d[49]), "+f"(d[50]), "+f"(d[51]), "+f"(d[52]), "+f"(d[53]), "+f"(d[54]), "+f"(d[55]), "+f"(d[56]), "+f"(d[57]), "+f"(d[58]), "+f"(d[59]), "+f"(d[60]), "+f"(d[61]), "+f"(d[62]), "+f"(d[63]), "+f"(d[64]), "+f"(d[65]), "+f"(d[66]), "+f"(d[67]), "+f"(d[68]), "+f"(d[69]), "+f"(d[70]), "+f"(d[71]), "+f"(d[72]), "+f"(d[73]), "+f"(d[74]), "+f"(d[75]), "+f"(d[76]), "+f"(d[77]), "+f"(d[78]), "+f"(d[79]), "+f"(d[80]), "+f"(d[81]), "+f"(d[82]), "+f"(d[83]), "+f"(d[84]), "+f"(d[85]), "+f"(d[86]), "+f"(d[87]), "+f"(d[88]), "+f"(d[89]), "+f"(d[90]), "+f"(d[91]), "+f"(d[92]), "+f"(d[93]), "+f"(d[94]), "+f"(d[95])
    : "l"(da), "l"(db), "r"(sd), "n"(TA), "n"(TB));
}

template<int TA, int TB> __device__ __forceinline__ void wgmma_ss_n8(float* d, uint64_t da, uint64_t db, int sd) {
  asm volatile("{\n.reg .pred p;\nsetp.ne.b32 p, %6, 0;\n"
    "wgmma.mma_async.sync.aligned.m64n8k16.f32.bf16.bf16 {%0, %1, %2, %3}, %4, %5, p, 1, 1, %7, %8;\n}"
    : "+f"(d[0]), "+f"(d[1]), "+f"(d[2]), "+f"(d[3])
    : "l"(da), "l"(db), "r"(sd), "n"(TA), "n"(TB));
}

constexpr int S_ = 2048, D_ = 640, F_ = 1536;

struct Scr {
  uint32_t flag[320 * 8];
  uint32_t epoch[256];
  uint2 cbsb[640];
  bf16 cimg[8 * 6 * 512];
  uint2 st2[8 * S_];
  uint2 modP[8 * 3840];
  bf16 kvT[D_ * S_];
  bf16 x1T[D_ * S_];
  bf16 AT[D_ * S_];
  bf16 ln1[3 * S_];
  bf16 xT[D_ * S_];
  uint4 PP[128 * 3 * 1280];
};
__device__ __align__(1024) Scr g_scr;
__device__ __forceinline__ uint32_t clk() { uint32_t c; asm volatile("mov.u32 %0, %%clock;" : "=r"(c) :: "memory"); return c; }
#define DEVSM 0
#define STAMP(id)
#define STAMPIF(c, id)
constexpr int FL_KV = 0, FL_R = 80, FL_C = 104, FL_X = 112;

constexpr int SM_Z = 1024, SM_EXT = 21504, SM_STAT = 27648, SM_SMALL = 29696, SM_CB = 30720, SM_RING = 34816, SM_TOTAL = SM_RING + 6 * 32768;
constexpr int SMALL_S = 0, SMALL_MOD = 256, SMALL_PV = 512, SMALL_GB = 848, SMALL_DUMMY = 1008, SMALL_E = 1012;
constexpr int JOB_SZ = 8896, JOB_V = 4416, JOB_SK = 8640, R_X = 5 * 32768;
constexpr int K1OFF = 4672, KSZ = 9472, CSZ = KSZ + 4224;
enum { B_U = 0, B_S = 5, B_FB = 10, B_PEER = 20, B_RECV = 24, B_EXT = 28, B_X1 = 29, B_MF = 33, B_XFREE = 36, B_XS0 = 37, B_BOX = 38, B_ST0 = 42,
       B_ST1 = 43, B_GB = 44, B_XC = 45,
       B_F1 = 48, B_E1 = 54, B_EB = 60,
       B_Z = 80, B_K = 85, B_EW = 88, B_ST2 = 94, B_KVS = 98,
       B_XS = 105, B_B = 106, B_X = 112 };
__device__ __forceinline__ uint32_t chan_base(uint32_t sb, int ch) { return sb + SM_RING + (2 + (ch >> 1)) * 32768 + (ch & 1) * CSZ; }
__device__ __forceinline__ uint32_t box_base(uint32_t sb, int cls) {
  return sb + SM_RING + (cls == 0 ? 46080 : cls == 1 ? 4 * 32768 + 14336 : cls == 2 ? 5 * 32768 + 22528 : 5 * 32768);
}

constexpr int XS_LN = SM_RING + 56320 + 8192;
__device__ __forceinline__ uint32_t xs_base(uint32_t sb, int r) { return sb + SM_RING + (r < 2 ? 56320 : R_X + 2048) + 4096 * r; }
__device__ __forceinline__ uint32_t xc_base(uint32_t sb, int r) { return sb + SM_RING + (r < 2 ? 4 * 32768 + 24576 : R_X + 2048) + 4096 * r; }

struct Params { CUtensorMap mX, mS, mWm, mXc, mA, mG, mU, mD, mX1, mO, mO2; };

__device__ __forceinline__ void flag_add(Scr* G, int id) { asm volatile("red.relaxed.gpu.global.add.u32 [%0], 1;" ::"l"(G->flag + 8 * id) : "memory"); }
__device__ __forceinline__ uint32_t rdback(const void* p) { uint32_t v; asm volatile("ld.relaxed.gpu.global.u32 %0, [%1];" : "=r"(v) : "l"(p) : "memory"); return v; }
__device__ __forceinline__ void st_tag(uint2* p, uint32_t v, uint32_t t) { asm volatile("st.relaxed.gpu.global.v2.u32 [%0], {%1, %2};" ::"l"(p), "r"(v), "r"(t) : "memory"); }
__device__ __forceinline__ uint2 ld_tag(const uint2* p) { uint2 v; asm volatile("ld.relaxed.gpu.global.v2.u32 {%0, %1}, [%2];" : "=r"(v.x), "=r"(v.y) : "l"(p) : "memory"); return v; }
__device__ __forceinline__ uint4 ld_tag2(const uint2* p) {
  uint4 v;
  asm volatile("ld.relaxed.gpu.global.v4.u32 {%0, %1, %2, %3}, [%4];" : "=r"(v.x), "=r"(v.y), "=r"(v.z), "=r"(v.w) : "l"(p) : "memory");
  return v;
}
__device__ __forceinline__ void rdwait(uint32_t sb, uint32_t v) { sts32(sb + SM_SMALL + SMALL_DUMMY, v); }
__device__ __forceinline__ void fence_async_s() { asm volatile("fence.proxy.async.shared::cta;" ::: "memory"); }
__device__ __forceinline__ void fence_async_g() { asm volatile("fence.proxy.async.global;" ::: "memory"); }
__device__ __forceinline__ void bulk_done() { asm volatile("cp.async.bulk.commit_group;\n\tcp.async.bulk.wait_group 0;" ::: "memory"); }
__device__ __forceinline__ void flag_wait(Scr* G, int id, uint32_t target) {
  const uint32_t* p = G->flag + 8 * id;
#pragma unroll 1
  for (int i = 0; i < (1 << 20); i++) {
    uint32_t v;
    asm volatile("ld.relaxed.gpu.global.u32 %0, [%1];" : "=r"(v) : "l"(p) : "memory");
    if ((int)(v - target) >= 0) return;
  }
  __trap();
}
__device__ __forceinline__ int ibase(int pb) {
  int w = pb >> 5, g = (pb >> 2) & 7, q = pb & 3;
  return 128 * (g >> 2) + 8 * ((2 * q - ((g >> 1) & 1)) & 7) + 2 * w + (g & 1);
}
__device__ __forceinline__ uint32_t hmul(uint32_t a, uint32_t b) { uint32_t d; asm("mul.rn.bf16x2 %0, %1, %2;" : "=r"(d) : "r"(a), "r"(b)); return d; }
__device__ __forceinline__ uint32_t hadd(uint32_t a, uint32_t b) { uint32_t d; asm("add.rn.bf16x2 %0, %1, %2;" : "=r"(d) : "r"(a), "r"(b)); return d; }
__device__ __forceinline__ uint32_t hsub(uint32_t a, uint32_t b) { uint32_t d; asm("sub.rn.bf16x2 %0, %1, %2;" : "=r"(d) : "r"(a), "r"(b)); return d; }
__device__ __forceinline__ uint32_t hfma(uint32_t a, uint32_t b, uint32_t c) { uint32_t d; asm("fma.rn.bf16x2 %0, %1, %2, %3;" : "=r"(d) : "r"(a), "r"(b), "r"(c)); return d; }
__device__ __forceinline__ uint32_t pack2(float lo, float hi) { uint32_t d; asm("cvt.rn.bf16x2.f32 %0, %1, %2;" : "=r"(d) : "f"(hi), "f"(lo)); return d; }
__device__ __forceinline__ float blo(uint32_t v) { return __uint_as_float(v << 16); }
__device__ __forceinline__ float bhi(uint32_t v) { return __uint_as_float(v & 0xffff0000u); }
__device__ __forceinline__ float rbf(float v) { return blo(pack2(v, 0.f)); }
template <int N> __device__ __forceinline__ void bfly(float* v, int mask, bool up) {
#pragma unroll
  for (int i = 0; i < N / 2; i++) {
    float send = up ? v[i] : v[i + N / 2], keep = up ? v[i + N / 2] : v[i];
    v[i] = keep + __shfl_xor_sync(0xffffffffu, send, mask);
  }
}
__device__ __forceinline__ int mod_col(int idx) {
  if (idx < 40) { int v = (idx >> 1) & 3; return (v == 3 ? 4 : v) * 640 + 128 * (idx >> 3) + 64 * (idx & 1); }
  int l = idx - 40;
  return l < 10 ? 3 * 640 + 64 * l : 5 * 640 + 64 * (l - 10);
}

__device__ __forceinline__ void kv_load(const bf16* gk, const bf16* gv, const bf16* gs, uint32_t sb, int b, int r, int tid) {
  const int row = tid >> 2, t = 64 * (b >> 2) + row, col = 128 * r + 32 * (b & 3);
  const uint32_t a = sb + SM_RING + r * JOB_SZ + row * 64 + (row >> 3) * 16 + (tid & 3) * 16;
  const int o = t * D_ + col + 8 * (tid & 3);
  cp16z(a, gk + (t < 3 ? o : o - 3 * D_), t < 3 ? 0 : 16);
  cp16(a + 2112, gk + o + 29 * D_);
  cp16(a + JOB_V, gv + o);
  cp16(a + JOB_V + 2112, gv + o + 32 * D_);
  if (tid < 12) cp16(a + 4224, gk + o + 61 * D_);
  else if (tid >= 112) cp16(sb + SM_RING + r * JOB_SZ + JOB_SK + 16 * (tid - 112), gs + 4 * col + 8 * (tid - 112));
}
__device__ __forceinline__ void kv_load_w(const bf16* gk, const bf16* gv, const bf16* gs, uint32_t sb, int b, int r, int lane) {
  const int t = 64 * (b >> 2) + (lane >> 2), col = 128 * r + 32 * (b & 3);
  const uint32_t a = sb + SM_RING + r * JOB_SZ + lane * 16;
  const int o = t * D_ + col + 8 * (lane & 3);
  cp16z(a, gk + (t < 3 ? o : o - 3 * D_), t < 3 ? 0 : 16);
#pragma unroll
  for (int i = 1; i < 8; i++) cp16(a + 528 * i, gk + o + (8 * i - 3) * D_);
  if (lane < 12) cp16(a + 4224, gk + o + 61 * D_);
  else if (lane >= 16) cp16(a + JOB_SK - 256, gs + 4 * col + 8 * (lane - 16));
#pragma unroll
  for (int i = 0; i < 8; i++) cp16(a + JOB_V + 528 * i, gv + o + 8 * i * D_);
  cp_arrive(sb + 8 * (B_B + r));
}
__device__ __forceinline__ void kv_job(Scr* G, uint32_t sb, int b, int r, int tid) {
  const int cp = 4 * (tid >> 5) + (tid & 3), tc = (tid >> 2) & 7;
  const uint32_t base = sb + SM_RING + r * JOB_SZ, ka = base + tc * 528 + cp * 4;
  mbar_wait(sb + 8 * (B_B + r), 0);
  STAMPIF(tid == 0, 56 + r);
  const uint4 sk = lds128(base + JOB_SK + 16 * cp);
  const uint32_t s0 = __byte_perm(sk.x, sk.z, 0x5410), s1 = __byte_perm(sk.x, sk.z, 0x7632), s2 = __byte_perm(sk.y, sk.w, 0x5410), s3 = __byte_perm(sk.y, sk.w, 0x7632);
  uint32_t kk[11], o[8];
#pragma unroll
  for (int i = 0; i < 11; i++) kk[i] = lds32(ka + 64 * i + 16 * (i >> 3));
#pragma unroll
  for (int i = 0; i < 8; i++) {
    uint32_t v = lds32(ka + JOB_V + 64 * i);
    uint32_t a = hadd(hadd(hadd(hmul(kk[i], s3), hmul(kk[i + 1], s2)), hmul(kk[i + 2], s1)), hmul(kk[i + 3], s0));
    o[i] = hmul(a, v);
  }
  bf16* dst = G->kvT + (128 * r + 32 * (b & 3) + 2 * cp) * S_ + 2040 - 64 * (b >> 2) - 8 * tc;
  *(uint4*)dst = make_uint4(__byte_perm(o[7], o[6], 0x5410), __byte_perm(o[5], o[4], 0x5410), __byte_perm(o[3], o[2], 0x5410), __byte_perm(o[1], o[0], 0x5410));
  *(uint4*)(dst + S_) = make_uint4(__byte_perm(o[7], o[6], 0x7632), __byte_perm(o[5], o[4], 0x7632), __byte_perm(o[3], o[2], 0x7632), __byte_perm(o[1], o[0], 0x7632));
}
__device__ __forceinline__ void kv_signal(Scr* G, uint32_t sb, int b, int r, int line, bool add) {
  rdwait(sb, rdback(G->kvT + (128 * r + 32 * (b & 3) + line) * S_ + 1984 - 64 * (b >> 2)));
  __syncwarp();
  if (add) flag_add(G, FL_KV + 16 * r + 4 * (b & 3) + (line >> 3));
}
__device__ __forceinline__ void mod_box(Scr* G, uint32_t sb, int b, int cls, uint32_t e1, int tid) {
  float a[4];
  const uint64_t da = mkdesc(box_base(sb, cls), 4096, 1024, 1), db = mkdesc(sb + SM_SMALL + SMALL_S, 16, 128, 0);
  mbar_wait(sb + 8 * (B_BOX + cls), 0);
  wg_fence();
#pragma unroll
  for (int n = 0; n < 5; n++) wgmma_ss_n8<1, 0>(a, da + 128 * n, db + 2 * n, n != 0);
  wg_commit();
  wg_wait<0>();
#pragma unroll
  for (int i = 0; i < 4; i++) asm volatile("" : "+f"(a[i])::"memory");
  if ((tid & 3) == 0) {
    uint2* p = G->modP + (b & 7) * 3840 + mod_col(16 * cls + (b >> 3)) + 16 * (tid >> 5) + ((tid >> 2) & 7);
    st_tag(p, __float_as_uint(a[0]), e1);
    st_tag(p + 8, __float_as_uint(a[2]), e1);
  }
}
__device__ __forceinline__ float sum8(float a) {
  a += __shfl_xor_sync(0xffffffffu, a, 4);
  a += __shfl_xor_sync(0xffffffffu, a, 2);
  a += __shfl_xor_sync(0xffffffffu, a, 1);
  return rbf(a);
}
__device__ __forceinline__ void mod_poll(const uint2* p, int o, uint32_t e1, float& r0, float& r1) {
  uint2 a, c;
#pragma unroll 1
  for (int i = 0;; i++) {
    a = ld_tag(p); c = ld_tag(p + o);
    if (__all_sync(0xffffffffu, a.y == e1 && c.y == e1)) break;
    if (i > (1 << 20)) __trap();
  }
  r0 = sum8(__uint_as_float(a.x)); r1 = sum8(__uint_as_float(c.x));
}
__device__ __forceinline__ float mod_fin(Scr* G, uint32_t sb, int b, int r0, uint32_t e1, int lane) {
  const int v = lane >> 3, c = (v == 3 ? 4 : v) * 640 + 128 * r0;
  float t0, t1;
  mod_poll(G->modP + (lane & 7) * 3840 + c + b, r0 < 4 ? 128 : 3 * 640 + 128 * v - c, e1, t0, t1);
  const float o = (v & 1) ? 1.f : 0.f;
  if ((lane & 7) == 0) {
    sts32(sb + SM_SMALL + SMALL_MOD + 16 * r0 + 4 * v, pack2(t0 + o, t0 + o));
    if (r0 < 4) sts32(sb + SM_SMALL + SMALL_MOD + 16 * r0 + 16 + 4 * v, pack2(t1 + o, t1 + o));
  }
  __syncwarp();
  if (lane == 0) mbar_arrive(sb + 8 * (B_MF + (r0 >> 1)));
  return t1;
}
__device__ __forceinline__ void load_x(const Params& P, uint32_t sb, int b, int h) {
  const uint32_t bar = sb + 8 * (B_X + h);
  mbar_expect(bar, 10240);
  tma5d(sb + SM_RING + R_X + h * 10240, &P.mX, 0, 0, 0, 5 * h, 191 - ibase(b), bar);
}
__device__ __forceinline__ void load_box(const Params& P, uint32_t sb, int b, int cls) {
  const uint32_t bar = sb + 8 * (B_BOX + cls);
  mbar_expect(bar, 10240);
  tma2d(box_base(sb, cls), &P.mWm, mod_col(16 * cls + (b >> 3)), 80 * (b & 7), bar);
}
__device__ __forceinline__ void load_ssm(const Params& P, uint32_t sb, int b, int r) {
  const uint32_t bar = sb + 8 * (B_S + r);
  mbar_expect(bar, 16 * 288);
  tma3d(chan_base(sb, r) + 128, &P.mS, 0, 0, 128 * r + b, bar);
}
__device__ __forceinline__ void k1_job(uint32_t sb, int r, int tid) {
  const uint32_t a0 = chan_base(sb, r) + 128 + 16 * tid + 32 * (tid >> 4);
  mbar_wait(sb + 8 * (B_S + r), 0);
#pragma unroll
  for (int n = 0; n < 2; n++) {
    const uint32_t a = a0 + 2304 * n;
    const uint4 v = lds128(a);
    const uint32_t pv = lds32(a - ((tid & 15) ? 4 : 36));
    sts128(a + K1OFF, make_uint4(__byte_perm(pv, v.x, 0x5432), __byte_perm(v.x, v.y, 0x5432), __byte_perm(v.y, v.z, 0x5432), __byte_perm(v.z, v.w, 0x5432)));
  }
}

__device__ __forceinline__ void pp_send(uint4* p, const float* a, uint32_t tag) {
#pragma unroll
  for (int i = 0; i < 5; i++)
    p[256 * i] = make_uint4(pack2(a[8 * i], a[8 * i + 1]), pack2(a[8 * i + 2], a[8 * i + 3]), pack2(a[8 * i + 4], a[8 * i + 5]), (pack2(a[8 * i + 6], a[8 * i + 7]) & ~1u) | tag);
}
__device__ __forceinline__ void pp_load(uint4* f, const uint4* p) {
#pragma unroll
  for (int i = 0; i < 5; i++) f[i] = ld_tag2((const uint2*)(p + 256 * i));
}
__device__ __forceinline__ void pp_wait(uint4* f, const uint4* p, uint32_t tag) {
  asm volatile("{\n.reg .pred p;\n.reg .b32 t, n;\nmov.b32 n, 0;\n"
               "L0:\nxor.b32 t, %3, %21;\nlop3.b32 t, t, %7, %21, 0xf6;\nlop3.b32 t, t, %11, %21, 0xf6;\nlop3.b32 t, t, %15, %21, 0xf6;\nlop3.b32 t, t, %19, %21, 0xf6;\n"
               "and.b32 t, t, 1;\nsetp.ne.b32 p, t, 0;\nvote.sync.any.pred p, p, 0xffffffff;\n@!p bra.uni L1;\n"
               "ld.relaxed.gpu.global.v4.u32 {%0, %1, %2, %3}, [%20];\nld.relaxed.gpu.global.v4.u32 {%4, %5, %6, %7}, [%20+4096];\n"
               "ld.relaxed.gpu.global.v4.u32 {%8, %9, %10, %11}, [%20+8192];\nld.relaxed.gpu.global.v4.u32 {%12, %13, %14, %15}, [%20+12288];\n"
               "ld.relaxed.gpu.global.v4.u32 {%16, %17, %18, %19}, [%20+16384];\n"
               "add.u32 n, n, 1;\nsetp.lt.u32 p, n, 1000000;\n@p bra.uni L0;\ntrap;\nL1:\n}"
               : "+r"(f[0].x), "+r"(f[0].y), "+r"(f[0].z), "+r"(f[0].w), "+r"(f[1].x), "+r"(f[1].y), "+r"(f[1].z), "+r"(f[1].w), "+r"(f[2].x), "+r"(f[2].y),
                 "+r"(f[2].z), "+r"(f[2].w), "+r"(f[3].x), "+r"(f[3].y), "+r"(f[3].z), "+r"(f[3].w), "+r"(f[4].x), "+r"(f[4].y), "+r"(f[4].z), "+r"(f[4].w)
               : "l"(p), "r"(tag) : "memory");
}
__device__ __forceinline__ void pp_add(float* a, const uint4* f, const uint4* e, bool first) {
#pragma unroll
  for (int i = 0; i < 5; i++) {
    const uint32_t v[4] = {f[i].x, f[i].y, f[i].z, f[i].w}, u[4] = {e[i].x, e[i].y, e[i].z, e[i].w};
#pragma unroll
    for (int j = 0; j < 8; j++) a[8 * i + j] = ((j & 1) ? bhi(v[j >> 1]) : blo(v[j >> 1])) + (!first ? a[8 * i + j] : (j & 1) ? bhi(u[j >> 1]) : blo(u[j >> 1]));
  }
}
__device__ __forceinline__ int out_col(int s, int n) { return 320 * (s & 1) + (n < 4 ? 32 * (s & 6) + 16 * n : 256 + 8 * (s & 6)); }
__device__ __forceinline__ void l2_prefetch(const void* p, int bytes) { asm volatile("cp.async.bulk.prefetch.L2.global [%0], %1;" ::"l"(p), "r"(bytes) : "memory"); }
__device__ __forceinline__ void pf_line(const void* p) { asm volatile("prefetch.global.L2 [%0];" ::"l"(p) : "memory"); }
__device__ __forceinline__ int role(int bx) {
  const int c = bx >> 1, d = c - 36, q = (d * 37) >> 8, k = d - 7 * q;
  const int rank = c < 4 ? 12 + c : c < 36 ? ((c - 4) & 7) * 8 + ((c - 4) >> 3) : (k ? k + 1 : 0) * 8 + 4 + q;
  return 8 * (rank & 15) + 2 * (rank >> 4) + (bx & 1);
}
enum { K_KV, K_SSM, K_BOX, K_PW, K_PD, K_PKV, K_PSSM, K_PBOX, K_W, K_X, K_ST, K_END = 15 };
#define E(t, bar, kind, r) ((t) << 16 | (bar) << 8 | (kind) << 4 | (r))
#define SCHED E(0, 255, K_KV, 1), E(0, B_B + 0, K_X, 1), E(0, B_B + 1, K_KV, 2), E(0, B_X + 0, K_SSM, 0), E(0, 255, K_SSM, 1), E(0, B_X + 1, K_KV, 3), \
              E(0, B_B + 2, K_BOX, 0), E(0, B_S + 1, K_KV, 4), E(0, B_B + 3, K_SSM, 2), E(0, 255, K_SSM, 3), E(0, B_BOX + 0, K_SSM, 4), E(0, 255, K_PW, 0), \
              E(0, B_B + 4, K_BOX, 1), E(0, B_BOX + 1, K_BOX, 2), E(0, B_BOX + 2, K_BOX, 3), E(0, 255, K_W, 0), E(0, 255, K_W, 1), E(0, 255, K_W, 2), \
              E(0, 255, K_PW, 1), E(0, 255, K_W, 3), E(0, 255, K_PW, 2), E(0, 255, K_W, 4), E(0, 255, K_PW, 3), E(0, 255, K_W, 5), \
              E(0, 255, K_PW, 4), E(0, 255, K_W, 6), E(0, 255, K_W, 7), E(0, 255, K_W, 8), E(0, 255, K_ST, 0), E(0, 255, K_ST, 1), \
              E(0, 255, K_ST, 2), E(0, 255, K_W, 9), E(0, 255, K_W, 10), E(0, 255, K_ST, 3), E(0, 255, K_ST, 4), E(0, 255, K_W, 11), \
              E(0, 255, K_PD, 0), E(0, 255, K_W, 12), E(0, 255, K_PD, 1), E(0, 255, K_W, 13), E(0, 255, K_PD, 2)
#define XPF 0
#define XBOTH 0
#define BOXP 0x3021
#define KV1F 1
#define PL1 12
#define PL2 14
#define SJ(h) (3 * (h))
constexpr uint32_t kSched[] = {SCHED, E(0, 255, K_END, 0)};
struct In { const bf16 *k, *v, *sk, *Wg, *Wu, *Wd, *ss; };
__device__ __forceinline__ void load_w(const Params& P, uint32_t sb, int s, int it) {
  const int st = it % 5;
  mbar_wait(sb + 8 * (B_E1 + st), (it / 5) & 1);
  const uint32_t a = sb + SM_RING + st * 32768 + 8192, fb = sb + 8 * (B_F1 + st);
  mbar_expect(fb, 24576);
#pragma unroll
  for (int j = 0; j < 3; j++) {
    tma2d(a + 8192 * j, &P.mG, 192 * s + 64 * j, 32 * it, fb);
    tma2d(a + 8192 * j + 4096, &P.mU, 192 * s + 64 * j, 32 * it, fb);
  }
}

template <int I> __device__ __forceinline__ int sched_run(const Params& P, const In& in, uint32_t sb, int b, int lane, uint32_t t_0) {
  constexpr uint32_t e = kSched[I];
  constexpr int kind = (e >> 4) & 15, r = e & 15, bar = (e >> 8) & 255;
  if constexpr (kind == K_END) return 0;
  else {
    if constexpr ((e >> 16) != 0) while (clk() - t_0 < (e >> 16));
    if (bar != 255 && (bar != B_BOX + 3 || b < 96)) mbar_wait(sb + 8 * bar, 0);
    if (kind == K_KV) kv_load_w(in.k, in.v, in.sk, sb, b, r, lane);
    else if (kind == K_PKV) {
      const bf16* kvp = (lane < 16 ? in.k : in.v) + (16 * b + (lane & 15)) * D_ + 128 * r;
      pf_line(kvp); pf_line(kvp + 64);
    } else {
      if (elect()) {
        if (kind == K_X) load_x(P, sb, b, 1);
        if (kind == K_SSM) load_ssm(P, sb, b, r);
        if (kind == K_BOX && (r < 3 || b < 96)) {
          if (r == 3) mbar_wait(sb + 8 * B_XFREE, 0);
          load_box(P, sb, b, r);
        }
        if (kind == K_PW) { l2_prefetch(in.Wg + (128 * r + b) * F_, 2 * F_); l2_prefetch(in.Wu + (128 * r + b) * F_, 2 * F_); }
        if (kind == K_PD) l2_prefetch(in.Wd + (512 * r + 4 * b) * D_, 8 * D_);
        if (kind == K_PSSM) l2_prefetch(in.ss + (128 * r + b) * S_, 4096);
        if (kind == K_PBOX && (r < 3 || b < 96)) tma_prefetch2d(&P.mWm, mod_col(16 * r + (b >> 3)), 80 * (b & 7));
        if (kind == K_ST && b < 96) {
          const int m = b >> 3, grp = m % 6;
          const uint32_t fb = sb + 8 * (r < 3 ? B_ST0 : B_ST1);
          if (r == 0) mbar_wait(sb + 8 * (B_EW + 4), 0);
          if (r % 3 == 0) mbar_expect(fb, r ? 16384 : 24576);
#pragma unroll
          for (int c = 2 * r; c < 2 * r + 2; c++)
            tma2d(sb + (c < 2 ? SM_EXT : SM_RING + R_X - 8192) + 4096 * c, (grp & 1) ? &P.mU : &P.mG, 192 * (b & 7) + 64 * (grp >> 1), (m < 6 ? 0 : 320) + 32 * c, fb);
        }
        if (kind == K_W) {
          if (r == 0) { mbar_wait(sb + 8 * B_XFREE, 0); mbar_wait(sb + 8 * (B_KVS + 4), 0); STAMP(70); }
          load_w(P, sb, b & 7, r);
        }
      }
      __syncwarp();
    }
    return sched_run<I + 1>(P, in, sb, b, lane, t_0) + (kind == K_W);
  }
}

__global__ void __launch_bounds__(512, 1) fused_kernel(const bf16* __restrict__ gk, const bf16* __restrict__ gv, const bf16* __restrict__ gsk,
                                                       const bf16* __restrict__ gD, const bf16* __restrict__ gc, Scr* G, const bf16* gWg, const bf16* gWu,
                                                       const bf16* gWd, const bf16* gx, const bf16* gss, const __grid_constant__ Params P) {
  extern __shared__ __align__(1024) char smem_raw[];
  const uint32_t sb = smem_u32(smem_raw), ring = sb + SM_RING;
  const int b = role(blockIdx.x), m = b >> 3, s = b & 7;
  const uint32_t t_0 = clk();
  const int wg = __shfl_sync(0xffffffffu, threadIdx.x >> 7, 0);
  const int tid = threadIdx.x & 127, lane = tid & 31;
  const int w = __shfl_sync(0xffffffffu, tid >> 5, 0);
  if (wg < 2) {
    if (threadIdx.x < 128) kv_load(gk, gv, gsk, sb, b, 0, tid);
    else if (tid < XPF) {
      const bf16* p = gx + (191 - ibase(b) + 64 * (tid & 1) + 256 * ((tid >> 1) & 7)) * D_ + 128 * (tid >> 4);
      pf_line(p); pf_line(p + 64);
    }
  } else {
    if (wg == 2) {
      if (tid < 40) {
        int c = tid & 7;
        sts128(chan_base(sb, tid >> 3) + (c < 2 ? 80 + c * K1OFF : KSZ + 4096 + (c - 2) * 16), make_uint4(0, 0, 0, 0));
      }
    }
    if (elect()) {
      const int j = 4 * (3 - wg) + w - 1;
      if (j < 2) asm volatile("prefetch.tensormap [%0];" ::"l"(&P.mS + j) : "memory");
      if (j < 0) {
        mbar_init(sb + 8 * B_X, 1);
        mbar_init(sb + 8 * (B_X + 1), 1);
        fence_async_s();
        load_x(P, sb, b, 0);
        if (XBOTH) load_x(P, sb, b, 1);
      } else {
        const int c = j < 3 ? 1 : j < 5 ? 2 : 4;
#pragma unroll
        for (int i = 0; i < 16; i++) mbar_init(sb + 128 * j + 8 * i, i < 8 || j < 6 ? c : i == 8 ? 5 : i == 9 ? 8 : i == 10 ? 128 : 32);
      }
    }
    fence_async_s();
  }
  __syncthreads();
  STAMPIF(threadIdx.x == 0, 55);

  if (wg == 3) {
    asm volatile("setmaxnreg.dec.sync.aligned.u32 24;");
    if (w < 2) {
     if (w == 0) {
      STAMPIF(lane == 0, 62);
      int it = sched_run<0>(P, In{gk, gv, gsk, gWg, gWu, gWd, gss}, sb, b, lane, __shfl_sync(0xffffffffu, t_0, 0));
      if (elect()) {
        STAMP(69);
#pragma unroll 1
        for (; it < 20; it++) load_w(P, sb, s, it);
#pragma unroll
        for (int k = 0; k < 10; k++) {
          const int st = k == 0 ? 5 : (k - 1) % 5, pe = k < 6 ? k / 3 : k & 1, d = k < 6 ? 2 - (k & 1) : k >> 1;
          mbar_wait(sb + 8 * (k < 6 ? B_E1 + st : B_EB + st), 0);
          mbar_expect(sb + 8 * (B_FB + k), 24576);
          tma2d(ring + st * 32768 + 8192, &P.mD, 320 * (s & 1) + (st > 3 ? 256 : 32 * ((s + 2 * d) & 6)), 192 * (s ^ pe), sb + 8 * (B_FB + k));
        }
      }
     } else {
      const uint32_t e1 = rdback(G->epoch + b) + 1;
      if (lane >= 3 && lane < 11) asm volatile("prefetch.tensormap [%0];" ::"l"(&P.mX + lane) : "memory");
      {
        uint32_t pend = 127;
        const uint32_t* fp = G->flag + 8 * (lane < 5 ? FL_KV + 16 * lane + (b >> 3) : FL_X + lane - 5);
#pragma unroll 1
        for (int i = 0; pend; i++) {
          uint32_t rdy = __ballot_sync(0xffffffffu, ((pend >> lane) & 1) && (int)(rdback(fp) - e1 * (lane < 5 ? 32 : 128)) >= 0);
          pend ^= rdy;
          if (rdy && elect()) {
            fence_async_g();
#pragma unroll 1
            for (uint32_t t = rdy & 31; t; t &= t - 1) {
              const int r = __ffs(t) - 1;
              mbar_expect(sb + 8 * (B_U + r), 4096);
              bulk_g2s(chan_base(sb, r) + KSZ, G->kvT + (128 * r + b) * S_, 4096, sb + 8 * (B_U + r));
              STAMP(40 + r);
            }
            if (rdy & 32) {
              mbar_expect(sb + 8 * B_XC, 16384);
              tma2d(xc_base(sb, 0), &P.mXc, 16 * b, 0, sb + 8 * B_XC);
              bulk_g2s(sb + SM_EXT, G->ln1, 8192, sb + 8 * B_XC);
              bulk_g2s(sb + SM_CB, G->ln1 + 2 * S_, 4096, sb + 8 * B_XC);
              STAMP(83);
            }
            if (rdy & 64) {
              mbar_expect(sb + 8 * (B_XC + 1), 4096);
              tma2d(xc_base(sb, 1), &P.mXc, 16 * (128 + b), 0, sb + 8 * (B_XC + 1));
              mbar_expect(sb + 8 * (B_XC + 2), 12288);
#pragma unroll
              for (int j = 2; j < 5; j++) tma2d(xc_base(sb, j), &P.mXc, 16 * (128 * j + b), 0, sb + 8 * (B_XC + 2));
              STAMP(84);
            }
          }
          __syncwarp();
          if (i > (1 << 20)) __trap();
        }
      }
      if (elect()) {
#pragma unroll 1
        for (int it = 0; it < 20; it++) {
          int st = it % 5;
          if ((it & 3) == 0) { flag_wait(G, FL_R + (it >> 2), e1 * 128); fence_async_g(); STAMP(45 + (it >> 2)); }
          mbar_wait(sb + 8 * (B_E1 + st), (it / 5) & 1);
          uint32_t fb = sb + 8 * (B_F1 + st);
          mbar_expect(fb, 8192);
          tma3d(ring + st * 32768, &P.mA, 0, 32 * it, m * 2, fb);
        }
        G->epoch[b] = e1;
      }
     }
    } else if (w == 2) {
      const uint32_t e1 = rdback(G->epoch + b) + 1;
      if (lane < 4) mbar_expect(sb + 8 * (B_RECV + lane), 12288);
      mbar_wait(sb + 8 * B_XS0, 0);
      bf16* xo = G->xT + b * 10240;
      {
        if (elect()) {
          bulk_s2g(xo, xs_base(sb, 0), 4096);
#pragma unroll
          for (int j = 0; j < 3; j++) bulk_s2g(G->ln1 + j * S_ + 16 * b, sb + XS_LN + 32 * j, 32);
          bulk_done();
        }
        __syncwarp();
        uint32_t v0 = rdback(xo + 64 * lane), v1 = rdback(G->ln1 + (lane % 3) * S_ + 16 * b);
        mbar_wait(sb + 8 * B_XS, 0);
        rdwait(sb, v0 ^ v1);
        __syncwarp();
        if (lane == 0) flag_add(G, FL_X);
        STAMPIF(lane == 0, 71);
        if (elect()) {
          bulk_s2g(xo + 2048, xs_base(sb, 1), 4096);
          bulk_s2g(xo + 4096, xs_base(sb, 2), 12288);
          bulk_done();
          mbar_arrive(sb + 8 * B_XFREE);
        }
        __syncwarp();
        v0 = rdback(xo + 2048 + 64 * lane); v1 = rdback(xo + 4096 + 64 * lane);
        uint32_t v2 = rdback(xo + 6144 + 64 * lane), v3 = rdback(xo + 8192 + 64 * lane);
        rdwait(sb, v0 ^ v1 ^ v2 ^ v3);
        __syncwarp();
        if (lane == 0) flag_add(G, FL_X + 1);
        STAMPIF(lane == 0, 72);
      }
      mod_fin(G, sb, b, 0, e1, lane);
      STAMPIF(lane == 0, 36);
#pragma unroll 1
      for (int r = 0; r < 5; r++) {
        mbar_wait(sb + 8 * (B_EW + r), 0);
        rdwait(sb, rdback(G->AT + (128 * r + b) * S_ + 64 * lane) ^ rdback(G->x1T + (128 * r + b) * S_ + 64 * lane));
        __syncwarp();
        if (lane == 0) flag_add(G, FL_R + r);
        STAMPIF(lane == 0, 90 + r);
      }
      if (elect()) {
        flag_wait(G, FL_R + 4, e1 * 128);
        fence_async_g();
        mbar_expect(sb + 8 * B_X1, 20480);
#pragma unroll
        for (int n = 0; n < 5; n++) tma3d(sb + SM_Z + 4096 * n, &P.mX1, 0, out_col(s, n), m * 2, sb + 8 * B_X1);
        STAMP(86);
        flag_wait(G, FL_C + s, e1 * 48);
        fence_async_g();
        STAMP(54);
        mbar_expect(sb + 8 * B_EXT, 6144);
        bulk_g2s(sb + SM_EXT, G->cimg + s * 3072, 6144, sb + 8 * B_EXT);
      }
    } else {
      const uint32_t e1 = rdback(G->epoch + b) + 1;
#pragma unroll 1
      for (int j = 0; j < 5; j++) {
        if (!KV1F && j == 1) continue;
        mbar_wait(sb + 8 * (B_KVS + j), 0);
        kv_signal(G, sb, b, j, lane, (lane & 7) == 0);
        STAMPIF(lane == 0, j > 1 ? 20 + j : 1 + j);
      }
      mod_fin(G, sb, b, 2, e1, lane);
      STAMPIF(lane == 0, 37);
      float t0 = mod_fin(G, sb, b, 4, e1, lane), t1, t2;
      STAMPIF(lane == 0, 38);
      const uint2* p = G->modP + (lane & 7) * 3840;
      mod_poll(p + 3 * 640 + 512 + b, 0, e1, t1, t2);
      mbar_wait(sb + 8 * B_MF, 0);
      if ((lane & 7) == 0 || lane == 1) {
        const int r = lane == 1 ? 4 : lane >> 3;
        st_tag(G->cbsb + 128 * r + b, __byte_perm(lds32(sb + SM_SMALL + SMALL_MOD + 16 * r + 12), __float_as_uint(lane == 1 ? t1 : t0), 0x7610), e1);
      }
      STAMPIF(lane == 0, 39);
#pragma unroll 1
      for (int n = 0; n < 10; n++) {
        mod_poll(p + 5 * 640 + out_col(s, n >> 1) + 8 * (n & 1) + 2 * (lane >> 3), 1, e1, t1, t2);
        if ((lane & 7) == 0) sts32(sb + SM_SMALL + SMALL_GB + 16 * n + (lane >> 1), pack2(t1, t2));
      }
      __syncwarp();
      if (lane == 0) mbar_arrive(sb + 8 * B_GB);
    }
  } else if (wg == 2) {
    asm volatile("setmaxnreg.dec.sync.aligned.u32 40;");
    const uint32_t e1 = rdback(G->epoch + b) + 1;
    if (tid == 0) sts32(sb + SM_SMALL + SMALL_E, e1);
    if (tid < 80) {
      float c = blo(*(const uint16_t*)(gc + 80 * (b & 7) + tid));
      sts16(sb + SM_SMALL + SMALL_S + 2 * tid, pack2(__fdividef(c, 1.f + __expf(-c)), 0.f));
    }
    fence_async_s();
    bar_sync(5, 128);
#pragma unroll 1
    for (int r = 2; r < 5; r++) {
      if (r == 3) { mod_box(G, sb, b, 0, e1, tid); STAMPIF(tid == 0, 27); }
      kv_job(G, sb, b, r, tid);
      __syncwarp();
      if (lane == 0) mbar_arrive(sb + 8 * (B_KVS + r));
    }
#pragma unroll 1
    for (int j = 2; j < 5; j++) {
      k1_job(sb, j, tid);
      __syncwarp();
      if (lane == 0) mbar_arrive(sb + 8 * (B_K + j - 2));
    }
    STAMPIF(tid == 0, 74);
#pragma unroll 1
    for (int r = 0; r < 5; r++) {
#pragma unroll 1
      for (int c = (BOXP >> 4 * r) & 15; c; c >>= 2) {
        if ((c & 3) < 3 || b < 96) mod_box(G, sb, b, c & 3, e1, tid);
        STAMPIF(tid == 0, (c & 3) == 1 ? 73 : (c & 3) == 2 ? 76 : 95);
      }
      if (r < 3) mbar_wait(sb + 8 * (B_XC + r), 0);
      STAMPIF(tid == 0 && r == 0, 28);
      uint32_t xv[8], hv[8];
#pragma unroll
      for (int n = 0; n < 2; n++) {
        const uint4 x4 = lds128(xc_base(sb, r) + 16 * tid + 2048 * n), m4 = lds128(sb + SM_EXT + 16 * tid + 2048 * n), s4 = lds128(sb + SM_EXT + 4096 + 16 * tid + 2048 * n);
        const uint4 l4 = lds128(sb + SM_CB + 16 * tid + 2048 * n);
        const uint32_t x_[4] = {x4.x, x4.y, x4.z, x4.w}, m_[4] = {m4.x, m4.y, m4.z, m4.w}, s_[4] = {s4.x, s4.y, s4.z, s4.w}, l_[4] = {l4.x, l4.y, l4.z, l4.w};
        if (16 * m == (tid & 112) + 128 * n) sts128(sb + SM_SMALL + SMALL_PV + 16 * (tid & 15), m4);
#pragma unroll
        for (int j = 0; j < 4; j++) {
          const uint32_t d = hsub(x_[j], m_[j]);
          xv[4 * n + j] = x_[j];
          hv[4 * n + j] = hfma(d, s_[j], hmul(d, l_[j]));
        }
      }
      mbar_wait(sb + 8 * (B_MF + (r >> 1)), 0);
      const uint4 md = lds128(sb + SM_SMALL + SMALL_MOD + 16 * r);
      mbar_wait(sb + 8 * (B_Z + r), 0);
      const uint32_t za = sb + SM_Z + r * 4096 + 16 * tid;
      uint4* pa = (uint4*)(G->AT + (128 * r + b) * S_) + tid;
#pragma unroll
      for (int n = 0; n < 2; n++) {
        const uint4 z4 = lds128(za + 2048 * n);
        const uint32_t z_[4] = {z4.x, z4.y, z4.z, z4.w};
        uint32_t o[4];
#pragma unroll
        for (int j = 0; j < 4; j++) o[j] = hadd(xv[4 * n + j], hmul(md.z, hmul(hadd(hmul(hv[4 * n + j], md.y), md.x), z_[j])));
        pa[128 * n] = make_uint4(hmul(o[0], md.w), hmul(o[1], md.w), hmul(o[2], md.w), hmul(o[3], md.w));
        pa[128 * n - D_ * S_ / 8] = make_uint4(o[0], o[1], o[2], o[3]);
      }
      __syncwarp();
      if (lane == 0) mbar_arrive(sb + 8 * (B_EW + r));
      STAMPIF(tid == 0, 29 + r);
      if (r == 1) {
        bar_sync(5, 128);
        if (tid == 0) mbar_arrive(sb + 8 * (B_E1 + 4));
      }
    }
    bar_sync(5, 128);
    STAMPIF(tid == 0, 88);
    float ca[4];
    const int grp = m % 6;
    if (m < 12) {
      if (tid < 80) {
        const uint2* p = G->cbsb + (m < 6 ? 0 : 320) + 4 * tid;
        uint4 a, c;
#pragma unroll 1
        for (int i = 0;; i++) {
          a = ld_tag2(p); c = ld_tag2(p + 2);
          if (a.y == e1 && a.w == e1 && c.y == e1 && c.w == e1) break;
          if (i > (1 << 20)) __trap();
        }
        STAMPIF(tid == 0, 89);
        const uint32_t d = sb + SM_CB + 32 * (tid >> 1) + 8 * (tid & 1);
        sts64(d, __byte_perm(a.x, a.z, 0x5410), __byte_perm(c.x, c.z, 0x5410));
        sts64(d + 16, __byte_perm(a.x, a.z, 0x7632), __byte_perm(c.x, c.z, 0x7632));
      }
      fence_async_s();
      bar_sync(5, 128);
      STAMPIF(tid == 0, 34);
      const uint64_t da = mkdesc(sb + SM_EXT, 4096, 1024, 1), db = mkdesc(sb + SM_CB, 32, 128, 0);
      mbar_wait(sb + 8 * B_ST0, 0);
      STAMPIF(tid == 0, 97);
      wg_fence();
#pragma unroll
      for (int n = 0; n < 20; n++) {
        if (n == 12) { wg_commit(); mbar_wait(sb + 8 * B_ST1, 0); wg_fence(); }
        wgmma_ss_n8<1, 0>(ca, da + 128 * n + (n < 4 ? 0 : (SM_RING + R_X - 8192 - SM_EXT) / 16), db + 4 * n, n != 0);
      }
      wg_commit();
      wg_wait<0>();
#pragma unroll
      for (int i = 0; i < 4; i++) asm volatile("" : "+f"(ca[i])::"memory");
      STAMPIF(tid == 0, 77);
      const int row = (m < 6 ? 0 : 4) + (lane & 3);
      uint16_t* dst = (uint16_t*)G->cimg + s * 3072 + grp * 512 + row * 64 + (lane >> 2);
#pragma unroll
      for (int j = 0; j < 2; j++) {
        const float c1 = __shfl_sync(0xffffffffu, ca[2 * j], lane & 28), c2 = __shfl_sync(0xffffffffu, ca[2 * j + 1], lane & 28);
        const float t = (lane & 2) ? c2 : c1, hi = rbf(t);
        dst[((2 * w + j) ^ row) << 3] = (uint16_t)pack2((lane & 1) ? t - hi : hi, 0.f);
      }
      rdwait(sb, rdback(dst - (lane >> 2) + (((2 * w) ^ row) << 3)));
      __syncwarp();
      if (lane == 0) flag_add(G, FL_C + s);
      STAMPIF(tid == 0, 35);
    }
    {
      const int j = 4 * ((lane >> 2) & 1) + (lane >> 3), row = 32 * w + 8 * (lane & 3) + (lane >> 2);
      bar_sync(5, 128);
      if (tid < 2) mbar_arrive(sb + 8 * (B_E1 + 5));
      const uint4 m4 = lds128(sb + SM_SMALL + SMALL_PV + 64 * w + 16 * (lane & 3));
      const uint32_t m_[4] = {m4.x, m4.y, m4.z, m4.w};
      float a[16];
#pragma unroll
      for (int i = 0; i < 16; i++) a[i] = 0.f;
      const uint32_t xa = sb + SM_Z + (w >> 1) * 2048 + 128 * j + (((4 * (w & 1) + (lane & 3)) ^ j) << 4);
      mbar_wait(sb + 8 * B_X1, 0);
      STAMPIF(tid == 0, 85);
#pragma unroll 2
      for (int n = 0; n < 10; n++) {
        const uint4 x4 = lds128(xa + 1024 * (n & 1) + 2048 * (n & 14));
        const uint32_t x_[4] = {x4.x, x4.y, x4.z, x4.w};
#pragma unroll
        for (int i = 0; i < 4; i++) {
          const float d0 = blo(x_[i]) - blo(m_[i]), d1 = bhi(x_[i]) - bhi(m_[i]);
          a[4 * i] += d0; a[4 * i + 1] += d0 * d0; a[4 * i + 2] += d1; a[4 * i + 3] += d1 * d1;
        }
      }
      bfly<16>(a, 16, lane & 16); bfly<8>(a, 8, lane & 8); bfly<4>(a, 4, lane & 4);
      uint2* p = G->st2 + 1024 * m + row;
      st_tag(p + 128 * s, __float_as_uint(a[0]), (__float_as_uint(a[1]) & ~15u) | (e1 & 15));
      STAMPIF(tid == 0, 87);
      float s1, s2;
#pragma unroll 1
      for (int i = 0;; i++) {
        uint32_t t = 0;
        s1 = 0.f; s2 = 0.f;
#pragma unroll
        for (int n = 0; n < 8; n++) { const uint2 v = ld_tag(p + 128 * n); s1 += __uint_as_float(v.x); s2 += __uint_as_float(v.y); t |= v.y ^ e1; }
        if (!(t & 15)) break;
        if (i > (1 << 20)) __trap();
      }
      const float pv = blo(lds32(sb + SM_SMALL + SMALL_PV + 4 * (row >> 1)) >> (16 * (row & 1)));
      const float mu = s1 * (1.f / D_), var = fmaxf(s2 * (1.f / D_) - mu * mu, 0.f);
      const float sd = rbf(__fsqrt_rn(rbf(rbf(var) + 1e-5f)));
      const uint32_t hm = pack2(-0.5f * (pv + mu), -0.5f * (pv + mu)), hs = pack2(0.5f * sd, 0.5f * sd);
      sts128(sb + SM_STAT + 16 * row, make_uint4(hm, hs, hm, hs));
      fence_async_s();
      __syncwarp();
      if (lane == 0) mbar_arrive(sb + 8 * B_ST2);
      STAMPIF(tid == 0, 21);
    }
  } else {
    if (wg == 0) cp_arrive(sb + 8 * B_B);
    asm volatile("setmaxnreg.inc.sync.aligned.u32 224;");
    STAMPIF(threadIdx.x == 0, 82);
    const int g = lane >> 2, q = lane & 3;
    if (wg == 1) bar_arrive(1, 256);
    uint32_t dv = *(const uint16_t*)(gD + 128 * wg + b);
    {
      const int t2 = threadIdx.x, w2 = 4 * wg + w;
      STAMPIF(t2 == 0, 20);
      if (KV1F || wg == 0) {
        kv_job(G, sb, b, wg, tid);
        __syncwarp();
        if (lane == 0) mbar_arrive(sb + 8 * (B_KVS + wg));
        STAMPIF(t2 == 0, 78);
      }
      mbar_wait(sb + 8 * B_X, 0);
      mbar_wait(sb + 8 * (B_X + 1), 0);
      STAMPIF(t2 == 0, 25);
      const uint32_t xr = ring + R_X + (15 - (t2 >> 4)) * 128;
      float pv = blo(lds32(xr)), s1 = 0.f, s2 = 0.f;
#pragma unroll
      for (int n = 0; n < 5; n++) {
        uint4 v = lds128(xr + 16 * (t2 & 7) + 2048 * ((t2 >> 3) & 1) + 4096 * n);
        uint32_t u[4] = {v.x, v.y, v.z, v.w};
#pragma unroll
        for (int j = 0; j < 4; j++) {
          float a = blo(u[j]) - pv, c = bhi(u[j]) - pv;
          s1 += a + c; s2 += a * a; s2 += c * c;
        }
      }
      uint32_t r[5][4];
      const uint32_t la = ring + R_X + wg * 2048 + (15 - (lane & 15)) * 128 + (((2 * w + (lane >> 4)) ^ (~lane & 7)) << 4);
#pragma unroll
      for (int n = 0; n < 5; n++) ldsm4t(r[n], la + n * 4096);
#pragma unroll
      for (int n = 0; n < 4; n++) sts64(xs_base(sb, n >> 1) + 512 * w2 + 256 * (n & 1) + 8 * lane, r[n >> 1][2 * (n & 1)], r[n >> 1][2 * (n & 1) + 1]);
#pragma unroll
      for (int o = 1; o < 16; o <<= 1) { s1 += __shfl_xor_sync(0xffffffffu, s1, o); s2 += __shfl_xor_sync(0xffffffffu, s2, o); }
      if ((t2 & 15) == 0) {
        float mu = s1 * (1.f / D_), var = fmaxf(s2 * (1.f / D_) - mu * mu, 0.f);
        const uint32_t a = sb + XS_LN + 8 * w + 4 * wg + (lane >> 3);
        sts16(a, pack2(pv + mu, 0.f));
        const float rs = __frcp_rn(rbf(__fsqrt_rn(rbf(rbf(var) + 1e-5f))));
        sts16(a + 32, pack2(rs, 0.f));
        sts16(a + 64, pack2(rs - rbf(rs), 0.f));
      }
      fence_async_s();
      bar_sync(6, 256);
      if (t2 == 0) mbar_arrive(sb + 8 * B_XS0);
      STAMPIF(t2 == 0, 75);
#pragma unroll
      for (int n = 4; n < 10; n++) sts64(xs_base(sb, n >> 1) + 512 * w2 + 256 * (n & 1) + 8 * lane, r[n >> 1][2 * (n & 1)], r[n >> 1][2 * (n & 1) + 1]);
      fence_async_s();
      __syncwarp();
      if (lane == 0) mbar_arrive(sb + 8 * B_XS);
      STAMPIF(t2 == 0, 26);
      if (!KV1F && wg == 1) {
        kv_job(G, sb, b, 1, tid);
        __syncwarp();
        kv_signal(G, sb, b, 1, 8 * w + (lane & 7), lane == 0);
        STAMPIF(tid == 0, 2);
      }
      k1_job(sb, wg, tid);
      bar_sync(3 + wg, 128);
      if (tid < 2) mbar_arrive(sb + 8 * (B_E1 + tid));
      STAMPIF(t2 == 0, 79);
    }
    {
      const int b0 = (g >> 1) & 1, b1 = g >> 2, u = q + 4 * b0 - w;
      const uint32_t fo = 128 + (g & 1) * K1OFF + 288 * b1 + 4 * u, fo0 = fo - (u < 0 ? 32 : 0);
      const uint32_t dsel = (b1 == 0 && u == 0) ? ((g & 1) ? 0x1044 : 0x4410) : 0x4444;
      const bool wrap = b0 && q == 0;
      const int src1 = b0 ? ((lane & 20) | ((q - 1) & 3)) : (lane | 8);
#pragma unroll 1
      for (int ch = wg; ch < 5; ch += 2) {
        const uint32_t base = chan_base(sb, ch);
        if (ch >= 2) { mbar_wait(sb + 8 * (B_K + ch - 2), 0); mbar_wait(sb + 8 * (B_S + ch), 0); }
        const uint32_t fa = base + fo, fa0 = base + fo0;
        uint32_t af[16][4];
#pragma unroll
        for (int j = 0; j < 16; j++) {
          const int o = 64 * (j & 1) + 576 * (j >> 1);
          af[j][0] = lds32(((j & 1) ? fa : fa0) + o); af[j][1] = lds32(fa + o + 128); af[j][2] = lds32(fa + o + 32); af[j][3] = lds32(fa + o + 160);
        }
        af[0][0] = hadd(af[0][0], __byte_perm(dv, 0, dsel));
        if (ch < 3) dv = *(const uint16_t*)(gD + 128 * (ch + 2) + b);
        mbar_wait(sb + 8 * (B_U + ch), 0);
        float acc[128];
        const uint64_t db = mkdesc(base + KSZ, 32, 128, 0);
        bar_sync(1 + wg, 256);
        STAMPIF(tid == 0, 3 + ch);
        wg_fence();
        wgmma_rs_n64<0>(acc + 96, af[0], db + 192, 0);
        wgmma_rs_n192<0>(acc, af[0], db, 0);
        wgmma_rs_n64<0>(acc + 96, af[1], db + 196, 1);
        wgmma_rs_n192<0>(acc, af[1], db + 4, 1);
        wgmma_rs_n32<0>(acc + 96, af[2], db + 224, 1);
        wgmma_rs_n192<0>(acc, af[2], db + 32, 1);
        wgmma_rs_n32<0>(acc + 96, af[3], db + 228, 1);
        wgmma_rs_n192<0>(acc, af[3], db + 36, 1);
        wgmma_rs_n192<0>(acc, af[4], db + 64, 1);
        wgmma_rs_n192<0>(acc, af[5], db + 68, 1);
        wgmma_rs_n160<0>(acc, af[6], db + 96, 1);
        wgmma_rs_n160<0>(acc, af[7], db + 100, 1);
        wgmma_rs_n128<0>(acc, af[8], db + 128, 1);
        wgmma_rs_n128<0>(acc, af[9], db + 132, 1);
        wgmma_rs_n96<0>(acc, af[10], db + 160, 1);
        wgmma_rs_n96<0>(acc, af[11], db + 164, 1);
        bar_arrive(2 - wg, 256);
        wgmma_rs_n64<0>(acc, af[12], db + 192, 1);
        wgmma_rs_n64<0>(acc, af[13], db + 196, 1);
        wgmma_rs_n32<0>(acc, af[14], db + 224, 1);
        wgmma_rs_n32<0>(acc, af[15], db + 228, 1);
        wg_commit();
        wg_wait<0>();
#pragma unroll
        for (int i = 0; i < 128; i++) asm volatile("" : "+f"(acc[i])::"memory");
        bar_sync(3 + wg, 128);
        if (tid == 0) mbar_arrive(sb + 8 * (B_E1 + 2 + (ch >> 1)));
        float S0[33], T[34];
#pragma unroll
        for (int i = 0; i < 31; i++) S0[i] = acc[4 * i] + acc[4 * i + 6];
        S0[31] = acc[124]; S0[32] = 0.f;
#pragma unroll
        for (int i = 0; i < 32; i++) {
          float s1 = i < 31 ? acc[4 * i + 1] + acc[4 * i + 7] : acc[125];
          T[i] = (wrap ? S0[i + 1] : S0[i]) + __shfl_sync(0xffffffffu, s1, src1);
        }
        T[32] = 0.f; T[33] = 0.f;
        uint32_t zz[8];
#pragma unroll
        for (int mu = 0; mu < 8; mu++) {
          float y0 = (b1 ? T[4 * mu + 4] : T[4 * mu]) + __shfl_xor_sync(0xffffffffu, T[4 * mu + 2], 16);
          float y1 = (b1 ? T[4 * mu + 5] : T[4 * mu + 1]) + __shfl_xor_sync(0xffffffffu, T[4 * mu + 3], 16);
          zz[mu] = pack2(y0, y1);
        }
        sts128(sb + SM_Z + ch * 4096 + tid * 32, make_uint4(zz[0], zz[4], zz[1], zz[5]));
        sts128(sb + SM_Z + ch * 4096 + tid * 32 + 16, make_uint4(zz[2], zz[6], zz[3], zz[7]));
        __syncwarp();
        if (lane == 0) mbar_arrive(sb + 8 * (B_Z + ch));
        STAMPIF(tid == 0, 8 + ch);
      }
      if (wg == 1) bar_sync(2, 256);
    }
    uint32_t hh[96];
    {
      float ga[192];
      float* ua = ga + 96;
      const uint64_t da0 = mkdesc(ring + wg * 4096, 4096, 1024, 1), db0 = mkdesc(ring + 8192, 4096, 1024, 1);
      int st = 0, ph = 0;
#pragma unroll 1
      for (int it = 0; it < 20; it++) {
        mbar_wait(sb + 8 * (B_F1 + st), ph);
        STAMPIF(tid == 0 && it == 0, 13 + wg);
        STAMPIF(threadIdx.x == 0, 100 + it);
        const uint64_t da = da0 + st * 2048, db = db0 + st * 2048;
        wg_fence();
        wgmma_ss_n192<1, 1>(ga, da, db, it != 0);
        wgmma_ss_n192<1, 1>(ua, da, db + 768, it != 0);
        wgmma_ss_n192<1, 1>(ga, da + 128, db + 128, 1);
        wgmma_ss_n192<1, 1>(ua, da + 128, db + 128 + 768, 1);
        wg_commit();
        wg_wait<1>();
        if (it > 0 && tid == 0) mbar_arrive(sb + 8 * (B_E1 + (st == 0 ? 4 : st - 1)));
        if (++st == 5) { st = 0; ph ^= 1; }
      }
      STAMPIF(threadIdx.x == 0, 61);
      if (tid == 0) {
        mbar_wait(sb + 8 * (B_E1 + 5), 0);
        mbar_arrive_remote(mapa(sb + 8 * (B_PEER + 2 * wg), (b & 1) ^ 1));
      }
      mbar_wait(sb + 8 * B_EXT, 0);
      mbar_wait(sb + 8 * B_ST2, 0);
      const uint64_t de = mkdesc(sb + SM_EXT, 1024, 0, 1), ds = mkdesc(sb + SM_STAT + wg * 1024, 0, 128, 0);
      wg_fence();
      wgmma_ss_n192<0, 1>(ga, ds, de, 1);
      wgmma_ss_n192<0, 1>(ua, ds, de + 192, 1);
      wg_commit();
      wg_wait<1>();
      if (tid == 0) {
        mbar_arrive(sb + 8 * (B_E1 + 4));
        mbar_arrive_remote(mapa(sb + 8 * (B_PEER + 2 * wg + 1), (b & 1) ^ 1));
      }
      wg_wait<0>();
#pragma unroll
      for (int i = 0; i < 192; i++) asm volatile("" : "+f"(ga[i])::"memory");
      STAMPIF(tid == 0, 15 + wg);
#pragma unroll
      for (int i = 0; i < 48; i++) {
        const int j = 64 * (i >> 4) + 2 * (i & 15);
        hh[i] = pack2(ga[j] * ga[j + 32], ga[j + 1] * ga[j + 33]);
        asm volatile("" : "+r"(hh[i])::"memory");
      }
    }
    float acc[80];
    uint4 pf[15];
    const uint32_t tag = lds32(sb + SM_SMALL + SMALL_E) & 1;
    uint4* const pp[3] = {G->PP + threadIdx.x, G->PP + 128 * 1280 + threadIdx.x, G->PP + 256 * 1280 + threadIdx.x};
    {
      const uint32_t la = ring + wg * 4096 + tid * 16, ra = mapa(la, (b & 1) ^ 1), rb = mapa(sb + 8 * (B_RECV + 2 * wg), (b & 1) ^ 1);
#pragma unroll
      for (int h = 0; h < 16; h++) {
        const int gr = h >> 1, pe = gr < 4 ? gr >> 1 : gr & 1, ac = gr < 4 ? gr & 1 : gr / 6, d = gr < 4 ? ac + 1 : ac + 3;
        if (h == 0) mbar_wait(sb + 8 * B_FB, 0);
        if (h == 4) mbar_wait(sb + 8 * (B_FB + 5), 0);
        if (!(h & 1)) mbar_wait(sb + 8 * (B_FB + gr + (gr < 4 ? 1 : 2)), 0);
        if (gr == 2) {
          mbar_wait(sb + 8 * (B_RECV + 2 * wg + (h & 1)), 0);
#pragma unroll
          for (int j = 6 * (h & 1); j < 6 * (h & 1) + 6; j++) {
            const uint4 v = lds128(la + (j < 2 ? 5 : (j >> 1) - 1) * 32768 + (j & 1) * 2048);
            hh[48 + 4 * j] = v.x; hh[49 + 4 * j] = v.y; hh[50 + 4 * j] = v.z; hh[51 + 4 * j] = v.w;
          }
        }
        STAMPIF(threadIdx.x == 0 && h % 4 == 0, 121 + h / 4);
        const uint64_t db = mkdesc(ring + (gr & 3) * 32768 + 8192, (5 - pe - (gr & 3)) * 32768 + 16 * ((s + 2 * d) & 6), 1024, 1);
        wg_fence();
#pragma unroll
        for (int j = 6 * (h & 1); j < 6 * (h & 1) + 6; j++) wgmma_rs_n80<1>(acc + 40 * ac, hh + 48 * pe + 4 * j, db + 128 * j, pe || j);
        wg_commit();
        if (h < 4) {
#pragma unroll
          for (int j = SJ(h); j < SJ(h + 1); j++) {
            if (j == 0 || j == 10) mbar_wait(sb + 8 * (B_PEER + 2 * wg + j / 10), 0);
            st_async4(ra + (j < 2 ? 5 : (j >> 1) - 1) * 32768 + (j & 1) * 2048, hh + 4 * j, rb + 8 * (j / 6));
          }
          STAMPIF(tid == 0 && h == 3, 81);
        }
        if (h == 2 || h == 4 || h == 6 || h == 8 || h == 12) {
          wg_wait<1>();
          if (h < 12 && tid == 0) mbar_arrive(sb + 8 * (B_EB + gr - 1));
          if (h >= 6) {
            const int i = h == 6 ? 1 : h == 8 ? 2 : 3;
            float* a = acc + 40 * (1 - ac);
#pragma unroll
            for (int j = 0; j < 40; j++) asm volatile("" : "+f"(a[j])::"memory");
            pp_send(pp[i - 1] + ((b & ~6) + ((b + 2 * i) & 6)) * 1280, a, tag);
            STAMPIF(threadIdx.x == 0, 50 + i);
          }
        }
        if (h == 5) bar_sync(3 + wg, 128);
        if (h == PL1) pp_load(pf, pp[0] + b * 1280);
        if (h == PL2) pp_load(pf + 5, pp[1] + b * 1280);
        if (h == 14) wg_wait<1>();
      }
    }
    STAMPIF(tid == 0, 17);
    uint32_t xr[20], gbv[10];
    mbar_wait(sb + 8 * B_X1, 0);
    mbar_wait(sb + 8 * B_GB, 0);
    float rs0 = 2.f * blo(lds32(sb + SM_STAT + (64 * wg + 16 * w + g) * 16 + 4)), rs1 = 2.f * blo(lds32(sb + SM_STAT + (64 * wg + 16 * w + g) * 16 + 132));
    {
      const uint32_t la = sb + SM_Z + wg * 2048 + (8 * (lane >> 4) + (lane & 7)) * 128 + (((2 * w + ((lane >> 3) & 1)) ^ (lane & 7)) << 4);
#pragma unroll
      for (int i = 0; i < 5; i++) ldsm4t(xr + 4 * i, la + i * 4096);
#pragma unroll
      for (int i = 0; i < 10; i++) gbv[i] = lds32(sb + SM_SMALL + SMALL_GB + 16 * i + 4 * q);
    }
    rs0 = __frcp_rn(rs0 * rs0); rs1 = __frcp_rn(rs1 * rs1);
#pragma unroll
    for (int i = 0; i < 3; i++) {
      pp_wait(pf + 5 * i, pp[i] + b * 1280, tag);
      if (i == 1) pp_load(pf + 10, pp[2] + b * 1280);
      STAMPIF(threadIdx.x == 0 && i < 2, 98 + i);
      if (i) pp_add(acc, pf + 5 * i, pf, i == 1);
#pragma unroll
      for (int j = 0; j < 40 && i == 1; j++) asm volatile("" : "+f"(acc[j])::"memory");
    }
#pragma unroll
    for (int i = 0; i < 40; i++) { acc[i] *= (i & 2) ? rs1 : rs0; asm volatile("" : "+f"(acc[i])::"memory"); }
    STAMPIF(threadIdx.x == 0, 125);
    wg_wait<0>();
    float* a = acc + 40;
#pragma unroll
    for (int i = 0; i < 40; i++) asm volatile("" : "+f"(a[i])::"memory");
    STAMPIF(tid == 0, 18);
    uint32_t ov[20];
#pragma unroll
    for (int i = 0; i < 10; i++) {
      ov[2 * i] = hadd(xr[2 * i], hmul(gbv[i], pack2(a[4 * i] * rs0 + acc[4 * i], a[4 * i + 1] * rs0 + acc[4 * i + 1])));
      ov[2 * i + 1] = hadd(xr[2 * i + 1], hmul(gbv[i], pack2(a[4 * i + 2] * rs1 + acc[4 * i + 2], a[4 * i + 3] * rs1 + acc[4 * i + 3])));
    }
    const uint32_t obuf = ring + w * 32768 + wg * 4096;
    const int orow = 15 - (4 * (lane & 2) + 2 * ((lane >> 2) & 3) + (lane & 1));
#pragma unroll
    for (int i = 0; i < 4; i++) stsm4(obuf + orow * 128 + (((lane >> 4) + 2 * i) ^ (orow & 7)) * 16, ov + 4 * i);
    stsm4(obuf + 2048 + orow * 32 + (lane >> 4) * 16, ov + 16);
    fence_async_s();
    __syncwarp();
    if (elect()) {
      const int t = 191 - ibase(8 * m + 4 * wg + w);
      tma_store4d(&P.mO, obuf, out_col(s, 0), 0, 0, t);
      tma_store4d(&P.mO2, obuf + 2048, out_col(s, 4), 0, 0, t);
      asm volatile("cp.async.bulk.commit_group;" ::: "memory");
      asm volatile("cp.async.bulk.wait_group.read 0;" ::: "memory");
    }
  }
}

typedef CUresult (*EncFn)(CUtensorMap*, CUtensorMapDataType, cuuint32_t, void*, const cuuint64_t*, const cuuint64_t*, const cuuint32_t*, const cuuint32_t*,
                          CUtensorMapInterleave, CUtensorMapSwizzle, CUtensorMapL2promotion, CUtensorMapFloatOOBfill);
static void mkmap(EncFn enc, CUtensorMap* m, const void* p, int rank, const cuuint64_t* dims, const cuuint64_t* strides, const cuuint32_t* box, CUtensorMapSwizzle sw) {
  cuuint32_t es[5] = {1, 1, 1, 1, 1};
  CUresult r = enc(m, CU_TENSOR_MAP_DATA_TYPE_BFLOAT16, rank, (void*)p, dims, strides, box, es, CU_TENSOR_MAP_INTERLEAVE_NONE, sw,
                   CU_TENSOR_MAP_L2_PROMOTION_L2_128B, CU_TENSOR_MAP_FLOAT_OOB_FILL_NONE);
  if (r != CUDA_SUCCESS) fprintf(stderr, "tensor map encode failed: %d\n", (int)r);
}

extern "C" void kernel_launch(void* const* d_in, const int* in_sizes, int n_in, void* d_out, int out_size) {
  void* fn = nullptr;
  cudaDriverEntryPointQueryResult qr;
  cudaGetDriverEntryPoint("cuTensorMapEncodeTiled", &fn, cudaEnableDefault, &qr);
  EncFn enc = (EncFn)fn;
  Scr* G;
  cudaGetSymbolAddress((void**)&G, g_scr);
  void *pAT = G->AT, *pX1 = G->x1T;
  Params P;
  { cuuint64_t d[] = {10240, 128}, st[] = {20480}; cuuint32_t bx[] = {16, 128}; mkmap(enc, &P.mXc, G->xT, 2, d, st, bx, CU_TENSOR_MAP_SWIZZLE_NONE); }
  { cuuint64_t d[] = {128, 16, 640}, st[] = {256, 4096}; cuuint32_t bx[] = {144, 16, 1}; mkmap(enc, &P.mS, d_in[4], 3, d, st, bx, CU_TENSOR_MAP_SWIZZLE_NONE); }
  { cuuint64_t d[] = {3840, 640}, st[] = {7680}; cuuint32_t bx[] = {64, 80}; mkmap(enc, &P.mWm, d_in[11], 2, d, st, bx, CU_TENSOR_MAP_SWIZZLE_128B); }
  { cuuint64_t d[] = {64, 640, 32}, st[] = {4096, 128}; cuuint32_t bx[] = {64, 32, 2}; mkmap(enc, &P.mA, pAT, 3, d, st, bx, CU_TENSOR_MAP_SWIZZLE_128B); }
  { cuuint64_t d[] = {64, 640, 32}, st[] = {4096, 128}; cuuint32_t bx[] = {64, 16, 2}; mkmap(enc, &P.mX1, pX1, 3, d, st, bx, CU_TENSOR_MAP_SWIZZLE_128B); }
  { cuuint64_t d[] = {1536, 640}, st[] = {3072}; cuuint32_t bx[] = {64, 32};
    mkmap(enc, &P.mG, d_in[7], 2, d, st, bx, CU_TENSOR_MAP_SWIZZLE_128B); mkmap(enc, &P.mU, d_in[8], 2, d, st, bx, CU_TENSOR_MAP_SWIZZLE_128B); }
  { cuuint64_t d[] = {640, 1536}, st[] = {1280}; cuuint32_t bx[] = {64, 192}; mkmap(enc, &P.mD, d_in[9], 2, d, st, bx, CU_TENSOR_MAP_SWIZZLE_128B); }
  { cuuint64_t d[] = {64, 2, 8, 10, 192}, st[] = {64 * 1280, 256 * 1280, 128, 1280}; cuuint32_t bx[] = {64, 2, 8, 5, 1}; mkmap(enc, &P.mX, d_in[0], 5, d, st, bx, CU_TENSOR_MAP_SWIZZLE_128B); }
  { cuuint64_t d[] = {640, 2, 8, 192}, st[] = {64 * 1280, 256 * 1280, 1280}; cuuint32_t bx[] = {64, 2, 8, 1}, bx2[] = {16, 2, 8, 1};
    mkmap(enc, &P.mO, d_out, 4, d, st, bx, CU_TENSOR_MAP_SWIZZLE_128B); mkmap(enc, &P.mO2, d_out, 4, d, st, bx2, CU_TENSOR_MAP_SWIZZLE_NONE); }
  cudaFuncSetAttribute(fused_kernel, cudaFuncAttributeMaxDynamicSharedMemorySize, SM_TOTAL + DEVSM);
  cudaLaunchConfig_t cfg = {};
  cfg.gridDim = dim3(128); cfg.blockDim = dim3(512); cfg.dynamicSmemBytes = SM_TOTAL + DEVSM; cfg.stream = cudaStreamPerThread;
  cudaLaunchAttribute at[1];
  at[0].id = cudaLaunchAttributeClusterDimension; at[0].val.clusterDim.x = 2; at[0].val.clusterDim.y = 1; at[0].val.clusterDim.z = 1;
  cfg.attrs = at; cfg.numAttrs = 1;
  cudaLaunchKernelEx(&cfg, fused_kernel, (const bf16*)d_in[1], (const bf16*)d_in[2], (const bf16*)d_in[3], (const bf16*)d_in[5], (const bf16*)d_in[10], G,
                     (const bf16*)d_in[7], (const bf16*)d_in[8], (const bf16*)d_in[9], (const bf16*)d_in[0], (const bf16*)d_in[4], P);
}
```

```cpp
#include <cuda_runtime.h>
#include <cuda.h>
#include <cuda_bf16.h>
#include <stdio.h>
#include <stdint.h>
typedef __nv_bfloat16 bf16;
__device__ __forceinline__ uint32_t smem_u32(const void* p) { return (uint32_t)__cvta_generic_to_shared(p); }
__device__ __forceinline__ void mbar_init(uint32_t bar, int cnt) { asm volatile("mbarrier.init.shared::cta.b64 [%0], %1;" ::"r"(bar), "r"(cnt) : "memory"); }
__device__ __forceinline__ void mbar_expect(uint32_t bar, int bytes) { asm volatile("mbarrier.arrive.expect_tx.shared::cta.b64 _, [%0], %1;" ::"r"(bar), "r"(bytes) : "memory"); }
__device__ __forceinline__ void mbar_arrive(uint32_t bar) { asm volatile("mbarrier.arrive.shared::cta.b64 _, [%0];" ::"r"(bar) : "memory"); }
__device__ __forceinline__ void mbar_arrive_remote(uint32_t bar) { asm volatile("mbarrier.arrive.relaxed.cluster.shared::cluster.b64 _, [%0];" ::"r"(bar) : "memory"); }
__device__ __forceinline__ uint32_t mapa(uint32_t a, uint32_t cta) { uint32_t r; asm("mapa.shared::cluster.u32 %0, %1, %2;" : "=r"(r) : "r"(a), "r"(cta)); return r; }
__device__ __forceinline__ bool mbar_try(uint32_t bar, int parity) {
  uint32_t ok;
  asm volatile("{\n.reg .pred p;\nmbarrier.try_wait.parity.shared::cta.b64 p, [%1], %2;\nselp.u32 %0, 1, 0, p;\n}" : "=r"(ok) : "r"(bar), "r"(parity) : "memory");
  return ok;
}
__device__ __forceinline__ void mbar_wait(uint32_t bar, int parity) {
#pragma unroll 1
  for (int i = 0; i < (1 << 20); i++) { if (mbar_try(bar, parity)) return; }
  __trap();
}
__device__ __forceinline__ bool elect() {
  uint32_t p;
  asm volatile("{\n.reg .pred P;\nelect.sync _|P, 0xffffffff;\nselp.u32 %0, 1, 0, P;\n}" : "=r"(p));
  return p;
}
__device__ __forceinline__ void tma2d(uint32_t dst, const CUtensorMap* m, int c0, int c1, uint32_t bar) {
  asm volatile("cp.async.bulk.tensor.2d.shared::cluster.global.mbarrier::complete_tx::bytes [%0], [%1, {%3, %4}], [%2];" ::"r"(dst), "l"(m), "r"(bar), "r"(c0), "r"(c1) : "memory");
}
__device__ __forceinline__ void tma3d(uint32_t dst, const CUtensorMap* m, int c0, int c1, int c2, uint32_t bar) {
  asm volatile("cp.async.bulk.tensor.3d.shared::cluster.global.mbarrier::complete_tx::bytes [%0], [%1, {%3, %4, %5}], [%2];" ::"r"(dst), "l"(m), "r"(bar), "r"(c0), "r"(c1), "r"(c2) : "memory");
}
__device__ __forceinline__ void tma4d(uint32_t dst, const CUtensorMap* m, int c0, int c1, int c2, int c3, uint32_t bar) {
  asm volatile("cp.async.bulk.tensor.4d.shared::cluster.global.mbarrier::complete_tx::bytes [%0], [%1, {%3, %4, %5, %6}], [%2];" ::"r"(dst), "l"(m), "r"(bar), "r"(c0), "r"(c1), "r"(c2), "r"(c3) : "memory");
}
__device__ __forceinline__ void tma5d(uint32_t dst, const CUtensorMap* m, int c0, int c1, int c2, int c3, int c4, uint32_t bar) {
  asm volatile("cp.async.bulk.tensor.5d.shared::cluster.global.mbarrier::complete_tx::bytes [%0], [%1, {%3, %4, %5, %6, %7}], [%2];" ::"r"(dst), "l"(m), "r"(bar), "r"(c0), "r"(c1), "r"(c2), "r"(c3), "r"(c4) : "memory");
}
__device__ __forceinline__ void tma_store2d(const CUtensorMap* m, uint32_t src, int c0, int c1) {
  asm volatile("cp.async.bulk.tensor.2d.global.shared::cta.bulk_group [%0, {%2, %3}], [%1];" ::"l"(m), "r"(src), "r"(c0), "r"(c1) : "memory");
}
__device__ __forceinline__ void tma_store4d(const CUtensorMap* m, uint32_t src, int c0, int c1, int c2, int c3) {
  asm volatile("cp.async.bulk.tensor.4d.global.shared::cta.bulk_group [%0, {%2, %3, %4, %5}], [%1];" ::"l"(m), "r"(src), "r"(c0), "r"(c1), "r"(c2), "r"(c3) : "memory");
}
__device__ __forceinline__ void tma_prefetch2d(const CUtensorMap* m, int c0, int c1) {
  asm volatile("cp.async.bulk.prefetch.tensor.2d.L2.global [%0, {%1, %2}];" ::"l"(m), "r"(c0), "r"(c1) : "memory");
}
__device__ __forceinline__ void bulk_g2s(uint32_t dst, const void* src, int bytes, uint32_t bar) {
  asm volatile("cp.async.bulk.shared::cluster.global.mbarrier::complete_tx::bytes [%0], [%1], %2, [%3];" ::"r"(dst), "l"(src), "r"(bytes), "r"(bar) : "memory");
}
__device__ __forceinline__ void bulk_s2g(void* dst, uint32_t src, int bytes) {
  asm volatile("cp.async.bulk.global.shared::cta.bulk_group [%0], [%1], %2;" ::"l"(dst), "r"(src), "r"(bytes) : "memory");
}
__device__ __forceinline__ void cp16(uint32_t dst, const void* src) { asm volatile("cp.async.cg.shared.global [%0], [%1], 16;" ::"r"(dst), "l"(src) : "memory"); }
__device__ __forceinline__ void cp16z(uint32_t dst, const void* src, int n) { asm volatile("cp.async.cg.shared.global [%0], [%1], 16, %2;" ::"r"(dst), "l"(src), "r"(n) : "memory"); }
__device__ __forceinline__ void cp_arrive(uint32_t bar) { asm volatile("cp.async.mbarrier.arrive.noinc.shared::cta.b64 [%0];" ::"r"(bar) : "memory"); }
__device__ __forceinline__ void st_async4(uint32_t dst, const uint32_t* v, uint32_t bar) {
  asm volatile("st.async.weak.shared::cluster.mbarrier::complete_tx::bytes.v4.b32 [%0], {%1, %2, %3, %4}, [%5];" ::"r"(dst), "r"(v[0]), "r"(v[1]), "r"(v[2]), "r"(v[3]), "r"(bar) : "memory");
}
__device__ __forceinline__ void wg_fence() { asm volatile("wgmma.fence.sync.aligned;" ::: "memory"); }
__device__ __forceinline__ void wg_commit() { asm volatile("wgmma.commit_group.sync.aligned;" ::: "memory"); }
template <int N> __device__ __forceinline__ void wg_wait() { asm volatile("wgmma.wait_group.sync.aligned %0;" ::"n"(N) : "memory"); }
__device__ __forceinline__ uint64_t mkdesc(uint32_t addr, uint32_t lbo, uint32_t sbo, uint32_t swz) {
  return (uint64_t)((addr & 0x3FFFF) >> 4) | ((uint64_t)(lbo >> 4) << 16) | ((uint64_t)(sbo >> 4) << 32) | ((uint64_t)swz << 62);
}
__device__ __forceinline__ void ldsm4t(uint32_t* r, uint32_t a) {
  asm volatile("ldmatrix.sync.aligned.m8n8.x4.trans.shared.b16 {%0,%1,%2,%3}, [%4];" : "=r"(r[0]), "=r"(r[1]), "=r"(r[2]), "=r"(r[3]) : "r"(a) : "memory");
}
__device__ __forceinline__ void stsm4(uint32_t a, const uint32_t* r) {
  asm volatile("stmatrix.sync.aligned.m8n8.x4.shared.b16 [%0], {%1,%2,%3,%4};" ::"r"(a), "r"(r[0]), "r"(r[1]), "r"(r[2]), "r"(r[3]) : "memory");
}
__device__ __forceinline__ void bar_sync(int id, int n) { asm volatile("bar.sync %0, %1;" ::"r"(id), "r"(n) : "memory"); }
__device__ __forceinline__ void bar_arrive(int id, int n) { asm volatile("bar.arrive %0, %1;" ::"r"(id), "r"(n) : "memory"); }
__device__ __forceinline__ uint32_t lds32(uint32_t a) { uint32_t v; asm volatile("ld.shared.b32 %0, [%1];" : "=r"(v) : "r"(a) : "memory"); return v; }
__device__ __forceinline__ uint2 lds64(uint32_t a) { uint2 v; asm volatile("ld.shared.v2.b32 {%0,%1}, [%2];" : "=r"(v.x), "=r"(v.y) : "r"(a) : "memory"); return v; }
__device__ __forceinline__ uint4 lds128(uint32_t a) { uint4 v; asm volatile("ld.shared.v4.b32 {%0,%1,%2,%3}, [%4];" : "=r"(v.x), "=r"(v.y), "=r"(v.z), "=r"(v.w) : "r"(a) : "memory"); return v; }
__device__ __forceinline__ void sts16(uint32_t a, uint32_t v) { asm volatile("st.shared.b16 [%0], %1;" ::"r"(a), "h"((uint16_t)v) : "memory"); }
__device__ __forceinline__ void sts32(uint32_t a, uint32_t v) { asm volatile("st.shared.b32 [%0], %1;" ::"r"(a), "r"(v) : "memory"); }
__device__ __forceinline__ void sts64(uint32_t a, uint32_t x, uint32_t y) { asm volatile("st.shared.v2.b32 [%0], {%1,%2};" ::"r"(a), "r"(x), "r"(y) : "memory"); }
__device__ __forceinline__ void sts128(uint32_t a, uint4 v) { asm volatile("st.shared.v4.b32 [%0], {%1,%2,%3,%4};" ::"r"(a), "r"(v.x), "r"(v.y), "r"(v.z), "r"(v.w) : "memory"); }
template<int TB> __device__ __forceinline__ void wgmma_rs_n128(float* d, const uint32_t* a, uint64_t db, int sd) {
  asm volatile("{\n.reg .pred p;\nsetp.ne.b32 p, %69, 0;\n"
    "wgmma.mma_async.sync.aligned.m64n128k16.f32.bf16.bf16 {%0, %1, %2, %3, %4, %5, %6, %7, %8, %9, %10, %11, %12, %13, %14, %15, %16, %17, %18, %19, %20, %21, %22, %23, %24, %25, %26, %27, %28, %29, %30, %31, %32, %33, %34, %35, %36, %37, %38, %39, %40, %41, %42, %43, %44, %45, %46, %47, %48, %49, %50, %51, %52, %53, %54, %55, %56, %57, %58, %59, %60, %61, %62, %63}, {%64, %65, %66, %67}, %68, p, 1, 1, %70;\n}"
    : "+f"(d[0]), "+f"(d[1]), "+f"(d[2]), "+f"(d[3]), "+f"(d[4]), "+f"(d[5]), "+f"(d[6]), "+f"(d[7]), "+f"(d[8]), "+f"(d[9]), "+f"(d[10]), "+f"(d[11]), "+f"(d[12]), "+f"(d[13]), "+f"(d[14]), "+f"(d[15]), "+f"(d[16]), "+f"(d[17]), "+f"(d[18]), "+f"(d[19]), "+f"(d[20]), "+f"(d[21]), "+f"(d[22]), "+f"(d[23]), "+f"(d[24]), "+f"(d[25]), "+f"(d[26]), "+f"(d[27]), "+f"(d[28]), "+f"(d[29]), "+f"(d[30]), "+f"(d[31]), "+f"(d[32]), "+f"(d[33]), "+f"(d[34]), "+f"(d[35]), "+f"(d[36]), "+f"(d[37]), "+f"(d[38]), "+f"(d[39]), "+f"(d[40]), "+f"(d[41]), "+f"(d[42]), "+f"(d[43]), "+f"(d[44]), "+f"(d[45]), "+f"(d[46]), "+f"(d[47]), "+f"(d[48]), "+f"(d[49]), "+f"(d[50]), "+f"(d[51]), "+f"(d[52]), "+f"(d[53]), "+f"(d[54]), "+f"(d[55]), "+f"(d[56]), "+f"(d[57]), "+f"(d[58]), "+f"(d[59]), "+f"(d[60]), "+f"(d[61]), "+f"(d[62]), "+f"(d[63])
    : "r"(a[0]), "r"(a[1]), "r"(a[2]), "r"(a[3]), "l"(db), "r"(sd), "n"(TB));
}

template<int TB> __device__ __forceinline__ void wgmma_rs_n160(float* d, const uint32_t* a, uint64_t db, int sd) {
  asm volatile("{\n.reg .pred p;\nsetp.ne.b32 p, %85, 0;\n"
    "wgmma.mma_async.sync.aligned.m64n160k16.f32.bf16.bf16 {%0, %1, %2, %3, %4, %5, %6, %7, %8, %9, %10, %11, %12, %13, %14, %15, %16, %17, %18, %19, %20, %21, %22, %23, %24, %25, %26, %27, %28, %29, %30, %31, %32, %33, %34, %35, %36, %37, %38, %39, %40, %41, %42, %43, %44, %45, %46, %47, %48, %49, %50, %51, %52, %53, %54, %55, %56, %57, %58, %59, %60, %61, %62, %63, %64, %65, %66, %67, %68, %69, %70, %71, %72, %73, %74, %75, %76, %77, %78, %79}, {%80, %81, %82, %83}, %84, p, 1, 1, %86;\n}"
    : "+f"(d[0]), "+f"(d[1]), "+f"(d[2]), "+f"(d[3]), "+f"(d[4]), "+f"(d[5]), "+f"(d[6]), "+f"(d[7]), "+f"(d[8]), "+f"(d[9]), "+f"(d[10]), "+f"(d[11]), "+f"(d[12]), "+f"(d[13]), "+f"(d[14]), "+f"(d[15]), "+f"(d[16]), "+f"(d[17]), "+f"(d[18]), "+f"(d[19]), "+f"(d[20]), "+f"(d[21]), "+f"(d[22]), "+f"(d[23]), "+f"(d[24]), "+f"(d[25]), "+f"(d[26]), "+f"(d[27]), "+f"(d[28]), "+f"(d[29]), "+f"(d[30]), "+f"(d[31]), "+f"(d[32]), "+f"(d[33]), "+f"(d[34]), "+f"(d[35]), "+f"(d[36]), "+f"(d[37]), "+f"(d[38]), "+f"(d[39]), "+f"(d[40]), "+f"(d[41]), "+f"(d[42]), "+f"(d[43]), "+f"(d[44]), "+f"(d[45]), "+f"(d[46]), "+f"(d[47]), "+f"(d[48]), "+f"(d[49]), "+f"(d[50]), "+f"(d[51]), "+f"(d[52]), "+f"(d[53]), "+f"(d[54]), "+f"(d[55]), "+f"(d[56]), "+f"(d[57]), "+f"(d[58]), "+f"(d[59]), "+f"(d[60]), "+f"(d[61]), "+f"(d[62]), "+f"(d[63]), "+f"(d[64]), "+f"(d[65]), "+f"(d[66]), "+f"(d[67]), "+f"(d[68]), "+f"(d[69]), "+f"(d[70]), "+f"(d[71]), "+f"(d[72]), "+f"(d[73]), "+f"(d[74]), "+f"(d[75]), "+f"(d[76]), "+f"(d[77]), "+f"(d[78]), "+f"(d[79])
    : "r"(a[0]), "r"(a[1]), "r"(a[2]), "r"(a[3]), "l"(db), "r"(sd), "n"(TB));
}

template<int TB> __device__ __forceinline__ void wgmma_rs_n192(float* d, const uint32_t* a, uint64_t db, int sd) {
  asm volatile("{\n.reg .pred p;\nsetp.ne.b32 p, %101, 0;\n"
    "wgmma.mma_async.sync.aligned.m64n192k16.f32.bf16.bf16 {%0, %1, %2, %3, %4, %5, %6, %7, %8, %9, %10, %11, %12, %13, %14, %15, %16, %17, %18, %19, %20, %21, %22, %23, %24, %25, %26, %27, %28, %29, %30, %31, %32, %33, %34, %35, %36, %37, %38, %39, %40, %41, %42, %43, %44, %45, %46, %47, %48, %49, %50, %51, %52, %53, %54, %55, %56, %57, %58, %59, %60, %61, %62, %63, %64, %65, %66, %67, %68, %69, %70, %71, %72, %73, %74, %75, %76, %77, %78, %79, %80, %81, %82, %83, %84, %85, %86, %87, %88, %89, %90, %91, %92, %93, %94, %95}, {%96, %97, %98, %99}, %100, p, 1, 1, %102;\n}"
    : "+f"(d[0]), "+f"(d[1]), "+f"(d[2]), "+f"(d[3]), "+f"(d[4]), "+f"(d[5]), "+f"(d[6]), "+f"(d[7]), "+f"(d[8]), "+f"(d[9]), "+f"(d[10]), "+f"(d[11]), "+f"(d[12]), "+f"(d[13]), "+f"(d[14]), "+f"(d[15]), "+f"(d[16]), "+f"(d[17]), "+f"(d[18]), "+f"(d[19]), "+f"(d[20]), "+f"(d[21]), "+f"(d[22]), "+f"(d[23]), "+f"(d[24]), "+f"(d[25]), "+f"(d[26]), "+f"(d[27]), "+f"(d[28]), "+f"(d[29]), "+f"(d[30]), "+f"(d[31]), "+f"(d[32]), "+f"(d[33]), "+f"(d[34]), "+f"(d[35]), "+f"(d[36]), "+f"(d[37]), "+f"(d[38]), "+f"(d[39]), "+f"(d[40]), "+f"(d[41]), "+f"(d[42]), "+f"(d[43]), "+f"(d[44]), "+f"(d[45]), "+f"(d[46]), "+f"(d[47]), "+f"(d[48]), "+f"(d[49]), "+f"(d[50]), "+f"(d[51]), "+f"(d[52]), "+f"(d[53]), "+f"(d[54]), "+f"(d[55]), "+f"(d[56]), "+f"(d[57]), "+f"(d[58]), "+f"(d[59]), "+f"(d[60]), "+f"(d[61]), "+f"(d[62]), "+f"(d[63]), "+f"(d[64]), "+f"(d[65]), "+f"(d[66]), "+f"(d[67]), "+f"(d[68]), "+f"(d[69]), "+f"(d[70]), "+f"(d[71]), "+f"(d[72]), "+f"(d[73]), "+f"(d[74]), "+f"(d[75]), "+f"(d[76]), "+f"(d[77]), "+f"(d[78]), "+f"(d[79]), "+f"(d[80]), "+f"(d[81]), "+f"(d[82]), "+f"(d[83]), "+f"(d[84]), "+f"(d[85]), "+f"(d[86]), "+f"(d[87]), "+f"(d[88]), "+f"(d[89]), "+f"(d[90]), "+f"(d[91]), "+f"(d[92]), "+f"(d[93]), "+f"(d[94]), "+f"(d[95])
    : "r"(a[0]), "r"(a[1]), "r"(a[2]), "r"(a[3]), "l"(db), "r"(sd), "n"(TB));
}

template<int TB> __device__ __forceinline__ void wgmma_rs_n32(float* d, const uint32_t* a, uint64_t db, int sd) {
  asm volatile("{\n.reg .pred p;\nsetp.ne.b32 p, %21, 0;\n"
    "wgmma.mma_async.sync.aligned.m64n32k16.f32.bf16.bf16 {%0, %1, %2, %3, %4, %5, %6, %7, %8, %9, %10, %11, %12, %13, %14, %15}, {%16, %17, %18, %19}, %20, p, 1, 1, %22;\n}"
    : "+f"(d[0]), "+f"(d[1]), "+f"(d[2]), "+f"(d[3]), "+f"(d[4]), "+f"(d[5]), "+f"(d[6]), "+f"(d[7]), "+f"(d[8]), "+f"(d[9]), "+f"(d[10]), "+f"(d[11]), "+f"(d[12]), "+f"(d[13]), "+f"(d[14]), "+f"(d[15])
    : "r"(a[0]), "r"(a[1]), "r"(a[2]), "r"(a[3]), "l"(db), "r"(sd), "n"(TB));
}

template<int TB> __device__ __forceinline__ void wgmma_rs_n64(float* d, const uint32_t* a, uint64_t db, int sd) {
  asm volatile("{\n.reg .pred p;\nsetp.ne.b32 p, %37, 0;\n"
    "wgmma.mma_async.sync.aligned.m64n64k16.f32.bf16.bf16 {%0, %1, %2, %3, %4, %5, %6, %7, %8, %9, %10, %11, %12, %13, %14, %15, %16, %17, %18, %19, %20, %21, %22, %23, %24, %25, %26, %27, %28, %29, %30, %31}, {%32, %33, %34, %35}, %36, p, 1, 1, %38;\n}"
    : "+f"(d[0]), "+f"(d[1]), "+f"(d[2]), "+f"(d[3]), "+f"(d[4]), "+f"(d[5]), "+f"(d[6]), "+f"(d[7]), "+f"(d[8]), "+f"(d[9]), "+f"(d[10]), "+f"(d[11]), "+f"(d[12]), "+f"(d[13]), "+f"(d[14]), "+f"(d[15]), "+f"(d[16]), "+f"(d[17]), "+f"(d[18]), "+f"(d[19]), "+f"(d[20]), "+f"(d[21]), "+f"(d[22]), "+f"(d[23]), "+f"(d[24]), "+f"(d[25]), "+f"(d[26]), "+f"(d[27]), "+f"(d[28]), "+f"(d[29]), "+f"(d[30]), "+f"(d[31])
    : "r"(a[0]), "r"(a[1]), "r"(a[2]), "r"(a[3]), "l"(db), "r"(sd), "n"(TB));
}

template<int TB> __device__ __forceinline__ void wgmma_rs_n80(float* d, const uint32_t* a, uint64_t db, int sd) {
  asm volatile("{\n.reg .pred p;\nsetp.ne.b32 p, %45, 0;\n"
    "wgmma.mma_async.sync.aligned.m64n80k16.f32.bf16.bf16 {%0, %1, %2, %3, %4, %5, %6, %7, %8, %9, %10, %11, %12, %13, %14, %15, %16, %17, %18, %19, %20, %21, %22, %23, %24, %25, %26, %27, %28, %29, %30, %31, %32, %33, %34, %35, %36, %37, %38, %39}, {%40, %41, %42, %43}, %44, p, 1, 1, %46;\n}"
    : "+f"(d[0]), "+f"(d[1]), "+f"(d[2]), "+f"(d[3]), "+f"(d[4]), "+f"(d[5]), "+f"(d[6]), "+f"(d[7]), "+f"(d[8]), "+f"(d[9]), "+f"(d[10]), "+f"(d[11]), "+f"(d[12]), "+f"(d[13]), "+f"(d[14]), "+f"(d[15]), "+f"(d[16]), "+f"(d[17]), "+f"(d[18]), "+f"(d[19]), "+f"(d[20]), "+f"(d[21]), "+f"(d[22]), "+f"(d[23]), "+f"(d[24]), "+f"(d[25]), "+f"(d[26]), "+f"(d[27]), "+f"(d[28]), "+f"(d[29]), "+f"(d[30]), "+f"(d[31]), "+f"(d[32]), "+f"(d[33]), "+f"(d[34]), "+f"(d[35]), "+f"(d[36]), "+f"(d[37]), "+f"(d[38]), "+f"(d[39])
    : "r"(a[0]), "r"(a[1]), "r"(a[2]), "r"(a[3]), "l"(db), "r"(sd), "n"(TB));
}

template<int TB> __device__ __forceinline__ void wgmma_rs_n96(float* d, const uint32_t* a, uint64_t db, int sd) {
  asm volatile("{\n.reg .pred p;\nsetp.ne.b32 p, %53, 0;\n"
    "wgmma.mma_async.sync.aligned.m64n96k16.f32.bf16.bf16 {%0, %1, %2, %3, %4, %5, %6, %7, %8, %9, %10, %11, %12, %13, %14, %15, %16, %17, %18, %19, %20, %21, %22, %23, %24, %25, %26, %27, %28, %29, %30, %31, %32, %33, %34, %35, %36, %37, %38, %39, %40, %41, %42, %43, %44, %45, %46, %47}, {%48, %49, %50, %51}, %52, p, 1, 1, %54;\n}"
    : "+f"(d[0]), "+f"(d[1]), "+f"(d[2]), "+f"(d[3]), "+f"(d[4]), "+f"(d[5]), "+f"(d[6]), "+f"(d[7]), "+f"(d[8]), "+f"(d[9]), "+f"(d[10]), "+f"(d[11]), "+f"(d[12]), "+f"(d[13]), "+f"(d[14]), "+f"(d[15]), "+f"(d[16]), "+f"(d[17]), "+f"(d[18]), "+f"(d[19]), "+f"(d[20]), "+f"(d[21]), "+f"(d[22]), "+f"(d[23]), "+f"(d[24]), "+f"(d[25]), "+f"(d[26]), "+f"(d[27]), "+f"(d[28]), "+f"(d[29]), "+f"(d[30]), "+f"(d[31]), "+f"(d[32]), "+f"(d[33]), "+f"(d[34]), "+f"(d[35]), "+f"(d[36]), "+f"(d[37]), "+f"(d[38]), "+f"(d[39]), "+f"(d[40]), "+f"(d[41]), "+f"(d[42]), "+f"(d[43]), "+f"(d[44]), "+f"(d[45]), "+f"(d[46]), "+f"(d[47])
    : "r"(a[0]), "r"(a[1]), "r"(a[2]), "r"(a[3]), "l"(db), "r"(sd), "n"(TB));
}

template<int TA, int TB> __device__ __forceinline__ void wgmma_ss_n192(float* d, uint64_t da, uint64_t db, int sd) {
  asm volatile("{\n.reg .pred p;\nsetp.ne.b32 p, %98, 0;\n"
    "wgmma.mma_async.sync.aligned.m64n192k16.f32.bf16.bf16 {%0, %1, %2, %3, %4, %5, %6, %7, %8, %9, %10, %11, %12, %13, %14, %15, %16, %17, %18, %19, %20, %21, %22, %23, %24, %25, %26, %27, %28, %29, %30, %31, %32, %33, %34, %35, %36, %37, %38, %39, %40, %41, %42, %43, %44, %45, %46, %47, %48, %49, %50, %51, %52, %53, %54, %55, %56, %57, %58, %59, %60, %61, %62, %63, %64, %65, %66, %67, %68, %69, %70, %71, %72, %73, %74, %75, %76, %77, %78, %79, %80, %81, %82, %83, %84, %85, %86, %87, %88, %89, %90, %91, %92, %93, %94, %95}, %96, %97, p, 1, 1, %99, %100;\n}"
    : "+f"(d[0]), "+f"(d[1]), "+f"(d[2]), "+f"(d[3]), "+f"(d[4]), "+f"(d[5]), "+f"(d[6]), "+f"(d[7]), "+f"(d[8]), "+f"(d[9]), "+f"(d[10]), "+f"(d[11]), "+f"(d[12]), "+f"(d[13]), "+f"(d[14]), "+f"(d[15]), "+f"(d[16]), "+f"(d[17]), "+f"(d[18]), "+f"(d[19]), "+f"(d[20]), "+f"(d[21]), "+f"(d[22]), "+f"(d[23]), "+f"(d[24]), "+f"(d[25]), "+f"(d[26]), "+f"(d[27]), "+f"(d[28]), "+f"(d[29]), "+f"(d[30]), "+f"(d[31]), "+f"(d[32]), "+f"(d[33]), "+f"(d[34]), "+f"(d[35]), "+f"(d[36]), "+f"(d[37]), "+f"(d[38]), "+f"(d[39]), "+f"(d[40]), "+f"(d[41]), "+f"(d[42]), "+f"(d[43]), "+f"(d[44]), "+f"(d[45]), "+f"(d[46]), "+f"(d[47]), "+f"(d[48]), "+f"(d[49]), "+f"(d[50]), "+f"(d[51]), "+f"(d[52]), "+f"(d[53]), "+f"(d[54]), "+f"(d[55]), "+f"(d[56]), "+f"(d[57]), "+f"(d[58]), "+f"(d[59]), "+f"(d[60]), "+f"(d[61]), "+f"(d[62]), "+f"(d[63]), "+f"(d[64]), "+f"(d[65]), "+f"(d[66]), "+f"(d[67]), "+f"(d[68]), "+f"(d[69]), "+f"(d[70]), "+f"(d[71]), "+f"(d[72]), "+f"(d[73]), "+f"(d[74]), "+f"(d[75]), "+f"(d[76]), "+f"(d[77]), "+f"(d[78]), "+f"(d[79]), "+f"(d[80]), "+f"(d[81]), "+f"(d[82]), "+f"(d[83]), "+f"(d[84]), "+f"(d[85]), "+f"(d[86]), "+f"(d[87]), "+f"(d[88]), "+f"(d[89]), "+f"(d[90]), "+f"(d[91]), "+f"(d[92]), "+f"(d[93]), "+f"(d[94]), "+f"(d[95])
    : "l"(da), "l"(db), "r"(sd), "n"(TA), "n"(TB));
}

template<int TA, int TB> __device__ __forceinline__ void wgmma_ss_n8(float* d, uint64_t da, uint64_t db, int sd) {
  asm volatile("{\n.reg .pred p;\nsetp.ne.b32 p, %6, 0;\n"
    "wgmma.mma_async.sync.aligned.m64n8k16.f32.bf16.bf16 {%0, %1, %2, %3}, %4, %5, p, 1, 1, %7, %8;\n}"
    : "+f"(d[0]), "+f"(d[1]), "+f"(d[2]), "+f"(d[3])
    : "l"(da), "l"(db), "r"(sd), "n"(TA), "n"(TB));
}

constexpr int S_ = 2048, D_ = 640, F_ = 1536;

struct Scr {
  uint32_t flag[320 * 8];
  uint32_t epoch[256];
  uint4 cbsb[2 * 128];
  uint4 pad[64];
  bf16 cimg[8 * 6 * 512];
  uint2 st2[S_];
  uint2 mc[3 * 128 * 4];
  uint2 modP[8 * 3840];
  bf16 kvT[D_ * S_];
  bf16 zT[D_ * S_];
  bf16 x1T[D_ * S_];
  bf16 AT[D_ * S_];
  uint4 PP[128 * 1280];
};
__device__ __align__(1024) Scr g_scr;
__device__ __forceinline__ uint32_t clk() { uint32_t c; asm volatile("mov.u32 %0, %%clock;" : "=r"(c) :: "memory"); return c; }
#define DEVSM 0
#define STAMP(id)
#define STAMPIF(c, id)
constexpr int FL_R = 0, FL_C = 104;
#define FD0 600
#define FD1 600
#define MD0 600
#define MD1 600
#define CD 600
#define SD 1000

constexpr int SM_X = 1024, SM_EXT = 21504, SM_SMALL = 29696, SM_STAT = 30720, SM_CB = 32768, SM_RING = 34816, SM_TOTAL = SM_RING + 6 * 32768;
constexpr int SMALL_S = 0, SMALL_MOD = 192, SMALL_LN = 224, SMALL_RED = 320, SMALL_GB = 848, SMALL_DUMMY = 1008, SMALL_E = 1012, SMALL_TS = 160;
constexpr int JOB_SZ = 10880, JOB_V = 5760, R_X = 5 * 32768;
constexpr int K1OFF = 4672, KSZ = 9472, CSZ = KSZ + 4224;
enum { B_KJ = 0, B_X = 5, B_FB = 10, B_PEER = 20, B_RECV = 24, B_EXT = 28, B_X1 = 29, B_MF = 33, B_BOX = 38, B_FP = 43, B_GB = 44, B_ST0 = 45,
       B_F1 = 48, B_E1 = 54, B_EB = 60,
       B_Z = 80, B_K = 85, B_EW = 88, B_ST2 = 94, B_XF = 95, B_LN = 96, B_KVS = 98, B_BD = 99,
       B_B = 106, B_S = 112 };
__device__ __forceinline__ uint32_t chan_base(uint32_t sb, int ch) { return sb + SM_RING + (2 + (ch >> 1)) * 32768 + (ch & 1) * CSZ; }
__device__ __forceinline__ uint32_t box_base(uint32_t sb, int cls) {
  return sb + SM_RING + (cls == 0 ? 55296 : cls == 1 ? 4 * 32768 + 14336 : cls == 2 ? 5 * 32768 + 22528 : 5 * 32768 + 12288);
}

struct Params { CUtensorMap mS, mX, mWm, mK, mV, mG, mU, mD, mO, mO2; };

__device__ __forceinline__ void flag_add(Scr* G, int id) { asm volatile("red.relaxed.gpu.global.add.u32 [%0], 1;" ::"l"(G->flag + 8 * id) : "memory"); }
__device__ __forceinline__ uint32_t rdback(const void* p) { uint32_t v; asm volatile("ld.relaxed.gpu.global.u32 %0, [%1];" : "=r"(v) : "l"(p) : "memory"); return v; }
__device__ __forceinline__ void st_tag(uint2* p, uint32_t v, uint32_t t) { asm volatile("st.relaxed.gpu.global.v2.u32 [%0], {%1, %2};" ::"l"(p), "r"(v), "r"(t) : "memory"); }
__device__ __forceinline__ void spin(uint32_t t, uint32_t d) { if (d) while (clk() - t < d); }
__device__ __forceinline__ uint2 ld_tag(const uint2* p) { uint2 v; asm volatile("ld.relaxed.gpu.global.v2.u32 {%0, %1}, [%2];" : "=r"(v.x), "=r"(v.y) : "l"(p) : "memory"); return v; }
__device__ __forceinline__ uint4 ld_tag2(const uint2* p) {
  uint4 v;
  asm volatile("ld.relaxed.gpu.global.v4.u32 {%0, %1, %2, %3}, [%4];" : "=r"(v.x), "=r"(v.y), "=r"(v.z), "=r"(v.w) : "l"(p) : "memory");
  return v;
}
__device__ __forceinline__ void rdwait(uint32_t sb, uint32_t v) { sts32(sb + SM_SMALL + SMALL_DUMMY, v); }
__device__ __forceinline__ void fence_async_s() { asm volatile("fence.proxy.async.shared::cta;" ::: "memory"); }
__device__ __forceinline__ void fence_async_g() { asm volatile("fence.proxy.async.global;" ::: "memory"); }
__device__ __forceinline__ void bulk_done() { asm volatile("cp.async.bulk.commit_group;\n\tcp.async.bulk.wait_group 0;" ::: "memory"); }
__device__ __forceinline__ void flag_wait(Scr* G, int id, uint32_t target) {
  const uint32_t* p = G->flag + 8 * id;
#pragma unroll 1
  for (int i = 0; i < (1 << 20); i++) {
    uint32_t v;
    asm volatile("ld.relaxed.gpu.global.u32 %0, [%1];" : "=r"(v) : "l"(p) : "memory");
    if ((int)(v - target) >= 0) return;
  }
  __trap();
}
__device__ __forceinline__ int tbase(int pb) { return 127 - (32 * (pb >> 6) + 8 * (pb & 8) + 4 * ((2 * (pb & 3) - ((pb >> 2) & 1)) & 7) + ((pb >> 4) & 3)); }
__device__ __forceinline__ uint32_t hmul(uint32_t a, uint32_t b) { uint32_t d; asm("mul.rn.bf16x2 %0, %1, %2;" : "=r"(d) : "r"(a), "r"(b)); return d; }
__device__ __forceinline__ uint32_t hadd(uint32_t a, uint32_t b) { uint32_t d; asm("add.rn.bf16x2 %0, %1, %2;" : "=r"(d) : "r"(a), "r"(b)); return d; }
__device__ __forceinline__ uint32_t hsub(uint32_t a, uint32_t b) { uint32_t d; asm("sub.rn.bf16x2 %0, %1, %2;" : "=r"(d) : "r"(a), "r"(b)); return d; }
__device__ __forceinline__ uint32_t hfma(uint32_t a, uint32_t b, uint32_t c) { uint32_t d; asm("fma.rn.bf16x2 %0, %1, %2, %3;" : "=r"(d) : "r"(a), "r"(b), "r"(c)); return d; }
__device__ __forceinline__ uint32_t pack2(float lo, float hi) { uint32_t d; asm("cvt.rn.bf16x2.f32 %0, %1, %2;" : "=r"(d) : "f"(hi), "f"(lo)); return d; }
__device__ __forceinline__ float blo(uint32_t v) { return __uint_as_float(v << 16); }
__device__ __forceinline__ float bhi(uint32_t v) { return __uint_as_float(v & 0xffff0000u); }
__device__ __forceinline__ float rbf(float v) { return blo(pack2(v, 0.f)); }
template <int N> __device__ __forceinline__ void bfly(float* v, int mask, bool up) {
#pragma unroll
  for (int i = 0; i < N / 2; i++) {
    float send = up ? v[i] : v[i + N / 2], keep = up ? v[i + N / 2] : v[i];
    v[i] = keep + __shfl_xor_sync(0xffffffffu, send, mask);
  }
}
__device__ __forceinline__ int mod_col(int idx) {
  if (idx < 40) { int v = (idx >> 1) & 3; return (v == 3 ? 4 : v) * 640 + 128 * (idx >> 3) + 64 * (idx & 1); }
  int l = idx - 40;
  return l < 10 ? 3 * 640 + 64 * l : 5 * 640 + 64 * (l - 10);
}

__device__ __forceinline__ void kv_load(const bf16* gk, const bf16* gv, const bf16* gs, uint32_t sb, int b, int r, int tid) {
  const int row = tid >> 2, col = 128 * r + 32 * (b & 3);
  const uint32_t a = sb + SM_RING + r * JOB_SZ + (row >> 3) * 80 + (tid & 3) * 16, ak = a + (row & 7) * 720, av = a + (row & 7) * 640 + JOB_V;
  const int o = (64 * (b >> 2) + row) * D_ + col + 8 * (tid & 3);
  cp16(ak + 80, gk + o);
  cp16(ak + 400, gk + o + 32 * D_);
  cp16(av, gv + o);
  cp16(av + 320, gv + o + 32 * D_);
  if (tid < 12) cp16z(ak + 3600, gk + (b < 4 ? o : o - 3 * D_), b < 4 ? 0 : 16);
  else if (tid >= 112) cp16(sb + SM_CB + 256 * r + 16 * (tid - 112), gs + 4 * col + 8 * (tid - 112));
}
__device__ __forceinline__ void load_kv(const Params& P, const bf16* gs, uint32_t sb, int b, int r) {
  const uint32_t a = sb + SM_RING + r * JOB_SZ, bar = sb + 8 * (B_B + r);
  const int cg = 4 * r + (b & 3);
  mbar_expect(bar, JOB_SZ + 256);
  tma4d(a, &P.mK, 0, cg, 8 * (b >> 2) - 1, 0, bar);
  tma4d(a + JOB_V, &P.mV, 0, cg, 8 * (b >> 2), 0, bar);
  bulk_g2s(sb + SM_CB + 256 * r, gs + 128 * cg, 256, bar);
}
__device__ __forceinline__ uint4* kv_dst(Scr* G, int b, int r, int tid) {
  return (uint4*)(G->kvT + (128 * r + 32 * (b & 3) + 8 * (tid >> 5) + 2 * (tid & 3)) * S_ + 2040 - 64 * (b >> 2)) - ((tid >> 2) & 7);
}
__device__ __forceinline__ void kv_job(Scr* G, uint32_t sb, int b, int r, int tid) {
  const int cp = 4 * (tid >> 5) + (tid & 3);
  const uint32_t ka = sb + SM_RING + r * JOB_SZ + ((tid >> 2) & 7) * 80 + cp * 4;
  mbar_wait(sb + 8 * (B_B + r), 0);
  STAMPIF(tid == 0, 56 + r);
  const uint4 sk = lds128(sb + SM_CB + 256 * r + 16 * cp);
  const uint32_t s0 = __byte_perm(sk.x, sk.z, 0x5410), s1 = __byte_perm(sk.x, sk.z, 0x7632), s2 = __byte_perm(sk.y, sk.w, 0x5410), s3 = __byte_perm(sk.y, sk.w, 0x7632);
  uint32_t kk[11], o[8];
#pragma unroll
  for (int i = 0; i < 11; i++) kk[i] = lds32(ka + 720 * ((i + 5) & 7) + 80 * ((i + 5) >> 3));
#pragma unroll
  for (int i = 0; i < 8; i++) {
    uint32_t v = lds32(ka + JOB_V + 640 * i);
    uint32_t a = hadd(hadd(hadd(hmul(kk[i], s3), hmul(kk[i + 1], s2)), hmul(kk[i + 2], s1)), hmul(kk[i + 3], s0));
    o[i] = hmul(a, v);
  }
  uint4* dst = kv_dst(G, b, r, tid);
  dst[0] = make_uint4(__byte_perm(o[7], o[6], 0x5410), __byte_perm(o[5], o[4], 0x5410), __byte_perm(o[3], o[2], 0x5410), __byte_perm(o[1], o[0], 0x5410) | 1);
  dst[256] = make_uint4(__byte_perm(o[7], o[6], 0x7632), __byte_perm(o[5], o[4], 0x7632), __byte_perm(o[3], o[2], 0x7632), __byte_perm(o[1], o[0], 0x7632) | 1);
  if (tid == 0) { sts32(sb + SM_SMALL + SMALL_TS + 4 * r, clk()); mbar_arrive(sb + 8 * (B_KJ + r)); }
}
__device__ __forceinline__ void u_wait(uint4& a, uint4& c, const void* p) {
  asm volatile("{\n.reg .pred p;\n.reg .b32 t, n;\nmov.b32 n, 0;\n"
               "L0:\nlop3.b32 t, %3, %7, 1, 0x80;\nsetp.eq.b32 p, t, 0;\nvote.sync.any.pred p, p, 0xffffffff;\n@!p bra.uni L1;\n"
               "ld.relaxed.gpu.global.v4.u32 {%0, %1, %2, %3}, [%8];\nld.relaxed.gpu.global.v4.u32 {%4, %5, %6, %7}, [%8+2048];\n"
               "add.u32 n, n, 1;\nsetp.lt.u32 p, n, 1000000;\n@p bra.uni L0;\ntrap;\nL1:\n}"
               : "+r"(a.x), "+r"(a.y), "+r"(a.z), "+r"(a.w), "+r"(c.x), "+r"(c.y), "+r"(c.z), "+r"(c.w) : "l"(p) : "memory");
}
__device__ __forceinline__ void mod_put(Scr* G, const float* a, int b, int cls, uint32_t e1, int tid) {
  if ((tid & 3) == 0) {
    uint2* p = G->modP + (b & 7) * 3840 + mod_col(16 * cls + (b >> 3)) + 16 * (tid >> 5) + ((tid >> 2) & 7);
    st_tag(p, __float_as_uint(a[0]), e1);
    st_tag(p + 8, __float_as_uint(a[2]), e1);
  }
}
__device__ __forceinline__ void mod_box(Scr* G, uint32_t sb, int b, int cls, uint32_t e1, int tid) {
  float a[4];
  const uint64_t da = mkdesc(box_base(sb, cls), 4096, 1024, 1), db = mkdesc(sb + SM_SMALL + SMALL_S, 16, 128, 0);
  mbar_wait(sb + 8 * (B_BOX + cls), 0);
  wg_fence();
#pragma unroll
  for (int n = 0; n < 5; n++) wgmma_ss_n8<1, 0>(a, da + 128 * n, db + 2 * n, n != 0);
  wg_commit();
  wg_wait<0>();
#pragma unroll
  for (int i = 0; i < 4; i++) asm volatile("" : "+f"(a[i])::"memory");
  mod_put(G, a, b, cls, e1, tid);
}
__device__ __forceinline__ float sum8(float a) {
  a += __shfl_xor_sync(0xffffffffu, a, 4);
  a += __shfl_xor_sync(0xffffffffu, a, 2);
  a += __shfl_xor_sync(0xffffffffu, a, 1);
  return rbf(a);
}
__device__ __forceinline__ void mod_poll(const uint2* p, int o, uint32_t e1, float& r0, float& r1, uint32_t sb = 0) {
  uint2 a, c;
#pragma unroll 1
  for (int i = 0;; i++) {
    a = ld_tag(p); c = ld_tag(p + o);
    const bool ok = __all_sync(0xffffffffu, a.y == e1 && c.y == e1);
    STAMPIF(sb && i < 2, 84 + i);
    if (ok) break;
    if (i > (1 << 20)) __trap();
  }
  STAMPIF(sb, 72);
  r0 = sum8(__uint_as_float(a.x)); r1 = sum8(__uint_as_float(c.x));
}
__device__ __forceinline__ float mod_fin(Scr* G, uint32_t sb, int b, int r0, uint32_t e1, int lane) {
  const int v = lane >> 3, c = (v == 3 ? 4 : v) * 640 + 128 * r0;
  float t0, t1;
  mbar_wait(sb + 8 * (B_BD + (r0 >> 1)), 0);
  STAMPIF(r0 == 0, 71);
  spin(clk(), r0 ? FD1 : FD0);
  mod_poll(G->modP + (lane & 7) * 3840 + c + b, r0 < 4 ? 128 : 3 * 640 + 128 * v - c, e1, t0, t1, r0 == 0 ? sb : 0);
  const float t = ((lane & 1) ? t1 : t0) + ((v & 1) ? 1.f : 0.f);
  const uint32_t lo = pack2(t, __shfl_xor_sync(0xffffffffu, t, 8)), hi = __shfl_xor_sync(0xffffffffu, lo, 16);
  if (lane < 4) {
    st_tag(G->mc + (64 * r0 + b) * 4 + lane, ((lane >> 1) ^ e1) & 1 ? 0 : ~lo, hi);
    sts32(sb + SM_SMALL + SMALL_MOD + 4 * (r0 + (lane & 1)), hi);
  }
  spin(clk(), r0 ? MD1 : MD0);
  __syncwarp();
  if (lane == 0) mbar_arrive(sb + 8 * (B_MF + (r0 >> 1)));
  return t1;
}
__device__ __forceinline__ void load_x(const Params& P, uint32_t sb, int b, int h) {
  const uint32_t bar = sb + 8 * (B_X + h);
  mbar_expect(bar, 10240);
  tma5d(sb + SM_X + h * 10240, &P.mX, 0, 0, 0, 5 * h, tbase(b), bar);
}
__device__ __forceinline__ uint32_t x_addr(uint32_t sb, int w, int lane) {
  const int rho = 15 - (4 * (lane >> 3) + 2 * (lane & 1) + ((lane >> 1) & 1));
  return sb + SM_X + (w >> 1) * 2048 + rho * 128 + (((2 * (w & 1) + (lane & 4)) ^ (rho & 7)) << 4);
}
__device__ __forceinline__ void ln1_job(uint32_t sb, int tid) {
  const uint32_t xr = sb + SM_X + 16 * tid;
  float pv, s1 = 0.f, s2 = 0.f, s3 = 0.f;
#pragma unroll 1
  for (int h = 0; h < 2; h++) {
    mbar_wait(sb + 8 * (B_X + h), 0);
    STAMPIF(tid == 0, 25);
    pv = blo(lds32(xr & ~127u));
#pragma unroll
    for (int n = 0; n < 5; n++) {
      const uint4 v = lds128(xr + 10240 * h + 2048 * n);
      const uint32_t u[4] = {v.x, v.y, v.z, v.w};
#pragma unroll
      for (int j = 0; j < 4; j++) {
        const float a = blo(u[j]) - pv, c = bhi(u[j]) - pv;
        s1 += a + c; s2 += a * a; s3 += c * c;
      }
    }
  }
  s2 += s3;
#pragma unroll
  for (int o = 1; o < 8; o <<= 1) { s1 += __shfl_xor_sync(0xffffffffu, s1, o); s2 += __shfl_xor_sync(0xffffffffu, s2, o); }
  const float mu = s1 * (1.f / D_), var = fmaxf(s2 * (1.f / D_) - mu * mu, 0.f);
  const float rs = __frcp_rn(rbf(__fsqrt_rn(rbf(rbf(var) + 1e-5f))));
  const int i = 15 - (tid >> 3), j = tid & 7;
  const float t0 = (j & 2) ? rs - rbf(rs) : pv + mu;
  if (j < 3) sts16(sb + SM_SMALL + SMALL_LN + 32 * j + 16 * (i & 1) + (i & 14), pack2((j & 1) ? rs : t0, 0.f));
  __syncwarp();
  if ((tid & 31) == 0) mbar_arrive(sb + 8 * B_LN);
  STAMPIF(tid == 0, 75);
}
__device__ __forceinline__ void load_box(const Params& P, uint32_t sb, int b, int cls) {
  const uint32_t bar = sb + 8 * (B_BOX + cls);
  mbar_expect(bar, 10240);
  tma2d(box_base(sb, cls), &P.mWm, mod_col(16 * cls + (b >> 3)), 80 * (b & 7), bar);
}
__device__ __forceinline__ void load_ssm(const Params& P, uint32_t sb, int b, int r) {
  const uint32_t bar = sb + 8 * (B_S + r);
  mbar_expect(bar, 16 * 288);
  tma3d(chan_base(sb, r) + 128, &P.mS, 0, 0, 128 * r + b, bar);
}
__device__ __forceinline__ void k1_job(uint32_t sb, int r, int tid) {
  const uint32_t a0 = chan_base(sb, r) + 128 + 16 * tid + 32 * (tid >> 4);
  mbar_wait(sb + 8 * (B_S + r), 0);
#pragma unroll
  for (int n = 0; n < 2; n++) {
    const uint32_t a = a0 + 2304 * n;
    const uint4 v = lds128(a);
    const uint32_t pv = lds32(a - ((tid & 15) ? 4 : 36));
    sts128(a + K1OFF, make_uint4(__byte_perm(pv, v.x, 0x5432), __byte_perm(v.x, v.y, 0x5432), __byte_perm(v.y, v.z, 0x5432), __byte_perm(v.z, v.w, 0x5432)));
  }
}

template <int ST> __device__ __forceinline__ void pp_send(uint4* p, const float* a, uint32_t tag) {
#pragma unroll
  for (int i = 0; i < 5; i++)
    p[ST * i] = make_uint4(pack2(a[8 * i], a[8 * i + 1]), pack2(a[8 * i + 2], a[8 * i + 3]), pack2(a[8 * i + 4], a[8 * i + 5]), (pack2(a[8 * i + 6], a[8 * i + 7]) & ~1u) | tag);
}
template <int ST> __device__ __forceinline__ void pp_load(uint4* f, const uint4* p) {
#pragma unroll
  for (int i = 0; i < 5; i++) f[i] = ld_tag2((const uint2*)(p + ST * i));
}
template <int ST> __device__ __forceinline__ void pp_wait(uint4* f, const uint4* p, uint32_t tag) {
  asm volatile("{\n.reg .pred p;\n.reg .b32 t, n;\nmov.b32 n, 0;\n"
               "L0:\nxor.b32 t, %3, %21;\nlop3.b32 t, t, %7, %21, 0xf6;\nlop3.b32 t, t, %11, %21, 0xf6;\nlop3.b32 t, t, %15, %21, 0xf6;\nlop3.b32 t, t, %19, %21, 0xf6;\n"
               "and.b32 t, t, 1;\nsetp.ne.b32 p, t, 0;\nvote.sync.any.pred p, p, 0xffffffff;\n@!p bra.uni L1;\n"
               "ld.relaxed.gpu.global.v4.u32 {%0, %1, %2, %3}, [%20];\nld.relaxed.gpu.global.v4.u32 {%4, %5, %6, %7}, [%20+%22];\n"
               "ld.relaxed.gpu.global.v4.u32 {%8, %9, %10, %11}, [%20+%23];\nld.relaxed.gpu.global.v4.u32 {%12, %13, %14, %15}, [%20+%24];\n"
               "ld.relaxed.gpu.global.v4.u32 {%16, %17, %18, %19}, [%20+%25];\n"
               "add.u32 n, n, 1;\nsetp.lt.u32 p, n, 1000000;\n@p bra.uni L0;\ntrap;\nL1:\n}"
               : "+r"(f[0].x), "+r"(f[0].y), "+r"(f[0].z), "+r"(f[0].w), "+r"(f[1].x), "+r"(f[1].y), "+r"(f[1].z), "+r"(f[1].w), "+r"(f[2].x), "+r"(f[2].y),
                 "+r"(f[2].z), "+r"(f[2].w), "+r"(f[3].x), "+r"(f[3].y), "+r"(f[3].z), "+r"(f[3].w), "+r"(f[4].x), "+r"(f[4].y), "+r"(f[4].z), "+r"(f[4].w)
               : "l"(p), "r"(tag), "n"(16 * ST), "n"(32 * ST), "n"(48 * ST), "n"(64 * ST) : "memory");
}
__device__ __forceinline__ void pp_add(float* a, const uint4* f, const uint4* e, bool first) {
#pragma unroll
  for (int i = 0; i < 5; i++) {
    const uint32_t v[4] = {f[i].x, f[i].y, f[i].z, f[i].w}, u[4] = {e[i].x, e[i].y, e[i].z, e[i].w};
#pragma unroll
    for (int j = 0; j < 8; j++) a[8 * i + j] = ((j & 1) ? bhi(v[j >> 1]) : blo(v[j >> 1])) + (!first ? a[8 * i + j] : (j & 1) ? bhi(u[j >> 1]) : blo(u[j >> 1]));
  }
}
__device__ __forceinline__ int out_col(int s, int n) { return 320 * (s & 1) + (n < 4 ? 32 * (s & 6) + 16 * n : 256 + 8 * (s & 6)); }
__device__ __forceinline__ void l2_prefetch(const void* p, int bytes) { asm volatile("cp.async.bulk.prefetch.L2.global [%0], %1;" ::"l"(p), "r"(bytes) : "memory"); }
__device__ __forceinline__ void pf_line(const void* p) { asm volatile("prefetch.global.L2 [%0];" ::"l"(p) : "memory"); }
__device__ __forceinline__ int role(int bx) {
  const int c = bx >> 1, d = c - 36, q = (d * 37) >> 8, k = d - 7 * q;
  const int rank = c < 4 ? 12 + c : c < 36 ? ((c - 4) & 7) * 8 + ((c - 4) >> 3) : (k ? k + 1 : 0) * 8 + 4 + q;
  return 8 * (rank & 15) + 2 * (rank >> 4) + (bx & 1);
}
enum { K_KV, K_SSM, K_BOX, K_PW, K_PD, K_PKV, K_PSSM, K_PBOX, K_W, K_X, K_ST, K_END = 15 };
#define E(t, bar, kind, r) ((t) << 16 | (bar) << 8 | (kind) << 4 | (r))
#define SCHED E(2800, 255, K_BOX, 0), E(3700, 255, K_KV, 2), E(4400, 255, K_SSM, 2), E(4800, 255, K_KV, 3), E(5500, 255, K_X, 0), E(6400, 255, K_X, 1), \
              E(7200, 255, K_SSM, 3), E(7600, 255, K_KV, 4), E(8300, 255, K_SSM, 4), E(8600, 255, K_BOX, 1), E(9500, 255, K_PW, 0), E(10100, 255, K_BOX, 2), \
              E(11000, 255, K_BOX, 3)
#define XPF 2
#define XBOTH 0
#define AUXP 0xfedcb30217ull
#define K1W 1
constexpr int aux_last(int mask) { int r = 0; for (uint64_t p = AUXP; p; p >>= 4) if ((mask >> (p & 15)) & 1) r = p & 15; return r; }
constexpr int kLastKv = aux_last(0x8e);
#define XC0 1
#define XI 013020000
#define PWM 0x3c
#define STM 0x7c0
#define PDM 0x3800
#define KVP0 1
#define KVP1 2
#define KV1L 0
#define CVT 1
#define UPOS 4
#define UD 1000
#define PL1 12
#define PL2 14
#define SJ(h) (3 * (h))
constexpr uint32_t kSched[] = {SCHED, E(0, 255, K_END, 0)};
struct In { const bf16 *k, *v, *sk, *Wg, *Wu, *Wd, *ss; };
__device__ __forceinline__ void load_w(const Params& P, uint32_t sb, int s, int it) {
  const int st = it % 5;
  mbar_wait(sb + 8 * (B_E1 + st), (it / 5) & 1);
  const uint32_t a = sb + SM_RING + st * 32768 + 8192, fb = sb + 8 * (B_F1 + st);
  mbar_expect(fb, 24576);
#pragma unroll
  for (int j = 0; j < 3; j++) {
    tma2d(a + 8192 * j, &P.mG, 192 * s + 64 * j, 32 * it, fb);
    tma2d(a + 8192 * j + 4096, &P.mU, 192 * s + 64 * j, 32 * it, fb);
  }
}

template <int I> __device__ __forceinline__ int sched_run(const Params& P, const In& in, uint32_t sb, int b, int lane, uint32_t t_0) {
  constexpr uint32_t e = kSched[I];
  constexpr int kind = (e >> 4) & 15, r = e & 15, bar = (e >> 8) & 255;
  if constexpr (kind == K_END) return 0;
  else {
    if constexpr ((e >> 16) != 0) while (clk() - t_0 < (e >> 16));
    if (bar != 255 && (bar != B_BOX + 3 || b < 96)) mbar_wait(sb + 8 * bar, 0);
    if (kind == K_PKV) {
      const bf16* kvp = (lane < 16 ? in.k : in.v) + (16 * b + (lane & 15)) * D_ + 128 * r;
      pf_line(kvp); pf_line(kvp + 64);
    } else {
      if (elect()) {
        if (kind == K_KV) load_kv(P, in.sk, sb, b, r);
        if (kind == K_X) load_x(P, sb, b, r);
        if (kind == K_SSM) load_ssm(P, sb, b, r);
        if (kind == K_BOX && (r < 3 || b < 96)) load_box(P, sb, b, r);
        if (kind == K_PW) { l2_prefetch(in.Wg + (128 * r + b) * F_, 2 * F_); l2_prefetch(in.Wu + (128 * r + b) * F_, 2 * F_); }
        if (kind == K_PSSM) l2_prefetch(in.ss + (128 * r + b) * S_, 4096);
        if (kind == K_PBOX && (r < 3 || b < 96)) tma_prefetch2d(&P.mWm, mod_col(16 * r + (b >> 3)), 80 * (b & 7));
      }
      __syncwarp();
    }
    return sched_run<I + 1>(P, in, sb, b, lane, t_0) + (kind == K_PW);
  }
}

__global__ void __launch_bounds__(512, 1) fused_kernel(const bf16* __restrict__ gk, const bf16* __restrict__ gv, const bf16* __restrict__ gsk,
                                                       const bf16* __restrict__ gD, const bf16* __restrict__ gc, Scr* G, const bf16* gWg, const bf16* gWu,
                                                       const bf16* gWd, const bf16* gx, const bf16* gss, const __grid_constant__ Params P) {
  extern __shared__ __align__(1024) char smem_raw[];
  const uint32_t sb = smem_u32(smem_raw), ring = sb + SM_RING;
  const int b = role(blockIdx.x), m = b >> 3, s = b & 7;
  const uint32_t t_0 = clk();
  const int wg = __shfl_sync(0xffffffffu, threadIdx.x >> 7, 0);
  const int tid = threadIdx.x & 127, lane = tid & 31;
  const int w = __shfl_sync(0xffffffffu, tid >> 5, 0);
  if (wg < 2) {
    if (!KV1L || wg == 0) kv_load(gk, gv, gsk, sb, b, wg, tid);
  } else {
    if (wg == 2) {
      if (tid < 40) {
        int c = tid & 7;
        sts128(chan_base(sb, tid >> 3) + (c < 2 ? 80 + c * K1OFF : KSZ + 4096 + (c - 2) * 16), make_uint4(0, 0, 0, 0));
      }
    }
    if (elect()) {
      const int j = 4 * (3 - wg) + w - 1;
      if (j < 4) asm volatile("prefetch.tensormap [%0];" ::"l"(&P.mX + j) : "memory");
      if (j < 0) {
#pragma unroll
        for (int i = 0; i < 5; i++) mbar_init(sb + 8 * (B_S + i), 1);
        fence_async_s();
        if (XPF > 0) load_ssm(P, sb, b, 0);
        if (XPF > 1) load_ssm(P, sb, b, 1);
      } else {
        const int c = j < 3 ? 1 : j < 5 ? 2 : 4;
#pragma unroll
        for (int i = 0; i < 16; i++) mbar_init(sb + 128 * j + 8 * i, i < 10 || j < 6 ? c : i < 12 ? 128 : 1);
      }
    }
    fence_async_s();
  }
  __syncthreads();
  STAMPIF(threadIdx.x == 0, 55);

  if (wg < 2) {
    if (KV1L && wg == 1) kv_load(gk, gv, gsk, sb, b, wg, tid);
    cp_arrive(sb + 8 * (B_B + wg));
    asm volatile("setmaxnreg.inc.sync.aligned.u32 224;");
    STAMPIF(threadIdx.x == 0, 82);
    const int g = lane >> 2, q = lane & 3;
    if (wg == 1) bar_arrive(1, 256);
    uint32_t dv = *(const uint16_t*)(gD + 128 * wg + b);
#pragma unroll 1
    for (int pr = wg ? KVP1 : KVP0; pr; pr >>= 4) {
      kv_job(G, sb, b, (pr & 15) - 1, tid);
      STAMPIF(tid == 0, (pr & 15) < 3 ? pr & 15 : 19 + (pr & 15));
    }
    k1_job(sb, wg, tid);
    bar_sync(3 + wg, 128);
    if (tid < 2) mbar_arrive(sb + 8 * (B_E1 + tid));
    STAMPIF(threadIdx.x == 0, 79);
    {
      const int b0 = (g >> 1) & 1, b1 = g >> 2, u = q + 4 * b0 - w;
      const uint32_t fo = 128 + (g & 1) * K1OFF + 288 * b1 + 4 * u, fo0 = fo - (u < 0 ? 32 : 0);
      const uint32_t dsel = (b1 == 0 && u == 0) ? ((g & 1) ? 0x1044 : 0x4410) : 0x4444;
      const bool wrap = b0 && q == 0;
      const int src1 = b0 ? ((lane & 20) | ((q - 1) & 3)) : (lane | 8);
      const uint2* pu = (const uint2*)(G->kvT + (128 * wg + b) * S_ + 8 * tid);
      uint4 u0 = make_uint4(0, 0, 0, 0), u1 = u0;
      if (UPOS & 1) { u0 = ld_tag2(pu); u1 = ld_tag2(pu + 256); }
#pragma unroll 1
      for (int ch = wg; ch < 5; ch += 2) {
        const uint32_t base = chan_base(sb, ch);
        if (ch >= 2) {
          mbar_wait(sb + 8 * (B_K + ch - 2), 0);
          if (UPOS & 4) { u0 = ld_tag2(pu); u1 = ld_tag2(pu + 256); }
          mbar_wait(sb + 8 * (B_S + ch), 0);
        }
        const uint32_t fa = base + fo, fa0 = base + fo0;
        uint32_t af[16][4];
#pragma unroll
        for (int j = 0; j < 16; j++) {
          const int o = 64 * (j & 1) + 576 * (j >> 1);
          af[j][0] = lds32(((j & 1) ? fa : fa0) + o); af[j][1] = lds32(fa + o + 128); af[j][2] = lds32(fa + o + 32); af[j][3] = lds32(fa + o + 160);
        }
        af[0][0] = hadd(af[0][0], __byte_perm(dv, 0, dsel));
        STAMPIF(tid == 0, 40 + ch);
        u_wait(u0, u1, pu);
        sts128(base + KSZ + 16 * tid, u0);
        sts128(base + KSZ + 2048 + 16 * tid, u1);
        fence_async_s();
        pu += 128 * S_ / 2;
        float acc[128];
        const uint64_t db = mkdesc(base + KSZ, 32, 128, 0);
        bar_sync(1 + wg, 256);
        wg_fence();
        wgmma_rs_n64<0>(acc + 96, af[0], db + 192, 0);
        wgmma_rs_n192<0>(acc, af[0], db, 0);
        wgmma_rs_n64<0>(acc + 96, af[1], db + 196, 1);
        wgmma_rs_n192<0>(acc, af[1], db + 4, 1);
        wgmma_rs_n32<0>(acc + 96, af[2], db + 224, 1);
        wgmma_rs_n192<0>(acc, af[2], db + 32, 1);
        wgmma_rs_n32<0>(acc + 96, af[3], db + 228, 1);
        wgmma_rs_n192<0>(acc, af[3], db + 36, 1);
        wgmma_rs_n192<0>(acc, af[4], db + 64, 1);
        wgmma_rs_n192<0>(acc, af[5], db + 68, 1);
        wgmma_rs_n160<0>(acc, af[6], db + 96, 1);
        wgmma_rs_n160<0>(acc, af[7], db + 100, 1);
        if (CVT == 2) wg_commit();
        wgmma_rs_n128<0>(acc, af[8], db + 128, 1);
        wgmma_rs_n128<0>(acc, af[9], db + 132, 1);
        if (CVT == 1) wg_commit();
        wgmma_rs_n96<0>(acc, af[10], db + 160, 1);
        wgmma_rs_n96<0>(acc, af[11], db + 164, 1);
        if (CVT == 0) bar_arrive(2 - wg, 256);
        wgmma_rs_n64<0>(acc, af[12], db + 192, 1);
        wgmma_rs_n64<0>(acc, af[13], db + 196, 1);
        wgmma_rs_n32<0>(acc, af[14], db + 224, 1);
        wgmma_rs_n32<0>(acc, af[15], db + 228, 1);
        wg_commit();
        if (ch < 3) asm volatile("ld.global.nc.u16 %0, [%1];" : "=r"(dv) : "l"(gD + 128 * (ch + 2) + b));
        if (CVT) { wg_wait<1>(); if (ch < 4) bar_arrive(2 - wg, 256); }
        STAMPIF(tid == 0, 3 + ch);
        wg_wait<0>();
#pragma unroll
        for (int i = 0; i < 128; i++) asm volatile("" : "+f"(acc[i])::"memory");
        bar_sync(3 + wg, 128);
        if (tid <= (ch >> 2)) mbar_arrive(sb + 8 * (B_E1 + 2 + (ch >> 1)));
        if (ch < 3 && !(UPOS & 14)) { u0 = ld_tag2(pu); u1 = ld_tag2(pu + 256); }
        float S0[33], T[34];
#pragma unroll
        for (int i = 0; i < 31; i++) S0[i] = acc[4 * i] + acc[4 * i + 6];
        S0[31] = acc[124]; S0[32] = 0.f;
#pragma unroll
        for (int i = 0; i < 32; i++) {
          float s1 = i < 31 ? acc[4 * i + 1] + acc[4 * i + 7] : acc[125];
          T[i] = (wrap ? S0[i + 1] : S0[i]) + __shfl_sync(0xffffffffu, s1, src1);
        }
        T[32] = 0.f; T[33] = 0.f;
        uint4* pz = (uint4*)(G->zT + (128 * ch + b) * S_) + ((tid & 120) | (2 * q) | (g & 1));
#pragma unroll
        for (int h = 0; h < 2; h++) {
          float y[8];
#pragma unroll
          for (int mu = 0; mu < 8; mu++) y[mu] = (b1 ? T[4 * mu + 4 + h] : T[4 * mu + h]) + __shfl_xor_sync(0xffffffffu, T[4 * mu + 2 + h], 16);
          pz[128 * h] = make_uint4(pack2(y[0], y[1]), pack2(y[2], y[3]), pack2(y[4], y[5]), pack2(y[6], y[7]) | 1);
        }
        if (ch < 3 && (UPOS & 2)) { u0 = ld_tag2(pu); u1 = ld_tag2(pu + 256); }
        if (UPOS & 8) u0.w = 0;
        __syncwarp();
        if (lane == 0) mbar_arrive(sb + 8 * (B_Z + ch));
        STAMPIF(tid == 0, 8 + ch);
      }
    }
    uint32_t hh[96];
    {
      float ga[192];
      float* ua = ga + 96;
      const uint64_t da0 = mkdesc(ring + wg * 2048, 512, 256, 3), db0 = mkdesc(ring + 8192, 4096, 1024, 1);
      int st = 0, ph = 0, cls = XC0;
      uint32_t xi = wg ? XI | 0xff000000u : 0xffu;
      mbar_wait(sb + 8 * B_BD, 0);
#pragma unroll 1
      for (int it = 0; it < 20; it++) {
#pragma unroll 1
        for (; (xi & 31) == it; xi >>= 6, cls++) {
          if (cls < 3 || b < 96) {
            float bx[4];
            mbar_wait(sb + 8 * (B_BOX + cls), 0);
            if (cls == 4) mbar_wait(sb + 8 * B_ST0, 0);
            uint64_t xa = mkdesc(cls < 4 ? box_base(sb, cls) : sb + SM_EXT, 4096, 1024, 1);
            uint64_t xb = cls < 4 ? mkdesc(sb + SM_SMALL + SMALL_S, 16, 128, 0) : mkdesc(sb + SM_CB + 256, 32, 128, 0);
#pragma unroll 1
            for (int n = 0; n < (cls < 4 ? 5 : 20); n++) {
              wg_fence();
              wgmma_ss_n8<1, 0>(bx, xa, xb, n != 0);
              wg_commit();
              xa += cls == 4 && n == 3 ? 128 + (SM_RING + R_X - 8192 - SM_EXT) / 16 : 128;
              xb += cls < 4 ? 2 : 4;
            }
            wg_wait<0>();
#pragma unroll
            for (int i = 0; i < 4; i++) asm volatile("" : "+f"(bx[i])::"memory");
            if (cls < 4) mod_put(G, bx, b, cls, lds32(sb + SM_SMALL + SMALL_E), tid);
            else {
              const int row = (m < 6 ? 0 : 4) + q;
              uint16_t* dst = (uint16_t*)G->cimg + s * 3072 + (m % 6) * 512 + row * 64 + g;
#pragma unroll
              for (int j = 0; j < 2; j++) {
                const float c1 = __shfl_sync(0xffffffffu, bx[2 * j], lane & 28), c2 = __shfl_sync(0xffffffffu, bx[2 * j + 1], lane & 28);
                const float t = (lane & 2) ? c2 : c1, hi = rbf(t);
                dst[((2 * w + j) ^ row) << 3] = (uint16_t)pack2((lane & 1) ? t - hi : hi, 0.f);
              }
            }
          }
          __syncwarp();
          if (lane == 0) mbar_arrive(sb + 8 * (B_BD + cls));
          STAMPIF(tid == 0, cls == 1 ? 73 : cls == 2 ? 76 : cls == 3 ? 95 : 77);
        }
        mbar_wait(sb + 8 * (B_F1 + st), ph);
        STAMPIF(tid == 0 && it == 0, 13 + wg);
        STAMPIF(threadIdx.x == 0, 100 + it);
        const uint64_t da = da0 + st * 2048, db = db0 + st * 2048;
        wg_fence();
        wgmma_ss_n192<1, 1>(ga, da, db, it != 0);
        wgmma_ss_n192<1, 1>(ua, da, db + 768, it != 0);
        wgmma_ss_n192<1, 1>(ga, da + 256, db + 128, 1);
        wgmma_ss_n192<1, 1>(ua, da + 256, db + 128 + 768, 1);
        wg_commit();
        wg_wait<1>();
        if (it > 0 && tid == 0) mbar_arrive(sb + 8 * (B_E1 + (st == 0 ? 4 : st - 1)));
        if (++st == 5) { st = 0; ph ^= 1; }
      }
      STAMPIF(threadIdx.x == 0, 61);
      if (tid == 0) {
        mbar_wait(sb + 8 * (B_E1 + 5), 0);
        mbar_arrive_remote(mapa(sb + 8 * (B_PEER + 2 * wg), (b & 1) ^ 1));
      }
      mbar_wait(sb + 8 * B_EXT, 0);
      mbar_wait(sb + 8 * B_ST2, 0);
      const uint64_t de = mkdesc(sb + SM_EXT, 1024, 0, 1), ds = mkdesc(sb + SM_STAT + wg * 1024, 0, 128, 0);
      wg_fence();
      wgmma_ss_n192<0, 1>(ga, ds, de, 1);
      wgmma_ss_n192<0, 1>(ua, ds, de + 192, 1);
      wg_commit();
      wg_wait<1>();
      if (tid == 0) {
        mbar_arrive(sb + 8 * (B_E1 + 4));
        mbar_arrive_remote(mapa(sb + 8 * (B_PEER + 2 * wg + 1), (b & 1) ^ 1));
      }
      wg_wait<0>();
#pragma unroll
      for (int i = 0; i < 192; i++) asm volatile("" : "+f"(ga[i])::"memory");
      STAMPIF(tid == 0, 15 + wg);
#pragma unroll
      for (int i = 0; i < 48; i++) {
        const int j = 64 * (i >> 4) + 2 * (i & 15);
        hh[i] = pack2(ga[j] * ga[j + 32], ga[j + 1] * ga[j + 33]);
        asm volatile("" : "+r"(hh[i])::"memory");
      }
    }
    float acc[80];
    uint4 pf[15];
    const uint32_t tag = lds32(sb + SM_SMALL + SMALL_E) & 1;
    uint4* const pp[3] = {G->PP + 10240 * m + threadIdx.x, (uint4*)G->zT + 16 * m + 256 * (threadIdx.x >> 4) + (tid & 15), (uint4*)G->kvT + 10240 * m + threadIdx.x};
    {
      const uint32_t la = ring + wg * 2048 + tid * 16, ra = mapa(la, (b & 1) ^ 1), rb = mapa(sb + 8 * (B_RECV + 2 * wg), (b & 1) ^ 1);
#pragma unroll
      for (int h = 0; h < 16; h++) {
        const int gr = h >> 1, pe = gr < 4 ? gr >> 1 : gr & 1, ac = gr < 4 ? gr & 1 : gr / 6, d = gr < 4 ? ac + 1 : ac + 3;
        if (h == 0) mbar_wait(sb + 8 * B_FB, 0);
        if (h == 4) mbar_wait(sb + 8 * (B_FB + 5), 0);
        if (!(h & 1)) mbar_wait(sb + 8 * (B_FB + gr + (gr < 4 ? 1 : 2)), 0);
        if (gr == 2) {
          mbar_wait(sb + 8 * (B_RECV + 2 * wg + (h & 1)), 0);
#pragma unroll
          for (int j = 6 * (h & 1); j < 6 * (h & 1) + 6; j++) {
            const uint4 v = lds128(la + (j < 2 ? 5 : (j >> 1) - 1) * 32768 + (j & 1) * 4096);
            hh[48 + 4 * j] = v.x; hh[49 + 4 * j] = v.y; hh[50 + 4 * j] = v.z; hh[51 + 4 * j] = v.w;
          }
        }
        STAMPIF(threadIdx.x == 0 && h % 4 == 0, 121 + h / 4);
        const uint64_t db = mkdesc(ring + (gr & 3) * 32768 + 8192, (5 - pe - (gr & 3)) * 32768 + 16 * ((s + 2 * d) & 6), 1024, 1);
        wg_fence();
#pragma unroll
        for (int j = 6 * (h & 1); j < 6 * (h & 1) + 6; j++) wgmma_rs_n80<1>(acc + 40 * ac, hh + 48 * pe + 4 * j, db + 128 * j, pe || j);
        wg_commit();
        if (h < 4) {
#pragma unroll
          for (int j = SJ(h); j < SJ(h + 1); j++) {
            if (j == 0 || j == 10) mbar_wait(sb + 8 * (B_PEER + 2 * wg + j / 10), 0);
            st_async4(ra + (j < 2 ? 5 : (j >> 1) - 1) * 32768 + (j & 1) * 4096, hh + 4 * j, rb + 8 * (j / 6));
          }
          STAMPIF(tid == 0 && h == 3, 81);
        }
        if (h == 2 || h == 4 || h == 6 || h == 8 || h == 12) {
          wg_wait<1>();
          if (h < 12 && tid == 0) mbar_arrive(sb + 8 * (B_EB + gr - 1));
          if (h >= 6) {
            const int i = h == 6 ? 1 : h == 8 ? 2 : 3;
            float* a = acc + 40 * (1 - ac);
#pragma unroll
            for (int j = 0; j < 40; j++) asm volatile("" : "+f"(a[j])::"memory");
            if (i == 2) pp_send<4096>(pp[1] + (s ^ 4) * 20480, a, 0);
            else pp_send<256>(pp[i - 1] + ((s + 2 * i) & 7) * 1280, a, i == 1 ? tag : 0);
            STAMPIF(threadIdx.x == 0, 50 + i);
          }
        }
        if (h == 5) bar_sync(3 + wg, 128);
        if (h == PL1) pp_load<256>(pf, pp[0] + s * 1280);
        if (h == PL2) pp_load<4096>(pf + 5, pp[1] + s * 20480);
        if (h == 14) wg_wait<1>();
      }
    }
    STAMPIF(tid == 0, 17);
    uint32_t xr[20], gbv[10];
    mbar_wait(sb + 8 * B_X1, 0);
    mbar_wait(sb + 8 * B_GB, 0);
    float rs0 = 2.f * blo(lds32(sb + SM_STAT + (64 * wg + 16 * w + g) * 16 + 4)), rs1 = 2.f * blo(lds32(sb + SM_STAT + (64 * wg + 16 * w + g) * 16 + 132));
    {
      const uint32_t la = sb + SM_X + (4 * wg + w) * 512 + (8 * (lane >> 4) + (lane & 7)) * 32 + ((((lane >> 3) ^ (lane >> 2)) & 1) << 4);
#pragma unroll
      for (int i = 0; i < 5; i++) ldsm4t(xr + 4 * i, la + i * 4096);
#pragma unroll
      for (int i = 0; i < 10; i++) gbv[i] = lds32(sb + SM_SMALL + SMALL_GB + 16 * i + 4 * q);
    }
    rs0 = __frcp_rn(rs0 * rs0); rs1 = __frcp_rn(rs1 * rs1);
#pragma unroll
    for (int i = 0; i < 3; i++) {
      if (i == 1) pp_wait<4096>(pf + 5, pp[1] + s * 20480, 0);
      else pp_wait<256>(pf + 5 * i, pp[i] + s * 1280, i ? 0 : tag);
      if (i == 1) pp_load<256>(pf + 10, pp[2] + s * 1280);
      STAMPIF(threadIdx.x == 0 && i < 2, 98 + i);
      if (i) pp_add(acc, pf + 5 * i, pf, i == 1);
#pragma unroll
      for (int j = 0; j < 40 && i == 1; j++) asm volatile("" : "+f"(acc[j])::"memory");
    }
#pragma unroll
    for (int i = 0; i < 40; i++) { acc[i] *= (i & 2) ? rs1 : rs0; asm volatile("" : "+f"(acc[i])::"memory"); }
    STAMPIF(threadIdx.x == 0, 125);
    wg_wait<0>();
    float* a = acc + 40;
#pragma unroll
    for (int i = 0; i < 40; i++) asm volatile("" : "+f"(a[i])::"memory");
    STAMPIF(tid == 0, 18);
    uint32_t ov[20];
#pragma unroll
    for (int i = 0; i < 10; i++) {
      ov[2 * i] = hadd(xr[2 * i], hmul(gbv[i], pack2(a[4 * i] * rs0 + acc[4 * i], a[4 * i + 1] * rs0 + acc[4 * i + 1])));
      ov[2 * i + 1] = hadd(xr[2 * i + 1], hmul(gbv[i], pack2(a[4 * i + 2] * rs1 + acc[4 * i + 2], a[4 * i + 3] * rs1 + acc[4 * i + 3])));
    }
    const uint32_t obuf = ring + w * 32768 + wg * 2048;
    const int orow = ~lane & 15;
#pragma unroll
    for (int i = 0; i < 4; i++) stsm4(obuf + orow * 128 + (((lane >> 4) + 2 * i) ^ (orow & 7)) * 16, ov + 4 * i);
    stsm4(obuf + 4096 + orow * 32 + (lane >> 4) * 16, ov + 16);
    fence_async_s();
    __syncwarp();
    if (elect()) {
      const int t = tbase(8 * m + 4 * wg + w);
      tma_store4d(&P.mO, obuf, out_col(s, 0), 0, 0, t);
      tma_store4d(&P.mO2, obuf + 4096, out_col(s, 4), 0, 0, t);
      asm volatile("cp.async.bulk.commit_group;" ::: "memory");
      asm volatile("cp.async.bulk.wait_group.read 0;" ::: "memory");
    }
  } else if (wg == 2) {
    asm volatile("setmaxnreg.dec.sync.aligned.u32 40;");
    const uint32_t e1 = rdback(G->epoch + b) + 1;
    if (tid == 0) sts32(sb + SM_SMALL + SMALL_E, e1);
    if (tid < 80) {
      float c = blo(*(const uint16_t*)(gc + 80 * (b & 7) + tid));
      sts16(sb + SM_SMALL + SMALL_S + 2 * tid, pack2(__fdividef(c, 1.f + __expf(-c)), 0.f));
    }
    fence_async_s();
    bar_sync(5, 128);
    int tl = tid;
#pragma unroll 1
    for (uint64_t pr = AUXP; pr; pr >>= 4) {
      asm volatile("" : "+r"(tl));
      const int op = pr & 15, tid = tl, lane = tid & 31;
      if (op == 0) {
        ln1_job(sb, tid);
      } else if (op < 4) {
        kv_job(G, sb, b, op + 1, tid);
        STAMPIF(tid == 0, 21 + op);
      } else if (!K1W && op < 7) {
        k1_job(sb, op - 2, tid);
        __syncwarp();
        if (lane == 0) mbar_arrive(sb + 8 * (B_K + op - 4));
        STAMPIF(tid == 0, 74);
      } else if (op < 11) {
        if (op < 10 || b < 96) mod_box(G, sb, b, op - 7, e1, tid);
        if (lane == 0) mbar_arrive(sb + 8 * (B_BD + op - 7));
        STAMPIF(tid == 0, op == 7 ? 27 : op == 8 ? 73 : op == 9 ? 76 : 95);
      } else {
        const int r = op - 11, cg = 8 * r + 4 * (w >> 1) + (lane & 2) + (w & 1), g = lane >> 2;
        const uint32_t xa = x_addr(sb, w, lane) + 4096 * r;
        mbar_wait(sb + 8 * B_LN, 0);
        uint32_t xv[8], hv[8];
        ldsm4t(xv, xa);
        ldsm4t(xv + 4, xa ^ 16);
        {
          const uint32_t la = sb + SM_SMALL + SMALL_LN + 16 * (lane & 1);
          const uint4 m4 = lds128(la), s4 = lds128(la + 32), l4 = lds128(la + 64);
          const uint32_t m_[4] = {m4.x, m4.y, m4.z, m4.w}, s_[4] = {s4.x, s4.y, s4.z, s4.w}, l_[4] = {l4.x, l4.y, l4.z, l4.w};
#pragma unroll
          for (int j = 0; j < 8; j++) {
            const int i = 4 * (j & 1) + (j >> 1);
            const uint32_t d = hsub(xv[i], m_[j >> 1]);
            hv[i] = hfma(d, s_[j >> 1], hmul(d, l_[j >> 1]));
            asm volatile("" : "+r"(hv[i])::"memory");
          }
        }
        const uint2* pz = (const uint2*)(G->zT + (16 * cg + g) * S_ + 16 * b + 8 * (lane & 1));
        const uint2* pc = G->mc + (128 * (r >> 1) + 16 * (cg & 7) + g) * 4 + 2 * (e1 & 1) + (r & 1);
        mbar_wait(sb + 8 * (B_MF + (r >> 1)), 0);
        mbar_wait(sb + 8 * (B_Z + r), 0);
        STAMPIF(tid == 0 && r == 0, 28);
        uint4 z[2];
        uint2 c[2];
#pragma unroll 1
        for (int i = 0;; i++) {
          z[0] = ld_tag2(pz); z[1] = ld_tag2(pz + 4096); c[0] = ld_tag(pc); c[1] = ld_tag(pc + 32);
          if (__all_sync(0xffffffffu, (z[0].w & z[1].w & 1) && c[0].x && c[1].x)) break;
          if (i > (1 << 20)) __trap();
        }
        STAMPIF(tid == 0 && r == 0, 83);
        ldsm4t(xv, xa);
        ldsm4t(xv + 4, xa ^ 16);
        uint4* pa = (uint4*)G->AT + ((40 * m + cg) * 8 + s) * 32 + 2 * g + ((lane ^ (lane >> 4)) & 1);
#pragma unroll
        for (int n = 0; n < 2; n++) {
          const uint32_t z_[4] = {z[n].x, z[n].y, z[n].z, z[n].w}, c0 = ~c[n].x;
          const uint32_t sa = __byte_perm(c0, 0, 0x1010), ca1 = __byte_perm(c0, 0, 0x3232), ga = __byte_perm(c[n].y, 0, 0x1010), cb1 = __byte_perm(c[n].y, 0, 0x3232);
          uint32_t o[4];
#pragma unroll
          for (int j = 0; j < 4; j++) o[j] = hadd(xv[4 * n + j], hmul(ga, hmul(hadd(hmul(hv[4 * n + j], ca1), sa), z_[j])));
          pa[16 * n] = make_uint4(hmul(o[0], cb1), hmul(o[1], cb1), hmul(o[2], cb1), hmul(o[3], cb1));
          pa[16 * n - D_ * S_ / 8] = make_uint4(o[0], o[1], o[2], o[3]);
          sts128(xa ^ (16 * n), make_uint4(o[0], o[1], o[2], o[3]));
        }
        __syncwarp();
        if (lane == 0) mbar_arrive(sb + 8 * (B_EW + r));
        STAMPIF(tid == 0, 29 + r);
      }
      if (op == kLastKv) { __syncwarp(); if (lane == 0) mbar_arrive(sb + 8 * B_KVS); }
    }
    if (m < 12) {
      const uint2* p = (const uint2*)(G->cbsb + 2 * tid + (m >= 6));
      uint4 a;
      mbar_wait(sb + 8 * B_FP, 0);
#pragma unroll 1
      for (int i = 0;; i++) {
        a = ld_tag2(p);
        if (__all_sync(0xffffffffu, a.w == e1)) break;
        if (i > (1 << 20)) __trap();
      }
      STAMPIF(tid == 0, 89);
      const uint32_t d = sb + SM_CB + 4 * (tid & 120) + 2 * (tid & 7) + (m < 6 ? 256 : 0);
      sts16(d, a.x); sts16(d + 16, a.x >> 16);
      sts16(d + 512, a.y); sts16(d + 528, a.y >> 16);
      sts16(d + 1024, a.z); sts16(d + 1040, a.z >> 16);
      fence_async_s();
      STAMPIF(tid == 0, 96);
      bar_sync(5, 128);
      if (tid == 0) mbar_arrive(sb + 8 * (B_BOX + 4));
      STAMPIF(tid == 0, 34);
    }
    {
      const uint4 m4 = lds128(sb + SM_SMALL + SMALL_LN + 16 * (lane & 1));
      const uint32_t m_[4] = {m4.x, m4.y, m4.z, m4.w}, xa = x_addr(sb, w, lane);
      float a[16];
#pragma unroll
      for (int i = 0; i < 16; i++) a[i] = 0.f;
#pragma unroll 2
      for (int n = 0; n < 10; n++) {
        const uint4 x4 = lds128((xa ^ (16 * (n & 1))) + 2048 * (n & 14));
        const uint32_t x_[4] = {x4.x, x4.y, x4.z, x4.w};
#pragma unroll
        for (int i = 0; i < 4; i++) {
          const float d0 = blo(x_[i]) - blo(m_[i]), d1 = bhi(x_[i]) - bhi(m_[i]);
          a[4 * i] += d0; a[4 * i + 1] += d0 * d0; a[4 * i + 2] += d1; a[4 * i + 3] += d1 * d1;
        }
      }
      STAMPIF(lane == 0, 67 + (w & 1) + 11 * (w >> 1));
      bfly<16>(a, 16, lane & 16); bfly<8>(a, 8, lane & 8); bfly<4>(a, 4, lane & 4); bfly<2>(a, 2, lane & 2);
      if (lane == 0) mbar_arrive(sb + 8 * B_XF);
      STAMPIF(tid == 0, 88);
      sts32(sb + SM_SMALL + SMALL_RED + 16 * lane + 4 * w, __float_as_uint(a[0]));
      bar_sync(5, 128);
      if (w == 0) {
        const uint4 v = lds128(sb + SM_SMALL + SMALL_RED + 16 * lane);
        const float s1 = __uint_as_float(v.x) + __uint_as_float(v.y) + __uint_as_float(v.z) + __uint_as_float(v.w), s2 = __shfl_xor_sync(0xffffffffu, s1, 2);
        const int p = 8 * (lane & 1) + (lane >> 2);
        const float pv = blo(lds32(sb + SM_SMALL + SMALL_LN + 4 * (p >> 1)) >> (16 * (p & 1)));
        const float mu = s1 * (1.f / D_), var = fmaxf(s2 * (1.f / D_) - mu * mu, 0.f);
        const float sd = rbf(__fsqrt_rn(rbf(rbf(var) + 1e-5f)));
        if (!(lane & 2)) st_tag(G->st2 + 16 * b + p, pack2(-0.5f * (pv + mu), 0.5f * sd), e1);
      }
      STAMPIF(tid == 0, 87);
    }
    {
      uint2 v;
      spin(clk(), SD);
#pragma unroll 1
      for (int i = 0;; i++) {
        v = ld_tag(G->st2 + 128 * m + tid);
        if (__all_sync(0xffffffffu, v.y == e1)) break;
        if (i > (1 << 20)) __trap();
      }
      const uint32_t hm = __byte_perm(v.x, 0, 0x1010), hs = __byte_perm(v.x, 0, 0x3232);
      sts128(sb + SM_STAT + 16 * tid, make_uint4(hm, hs, hm, hs));
      fence_async_s();
      __syncwarp();
      if (lane == 0) mbar_arrive(sb + 8 * B_ST2);
      STAMPIF(tid == 0, 21);
    }
  } else {
    asm volatile("setmaxnreg.dec.sync.aligned.u32 24;");
    if (w != 0) {
    if (w == 2 && lane < 5) asm volatile("prefetch.tensormap [%0];" ::"l"(&P.mG + lane) : "memory");
    if (K1W && (w & 1)) {
#pragma unroll 1
      for (int j = 4; j < 10; j++) {
        k1_job(sb, j >> 1, 64 * (j & 1) + 16 * (w & 2) + lane);
        if (UD && w == 1 && (j & 1)) {
          mbar_wait(sb + 8 * (B_KJ + (j >> 1)), 0);
          const uint32_t t = lds32(sb + SM_SMALL + SMALL_TS + 4 * (j >> 1));
          while (clk() - t < UD);
        }
        __syncwarp();
        if (lane == 0) mbar_arrive(sb + 8 * (B_K + (j >> 1) - 2));
      }
      STAMPIF(tid == 32, 74);
    }
    if (w == 1) {
     {
      const uint32_t e1 = rdback(G->epoch + b) + 1;
      if (elect()) {
        mbar_wait(sb + 8 * B_KVS, 0);
        mbar_wait(sb + 8 * B_EW, 0);
#pragma unroll 1
        for (int it = 0; it < 20; it++) {
          int st = it % 5;
          if ((it & 3) == 0) { flag_wait(G, FL_R + 5 * m + (it >> 2), e1 * 8); fence_async_g(); STAMP(45 + (it >> 2)); }
          mbar_wait(sb + 8 * (B_E1 + st), (it / 5) & 1);
          uint32_t fb = sb + 8 * (B_F1 + st);
          mbar_expect(fb, 8192);
          bulk_g2s(ring + st * 32768, G->AT + (20 * m + it) * 4096, 8192, fb);
        }
        mbar_wait(sb + 8 * B_XF, 0);
        mbar_expect(sb + 8 * B_X1, 20480);
        bulk_g2s(sb + SM_X, G->x1T + (640 * m + out_col(s, 0)) * 128, 16384, sb + 8 * B_X1);
        bulk_g2s(sb + SM_X + 16384, G->x1T + (640 * m + out_col(s, 4)) * 128, 4096, sb + 8 * B_X1);
        STAMP(86);
        G->epoch[b] = e1;
      }
     }
    } else if (w == 2) {
      const uint32_t e1 = rdback(G->epoch + b) + 1;
      if (lane < 4) mbar_expect(sb + 8 * (B_RECV + lane), 12288);
      mod_fin(G, sb, b, 0, e1, lane);
      STAMPIF(lane == 0, 36);
#pragma unroll 1
      for (int r = 0; r < 5; r++) {
        const bf16* p = G->AT + ((40 * m + 8 * r + (lane >> 2)) * 8 + s) * 256 + 64 * (lane & 3);
        mbar_wait(sb + 8 * (B_EW + r), 0);
        rdwait(sb, rdback(p) ^ rdback(p - D_ * S_));
        __syncwarp();
        if (lane == 0) flag_add(G, FL_R + 5 * m + r);
        STAMPIF(lane == 0, 90 + r);
      }
      mbar_wait(sb + 8 * (B_BD + 4), 0);
      if (lane < 2) mbar_arrive(sb + 8 * (B_E1 + 5));
      if (m < 12) {
        rdwait(sb, rdback(G->cimg + s * 3072 + (m % 6) * 512 + (m < 6 ? 0 : 256) + 64 * (lane & 3)));
        __syncwarp();
        if (lane == 0) flag_add(G, FL_C + s);
        STAMPIF(lane == 0, 35);
      }
      if (elect()) {
        flag_wait(G, FL_C + s, e1 * 12);
        fence_async_g();
        STAMP(54);
        mbar_expect(sb + 8 * B_EXT, 6144);
        bulk_g2s(sb + SM_EXT, G->cimg + s * 3072, 6144, sb + 8 * B_EXT);
      }
    } else {
      const uint32_t e1 = rdback(G->epoch + b) + 1;
      mod_fin(G, sb, b, 2, e1, lane);
      STAMPIF(lane == 0, 37);
      float t0 = mod_fin(G, sb, b, 4, e1, lane), t1, t2;
      STAMPIF(lane == 0, 38);
      const uint2* p = G->modP + (lane & 7) * 3840;
      mbar_wait(sb + 8 * (B_BD + 3), 0);
      mod_poll(p + 3 * 640 + 512 + b, 0, e1, t1, t2);
      mbar_wait(sb + 8 * B_MF, 0);
      if ((lane & 6) == 0) {
        const uint32_t v = __byte_perm(lds32(sb + SM_SMALL + SMALL_MOD + 4 * (lane == 1 ? 4 : lane >> 3)), __float_as_uint(lane == 1 ? t1 : t0), 0x7632);
        asm volatile("st.relaxed.gpu.global.u32 [%0], %1;" ::"l"((uint32_t*)G->cbsb + 8 * b + ((0x75423160 >> ((lane & 24) + 4 * (lane & 1))) & 7)), "r"((lane & 9) == 9 ? e1 : v) : "memory");
      }
      STAMPIF(lane == 0, 39);
      spin(clk(), CD);
      __syncwarp();
      if (lane == 0) mbar_arrive(sb + 8 * B_FP);
#pragma unroll 1
      for (int n = 0; n < 10; n++) {
        mod_poll(p + 5 * 640 + out_col(s, n >> 1) + 8 * (n & 1) + 2 * (lane >> 3), 1, e1, t1, t2);
        if ((lane & 7) == 0) sts32(sb + SM_SMALL + SMALL_GB + 16 * n + (lane >> 1), pack2(t1, t2));
      }
      __syncwarp();
      if (lane == 0) mbar_arrive(sb + 8 * B_GB);
    }
    } else {
      STAMPIF(lane == 0, 62);
      int rw = sched_run<0>(P, In{gk, gv, gsk, gWg, gWu, gWd, gss}, sb, b, lane, __shfl_sync(0xffffffffu, t_0, 0));
      if (elect()) {
        STAMP(69);
        mbar_wait(sb + 8 * B_KVS, 0);
        STAMP(70);
        int rd = 0, c = 0;
#pragma unroll 1
        for (int it = 0; it < 20; it++) {
          if (it == 4) mbar_wait(sb + 8 * (B_BD + 1), 0);
          load_w(P, sb, s, it);
          if ((PWM >> it) & 1) { l2_prefetch(gWg + (128 * rw + b) * F_, 2 * F_); l2_prefetch(gWu + (128 * rw + b) * F_, 2 * F_); rw++; }
          if ((PDM >> it) & 1) { l2_prefetch(gWd + (512 * rd + 4 * b) * D_, 8 * D_); rd++; }
          if (((STM >> it) & 1) && b < 96) {
            const int grp = m % 6;
            if (c == 4) { mbar_wait(sb + 8 * (B_BD + 2), 0); mbar_wait(sb + 8 * (B_BD + 3), 0); }
            if (c == 0) mbar_expect(sb + 8 * B_ST0, 40960);
#pragma unroll
            for (int j = 0; j < 2; j++, c++)
              tma2d(sb + (c < 2 ? SM_EXT : SM_RING + R_X - 8192) + 4096 * c, &P.mG + (grp & 1), 192 * s + 64 * (grp >> 1), (m < 6 ? 0 : 320) + 32 * c, sb + 8 * B_ST0);
          }
        }
#pragma unroll
        for (int k = 0; k < 10; k++) {
          const int st = k == 0 ? 5 : (k - 1) % 5, pe = k < 6 ? k / 3 : k & 1, d = k < 6 ? 2 - (k & 1) : k >> 1;
          mbar_wait(sb + 8 * (k < 6 ? B_E1 + st : B_EB + st), 0);
          mbar_expect(sb + 8 * (B_FB + k), 24576);
          tma2d(ring + st * 32768 + 8192, &P.mD, 320 * (s & 1) + (st > 3 ? 256 : 32 * ((s + 2 * d) & 6)), 192 * (s ^ pe), sb + 8 * (B_FB + k));
        }
      }
    }
  }
}

typedef CUresult (*EncFn)(CUtensorMap*, CUtensorMapDataType, cuuint32_t, void*, const cuuint64_t*, const cuuint64_t*, const cuuint32_t*, const cuuint32_t*,
                          CUtensorMapInterleave, CUtensorMapSwizzle, CUtensorMapL2promotion, CUtensorMapFloatOOBfill);
static void mkmap(EncFn enc, CUtensorMap* m, const void* p, int rank, const cuuint64_t* dims, const cuuint64_t* strides, const cuuint32_t* box, CUtensorMapSwizzle sw) {
  cuuint32_t es[5] = {1, 1, 1, 1, 1};
  CUresult r = enc(m, CU_TENSOR_MAP_DATA_TYPE_BFLOAT16, rank, (void*)p, dims, strides, box, es, CU_TENSOR_MAP_INTERLEAVE_NONE, sw,
                   CU_TENSOR_MAP_L2_PROMOTION_L2_128B, CU_TENSOR_MAP_FLOAT_OOB_FILL_NONE);
  if (r != CUDA_SUCCESS) fprintf(stderr, "tensor map encode failed: %d\n", (int)r);
}

extern "C" void kernel_launch(void* const* d_in, const int* in_sizes, int n_in, void* d_out, int out_size) {
  void* fn = nullptr;
  cudaDriverEntryPointQueryResult qr;
  cudaGetDriverEntryPoint("cuTensorMapEncodeTiled", &fn, cudaEnableDefault, &qr);
  EncFn enc = (EncFn)fn;
  Scr* G;
  cudaGetSymbolAddress((void**)&G, g_scr);
  Params P;
  { cuuint64_t d[] = {128, 16, 640}, st[] = {256, 4096}; cuuint32_t bx[] = {144, 16, 1}; mkmap(enc, &P.mS, d_in[4], 3, d, st, bx, CU_TENSOR_MAP_SWIZZLE_NONE); }
  { cuuint64_t d[] = {3840, 640}, st[] = {7680}; cuuint32_t bx[] = {64, 80}; mkmap(enc, &P.mWm, d_in[11], 2, d, st, bx, CU_TENSOR_MAP_SWIZZLE_128B); }
  { cuuint64_t d[] = {32, 20, 256, 8}, st[] = {64, 10240, 1280}; cuuint32_t bx[] = {40, 1, 9, 8}, bx2[] = {40, 1, 8, 8};
    mkmap(enc, &P.mK, d_in[1], 4, d, st, bx, CU_TENSOR_MAP_SWIZZLE_NONE); mkmap(enc, &P.mV, d_in[2], 4, d, st, bx2, CU_TENSOR_MAP_SWIZZLE_NONE); }
  { cuuint64_t d[] = {1536, 640}, st[] = {3072}; cuuint32_t bx[] = {64, 32};
    mkmap(enc, &P.mG, d_in[7], 2, d, st, bx, CU_TENSOR_MAP_SWIZZLE_128B); mkmap(enc, &P.mU, d_in[8], 2, d, st, bx, CU_TENSOR_MAP_SWIZZLE_128B); }
  { cuuint64_t d[] = {640, 1536}, st[] = {1280}; cuuint32_t bx[] = {64, 192}; mkmap(enc, &P.mD, d_in[9], 2, d, st, bx, CU_TENSOR_MAP_SWIZZLE_128B); }
  { cuuint64_t d[] = {64, 2, 8, 10, 128}, st[] = {1280, 256 * 1280, 128, 2560}; cuuint32_t bx[] = {64, 2, 8, 5, 1}; mkmap(enc, &P.mX, d_in[0], 5, d, st, bx, CU_TENSOR_MAP_SWIZZLE_128B); }
  { cuuint64_t d[] = {640, 8, 2, 128}, st[] = {256 * 1280, 1280, 2560}; cuuint32_t bx[] = {64, 8, 2, 1}, bx2[] = {16, 8, 2, 1};
    mkmap(enc, &P.mO, d_out, 4, d, st, bx, CU_TENSOR_MAP_SWIZZLE_128B); mkmap(enc, &P.mO2, d_out, 4, d, st, bx2, CU_TENSOR_MAP_SWIZZLE_NONE); }
  cudaFuncSetAttribute(fused_kernel, cudaFuncAttributeMaxDynamicSharedMemorySize, SM_TOTAL + DEVSM);
  cudaLaunchConfig_t cfg = {};
  cfg.gridDim = dim3(128); cfg.blockDim = dim3(512); cfg.dynamicSmemBytes = SM_TOTAL + DEVSM; cfg.stream = cudaStreamPerThread;
  cudaLaunchAttribute at[1];
  at[0].id = cudaLaunchAttributeClusterDimension; at[0].val.clusterDim.x = 2; at[0].val.clusterDim.y = 1; at[0].val.clusterDim.z = 1;
  cfg.attrs = at; cfg.numAttrs = 1;
  cudaLaunchKernelEx(&cfg, fused_kernel, (const bf16*)d_in[1], (const bf16*)d_in[2], (const bf16*)d_in[3], (const bf16*)d_in[5], (const bf16*)d_in[10], G,
                     (const bf16*)d_in[7], (const bf16*)d_in[8], (const bf16*)d_in[9], (const bf16*)d_in[0], (const bf16*)d_in[4], P);
}
```

```cpp
#include <cuda_runtime.h>
#include <cuda.h>
#include <cuda_bf16.h>
#include <stdio.h>
#include <stdint.h>
typedef __nv_bfloat16 bf16;
__device__ __forceinline__ uint32_t smem_u32(const void* p) { return (uint32_t)__cvta_generic_to_shared(p); }
__device__ __forceinline__ void mbar_init(uint32_t bar, int cnt) { asm volatile("mbarrier.init.shared::cta.b64 [%0], %1;" ::"r"(bar), "r"(cnt) : "memory"); }
__device__ __forceinline__ void mbar_expect(uint32_t bar, int bytes) { asm volatile("mbarrier.arrive.expect_tx.shared::cta.b64 _, [%0], %1;" ::"r"(bar), "r"(bytes) : "memory"); }
__device__ __forceinline__ void mbar_arrive(uint32_t bar) { asm volatile("mbarrier.arrive.shared::cta.b64 _, [%0];" ::"r"(bar) : "memory"); }
__device__ __forceinline__ void mbar_arrive_remote(uint32_t bar) { asm volatile("mbarrier.arrive.relaxed.cluster.shared::cluster.b64 _, [%0];" ::"r"(bar) : "memory"); }
__device__ __forceinline__ uint32_t mapa(uint32_t a, uint32_t cta) { uint32_t r; asm("mapa.shared::cluster.u32 %0, %1, %2;" : "=r"(r) : "r"(a), "r"(cta)); return r; }
__device__ __forceinline__ bool mbar_try(uint32_t bar, int parity) {
  uint32_t ok;
  asm volatile("{\n.reg .pred p;\nmbarrier.try_wait.parity.shared::cta.b64 p, [%1], %2;\nselp.u32 %0, 1, 0, p;\n}" : "=r"(ok) : "r"(bar), "r"(parity) : "memory");
  return ok;
}
__device__ __forceinline__ void mbar_wait(uint32_t bar, int parity) {
#pragma unroll 1
  for (int i = 0; i < (1 << 20); i++) { if (mbar_try(bar, parity)) return; }
  __trap();
}
__device__ __forceinline__ bool elect() {
  uint32_t p;
  asm volatile("{\n.reg .pred P;\nelect.sync _|P, 0xffffffff;\nselp.u32 %0, 1, 0, P;\n}" : "=r"(p));
  return p;
}
__device__ __forceinline__ void tma2d(uint32_t dst, const CUtensorMap* m, int c0, int c1, uint32_t bar) {
  asm volatile("cp.async.bulk.tensor.2d.shared::cluster.global.mbarrier::complete_tx::bytes [%0], [%1, {%3, %4}], [%2];" ::"r"(dst), "l"(m), "r"(bar), "r"(c0), "r"(c1) : "memory");
}
__device__ __forceinline__ void tma3d(uint32_t dst, const CUtensorMap* m, int c0, int c1, int c2, uint32_t bar) {
  asm volatile("cp.async.bulk.tensor.3d.shared::cluster.global.mbarrier::complete_tx::bytes [%0], [%1, {%3, %4, %5}], [%2];" ::"r"(dst), "l"(m), "r"(bar), "r"(c0), "r"(c1), "r"(c2) : "memory");
}
__device__ __forceinline__ void tma4d(uint32_t dst, const CUtensorMap* m, int c0, int c1, int c2, int c3, uint32_t bar) {
  asm volatile("cp.async.bulk.tensor.4d.shared::cluster.global.mbarrier::complete_tx::bytes [%0], [%1, {%3, %4, %5, %6}], [%2];" ::"r"(dst), "l"(m), "r"(bar), "r"(c0), "r"(c1), "r"(c2), "r"(c3) : "memory");
}
__device__ __forceinline__ void tma5d(uint32_t dst, const CUtensorMap* m, int c0, int c1, int c2, int c3, int c4, uint32_t bar) {
  asm volatile("cp.async.bulk.tensor.5d.shared::cluster.global.mbarrier::complete_tx::bytes [%0], [%1, {%3, %4, %5, %6, %7}], [%2];" ::"r"(dst), "l"(m), "r"(bar), "r"(c0), "r"(c1), "r"(c2), "r"(c3), "r"(c4) : "memory");
}
__device__ __forceinline__ void tma_store2d(const CUtensorMap* m, uint32_t src, int c0, int c1) {
  asm volatile("cp.async.bulk.tensor.2d.global.shared::cta.bulk_group [%0, {%2, %3}], [%1];" ::"l"(m), "r"(src), "r"(c0), "r"(c1) : "memory");
}
__device__ __forceinline__ void tma_store4d(const CUtensorMap* m, uint32_t src, int c0, int c1, int c2, int c3) {
  asm volatile("cp.async.bulk.tensor.4d.global.shared::cta.bulk_group [%0, {%2, %3, %4, %5}], [%1];" ::"l"(m), "r"(src), "r"(c0), "r"(c1), "r"(c2), "r"(c3) : "memory");
}
__device__ __forceinline__ void tma_prefetch2d(const CUtensorMap* m, int c0, int c1) {
  asm volatile("cp.async.bulk.prefetch.tensor.2d.L2.global [%0, {%1, %2}];" ::"l"(m), "r"(c0), "r"(c1) : "memory");
}
__device__ __forceinline__ void bulk_g2s(uint32_t dst, const void* src, int bytes, uint32_t bar) {
  asm volatile("cp.async.bulk.shared::cluster.global.mbarrier::complete_tx::bytes [%0], [%1], %2, [%3];" ::"r"(dst), "l"(src), "r"(bytes), "r"(bar) : "memory");
}
__device__ __forceinline__ void bulk_s2g(void* dst, uint32_t src, int bytes) {
  asm volatile("cp.async.bulk.global.shared::cta.bulk_group [%0], [%1], %2;" ::"l"(dst), "r"(src), "r"(bytes) : "memory");
}
__device__ __forceinline__ void cp16(uint32_t dst, const void* src) { asm volatile("cp.async.cg.shared.global [%0], [%1], 16;" ::"r"(dst), "l"(src) : "memory"); }
__device__ __forceinline__ void cp16z(uint32_t dst, const void* src, int n) { asm volatile("cp.async.cg.shared.global [%0], [%1], 16, %2;" ::"r"(dst), "l"(src), "r"(n) : "memory"); }
__device__ __forceinline__ void cp_arrive(uint32_t bar) { asm volatile("cp.async.mbarrier.arrive.noinc.shared::cta.b64 [%0];" ::"r"(bar) : "memory"); }
__device__ __forceinline__ void st_async4(uint32_t dst, const uint32_t* v, uint32_t bar) {
  asm volatile("st.async.weak.shared::cluster.mbarrier::complete_tx::bytes.v4.b32 [%0], {%1, %2, %3, %4}, [%5];" ::"r"(dst), "r"(v[0]), "r"(v[1]), "r"(v[2]), "r"(v[3]), "r"(bar) : "memory");
}
__device__ __forceinline__ void wg_fence() { asm volatile("wgmma.fence.sync.aligned;" ::: "memory"); }
__device__ __forceinline__ void wg_commit() { asm volatile("wgmma.commit_group.sync.aligned;" ::: "memory"); }
template <int N> __device__ __forceinline__ void wg_wait() { asm volatile("wgmma.wait_group.sync.aligned %0;" ::"n"(N) : "memory"); }
__device__ __forceinline__ uint64_t mkdesc(uint32_t addr, uint32_t lbo, uint32_t sbo, uint32_t swz) {
  return (uint64_t)((addr & 0x3FFFF) >> 4) | ((uint64_t)(lbo >> 4) << 16) | ((uint64_t)(sbo >> 4) << 32) | ((uint64_t)swz << 62);
}
__device__ __forceinline__ void ldsm4t(uint32_t* r, uint32_t a) {
  asm volatile("ldmatrix.sync.aligned.m8n8.x4.trans.shared.b16 {%0,%1,%2,%3}, [%4];" : "=r"(r[0]), "=r"(r[1]), "=r"(r[2]), "=r"(r[3]) : "r"(a) : "memory");
}
__device__ __forceinline__ void stsm4(uint32_t a, const uint32_t* r) {
  asm volatile("stmatrix.sync.aligned.m8n8.x4.shared.b16 [%0], {%1,%2,%3,%4};" ::"r"(a), "r"(r[0]), "r"(r[1]), "r"(r[2]), "r"(r[3]) : "memory");
}
__device__ __forceinline__ void bar_sync(int id, int n) { asm volatile("bar.sync %0, %1;" ::"r"(id), "r"(n) : "memory"); }
__device__ __forceinline__ void bar_arrive(int id, int n) { asm volatile("bar.arrive %0, %1;" ::"r"(id), "r"(n) : "memory"); }
__device__ __forceinline__ uint32_t lds32(uint32_t a) { uint32_t v; asm volatile("ld.shared.b32 %0, [%1];" : "=r"(v) : "r"(a) : "memory"); return v; }
__device__ __forceinline__ uint2 lds64(uint32_t a) { uint2 v; asm volatile("ld.shared.v2.b32 {%0,%1}, [%2];" : "=r"(v.x), "=r"(v.y) : "r"(a) : "memory"); return v; }
__device__ __forceinline__ uint4 lds128(uint32_t a) { uint4 v; asm volatile("ld.shared.v4.b32 {%0,%1,%2,%3}, [%4];" : "=r"(v.x), "=r"(v.y), "=r"(v.z), "=r"(v.w) : "r"(a) : "memory"); return v; }
__device__ __forceinline__ void sts16(uint32_t a, uint32_t v) { asm volatile("st.shared.b16 [%0], %1;" ::"r"(a), "h"((uint16_t)v) : "memory"); }
__device__ __forceinline__ void sts32(uint32_t a, uint32_t v) { asm volatile("st.shared.b32 [%0], %1;" ::"r"(a), "r"(v) : "memory"); }
__device__ __forceinline__ void sts64(uint32_t a, uint32_t x, uint32_t y) { asm volatile("st.shared.v2.b32 [%0], {%1,%2};" ::"r"(a), "r"(x), "r"(y) : "memory"); }
__device__ __forceinline__ void sts128(uint32_t a, uint4 v) { asm volatile("st.shared.v4.b32 [%0], {%1,%2,%3,%4};" ::"r"(a), "r"(v.x), "r"(v.y), "r"(v.z), "r"(v.w) : "memory"); }
template<int TB> __device__ __forceinline__ void wgmma_rs_n128(float* d, const uint32_t* a, uint64_t db, int sd) {
  asm volatile("{\n.reg .pred p;\nsetp.ne.b32 p, %69, 0;\n"
    "wgmma.mma_async.sync.aligned.m64n128k16.f32.bf16.bf16 {%0, %1, %2, %3, %4, %5, %6, %7, %8, %9, %10, %11, %12, %13, %14, %15, %16, %17, %18, %19, %20, %21, %22, %23, %24, %25, %26, %27, %28, %29, %30, %31, %32, %33, %34, %35, %36, %37, %38, %39, %40, %41, %42, %43, %44, %45, %46, %47, %48, %49, %50, %51, %52, %53, %54, %55, %56, %57, %58, %59, %60, %61, %62, %63}, {%64, %65, %66, %67}, %68, p, 1, 1, %70;\n}"
    : "+f"(d[0]), "+f"(d[1]), "+f"(d[2]), "+f"(d[3]), "+f"(d[4]), "+f"(d[5]), "+f"(d[6]), "+f"(d[7]), "+f"(d[8]), "+f"(d[9]), "+f"(d[10]), "+f"(d[11]), "+f"(d[12]), "+f"(d[13]), "+f"(d[14]), "+f"(d[15]), "+f"(d[16]), "+f"(d[17]), "+f"(d[18]), "+f"(d[19]), "+f"(d[20]), "+f"(d[21]), "+f"(d[22]), "+f"(d[23]), "+f"(d[24]), "+f"(d[25]), "+f"(d[26]), "+f"(d[27]), "+f"(d[28]), "+f"(d[29]), "+f"(d[30]), "+f"(d[31]), "+f"(d[32]), "+f"(d[33]), "+f"(d[34]), "+f"(d[35]), "+f"(d[36]), "+f"(d[37]), "+f"(d[38]), "+f"(d[39]), "+f"(d[40]), "+f"(d[41]), "+f"(d[42]), "+f"(d[43]), "+f"(d[44]), "+f"(d[45]), "+f"(d[46]), "+f"(d[47]), "+f"(d[48]), "+f"(d[49]), "+f"(d[50]), "+f"(d[51]), "+f"(d[52]), "+f"(d[53]), "+f"(d[54]), "+f"(d[55]), "+f"(d[56]), "+f"(d[57]), "+f"(d[58]), "+f"(d[59]), "+f"(d[60]), "+f"(d[61]), "+f"(d[62]), "+f"(d[63])
    : "r"(a[0]), "r"(a[1]), "r"(a[2]), "r"(a[3]), "l"(db), "r"(sd), "n"(TB));
}

template<int TB> __device__ __forceinline__ void wgmma_rs_n160(float* d, const uint32_t* a, uint64_t db, int sd) {
  asm volatile("{\n.reg .pred p;\nsetp.ne.b32 p, %85, 0;\n"
    "wgmma.mma_async.sync.aligned.m64n160k16.f32.bf16.bf16 {%0, %1, %2, %3, %4, %5, %6, %7, %8, %9, %10, %11, %12, %13, %14, %15, %16, %17, %18, %19, %20, %21, %22, %23, %24, %25, %26, %27, %28, %29, %30, %31, %32, %33, %34, %35, %36, %37, %38, %39, %40, %41, %42, %43, %44, %45, %46, %47, %48, %49, %50, %51, %52, %53, %54, %55, %56, %57, %58, %59, %60, %61, %62, %63, %64, %65, %66, %67, %68, %69, %70, %71, %72, %73, %74, %75, %76, %77, %78, %79}, {%80, %81, %82, %83}, %84, p, 1, 1, %86;\n}"
    : "+f"(d[0]), "+f"(d[1]), "+f"(d[2]), "+f"(d[3]), "+f"(d[4]), "+f"(d[5]), "+f"(d[6]), "+f"(d[7]), "+f"(d[8]), "+f"(d[9]), "+f"(d[10]), "+f"(d[11]), "+f"(d[12]), "+f"(d[13]), "+f"(d[14]), "+f"(d[15]), "+f"(d[16]), "+f"(d[17]), "+f"(d[18]), "+f"(d[19]), "+f"(d[20]), "+f"(d[21]), "+f"(d[22]), "+f"(d[23]), "+f"(d[24]), "+f"(d[25]), "+f"(d[26]), "+f"(d[27]), "+f"(d[28]), "+f"(d[29]), "+f"(d[30]), "+f"(d[31]), "+f"(d[32]), "+f"(d[33]), "+f"(d[34]), "+f"(d[35]), "+f"(d[36]), "+f"(d[37]), "+f"(d[38]), "+f"(d[39]), "+f"(d[40]), "+f"(d[41]), "+f"(d[42]), "+f"(d[43]), "+f"(d[44]), "+f"(d[45]), "+f"(d[46]), "+f"(d[47]), "+f"(d[48]), "+f"(d[49]), "+f"(d[50]), "+f"(d[51]), "+f"(d[52]), "+f"(d[53]), "+f"(d[54]), "+f"(d[55]), "+f"(d[56]), "+f"(d[57]), "+f"(d[58]), "+f"(d[59]), "+f"(d[60]), "+f"(d[61]), "+f"(d[62]), "+f"(d[63]), "+f"(d[64]), "+f"(d[65]), "+f"(d[66]), "+f"(d[67]), "+f"(d[68]), "+f"(d[69]), "+f"(d[70]), "+f"(d[71]), "+f"(d[72]), "+f"(d[73]), "+f"(d[74]), "+f"(d[75]), "+f"(d[76]), "+f"(d[77]), "+f"(d[78]), "+f"(d[79])
    : "r"(a[0]), "r"(a[1]), "r"(a[2]), "r"(a[3]), "l"(db), "r"(sd), "n"(TB));
}

template<int TB> __device__ __forceinline__ void wgmma_rs_n192(float* d, const uint32_t* a, uint64_t db, int sd) {
  asm volatile("{\n.reg .pred p;\nsetp.ne.b32 p, %101, 0;\n"
    "wgmma.mma_async.sync.aligned.m64n192k16.f32.bf16.bf16 {%0, %1, %2, %3, %4, %5, %6, %7, %8, %9, %10, %11, %12, %13, %14, %15, %16, %17, %18, %19, %20, %21, %22, %23, %24, %25, %26, %27, %28, %29, %30, %31, %32, %33, %34, %35, %36, %37, %38, %39, %40, %41, %42, %43, %44, %45, %46, %47, %48, %49, %50, %51, %52, %53, %54, %55, %56, %57, %58, %59, %60, %61, %62, %63, %64, %65, %66, %67, %68, %69, %70, %71, %72, %73, %74, %75, %76, %77, %78, %79, %80, %81, %82, %83, %84, %85, %86, %87, %88, %89, %90, %91, %92, %93, %94, %95}, {%96, %97, %98, %99}, %100, p, 1, 1, %102;\n}"
    : "+f"(d[0]), "+f"(d[1]), "+f"(d[2]), "+f"(d[3]), "+f"(d[4]), "+f"(d[5]), "+f"(d[6]), "+f"(d[7]), "+f"(d[8]), "+f"(d[9]), "+f"(d[10]), "+f"(d[11]), "+f"(d[12]), "+f"(d[13]), "+f"(d[14]), "+f"(d[15]), "+f"(d[16]), "+f"(d[17]), "+f"(d[18]), "+f"(d[19]), "+f"(d[20]), "+f"(d[21]), "+f"(d[22]), "+f"(d[23]), "+f"(d[24]), "+f"(d[25]), "+f"(d[26]), "+f"(d[27]), "+f"(d[28]), "+f"(d[29]), "+f"(d[30]), "+f"(d[31]), "+f"(d[32]), "+f"(d[33]), "+f"(d[34]), "+f"(d[35]), "+f"(d[36]), "+f"(d[37]), "+f"(d[38]), "+f"(d[39]), "+f"(d[40]), "+f"(d[41]), "+f"(d[42]), "+f"(d[43]), "+f"(d[44]), "+f"(d[45]), "+f"(d[46]), "+f"(d[47]), "+f"(d[48]), "+f"(d[49]), "+f"(d[50]), "+f"(d[51]), "+f"(d[52]), "+f"(d[53]), "+f"(d[54]), "+f"(d[55]), "+f"(d[56]), "+f"(d[57]), "+f"(d[58]), "+f"(d[59]), "+f"(d[60]), "+f"(d[61]), "+f"(d[62]), "+f"(d[63]), "+f"(d[64]), "+f"(d[65]), "+f"(d[66]), "+f"(d[67]), "+f"(d[68]), "+f"(d[69]), "+f"(d[70]), "+f"(d[71]), "+f"(d[72]), "+f"(d[73]), "+f"(d[74]), "+f"(d[75]), "+f"(d[76]), "+f"(d[77]), "+f"(d[78]), "+f"(d[79]), "+f"(d[80]), "+f"(d[81]), "+f"(d[82]), "+f"(d[83]), "+f"(d[84]), "+f"(d[85]), "+f"(d[86]), "+f"(d[87]), "+f"(d[88]), "+f"(d[89]), "+f"(d[90]), "+f"(d[91]), "+f"(d[92]), "+f"(d[93]), "+f"(d[94]), "+f"(d[95])
    : "r"(a[0]), "r"(a[1]), "r"(a[2]), "r"(a[3]), "l"(db), "r"(sd), "n"(TB));
}

template<int TB> __device__ __forceinline__ void wgmma_rs_n32(float* d, const uint32_t* a, uint64_t db, int sd) {
  asm volatile("{\n.reg .pred p;\nsetp.ne.b32 p, %21, 0;\n"
    "wgmma.mma_async.sync.aligned.m64n32k16.f32.bf16.bf16 {%0, %1, %2, %3, %4, %5, %6, %7, %8, %9, %10, %11, %12, %13, %14, %15}, {%16, %17, %18, %19}, %20, p, 1, 1, %22;\n}"
    : "+f"(d[0]), "+f"(d[1]), "+f"(d[2]), "+f"(d[3]), "+f"(d[4]), "+f"(d[5]), "+f"(d[6]), "+f"(d[7]), "+f"(d[8]), "+f"(d[9]), "+f"(d[10]), "+f"(d[11]), "+f"(d[12]), "+f"(d[13]), "+f"(d[14]), "+f"(d[15])
    : "r"(a[0]), "r"(a[1]), "r"(a[2]), "r"(a[3]), "l"(db), "r"(sd), "n"(TB));
}

template<int TB> __device__ __forceinline__ void wgmma_rs_n64(float* d, const uint32_t* a, uint64_t db, int sd) {
  asm volatile("{\n.reg .pred p;\nsetp.ne.b32 p, %37, 0;\n"
    "wgmma.mma_async.sync.aligned.m64n64k16.f32.bf16.bf16 {%0, %1, %2, %3, %4, %5, %6, %7, %8, %9, %10, %11, %12, %13, %14, %15, %16, %17, %18, %19, %20, %21, %22, %23, %24, %25, %26, %27, %28, %29, %30, %31}, {%32, %33, %34, %35}, %36, p, 1, 1, %38;\n}"
    : "+f"(d[0]), "+f"(d[1]), "+f"(d[2]), "+f"(d[3]), "+f"(d[4]), "+f"(d[5]), "+f"(d[6]), "+f"(d[7]), "+f"(d[8]), "+f"(d[9]), "+f"(d[10]), "+f"(d[11]), "+f"(d[12]), "+f"(d[13]), "+f"(d[14]), "+f"(d[15]), "+f"(d[16]), "+f"(d[17]), "+f"(d[18]), "+f"(d[19]), "+f"(d[20]), "+f"(d[21]), "+f"(d[22]), "+f"(d[23]), "+f"(d[24]), "+f"(d[25]), "+f"(d[26]), "+f"(d[27]), "+f"(d[28]), "+f"(d[29]), "+f"(d[30]), "+f"(d[31])
    : "r"(a[0]), "r"(a[1]), "r"(a[2]), "r"(a[3]), "l"(db), "r"(sd), "n"(TB));
}

template<int TB> __device__ __forceinline__ void wgmma_rs_n80(float* d, const uint32_t* a, uint64_t db, int sd) {
  asm volatile("{\n.reg .pred p;\nsetp.ne.b32 p, %45, 0;\n"
    "wgmma.mma_async.sync.aligned.m64n80k16.f32.bf16.bf16 {%0, %1, %2, %3, %4, %5, %6, %7, %8, %9, %10, %11, %12, %13, %14, %15, %16, %17, %18, %19, %20, %21, %22, %23, %24, %25, %26, %27, %28, %29, %30, %31, %32, %33, %34, %35, %36, %37, %38, %39}, {%40, %41, %42, %43}, %44, p, 1, 1, %46;\n}"
    : "+f"(d[0]), "+f"(d[1]), "+f"(d[2]), "+f"(d[3]), "+f"(d[4]), "+f"(d[5]), "+f"(d[6]), "+f"(d[7]), "+f"(d[8]), "+f"(d[9]), "+f"(d[10]), "+f"(d[11]), "+f"(d[12]), "+f"(d[13]), "+f"(d[14]), "+f"(d[15]), "+f"(d[16]), "+f"(d[17]), "+f"(d[18]), "+f"(d[19]), "+f"(d[20]), "+f"(d[21]), "+f"(d[22]), "+f"(d[23]), "+f"(d[24]), "+f"(d[25]), "+f"(d[26]), "+f"(d[27]), "+f"(d[28]), "+f"(d[29]), "+f"(d[30]), "+f"(d[31]), "+f"(d[32]), "+f"(d[33]), "+f"(d[34]), "+f"(d[35]), "+f"(d[36]), "+f"(d[37]), "+f"(d[38]), "+f"(d[39])
    : "r"(a[0]), "r"(a[1]), "r"(a[2]), "r"(a[3]), "l"(db), "r"(sd), "n"(TB));
}

template<int TB> __device__ __forceinline__ void wgmma_rs_n96(float* d, const uint32_t* a, uint64_t db, int sd) {
  asm volatile("{\n.reg .pred p;\nsetp.ne.b32 p, %53, 0;\n"
    "wgmma.mma_async.sync.aligned.m64n96k16.f32.bf16.bf16 {%0, %1, %2, %3, %4, %5, %6, %7, %8, %9, %10, %11, %12, %13, %14, %15, %16, %17, %18, %19, %20, %21, %22, %23, %24, %25, %26, %27, %28, %29, %30, %31, %32, %33, %34, %35, %36, %37, %38, %39, %40, %41, %42, %43, %44, %45, %46, %47}, {%48, %49, %50, %51}, %52, p, 1, 1, %54;\n}"
    : "+f"(d[0]), "+f"(d[1]), "+f"(d[2]), "+f"(d[3]), "+f"(d[4]), "+f"(d[5]), "+f"(d[6]), "+f"(d[7]), "+f"(d[8]), "+f"(d[9]), "+f"(d[10]), "+f"(d[11]), "+f"(d[12]), "+f"(d[13]), "+f"(d[14]), "+f"(d[15]), "+f"(d[16]), "+f"(d[17]), "+f"(d[18]), "+f"(d[19]), "+f"(d[20]), "+f"(d[21]), "+f"(d[22]), "+f"(d[23]), "+f"(d[24]), "+f"(d[25]), "+f"(d[26]), "+f"(d[27]), "+f"(d[28]), "+f"(d[29]), "+f"(d[30]), "+f"(d[31]), "+f"(d[32]), "+f"(d[33]), "+f"(d[34]), "+f"(d[35]), "+f"(d[36]), "+f"(d[37]), "+f"(d[38]), "+f"(d[39]), "+f"(d[40]), "+f"(d[41]), "+f"(d[42]), "+f"(d[43]), "+f"(d[44]), "+f"(d[45]), "+f"(d[46]), "+f"(d[47])
    : "r"(a[0]), "r"(a[1]), "r"(a[2]), "r"(a[3]), "l"(db), "r"(sd), "n"(TB));
}

template<int TA, int TB> __device__ __forceinline__ void wgmma_ss_n192(float* d, uint64_t da, uint64_t db, int sd) {
  asm volatile("{\n.reg .pred p;\nsetp.ne.b32 p, %98, 0;\n"
    "wgmma.mma_async.sync.aligned.m64n192k16.f32.bf16.bf16 {%0, %1, %2, %3, %4, %5, %6, %7, %8, %9, %10, %11, %12, %13, %14, %15, %16, %17, %18, %19, %20, %21, %22, %23, %24, %25, %26, %27, %28, %29, %30, %31, %32, %33, %34, %35, %36, %37, %38, %39, %40, %41, %42, %43, %44, %45, %46, %47, %48, %49, %50, %51, %52, %53, %54, %55, %56, %57, %58, %59, %60, %61, %62, %63, %64, %65, %66, %67, %68, %69, %70, %71, %72, %73, %74, %75, %76, %77, %78, %79, %80, %81, %82, %83, %84, %85, %86, %87, %88, %89, %90, %91, %92, %93, %94, %95}, %96, %97, p, 1, 1, %99, %100;\n}"
    : "+f"(d[0]), "+f"(d[1]), "+f"(d[2]), "+f"(d[3]), "+f"(d[4]), "+f"(d[5]), "+f"(d[6]), "+f"(d[7]), "+f"(d[8]), "+f"(d[9]), "+f"(d[10]), "+f"(d[11]), "+f"(d[12]), "+f"(d[13]), "+f"(d[14]), "+f"(d[15]), "+f"(d[16]), "+f"(d[17]), "+f"(d[18]), "+f"(d[19]), "+f"(d[20]), "+f"(d[21]), "+f"(d[22]), "+f"(d[23]), "+f"(d[24]), "+f"(d[25]), "+f"(d[26]), "+f"(d[27]), "+f"(d[28]), "+f"(d[29]), "+f"(d[30]), "+f"(d[31]), "+f"(d[32]), "+f"(d[33]), "+f"(d[34]), "+f"(d[35]), "+f"(d[36]), "+f"(d[37]), "+f"(d[38]), "+f"(d[39]), "+f"(d[40]), "+f"(d[41]), "+f"(d[42]), "+f"(d[43]), "+f"(d[44]), "+f"(d[45]), "+f"(d[46]), "+f"(d[47]), "+f"(d[48]), "+f"(d[49]), "+f"(d[50]), "+f"(d[51]), "+f"(d[52]), "+f"(d[53]), "+f"(d[54]), "+f"(d[55]), "+f"(d[56]), "+f"(d[57]), "+f"(d[58]), "+f"(d[59]), "+f"(d[60]), "+f"(d[61]), "+f"(d[62]), "+f"(d[63]), "+f"(d[64]), "+f"(d[65]), "+f"(d[66]), "+f"(d[67]), "+f"(d[68]), "+f"(d[69]), "+f"(d[70]), "+f"(d[71]), "+f"(d[72]), "+f"(d[73]), "+f"(d[74]), "+f"(d[75]), "+f"(d[76]), "+f"(d[77]), "+f"(d[78]), "+f"(d[79]), "+f"(d[80]), "+f"(d[81]), "+f"(d[82]), "+f"(d[83]), "+f"(d[84]), "+f"(d[85]), "+f"(d[86]), "+f"(d[87]), "+f"(d[88]), "+f"(d[89]), "+f"(d[90]), "+f"(d[91]), "+f"(d[92]), "+f"(d[93]), "+f"(d[94]), "+f"(d[95])
    : "l"(da), "l"(db), "r"(sd), "n"(TA), "n"(TB));
}

template<int TA, int TB> __device__ __forceinline__ void wgmma_ss_n8(float* d, uint64_t da, uint64_t db, int sd) {
  asm volatile("{\n.reg .pred p;\nsetp.ne.b32 p, %6, 0;\n"
    "wgmma.mma_async.sync.aligned.m64n8k16.f32.bf16.bf16 {%0, %1, %2, %3}, %4, %5, p, 1, 1, %7, %8;\n}"
    : "+f"(d[0]), "+f"(d[1]), "+f"(d[2]), "+f"(d[3])
    : "l"(da), "l"(db), "r"(sd), "n"(TA), "n"(TB));
}

constexpr int S_ = 2048, D_ = 640, F_ = 1536;

struct Scr {
  uint32_t flag[32 * 8];
  uint32_t mv[2 * 2048];
  bf16 cimg[8 * 6 * 512];
  uint2 st2[S_];
  bf16 kvT[D_ * S_];
  bf16 zT[D_ * S_];
  bf16 x1T[D_ * S_];
  bf16 AT[D_ * S_];
  uint4 PP[128 * 1280];
};
__device__ __align__(1024) Scr g_scr;
__device__ __forceinline__ uint32_t clk() { uint32_t c; asm volatile("mov.u32 %0, %%clock;" : "=r"(c) :: "memory"); return c; }
#define DEVSM 0
#define STAMP(id)
#define STAMPIF(c, id)
constexpr int FL_X = 5, FL_C = 128;
#define CD 600
#define SD 1000

constexpr int SM_X = 1024, SM_EXT = 21504, SM_SMALL = 29696, SM_STAT = 30720, SM_CB = 32768, SM_RING = 34816, SM_TOTAL = SM_RING + 6 * 32768;
constexpr int SMALL_LN = 224, SMALL_RED = 320, SMALL_DUMMY = 1008, SMALL_E = 1012, SMALL_TS = 160;
constexpr int JOB_SZ = 10880, JOB_V = 5760, R_X = 5 * 32768, R_BOX = R_X + 12288;
constexpr int K1OFF = 4672, KSZ = 9472, CSZ = KSZ + 4224;
enum { B_KJ = 0, B_X = 5, B_FB = 10, B_PEER = 20, B_RECV = 24, B_EXT = 28, B_X1 = 29, B_BOX = 38, B_F = 44, B_ST0 = 45, B_GB = 46,
       B_F1 = 48, B_E1 = 54, B_EB = 60,
       B_Z = 80, B_K = 85, B_EW = 88, B_ST2 = 94, B_XF = 95, B_LN = 96, B_KVS = 98, B_BD = 99,
       B_B = 106, B_S = 112 };
__device__ __forceinline__ uint32_t chan_base(uint32_t sb, int ch) { return sb + SM_RING + (2 + (ch >> 1)) * 32768 + (ch & 1) * CSZ; }

struct Params { CUtensorMap mS, mX, mWm, mK, mV, mG, mU, mD, mO, mO2; };

__device__ __forceinline__ void flag_add(Scr* G, int id) { asm volatile("red.relaxed.gpu.global.add.u32 [%0], 1;" ::"l"(G->flag + id) : "memory"); }
__device__ __forceinline__ uint32_t rdback(const void* p) { uint32_t v; asm volatile("ld.relaxed.gpu.global.u32 %0, [%1];" : "=r"(v) : "l"(p) : "memory"); return v; }
__device__ __forceinline__ void st_tag(uint2* p, uint32_t v, uint32_t t) { asm volatile("st.relaxed.gpu.global.v2.u32 [%0], {%1, %2};" ::"l"(p), "r"(v), "r"(t) : "memory"); }
__device__ __forceinline__ void spin(uint32_t t, uint32_t d) { if (d) while (clk() - t < d); }
__device__ __forceinline__ uint2 ld_tag(const uint2* p) { uint2 v; asm volatile("ld.relaxed.gpu.global.v2.u32 {%0, %1}, [%2];" : "=r"(v.x), "=r"(v.y) : "l"(p) : "memory"); return v; }
__device__ __forceinline__ uint4 ld_tag2(const uint2* p) {
  uint4 v;
  asm volatile("ld.relaxed.gpu.global.v4.u32 {%0, %1, %2, %3}, [%4];" : "=r"(v.x), "=r"(v.y), "=r"(v.z), "=r"(v.w) : "l"(p) : "memory");
  return v;
}
__device__ __forceinline__ void rdwait(uint32_t sb, uint32_t v) { sts32(sb + SM_SMALL + SMALL_DUMMY, v); }
__device__ __forceinline__ void fence_async_s() { asm volatile("fence.proxy.async.shared::cta;" ::: "memory"); }
__device__ __forceinline__ void fence_async_g() { asm volatile("fence.proxy.async.global;" ::: "memory"); }
__device__ __forceinline__ void bulk_done() { asm volatile("cp.async.bulk.commit_group;\n\tcp.async.bulk.wait_group 0;" ::: "memory"); }
__device__ __forceinline__ void flag_wait(Scr* G, int id, uint32_t target) {
  const uint32_t* p = G->flag + id;
#pragma unroll 1
  for (int i = 0; i < (1 << 20); i++) {
    uint32_t v;
    asm volatile("ld.relaxed.gpu.global.u32 %0, [%1];" : "=r"(v) : "l"(p) : "memory");
    if ((int)(v - target) >= 0) return;
  }
  __trap();
}
__device__ __forceinline__ int tbase(int pb) { return 127 - (32 * (pb >> 6) + 8 * (pb & 8) + 4 * ((2 * (pb & 3) - ((pb >> 2) & 1)) & 7) + ((pb >> 4) & 3)); }
__device__ __forceinline__ uint32_t hmul(uint32_t a, uint32_t b) { uint32_t d; asm("mul.rn.bf16x2 %0, %1, %2;" : "=r"(d) : "r"(a), "r"(b)); return d; }
__device__ __forceinline__ uint32_t hadd(uint32_t a, uint32_t b) { uint32_t d; asm("add.rn.bf16x2 %0, %1, %2;" : "=r"(d) : "r"(a), "r"(b)); return d; }
__device__ __forceinline__ uint32_t hsub(uint32_t a, uint32_t b) { uint32_t d; asm("sub.rn.bf16x2 %0, %1, %2;" : "=r"(d) : "r"(a), "r"(b)); return d; }
__device__ __forceinline__ uint32_t hfma(uint32_t a, uint32_t b, uint32_t c) { uint32_t d; asm("fma.rn.bf16x2 %0, %1, %2, %3;" : "=r"(d) : "r"(a), "r"(b), "r"(c)); return d; }
__device__ __forceinline__ uint32_t pack2(float lo, float hi) { uint32_t d; asm("cvt.rn.bf16x2.f32 %0, %1, %2;" : "=r"(d) : "f"(hi), "f"(lo)); return d; }
__device__ __forceinline__ float blo(uint32_t v) { return __uint_as_float(v << 16); }
__device__ __forceinline__ float bhi(uint32_t v) { return __uint_as_float(v & 0xffff0000u); }
__device__ __forceinline__ float rbf(float v) { return blo(pack2(v, 0.f)); }
template <int N> __device__ __forceinline__ void bfly(float* v, int mask, bool up) {
#pragma unroll
  for (int i = 0; i < N / 2; i++) {
    float send = up ? v[i] : v[i + N / 2], keep = up ? v[i + N / 2] : v[i];
    v[i] = keep + __shfl_xor_sync(0xffffffffu, send, mask);
  }
}
__device__ __forceinline__ bool mod_first(int b) { return !(b & 1) || !(b & 6); }
__device__ __forceinline__ int mod_grp(int b, int j) {
  const int m = b >> 3, s = b & 7, t = 16 * s + m, v = j ? (t * 43) >> 10 : s >> 1;
  if (j == 2) return b + 112;
  if (j == 0 && s == 1) return m + (m < 8 ? 152 : 192);
  return v < 4 ? (v == 3 ? 160 : 40 * v) + (j ? 16 + t - 24 * v : m) : t + 24;
}

__device__ __forceinline__ void kv_load(const bf16* gk, const bf16* gv, const bf16* gs, uint32_t sb, int b, int r, int tid) {
  const int row = tid >> 2, col = 128 * r + 32 * (b & 3);
  const uint32_t a = sb + SM_RING + r * JOB_SZ + (row >> 3) * 80 + (tid & 3) * 16, ak = a + (row & 7) * 720, av = a + (row & 7) * 640 + JOB_V;
  const int o = (64 * (b >> 2) + row) * D_ + col + 8 * (tid & 3);
  cp16(ak + 80, gk + o);
  cp16(ak + 400, gk + o + 32 * D_);
  cp16(av, gv + o);
  cp16(av + 320, gv + o + 32 * D_);
  if (tid < 12) cp16z(ak + 3600, gk + (b < 4 ? o : o - 3 * D_), b < 4 ? 0 : 16);
  else if (tid >= 112) cp16(sb + SM_CB + 256 * r + 16 * (tid - 112), gs + 4 * col + 8 * (tid - 112));
}
__device__ __forceinline__ void load_kv(const Params& P, const bf16* gs, uint32_t sb, int b, int r) {
  const uint32_t a = sb + SM_RING + r * JOB_SZ, bar = sb + 8 * (B_B + r);
  const int cg = 4 * r + (b & 3);
  mbar_expect(bar, JOB_SZ + 256);
  tma4d(a, &P.mK, 0, cg, 8 * (b >> 2) - 1, 0, bar);
  tma4d(a + JOB_V, &P.mV, 0, cg, 8 * (b >> 2), 0, bar);
  bulk_g2s(sb + SM_CB + 256 * r, gs + 128 * cg, 256, bar);
}
__device__ __forceinline__ uint4* kv_dst(Scr* G, int b, int r, int tid) {
  return (uint4*)(G->kvT + (128 * r + 32 * (b & 3) + 8 * (tid >> 5) + 2 * (tid & 3)) * S_ + 2040 - 64 * (b >> 2)) - ((tid >> 2) & 7);
}
__device__ __forceinline__ void kv_job(Scr* G, uint32_t sb, int b, int r, int tid) {
  const int cp = 4 * (tid >> 5) + (tid & 3);
  const uint32_t ka = sb + SM_RING + r * JOB_SZ + ((tid >> 2) & 7) * 80 + cp * 4;
  mbar_wait(sb + 8 * (B_B + r), 0);
  STAMPIF(tid == 0, 56 + r);
  const uint4 sk = lds128(sb + SM_CB + 256 * r + 16 * cp);
  const uint32_t s0 = __byte_perm(sk.x, sk.z, 0x5410), s1 = __byte_perm(sk.x, sk.z, 0x7632), s2 = __byte_perm(sk.y, sk.w, 0x5410), s3 = __byte_perm(sk.y, sk.w, 0x7632);
  uint32_t kk[11], o[8];
#pragma unroll
  for (int i = 0; i < 11; i++) kk[i] = lds32(ka + 720 * ((i + 5) & 7) + 80 * ((i + 5) >> 3));
#pragma unroll
  for (int i = 0; i < 8; i++) {
    uint32_t v = lds32(ka + JOB_V + 640 * i);
    o[i] = hmul(hfma(kk[i + 3], s0, hfma(kk[i + 2], s1, hfma(kk[i + 1], s2, hmul(kk[i], s3)))), v);
  }
  uint4* dst = kv_dst(G, b, r, tid);
  dst[0] = make_uint4(__byte_perm(o[7], o[6], 0x5410), __byte_perm(o[5], o[4], 0x5410), __byte_perm(o[3], o[2], 0x5410), __byte_perm(o[1], o[0], 0x5410) | 1);
  dst[256] = make_uint4(__byte_perm(o[7], o[6], 0x7632), __byte_perm(o[5], o[4], 0x7632), __byte_perm(o[3], o[2], 0x7632), __byte_perm(o[1], o[0], 0x7632) | 1);
  if (tid == 0) { sts32(sb + SM_SMALL + SMALL_TS + 4 * r, clk()); mbar_arrive(sb + 8 * (B_KJ + r)); }
}
__device__ __forceinline__ void u_wait(uint4& a, uint4& c, const void* p) {
  asm volatile("{\n.reg .pred p;\n.reg .b32 t, n;\nmov.b32 n, 0;\n"
               "L0:\nlop3.b32 t, %3, %7, 1, 0x80;\nsetp.eq.b32 p, t, 0;\nvote.sync.any.pred p, p, 0xffffffff;\n@!p bra.uni L1;\n"
               "ld.relaxed.gpu.global.v4.u32 {%0, %1, %2, %3}, [%8];\nld.relaxed.gpu.global.v4.u32 {%4, %5, %6, %7}, [%8+2048];\n"
               "add.u32 n, n, 1;\nsetp.lt.u32 p, n, 1000000;\n@p bra.uni L0;\ntrap;\nL1:\n}"
               : "+r"(a.x), "+r"(a.y), "+r"(a.z), "+r"(a.w), "+r"(c.x), "+r"(c.y), "+r"(c.z), "+r"(c.w) : "l"(p) : "memory");
}
__device__ __forceinline__ uint64_t box_a(uint32_t sb) { return mkdesc(sb + SM_RING + R_BOX, 256, 1024, 3); }
__device__ __forceinline__ uint64_t box_b(uint32_t sb) { return mkdesc(sb + SM_STAT, 64, 128, 0); }
__device__ __forceinline__ void mod_put(Scr* G, uint32_t sb, const float* a, int b, int j, uint32_t e1, int tid) {
  const uint32_t red = sb + SM_STAT + 1536;
  if ((tid & 3) == tid >> 6) sts64(red + 32 * ((tid >> 2) & 7) + 8 * (tid >> 5), __float_as_uint((tid & 32) ? a[1] : a[0]), __float_as_uint((tid & 32) ? a[3] : a[2]));
  bar_sync(j ? 4 : 5, 128);
  if (tid < 16) {
    const uint4 u = lds128(red + 32 * (tid & 7)), v = lds128(red + 32 * (tid & 7) + 16);
    asm volatile("" : "+r"(b));
    const int grp = mod_grp(b, j);
    const uint32_t one = (grp >= 40 && grp < 80) || (grp >= 160 && grp < 200) ? 0x3f803f80u : 0u;
    const float lo = __uint_as_float(u.x) + __uint_as_float(u.z) + __uint_as_float(v.x) + __uint_as_float(v.z);
    const float hi = __uint_as_float(u.y) + __uint_as_float(u.w) + __uint_as_float(v.y) + __uint_as_float(v.w);
    asm volatile("st.relaxed.gpu.global.u32 [%0], %1;" ::"l"(G->mv + 8 * grp + 256 * (tid & 8) + (tid & 7)),
                 "r"(((tid >> 3) ^ e1) & 1 ? 0 : ~hadd(pack2(lo, hi), one)) : "memory");
  }
}
__device__ __forceinline__ void mod_box(Scr* G, uint32_t sb, int b, int j, uint32_t e1, int tid) {
  float a[4];
  uint64_t da = box_a(sb), db = box_b(sb);
#pragma unroll
  for (int h = 0; h < 2; h++) {
    mbar_wait(sb + 8 * (B_BOX + 2 * j + h), 0);
    STAMPIF(tid == 0 && j == 0, 71 + h);
    wg_fence();
#pragma unroll
    for (int n = 5 * h; n < 5 * h + 5; n++) wgmma_ss_n8<1, 0>(a, da + 128 * n, db + 8 * n, n != 0);
    wg_commit();
  }
  wg_wait<0>();
#pragma unroll
  for (int i = 0; i < 4; i++) asm volatile("" : "+f"(a[i])::"memory");
  mod_put(G, sb, a, b, j, e1, tid);
}
__device__ __forceinline__ void a_check(uint32_t sa, const void* ga, uint32_t tag) {
  asm volatile("{\n.reg .pred p;\n.reg .b32 t, n, x, y, z;\n.reg .b64 g;\n"
               "ld.shared.b32 t, [%0];\nlop3.b32 t, t, %2, 1, 0x28;\nsetp.ne.b32 p, t, 0;\nvote.sync.any.pred p, p, 0xffffffff;\n@!p bra.uni L1;\nmov.b32 n, 0;\n"
               "L0:\nld.relaxed.gpu.global.b32 t, [%1];\nlop3.b32 t, t, %2, 1, 0x28;\nsetp.ne.b32 p, t, 0;\nvote.sync.any.pred p, p, 0xffffffff;\n@!p bra.uni L2;\n"
               "add.u32 n, n, 1;\nsetp.lt.u32 p, n, 1000000;\n@p bra.uni L0;\ntrap;\nL2:\n"
               "and.b64 g, %1, -32;\nand.b32 n, %0, -32;\n"
               "ld.relaxed.gpu.global.v4.b32 {t, x, y, z}, [g];\nst.shared.v4.b32 [n], {t, x, y, z};\n"
               "ld.relaxed.gpu.global.v4.b32 {t, x, y, z}, [g+16];\nst.shared.v4.b32 [n+16], {t, x, y, z};\n"
               "fence.proxy.async.shared::cta;\nbar.warp.sync 0xffffffff;\nL1:\n}" ::"r"(sa), "l"(ga), "r"(tag) : "memory");
}
__device__ __forceinline__ void z_wait(uint4& a, uint4& c, uint32_t* v, const void* p, const void* q) {
  asm volatile("{\n.reg .pred p;\n.reg .b32 t, n;\nmov.b32 n, 0;\n"
               "L0:\nlop3.b32 t, %3, %7, 1, 0x80;\nmin.u32 t, t, %8;\nmin.u32 t, t, %9;\nmin.u32 t, t, %10;\nmin.u32 t, t, %11;\n"
               "setp.eq.b32 p, t, 0;\nvote.sync.any.pred p, p, 0xffffffff;\n@!p bra.uni L1;\n"
               "ld.relaxed.gpu.global.v4.u32 {%0, %1, %2, %3}, [%12];\nld.relaxed.gpu.global.v4.u32 {%4, %5, %6, %7}, [%12+32768];\n"
               "ld.relaxed.gpu.global.u32 %8, [%13];\nld.relaxed.gpu.global.u32 %9, [%13+1280];\nld.relaxed.gpu.global.u32 %10, [%13+2560];\nld.relaxed.gpu.global.u32 %11, [%13+5120];\n"
               "add.u32 n, n, 1;\nsetp.lt.u32 p, n, 1000000;\n@p bra.uni L0;\ntrap;\nL1:\n}"
               : "+r"(a.x), "+r"(a.y), "+r"(a.z), "+r"(a.w), "+r"(c.x), "+r"(c.y), "+r"(c.z), "+r"(c.w), "+r"(v[0]), "+r"(v[1]), "+r"(v[2]), "+r"(v[3])
               : "l"(p), "l"(q) : "memory");
}
__device__ __forceinline__ void load_x(const Params& P, uint32_t sb, int b, int h) {
  const uint32_t bar = sb + 8 * (B_X + h);
  mbar_expect(bar, 10240);
  tma5d(sb + SM_X + h * 10240, &P.mX, 0, 0, 0, 5 * h, tbase(b), bar);
}
__device__ __forceinline__ uint32_t x_addr(uint32_t sb, int w, int lane) {
  const int rho = 15 - (4 * (lane >> 3) + 2 * (lane & 1) + ((lane >> 1) & 1));
  return sb + SM_X + (w >> 1) * 2048 + rho * 128 + (((2 * (w & 1) + (lane & 4)) ^ (rho & 7)) << 4);
}
__device__ __forceinline__ void ln1_job(uint32_t sb, int tid) {
  const uint32_t xr = sb + SM_X + 16 * tid;
  float pv, s1 = 0.f, s2 = 0.f, s3 = 0.f;
#pragma unroll 1
  for (int h = 0; h < 2; h++) {
    mbar_wait(sb + 8 * (B_X + h), 0);
    STAMPIF(tid == 0, 25);
    pv = blo(lds32(xr & ~127u));
#pragma unroll
    for (int n = 0; n < 5; n++) {
      const uint4 v = lds128(xr + 10240 * h + 2048 * n);
      const uint32_t u[4] = {v.x, v.y, v.z, v.w};
#pragma unroll
      for (int j = 0; j < 4; j++) {
        const float a = blo(u[j]) - pv, c = bhi(u[j]) - pv;
        s1 += a + c; s2 += a * a; s3 += c * c;
      }
    }
  }
  s2 += s3;
#pragma unroll
  for (int o = 1; o < 8; o <<= 1) { s1 += __shfl_xor_sync(0xffffffffu, s1, o); s2 += __shfl_xor_sync(0xffffffffu, s2, o); }
  const float mu = s1 * (1.f / D_), var = fmaxf(s2 * (1.f / D_) - mu * mu, 0.f);
  const float rs = __frcp_rn(rbf(__fsqrt_rn(rbf(rbf(var) + 1e-5f))));
  const int i = 15 - (tid >> 3), j = tid & 7;
  if (j < 2) sts16(sb + SM_SMALL + SMALL_LN + 32 * j + 16 * (i & 1) + (i & 14), pack2(j ? rs : pv + mu, 0.f));
  bar_sync(5, 128);
  STAMPIF(tid == 0, 75);
}
__device__ __forceinline__ void load_box(const Params& P, uint32_t sb, int b, int cls) {
  const uint32_t bar = sb + 8 * (B_BOX + cls);
  mbar_expect(bar, 10240);
  tma3d(sb + SM_RING + R_BOX + 10240 * (cls & 1), &P.mWm, 16 * mod_grp(b, cls >> 1), 0, 5 * (cls & 1), bar);
}
__device__ __forceinline__ void load_ssm(const Params& P, uint32_t sb, int b, int r) {
  const uint32_t bar = sb + 8 * (B_S + r);
  mbar_expect(bar, 16 * 288);
  tma3d(chan_base(sb, r) + 128, &P.mS, 0, 0, 128 * r + b, bar);
}
__device__ __forceinline__ void k1_job(uint32_t sb, int r, int tid) {
  const uint32_t a0 = chan_base(sb, r) + 128 + 16 * tid + 32 * (tid >> 4);
  mbar_wait(sb + 8 * (B_S + r), 0);
#pragma unroll
  for (int n = 0; n < 2; n++) {
    const uint32_t a = a0 + 2304 * n;
    const uint4 v = lds128(a);
    const uint32_t pv = lds32(a - ((tid & 15) ? 4 : 36));
    sts128(a + K1OFF, make_uint4(__byte_perm(pv, v.x, 0x5432), __byte_perm(v.x, v.y, 0x5432), __byte_perm(v.y, v.z, 0x5432), __byte_perm(v.z, v.w, 0x5432)));
  }
}

template <int ST> __device__ __forceinline__ void pp_send(uint4* p, const float* a, uint32_t tag) {
#pragma unroll
  for (int i = 0; i < 5; i++)
    p[ST * i] = make_uint4(pack2(a[8 * i], a[8 * i + 1]), pack2(a[8 * i + 2], a[8 * i + 3]), pack2(a[8 * i + 4], a[8 * i + 5]), (pack2(a[8 * i + 6], a[8 * i + 7]) & ~1u) | tag);
}
template <int ST> __device__ __forceinline__ void pp_load(uint4* f, const uint4* p) {
#pragma unroll
  for (int i = 0; i < 5; i++) f[i] = ld_tag2((const uint2*)(p + ST * i));
}
template <int ST> __device__ __forceinline__ void pp_wait(uint4* f, const uint4* p, uint32_t tag) {
  asm volatile("{\n.reg .pred p;\n.reg .b32 t, n;\nmov.b32 n, 0;\n"
               "L0:\nxor.b32 t, %3, %21;\nlop3.b32 t, t, %7, %21, 0xf6;\nlop3.b32 t, t, %11, %21, 0xf6;\nlop3.b32 t, t, %15, %21, 0xf6;\nlop3.b32 t, t, %19, %21, 0xf6;\n"
               "and.b32 t, t, 1;\nsetp.ne.b32 p, t, 0;\nvote.sync.any.pred p, p, 0xffffffff;\n@!p bra.uni L1;\n"
               "ld.relaxed.gpu.global.v4.u32 {%0, %1, %2, %3}, [%20];\nld.relaxed.gpu.global.v4.u32 {%4, %5, %6, %7}, [%20+%22];\n"
               "ld.relaxed.gpu.global.v4.u32 {%8, %9, %10, %11}, [%20+%23];\nld.relaxed.gpu.global.v4.u32 {%12, %13, %14, %15}, [%20+%24];\n"
               "ld.relaxed.gpu.global.v4.u32 {%16, %17, %18, %19}, [%20+%25];\n"
               "add.u32 n, n, 1;\nsetp.lt.u32 p, n, 1000000;\n@p bra.uni L0;\ntrap;\nL1:\n}"
               : "+r"(f[0].x), "+r"(f[0].y), "+r"(f[0].z), "+r"(f[0].w), "+r"(f[1].x), "+r"(f[1].y), "+r"(f[1].z), "+r"(f[1].w), "+r"(f[2].x), "+r"(f[2].y),
                 "+r"(f[2].z), "+r"(f[2].w), "+r"(f[3].x), "+r"(f[3].y), "+r"(f[3].z), "+r"(f[3].w), "+r"(f[4].x), "+r"(f[4].y), "+r"(f[4].z), "+r"(f[4].w)
               : "l"(p), "r"(tag), "n"(16 * ST), "n"(32 * ST), "n"(48 * ST), "n"(64 * ST) : "memory");
}
__device__ __forceinline__ void pp_add(float* a, const uint4* f, const uint4* e, bool first) {
#pragma unroll
  for (int i = 0; i < 5; i++) {
    const uint32_t v[4] = {f[i].x, f[i].y, f[i].z, f[i].w}, u[4] = {e[i].x, e[i].y, e[i].z, e[i].w};
#pragma unroll
    for (int j = 0; j < 8; j++) a[8 * i + j] = ((j & 1) ? bhi(v[j >> 1]) : blo(v[j >> 1])) + (!first ? a[8 * i + j] : (j & 1) ? bhi(u[j >> 1]) : blo(u[j >> 1]));
  }
}
__device__ __forceinline__ int out_col(int s, int n) { return 320 * (s & 1) + (n < 4 ? 32 * (s & 6) + 16 * n : 256 + 8 * (s & 6)); }
__device__ __forceinline__ void l2_prefetch(const void* p, int bytes) { asm volatile("cp.async.bulk.prefetch.L2.global [%0], %1;" ::"l"(p), "r"(bytes) : "memory"); }
__device__ __forceinline__ void pf_line(const void* p) { asm volatile("prefetch.global.L2 [%0];" ::"l"(p) : "memory"); }
__device__ __forceinline__ int role(int bx) {
  const int c = bx >> 1, d = c - 36, q = (d * 37) >> 8, k = d - 7 * q;
  const int rank = c < 4 ? 12 + c : c < 36 ? ((c - 4) & 7) * 8 + ((c - 4) >> 3) : (k ? k + 1 : 0) * 8 + 4 + q;
  return 8 * (rank & 15) + 2 * (rank >> 4) + (bx & 1);
}
enum { K_KV, K_SSM, K_BOX, K_PW, K_PD, K_PKV, K_PSSM, K_PBOX, K_W, K_X, K_ST, K_END = 15 };
#define E(t, bar, kind, r) ((t) << 16 | (bar) << 8 | (kind) << 4 | (r))
#define SCHED E(2800, 255, K_BOX, 0), E(0, 255, K_BOX, 1), E(3700, 255, K_KV, 2), E(4400, 255, K_SSM, 2), E(4800, 255, K_KV, 3), E(5500, 255, K_X, 0), \
              E(6400, 255, K_X, 1), E(7200, 255, K_SSM, 3), E(7600, 255, K_KV, 4), E(8300, 255, K_SSM, 4), E(8600, 255, K_BOX, 2), E(9500, 255, K_PW, 0), \
              E(10100, 255, K_BOX, 3)
#define XPF 2
#define XBOTH 0
#define AUXP 0xfedcb30217ull
constexpr int aux_last(int mask) { int r = 0; for (uint64_t p = AUXP; p; p >>= 4) if ((mask >> (p & 15)) & 1) r = p & 15; return r; }
constexpr int kLastKv = aux_last(0x0e);
#define XI 8
#define XW 0
#define PWM 0x3c
#define STM 0x7c0
#define PDM 0x3800
#define KVP0 1
#define KVP1 2
#define KV1L 0
#define CVT 1
#define UPOS 4
#define UD 1000
#define PL1 12
#define PL2 14
#define SJ(h) (3 * (h))
constexpr uint32_t kSched[] = {SCHED, E(0, 255, K_END, 0)};
struct In { const bf16 *k, *v, *sk, *Wg, *Wu, *Wd, *ss; };
__device__ __forceinline__ void load_w(const Params& P, uint32_t sb, int s, int it) {
  const int st = it % 5;
  mbar_wait(sb + 8 * (B_E1 + st), (it / 5) & 1);
  const uint32_t a = sb + SM_RING + st * 32768 + 8192, fb = sb + 8 * (B_F1 + st);
  mbar_expect(fb, 24576);
#pragma unroll
  for (int j = 0; j < 3; j++) {
    tma2d(a + 8192 * j, &P.mG, 192 * s + 64 * j, 32 * it, fb);
    tma2d(a + 8192 * j + 4096, &P.mU, 192 * s + 64 * j, 32 * it, fb);
  }
}

template <int I> __device__ __forceinline__ int sched_run(const Params& P, const In& in, uint32_t sb, int b, int lane, uint32_t t_0) {
  constexpr uint32_t e = kSched[I];
  constexpr int kind = (e >> 4) & 15, r = e & 15, bar = (e >> 8) & 255;
  if constexpr (kind == K_END) return 0;
  else {
    if constexpr ((e >> 16) != 0) while (clk() - t_0 < (e >> 16));
    if (bar != 255) mbar_wait(sb + 8 * bar, 0);
    if (kind == K_BOX && r == 2) mbar_wait(sb + 8 * B_BD, 0);
    if (kind == K_PKV) {
      const bf16* kvp = (lane < 16 ? in.k : in.v) + (16 * b + (lane & 15)) * D_ + 128 * r;
      pf_line(kvp); pf_line(kvp + 64);
    } else {
      if (elect()) {
        if (kind == K_KV) load_kv(P, in.sk, sb, b, r);
        if (kind == K_X) load_x(P, sb, b, r);
        if (kind == K_SSM) load_ssm(P, sb, b, r);
        if (kind == K_BOX && (r > 1 || mod_first(b))) load_box(P, sb, b, r);
        if (kind == K_PW) { l2_prefetch(in.Wg + (128 * r + b) * F_, 2 * F_); l2_prefetch(in.Wu + (128 * r + b) * F_, 2 * F_); }
        if (kind == K_PSSM) l2_prefetch(in.ss + (128 * r + b) * S_, 4096);
      }
      __syncwarp();
    }
    return sched_run<I + 1>(P, in, sb, b, lane, t_0) + (kind == K_PW);
  }
}

__global__ void __launch_bounds__(512, 1) fused_kernel(const bf16* __restrict__ gk, const bf16* __restrict__ gv, const bf16* __restrict__ gsk,
                                                       const bf16* __restrict__ gD, const bf16* __restrict__ gc, Scr* G, const bf16* gWg, const bf16* gWu,
                                                       const bf16* gWd, const bf16* gx, const bf16* gss, const __grid_constant__ Params P) {
  extern __shared__ __align__(1024) char smem_raw[];
  const uint32_t sb = smem_u32(smem_raw), ring = sb + SM_RING;
  const int b = role(blockIdx.x), m = b >> 3, s = b & 7;
  const uint32_t t_0 = clk();
  const int wg = __shfl_sync(0xffffffffu, threadIdx.x >> 7, 0);
  const int tid = threadIdx.x & 127, lane = tid & 31;
  const int w = __shfl_sync(0xffffffffu, tid >> 5, 0);
  if (wg < 2) {
    if (!KV1L || wg == 0) kv_load(gk, gv, gsk, sb, b, wg, tid);
  } else {
    if (wg == 2) {
      if (tid < 40) {
        int c = tid & 7;
        sts128(chan_base(sb, tid >> 3) + (c < 2 ? 80 + c * K1OFF : KSZ + 4096 + (c - 2) * 16), make_uint4(0, 0, 0, 0));
      }
    }
    if (elect()) {
      const int j = 4 * (3 - wg) + w - 1;
      if (j < 4) asm volatile("prefetch.tensormap [%0];" ::"l"(&P.mX + j) : "memory");
      if (j < 0) {
#pragma unroll
        for (int i = 0; i < 5; i++) mbar_init(sb + 8 * (B_S + i), 1);
        fence_async_s();
        if (XPF > 0) load_ssm(P, sb, b, 0);
        if (XPF > 1) load_ssm(P, sb, b, 1);
      } else {
        const int c = j < 3 ? 1 : j < 5 ? 2 : 4;
#pragma unroll
        for (int i = 0; i < 16; i++) mbar_init(sb + 128 * j + 8 * i, i < 10 || j < 6 ? c : i < 12 ? 128 : 1);
      }
    }
    fence_async_s();
  }
  __syncthreads();
  STAMPIF(threadIdx.x == 0, 55);

  if (wg < 2) {
    if (KV1L && wg == 1) kv_load(gk, gv, gsk, sb, b, wg, tid);
    cp_arrive(sb + 8 * (B_B + wg));
    asm volatile("setmaxnreg.inc.sync.aligned.u32 224;");
    STAMPIF(threadIdx.x == 0, 82);
    const int g = lane >> 2, q = lane & 3;
    if (wg == 1) bar_arrive(1, 256);
    uint32_t dv = *(const uint16_t*)(gD + 128 * wg + b);
#pragma unroll 1
    for (int pr = wg ? KVP1 : KVP0; pr; pr >>= 4) {
      kv_job(G, sb, b, (pr & 15) - 1, tid);
      STAMPIF(tid == 0, (pr & 15) < 3 ? pr & 15 : 19 + (pr & 15));
    }
    k1_job(sb, wg, tid);
    bar_sync(3 + wg, 128);
    if (tid < 2) mbar_arrive(sb + 8 * (B_E1 + tid));
    STAMPIF(threadIdx.x == 0, 79);
    {
      const int b0 = (g >> 1) & 1, b1 = g >> 2, u = q + 4 * b0 - w;
      const uint32_t fo = 128 + (g & 1) * K1OFF + 288 * b1 + 4 * u, fo0 = fo - (u < 0 ? 32 : 0);
      const uint32_t dsel = (b1 == 0 && u == 0) ? ((g & 1) ? 0x1044 : 0x4410) : 0x4444;
      const bool wrap = b0 && q == 0;
      const int src1 = b0 ? ((lane & 20) | ((q - 1) & 3)) : (lane | 8);
      const uint2* pu = (const uint2*)(G->kvT + (128 * wg + b) * S_ + 8 * tid);
      uint4 u0 = make_uint4(0, 0, 0, 0), u1 = u0;
      if (UPOS & 1) { u0 = ld_tag2(pu); u1 = ld_tag2(pu + 256); }
#pragma unroll 1
      for (int ch = wg; ch < 5; ch += 2) {
        const uint32_t base = chan_base(sb, ch);
        if (ch >= 2) {
          mbar_wait(sb + 8 * (B_K + ch - 2), 0);
          if (UPOS & 4) { u0 = ld_tag2(pu); u1 = ld_tag2(pu + 256); }
          mbar_wait(sb + 8 * (B_S + ch), 0);
        }
        const uint32_t fa = base + fo, fa0 = base + fo0;
        uint32_t af[16][4];
#pragma unroll
        for (int j = 0; j < 16; j++) {
          const int o = 64 * (j & 1) + 576 * (j >> 1);
          af[j][0] = lds32(((j & 1) ? fa : fa0) + o); af[j][1] = lds32(fa + o + 128); af[j][2] = lds32(fa + o + 32); af[j][3] = lds32(fa + o + 160);
        }
        af[0][0] = hadd(af[0][0], __byte_perm(dv, 0, dsel));
        STAMPIF(tid == 0, 40 + ch);
        u_wait(u0, u1, pu);
        sts128(base + KSZ + 16 * tid, u0);
        sts128(base + KSZ + 2048 + 16 * tid, u1);
        fence_async_s();
        pu += 128 * S_ / 2;
        float acc[128];
        const uint64_t db = mkdesc(base + KSZ, 32, 128, 0);
        bar_sync(1 + wg, 256);
        wg_fence();
        wgmma_rs_n64<0>(acc + 96, af[0], db + 192, 0);
        wgmma_rs_n192<0>(acc, af[0], db, 0);
        wgmma_rs_n64<0>(acc + 96, af[1], db + 196, 1);
        wgmma_rs_n192<0>(acc, af[1], db + 4, 1);
        wgmma_rs_n32<0>(acc + 96, af[2], db + 224, 1);
        wgmma_rs_n192<0>(acc, af[2], db + 32, 1);
        wgmma_rs_n32<0>(acc + 96, af[3], db + 228, 1);
        wgmma_rs_n192<0>(acc, af[3], db + 36, 1);
        wgmma_rs_n192<0>(acc, af[4], db + 64, 1);
        wgmma_rs_n192<0>(acc, af[5], db + 68, 1);
        wgmma_rs_n160<0>(acc, af[6], db + 96, 1);
        wgmma_rs_n160<0>(acc, af[7], db + 100, 1);
        if (CVT == 2) wg_commit();
        wgmma_rs_n128<0>(acc, af[8], db + 128, 1);
        wgmma_rs_n128<0>(acc, af[9], db + 132, 1);
        if (CVT == 1) wg_commit();
        wgmma_rs_n96<0>(acc, af[10], db + 160, 1);
        wgmma_rs_n96<0>(acc, af[11], db + 164, 1);
        if (CVT == 0) bar_arrive(2 - wg, 256);
        wgmma_rs_n64<0>(acc, af[12], db + 192, 1);
        wgmma_rs_n64<0>(acc, af[13], db + 196, 1);
        wgmma_rs_n32<0>(acc, af[14], db + 224, 1);
        wgmma_rs_n32<0>(acc, af[15], db + 228, 1);
        wg_commit();
        if (ch < 3) asm volatile("ld.global.nc.u16 %0, [%1];" : "=r"(dv) : "l"(gD + 128 * (ch + 2) + b));
        if (CVT) { wg_wait<1>(); if (ch < 4) bar_arrive(2 - wg, 256); }
        STAMPIF(tid == 0, 3 + ch);
        wg_wait<0>();
#pragma unroll
        for (int i = 0; i < 128; i++) asm volatile("" : "+f"(acc[i])::"memory");
        bar_sync(3 + wg, 128);
        if (tid <= (ch >> 2)) mbar_arrive(sb + 8 * (B_E1 + 2 + (ch >> 1)));
        if (ch < 3 && !(UPOS & 14)) { u0 = ld_tag2(pu); u1 = ld_tag2(pu + 256); }
        float S0[33], T[34];
#pragma unroll
        for (int i = 0; i < 31; i++) S0[i] = acc[4 * i] + acc[4 * i + 6];
        S0[31] = acc[124]; S0[32] = 0.f;
#pragma unroll
        for (int i = 0; i < 32; i++) {
          float s1 = i < 31 ? acc[4 * i + 1] + acc[4 * i + 7] : acc[125];
          T[i] = (wrap ? S0[i + 1] : S0[i]) + __shfl_sync(0xffffffffu, s1, src1);
        }
        T[32] = 0.f; T[33] = 0.f;
        uint4* pz = (uint4*)(G->zT + (128 * ch + b) * S_) + ((tid & 120) | (2 * q) | (g & 1));
#pragma unroll
        for (int h = 0; h < 2; h++) {
          float y[8];
#pragma unroll
          for (int mu = 0; mu < 8; mu++) y[mu] = (b1 ? T[4 * mu + 4 + h] : T[4 * mu + h]) + __shfl_xor_sync(0xffffffffu, T[4 * mu + 2 + h], 16);
          pz[128 * h] = make_uint4(pack2(y[0], y[1]), pack2(y[2], y[3]), pack2(y[4], y[5]), pack2(y[6], y[7]) | 1);
        }
        if (ch < 3 && (UPOS & 2)) { u0 = ld_tag2(pu); u1 = ld_tag2(pu + 256); }
        if (UPOS & 8) u0.w = 0;
        __syncwarp();
        if (lane == 0) mbar_arrive(sb + 8 * (B_Z + ch));
        STAMPIF(tid == 0, 8 + ch);
      }
    }
    uint32_t hh[96];
    {
      float ga[192];
      float* ua = ga + 96;
      const uint64_t da0 = mkdesc(ring + wg * 2048, 512, 256, 3), db0 = mkdesc(ring + 8192, 4096, 1024, 1);
      int st = 0, ph = 0;
      mbar_wait(sb + 8 * B_BD, 0);
      const uint32_t e1 = lds32(sb + SM_SMALL + SMALL_E);
      if (wg) {
        mod_box(G, sb, b, 1, e1, tid);
        __syncwarp();
        if (lane == 0) mbar_arrive(sb + 8 * (B_BD + 1));
        STAMPIF(tid == 0, 73);
      }
      const int ao = 256 * (lane & 16) + 16 * (threadIdx.x & 224) + 32 * (lane & 15) + 4 * (lane & 4) + (lane & 8) + 4;
      const bool cs = b < 96;
      const int x0 = wg ? XI : 99, x1 = x0 + (cs ? 4 : 2), xs = cs ? 4 : 8;
      uint64_t xa = cs ? mkdesc(sb + SM_EXT, 4096, 1024, 1) : box_a(sb), xb = cs ? mkdesc(sb + SM_CB, 32, 128, 0) : box_b(sb);
      uint64_t ya = xa + (cs ? (SM_RING + R_X - SM_EXT) / 16 : 256), yb = xb + 16;
      float bx[4];
#pragma unroll 1
      for (int it = 0; it < 20; it++) {
        if (it == x0) {
          mbar_wait(sb + 8 * (cs ? B_F : B_BOX + 4), 0);
          mbar_wait(sb + 8 * (cs ? B_ST0 : B_BOX + 5), 0);
          STAMPIF(tid == 0, 76);
        }
        if (it == x1 + XW) {
          wg_wait<XW>();
#pragma unroll
          for (int i = 0; i < 4; i++) asm volatile("" : "+f"(bx[i])::"memory");
          if (!cs) mod_put(G, sb, bx, b, 2, e1, tid);
          else {
            const int row = (m < 6 ? 0 : 4) + q;
            uint16_t* dst = (uint16_t*)G->cimg + s * 3072 + (m % 6) * 512 + row * 64 + g;
#pragma unroll
            for (int j = 0; j < 2; j++) {
              const float c1 = __shfl_sync(0xffffffffu, bx[2 * j], lane & 28), c2 = __shfl_sync(0xffffffffu, bx[2 * j + 1], lane & 28);
              const float t = (lane & 2) ? c2 : c1, hi = rbf(t);
              dst[((2 * w + j) ^ row) << 3] = (uint16_t)pack2((lane & 1) ? t - hi : hi, 0.f);
            }
          }
          __syncwarp();
          if (lane == 0) mbar_arrive(sb + 8 * (B_BD + 2));
          STAMPIF(tid == 0, 77);
        }
        mbar_wait(sb + 8 * (B_F1 + st), ph);
        a_check(ring + st * 32768 + ao, (const char*)G->AT + (20 * m + it) * 8192 + ao, e1);
        STAMPIF(tid == 0 && it == 0, 13 + wg);
        STAMPIF(threadIdx.x == 0, 100 + it);
        const uint64_t da = da0 + st * 2048, db = db0 + st * 2048;
        if (it >= x0 && it < x1) {
          wg_fence();
          wgmma_ss_n8<1, 0>(bx, xa, xb, it != x0);
          wgmma_ss_n192<1, 1>(ga, da, db, 1);
          wgmma_ss_n8<1, 0>(bx, ya, yb, 1);
          wgmma_ss_n192<1, 1>(ua, da, db + 768, 1);
          wgmma_ss_n8<1, 0>(bx, ya + 128, yb + xs, 1);
          wgmma_ss_n192<1, 1>(ga, da + 256, db + 128, 1);
          wgmma_ss_n8<1, 0>(bx, ya + 256, yb + 2 * xs, 1);
          wgmma_ss_n192<1, 1>(ua, da + 256, db + 128 + 768, 1);
          wgmma_ss_n8<1, 0>(bx, ya + 384, yb + 3 * xs, 1);
          wg_commit();
          xa += 128; xb += xs; ya += 512; yb += 4 * xs;
        } else {
          wg_fence();
          wgmma_ss_n192<1, 1>(ga, da, db, it != 0);
          wgmma_ss_n192<1, 1>(ua, da, db + 768, it != 0);
          wgmma_ss_n192<1, 1>(ga, da + 256, db + 128, 1);
          wgmma_ss_n192<1, 1>(ua, da + 256, db + 128 + 768, 1);
          wg_commit();
        }
        wg_wait<1>();
        if (it > 0 && tid == 0) mbar_arrive(sb + 8 * (B_E1 + (st == 0 ? 4 : st - 1)));
        if (++st == 5) { st = 0; ph ^= 1; }
      }
      STAMPIF(threadIdx.x == 0, 61);
      if (tid == 0) {
        mbar_wait(sb + 8 * (B_E1 + 5), 0);
        mbar_arrive_remote(mapa(sb + 8 * (B_PEER + 2 * wg), (b & 1) ^ 1));
      }
      mbar_wait(sb + 8 * B_EXT, 0);
      mbar_wait(sb + 8 * B_ST2, 0);
      const uint64_t de = mkdesc(sb + SM_EXT, 1024, 0, 1), ds = mkdesc(sb + SM_STAT + wg * 1024, 0, 128, 0);
      wg_fence();
      wgmma_ss_n192<0, 1>(ga, ds, de, 1);
      wgmma_ss_n192<0, 1>(ua, ds, de + 192, 1);
      wg_commit();
      wg_wait<1>();
      if (tid == 0) {
        mbar_arrive(sb + 8 * (B_E1 + 4));
        mbar_arrive_remote(mapa(sb + 8 * (B_PEER + 2 * wg + 1), (b & 1) ^ 1));
      }
      wg_wait<0>();
#pragma unroll
      for (int i = 0; i < 192; i++) asm volatile("" : "+f"(ga[i])::"memory");
      STAMPIF(tid == 0, 15 + wg);
#pragma unroll
      for (int i = 0; i < 48; i++) {
        const int j = 64 * (i >> 4) + 2 * (i & 15);
        hh[i] = pack2(ga[j] * ga[j + 32], ga[j + 1] * ga[j + 33]);
        asm volatile("" : "+r"(hh[i])::"memory");
      }
    }
    float acc[80];
    uint4 pf[15];
    const uint32_t tag = lds32(sb + SM_SMALL + SMALL_E) & 1;
    uint4* const pp[3] = {G->PP + 10240 * m + threadIdx.x, (uint4*)G->zT + 16 * m + 256 * (threadIdx.x >> 4) + (tid & 15), (uint4*)G->kvT + 10240 * m + threadIdx.x};
    {
      const uint32_t la = ring + wg * 2048 + tid * 16, ra = mapa(la, (b & 1) ^ 1), rb = mapa(sb + 8 * (B_RECV + 2 * wg), (b & 1) ^ 1);
#pragma unroll
      for (int h = 0; h < 16; h++) {
        const int gr = h >> 1, pe = gr < 4 ? gr >> 1 : gr & 1, ac = gr < 4 ? gr & 1 : gr / 6, d = gr < 4 ? ac + 1 : ac + 3;
        if (h == 0) mbar_wait(sb + 8 * B_FB, 0);
        if (h == 4) mbar_wait(sb + 8 * (B_FB + 5), 0);
        if (!(h & 1)) mbar_wait(sb + 8 * (B_FB + gr + (gr < 4 ? 1 : 2)), 0);
        if (gr == 2) {
          mbar_wait(sb + 8 * (B_RECV + 2 * wg + (h & 1)), 0);
#pragma unroll
          for (int j = 6 * (h & 1); j < 6 * (h & 1) + 6; j++) {
            const uint4 v = lds128(la + (j < 2 ? 5 : (j >> 1) - 1) * 32768 + (j & 1) * 4096);
            hh[48 + 4 * j] = v.x; hh[49 + 4 * j] = v.y; hh[50 + 4 * j] = v.z; hh[51 + 4 * j] = v.w;
          }
        }
        STAMPIF(threadIdx.x == 0 && h % 4 == 0, 121 + h / 4);
        const uint64_t db = mkdesc(ring + (gr & 3) * 32768 + 8192, (5 - pe - (gr & 3)) * 32768 + 16 * ((s + 2 * d) & 6), 1024, 1);
        wg_fence();
#pragma unroll
        for (int j = 6 * (h & 1); j < 6 * (h & 1) + 6; j++) wgmma_rs_n80<1>(acc + 40 * ac, hh + 48 * pe + 4 * j, db + 128 * j, pe || j);
        wg_commit();
        if (h < 4) {
#pragma unroll
          for (int j = SJ(h); j < SJ(h + 1); j++) {
            if (j == 0 || j == 10) mbar_wait(sb + 8 * (B_PEER + 2 * wg + j / 10), 0);
            st_async4(ra + (j < 2 ? 5 : (j >> 1) - 1) * 32768 + (j & 1) * 4096, hh + 4 * j, rb + 8 * (j / 6));
          }
          STAMPIF(tid == 0 && h == 3, 81);
        }
        if (h == 2 || h == 4 || h == 6 || h == 8 || h == 12) {
          wg_wait<1>();
          if (h < 12 && tid == 0) mbar_arrive(sb + 8 * (B_EB + gr - 1));
          if (h >= 6) {
            const int i = h == 6 ? 1 : h == 8 ? 2 : 3;
            float* a = acc + 40 * (1 - ac);
#pragma unroll
            for (int j = 0; j < 40; j++) asm volatile("" : "+f"(a[j])::"memory");
            if (i == 2) pp_send<4096>(pp[1] + (s ^ 4) * 20480, a, 0);
            else pp_send<256>(pp[i - 1] + ((s + 2 * i) & 7) * 1280, a, i == 1 ? tag : 0);
            STAMPIF(threadIdx.x == 0, 50 + i);
          }
        }
        if (h == 5) bar_sync(3 + wg, 128);
        if (h == PL1) pp_load<256>(pf, pp[0] + s * 1280);
        if (h == PL2) pp_load<4096>(pf + 5, pp[1] + s * 20480);
        if (h == 14) wg_wait<1>();
      }
    }
    STAMPIF(tid == 0, 17);
    uint32_t xr[20], gbv[10];
    mbar_wait(sb + 8 * B_X1, 0);
    mbar_wait(sb + 8 * B_GB, 0);
    float rs0 = 2.f * blo(lds32(sb + SM_STAT + (64 * wg + 16 * w + g) * 16 + 4)), rs1 = 2.f * blo(lds32(sb + SM_STAT + (64 * wg + 16 * w + g) * 16 + 132));
    {
      const uint32_t la = sb + SM_X + (4 * wg + w) * 512 + (8 * (lane >> 4) + (lane & 7)) * 32 + ((((lane >> 3) ^ (lane >> 2)) & 1) << 4);
#pragma unroll
      for (int i = 0; i < 5; i++) ldsm4t(xr + 4 * i, la + i * 4096);
#pragma unroll
      for (int i = 0; i < 10; i++) gbv[i] = lds32(sb + SM_CB + 1280 + 32 * i + 4 * q);
    }
    rs0 = __frcp_rn(rs0 * rs0); rs1 = __frcp_rn(rs1 * rs1);
#pragma unroll
    for (int i = 0; i < 3; i++) {
      if (i == 1) pp_wait<4096>(pf + 5, pp[1] + s * 20480, 0);
      else pp_wait<256>(pf + 5 * i, pp[i] + s * 1280, i ? 0 : tag);
      if (i == 1) pp_load<256>(pf + 10, pp[2] + s * 1280);
      STAMPIF(threadIdx.x == 0 && i < 2, 98 + i);
      if (i) pp_add(acc, pf + 5 * i, pf, i == 1);
#pragma unroll
      for (int j = 0; j < 40 && i == 1; j++) asm volatile("" : "+f"(acc[j])::"memory");
    }
#pragma unroll
    for (int i = 0; i < 40; i++) { acc[i] *= (i & 2) ? rs1 : rs0; asm volatile("" : "+f"(acc[i])::"memory"); }
    STAMPIF(threadIdx.x == 0, 125);
    wg_wait<0>();
    float* a = acc + 40;
#pragma unroll
    for (int i = 0; i < 40; i++) asm volatile("" : "+f"(a[i])::"memory");
    STAMPIF(tid == 0, 18);
    uint32_t ov[20];
#pragma unroll
    for (int i = 0; i < 10; i++) {
      ov[2 * i] = hadd(xr[2 * i], hmul(gbv[i], pack2(a[4 * i] * rs0 + acc[4 * i], a[4 * i + 1] * rs0 + acc[4 * i + 1])));
      ov[2 * i + 1] = hadd(xr[2 * i + 1], hmul(gbv[i], pack2(a[4 * i + 2] * rs1 + acc[4 * i + 2], a[4 * i + 3] * rs1 + acc[4 * i + 3])));
    }
    const uint32_t obuf = ring + w * 32768 + wg * 2048;
    const int orow = ~lane & 15;
#pragma unroll
    for (int i = 0; i < 4; i++) stsm4(obuf + orow * 128 + (((lane >> 4) + 2 * i) ^ (orow & 7)) * 16, ov + 4 * i);
    stsm4(obuf + 4096 + orow * 32 + (lane >> 4) * 16, ov + 16);
    fence_async_s();
    __syncwarp();
    if (elect()) {
      const int t = tbase(8 * m + 4 * wg + w);
      tma_store4d(&P.mO, obuf, out_col(s, 0), 0, 0, t);
      tma_store4d(&P.mO2, obuf + 4096, out_col(s, 4), 0, 0, t);
      asm volatile("cp.async.bulk.commit_group;" ::: "memory");
      asm volatile("cp.async.bulk.wait_group.read 0;" ::: "memory");
    }
  } else if (wg == 2) {
    asm volatile("setmaxnreg.dec.sync.aligned.u32 40;");
    const uint32_t e1 = (rdback(G->flag + 8 * m + 4) >> 5) + 1;
    if (tid < 80) {
      uint4 c = ((const uint4*)gc)[tid];
#pragma unroll 1
      for (int i = 0; i < 4; i++) {
        const float lo = blo(c.x), hi = bhi(c.x);
        sts32(sb + SM_STAT + 16 * tid + 4 * i, pack2(__fdividef(lo, 1.f + __expf(-lo)), __fdividef(hi, 1.f + __expf(-hi))));
        c.x = c.y; c.y = c.z; c.z = c.w;
      }
    }
    if (tid == 0) sts32(sb + SM_SMALL + SMALL_E, e1);
    fence_async_s();
    bar_sync(5, 128);
    int tl = tid;
#pragma unroll 1
    for (uint64_t pr = AUXP; pr; pr >>= 4) {
      asm volatile("" : "+r"(tl));
      const int op = pr & 15, tid = tl, lane = tid & 31;
      if (op == 0) {
        ln1_job(sb, tid);
      } else if (op < 4) {
        kv_job(G, sb, b, op + 1, tid);
        STAMPIF(tid == 0, 21 + op);
      } else if (op < 11) {
        if (mod_first(b)) mod_box(G, sb, b, 0, e1, tid);
        __syncwarp();
        if (lane == 0) mbar_arrive(sb + 8 * B_BD);
        STAMPIF(tid == 0, 27);
      } else {
        const int r = op - 11, cg = 8 * r + 4 * (w >> 1) + (lane & 2) + (w & 1), g = lane >> 2;
        const uint2* pz = (const uint2*)(G->zT + (16 * cg + g) * S_ + 16 * b + 8 * (lane & 1));
        const uint32_t* pc = G->mv + 2048 * (e1 & 1) + 8 * cg + g;
        mbar_wait(sb + 8 * (B_BD + (r > 1)), 0);
        mbar_wait(sb + 8 * (B_Z + r), 0);
        STAMPIF(tid == 0 && r == 0, 28);
        uint4 z[2] = {ld_tag2(pz), ld_tag2(pz + 4096)};
        uint32_t c[4] = {rdback(pc), rdback(pc + 320), rdback(pc + 640), rdback(pc + 1280)}, xv[8];
        const uint32_t xa = x_addr(sb, w, lane) + 4096 * r, la = sb + SM_SMALL + SMALL_LN + 16 * (lane & 1);
        const uint4 m4 = lds128(la), s4 = lds128(la + 32);
        const uint32_t m_[4] = {m4.x, m4.y, m4.z, m4.w}, s_[4] = {s4.x, s4.y, s4.z, s4.w};
        ldsm4t(xv, xa);
        ldsm4t(xv + 4, xa ^ 16);
        z_wait(z[0], z[1], c, pz, pc);
        STAMPIF(tid == 0 && r == 0, 83);
        uint4* pa = (uint4*)G->AT + ((40 * m + cg) * 8 + s) * 32 + 2 * g + ((lane ^ (lane >> 4)) & 1);
#pragma unroll
        for (int j = 0; j < 4; j++) c[j] = ~c[j];
#pragma unroll
        for (int n = 0; n < 2; n++) {
          const uint32_t z_[4] = {z[n].x, z[n].y, z[n].z, z[n].w}, sel = n ? 0x3232 : 0x1010;
          const uint32_t sa = __byte_perm(c[0], 0, sel), ca1 = __byte_perm(c[1], 0, sel), ga = __byte_perm(c[2], 0, sel), cb1 = __byte_perm(c[3], 0, sel);
          uint32_t o[4], a[4];
#pragma unroll
          for (int j = 0; j < 4; j++) {
            o[j] = hfma(ga, hmul(hfma(hmul(hsub(xv[4 * n + j], m_[j]), s_[j]), ca1, sa), z_[j]), xv[4 * n + j]);
            a[j] = hmul(o[j], cb1);
          }
          a[2 * n + 1] = (a[2 * n + 1] & ~1u) | (e1 & 1);
          pa[16 * n] = make_uint4(a[0], a[1], a[2], a[3]);
          if (n) { __syncwarp(); if (lane == 0) flag_add(G, 8 * m + r); }
          pa[16 * n - D_ * S_ / 8] = make_uint4(o[0], o[1], o[2], o[3]);
          sts128(xa ^ (16 * n), make_uint4(o[0], o[1], o[2], o[3]));
        }
        __syncwarp();
        if (lane == 0) mbar_arrive(sb + 8 * (B_EW + r));
        STAMPIF(tid == 0, 29 + r);
      }
      if (op == kLastKv) { __syncwarp(); if (lane == 0) mbar_arrive(sb + 8 * B_KVS); }
    }
    {
      const uint4 m4 = lds128(sb + SM_SMALL + SMALL_LN + 16 * (lane & 1));
      const uint32_t m_[4] = {m4.x, m4.y, m4.z, m4.w}, xa = x_addr(sb, w, lane);
      float a[16];
#pragma unroll
      for (int i = 0; i < 16; i++) a[i] = 0.f;
#pragma unroll 2
      for (int n = 0; n < 10; n++) {
        const uint4 x4 = lds128((xa ^ (16 * (n & 1))) + 2048 * (n & 14));
        const uint32_t x_[4] = {x4.x, x4.y, x4.z, x4.w};
#pragma unroll
        for (int i = 0; i < 4; i++) {
          const float d0 = blo(x_[i]) - blo(m_[i]), d1 = bhi(x_[i]) - bhi(m_[i]);
          a[4 * i] += d0; a[4 * i + 1] += d0 * d0; a[4 * i + 2] += d1; a[4 * i + 3] += d1 * d1;
        }
      }
      STAMPIF(lane == 0, 67 + (w & 1) + 11 * (w >> 1));
      bfly<16>(a, 16, lane & 16); bfly<8>(a, 8, lane & 8); bfly<4>(a, 4, lane & 4); bfly<2>(a, 2, lane & 2);
      if (lane == 0) mbar_arrive(sb + 8 * B_XF);
      STAMPIF(tid == 0, 88);
      sts32(sb + SM_SMALL + SMALL_RED + 16 * lane + 4 * w, __float_as_uint(a[0]));
      bar_sync(5, 128);
      if (w == 0) {
        const uint4 v = lds128(sb + SM_SMALL + SMALL_RED + 16 * lane);
        const float s1 = __uint_as_float(v.x) + __uint_as_float(v.y) + __uint_as_float(v.z) + __uint_as_float(v.w), s2 = __shfl_xor_sync(0xffffffffu, s1, 2);
        const int p = 8 * (lane & 1) + (lane >> 2);
        const float pv = blo(lds32(sb + SM_SMALL + SMALL_LN + 4 * (p >> 1)) >> (16 * (p & 1)));
        const float mu = s1 * (1.f / D_), var = fmaxf(s2 * (1.f / D_) - mu * mu, 0.f);
        const float sd = rbf(__fsqrt_rn(rbf(rbf(var) + 1e-5f)));
        if (!(lane & 2)) st_tag(G->st2 + 16 * b + p, pack2(-0.5f * (pv + mu), 0.5f * sd), e1);
      }
      STAMPIF(tid == 0, 87);
    }
    {
      uint2 v;
      spin(clk(), SD);
      mbar_wait(sb + 8 * (B_BD + 2), 0);
#pragma unroll 1
      for (int i = 0;; i++) {
        v = ld_tag(G->st2 + 128 * m + tid);
        if (__all_sync(0xffffffffu, v.y == e1)) break;
        if (i > (1 << 20)) __trap();
      }
      const uint32_t hm = __byte_perm(v.x, 0, 0x1010), hs = __byte_perm(v.x, 0, 0x3232);
      sts128(sb + SM_STAT + 16 * tid, make_uint4(hm, hs, hm, hs));
      fence_async_s();
      __syncwarp();
      if (lane == 0) mbar_arrive(sb + 8 * B_ST2);
      STAMPIF(tid == 0, 21);
    }
  } else {
    asm volatile("setmaxnreg.dec.sync.aligned.u32 24;");
    if (w != 0) {
    if (w == 2 && lane < 5) asm volatile("prefetch.tensormap [%0];" ::"l"(&P.mG + lane) : "memory");
    if (w & 1) {
#pragma unroll 1
      for (int j = 4; j < 10; j++) {
        k1_job(sb, j >> 1, 64 * (j & 1) + 16 * (w & 2) + lane);
        if (UD && w == 1 && (j & 1)) {
          mbar_wait(sb + 8 * (B_KJ + (j >> 1)), 0);
          const uint32_t t = lds32(sb + SM_SMALL + SMALL_TS + 4 * (j >> 1));
          while (clk() - t < UD);
        }
        __syncwarp();
        if (lane == 0) mbar_arrive(sb + 8 * (B_K + (j >> 1) - 2));
      }
      STAMPIF(tid == 32, 74);
    }
    if (w == 1) {
     {
      if (elect()) {
        mbar_wait(sb + 8 * B_KVS, 0);
        mbar_wait(sb + 8 * B_EW, 0);
        const uint32_t e1 = lds32(sb + SM_SMALL + SMALL_E);
#pragma unroll 1
        for (int it = 0; it < 20; it++) {
          int st = it % 5;
          if ((it & 3) == 0) { flag_wait(G, 8 * m + (it >> 2), e1 * 32); STAMP(45 + (it >> 2)); }
          mbar_wait(sb + 8 * (B_E1 + st), (it / 5) & 1);
          uint32_t fb = sb + 8 * (B_F1 + st);
          mbar_expect(fb, 8192);
          bulk_g2s(ring + st * 32768, G->AT + (20 * m + it) * 4096, 8192, fb);
        }
        mbar_wait(sb + 8 * B_XF, 0);
        flag_wait(G, 8 * m + FL_X, e1 * 8);
        fence_async_g();
        mbar_expect(sb + 8 * B_X1, 20480);
        bulk_g2s(sb + SM_X, G->x1T + (640 * m + out_col(s, 0)) * 128, 16384, sb + 8 * B_X1);
        bulk_g2s(sb + SM_X + 16384, G->x1T + (640 * m + out_col(s, 4)) * 128, 4096, sb + 8 * B_X1);
        STAMP(86);
      }
     }
    } else if (w == 2) {
      if (lane < 4) mbar_expect(sb + 8 * (B_RECV + lane), 12288);
      mbar_wait(sb + 8 * (B_EW + 4), 0);
      const uint32_t e1 = lds32(sb + SM_SMALL + SMALL_E);
      {
        const bf16* p = G->x1T + ((40 * m + (lane >> 2)) * 8 + s) * 256 + 64 * (lane & 3);
        uint32_t v = 0;
#pragma unroll
        for (int r = 0; r < 5; r++) v ^= rdback(p + 16384 * r);
        rdwait(sb, v);
        __syncwarp();
        if (lane == 0) flag_add(G, 8 * m + FL_X);
        STAMPIF(lane == 0, 94);
      }
      mbar_wait(sb + 8 * (B_BD + 2), 0);
      if (lane < 2) mbar_arrive(sb + 8 * (B_E1 + 5));
      if (m < 12) {
        rdwait(sb, rdback(G->cimg + s * 3072 + (m % 6) * 512 + (m < 6 ? 0 : 256) + 64 * (lane & 3)));
        __syncwarp();
        if (lane == 0) flag_add(G, FL_C + 8 * s);
        STAMPIF(lane == 0, 35);
      }
      if (elect()) {
        flag_wait(G, FL_C + 8 * s, e1 * 12);
        fence_async_g();
        STAMP(54);
        mbar_expect(sb + 8 * B_EXT, 6144);
        bulk_g2s(sb + SM_EXT, G->cimg + s * 3072, 6144, sb + 8 * B_EXT);
      }
    } else {
      mbar_wait(sb + 8 * B_KVS, 0);
      mbar_wait(sb + 8 * (B_BD + 1), 0);
      if (b >= 96 && elect()) { load_box(P, sb, b, 4); load_box(P, sb, b, 5); }
      spin(clk(), CD);
      __syncwarp();
      const uint32_t* p = G->mv + 2048 * (lds32(sb + SM_SMALL + SMALL_E) & 1) + 4 * (lane & 1);
#pragma unroll 1
      for (int n = 0; n < 4; n++) {
        if (n == 3) {
          fence_async_s();
          __syncwarp();
          if (lane == 0) mbar_arrive(sb + 8 * B_F);
          STAMPIF(lane == 0, 34);
          mbar_wait(sb + 8 * B_ST2, 0);
        }
        const int j = n < 3 ? min(16 * n + (lane >> 1), 39) : min(40 + (lane >> 1), 44), k = j < 20 ? j : j - 20;
        const uint2* pj = (const uint2*)(p + (j < 40 ? 8 * (k + (j < 20 ? 160 : 120) + (m < 6 ? 0 : 20)) : 1600 + out_col(s, k - 20) / 2));
        uint4 a;
#pragma unroll 1
        for (int i = 0;; i++) {
          a = ld_tag2(pj);
          if (__all_sync(0xffffffffu, a.x != 0)) break;
          if (i > (1 << 20)) __trap();
        }
        const uint32_t d = sb + SM_CB + 64 * k + 8 * (lane & 1) + (j >= 20 && j < 40 ? 16 : 0);
        sts64(d, ~__byte_perm(a.x, a.y, 0x5410), ~__byte_perm(a.z, a.w, 0x5410));
        sts64(d + 32, ~__byte_perm(a.x, a.y, 0x7632), ~__byte_perm(a.z, a.w, 0x7632));
      }
      __syncwarp();
      if (lane == 0) mbar_arrive(sb + 8 * B_GB);
      STAMPIF(lane == 0, 39);
    }
    } else {
      STAMPIF(lane == 0, 62);
      int rw = sched_run<0>(P, In{gk, gv, gsk, gWg, gWu, gWd, gss}, sb, b, lane, __shfl_sync(0xffffffffu, t_0, 0));
      if (elect()) {
        STAMP(69);
        mbar_wait(sb + 8 * B_KVS, 0);
        STAMP(70);
        int rd = 0, c = 0;
#pragma unroll 1
        for (int it = 0; it < 20; it++) {
          load_w(P, sb, s, it);
          if ((PWM >> it) & 1) { l2_prefetch(gWg + (128 * rw + b) * F_, 2 * F_); l2_prefetch(gWu + (128 * rw + b) * F_, 2 * F_); rw++; }
          if ((PDM >> it) & 1) { l2_prefetch(gWd + (512 * rd + 4 * b) * D_, 8 * D_); rd++; }
          if (((STM >> it) & 1) && b < 96) {
            const int grp = m % 6;
            if (c == 4) mbar_wait(sb + 8 * (B_BD + 1), 0);
            if (c == 0) mbar_expect(sb + 8 * B_ST0, 40960);
#pragma unroll
            for (int j = 0; j < 2; j++, c++)
              tma2d(sb + (c < 2 ? SM_EXT : SM_RING + R_X - 8192) + 4096 * c, &P.mG + (grp & 1), 192 * s + 64 * (grp >> 1), (m < 6 ? 0 : 320) + 32 * c, sb + 8 * B_ST0);
          }
        }
#pragma unroll
        for (int k = 0; k < 10; k++) {
          const int st = k == 0 ? 5 : (k - 1) % 5, pe = k < 6 ? k / 3 : k & 1, d = k < 6 ? 2 - (k & 1) : k >> 1;
          mbar_wait(sb + 8 * (k < 6 ? B_E1 + st : B_EB + st), 0);
          mbar_expect(sb + 8 * (B_FB + k), 24576);
          tma2d(ring + st * 32768 + 8192, &P.mD, 320 * (s & 1) + (st > 3 ? 256 : 32 * ((s + 2 * d) & 6)), 192 * (s ^ pe), sb + 8 * (B_FB + k));
        }
      }
    }
  }
}

typedef CUresult (*EncFn)(CUtensorMap*, CUtensorMapDataType, cuuint32_t, void*, const cuuint64_t*, const cuuint64_t*, const cuuint32_t*, const cuuint32_t*,
                          CUtensorMapInterleave, CUtensorMapSwizzle, CUtensorMapL2promotion, CUtensorMapFloatOOBfill);
static void mkmap(EncFn enc, CUtensorMap* m, const void* p, int rank, const cuuint64_t* dims, const cuuint64_t* strides, const cuuint32_t* box, CUtensorMapSwizzle sw) {
  cuuint32_t es[5] = {1, 1, 1, 1, 1};
  CUresult r = enc(m, CU_TENSOR_MAP_DATA_TYPE_BFLOAT16, rank, (void*)p, dims, strides, box, es, CU_TENSOR_MAP_INTERLEAVE_NONE, sw,
                   CU_TENSOR_MAP_L2_PROMOTION_L2_128B, CU_TENSOR_MAP_FLOAT_OOB_FILL_NONE);
  if (r != CUDA_SUCCESS) fprintf(stderr, "tensor map encode failed: %d\n", (int)r);
}

extern "C" void kernel_launch(void* const* d_in, const int* in_sizes, int n_in, void* d_out, int out_size) {
  void* fn = nullptr;
  cudaDriverEntryPointQueryResult qr;
  cudaGetDriverEntryPoint("cuTensorMapEncodeTiled", &fn, cudaEnableDefault, &qr);
  EncFn enc = (EncFn)fn;
  Scr* G;
  cudaGetSymbolAddress((void**)&G, g_scr);
  Params P;
  { cuuint64_t d[] = {128, 16, 640}, st[] = {256, 4096}; cuuint32_t bx[] = {144, 16, 1}; mkmap(enc, &P.mS, d_in[4], 3, d, st, bx, CU_TENSOR_MAP_SWIZZLE_NONE); }
  { cuuint64_t d[] = {3840, 64, 10}, st[] = {7680, 64 * 7680}; cuuint32_t bx[] = {16, 64, 5}; mkmap(enc, &P.mWm, d_in[11], 3, d, st, bx, CU_TENSOR_MAP_SWIZZLE_32B); }
  { cuuint64_t d[] = {32, 20, 256, 8}, st[] = {64, 10240, 1280}; cuuint32_t bx[] = {40, 1, 9, 8}, bx2[] = {40, 1, 8, 8};
    mkmap(enc, &P.mK, d_in[1], 4, d, st, bx, CU_TENSOR_MAP_SWIZZLE_NONE); mkmap(enc, &P.mV, d_in[2], 4, d, st, bx2, CU_TENSOR_MAP_SWIZZLE_NONE); }
  { cuuint64_t d[] = {1536, 640}, st[] = {3072}; cuuint32_t bx[] = {64, 32};
    mkmap(enc, &P.mG, d_in[7], 2, d, st, bx, CU_TENSOR_MAP_SWIZZLE_128B); mkmap(enc, &P.mU, d_in[8], 2, d, st, bx, CU_TENSOR_MAP_SWIZZLE_128B); }
  { cuuint64_t d[] = {640, 1536}, st[] = {1280}; cuuint32_t bx[] = {64, 192}; mkmap(enc, &P.mD, d_in[9], 2, d, st, bx, CU_TENSOR_MAP_SWIZZLE_128B); }
  { cuuint64_t d[] = {64, 2, 8, 10, 128}, st[] = {1280, 256 * 1280, 128, 2560}; cuuint32_t bx[] = {64, 2, 8, 5, 1}; mkmap(enc, &P.mX, d_in[0], 5, d, st, bx, CU_TENSOR_MAP_SWIZZLE_128B); }
  { cuuint64_t d[] = {640, 8, 2, 128}, st[] = {256 * 1280, 1280, 2560}; cuuint32_t bx[] = {64, 8, 2, 1}, bx2[] = {16, 8, 2, 1};
    mkmap(enc, &P.mO, d_out, 4, d, st, bx, CU_TENSOR_MAP_SWIZZLE_128B); mkmap(enc, &P.mO2, d_out, 4, d, st, bx2, CU_TENSOR_MAP_SWIZZLE_NONE); }
  cudaFuncSetAttribute(fused_kernel, cudaFuncAttributeMaxDynamicSharedMemorySize, SM_TOTAL + DEVSM);
  cudaLaunchConfig_t cfg = {};
  cfg.gridDim = dim3(128); cfg.blockDim = dim3(512); cfg.dynamicSmemBytes = SM_TOTAL + DEVSM; cfg.stream = cudaStreamPerThread;
  cudaLaunchAttribute at[1];
  at[0].id = cudaLaunchAttributeClusterDimension; at[0].val.clusterDim.x = 2; at[0].val.clusterDim.y = 1; at[0].val.clusterDim.z = 1;
  cfg.attrs = at; cfg.numAttrs = 1;
  cudaLaunchKernelEx(&cfg, fused_kernel, (const bf16*)d_in[1], (const bf16*)d_in[2], (const bf16*)d_in[3], (const bf16*)d_in[5], (const bf16*)d_in[10], G,
                     (const bf16*)d_in[7], (const bf16*)d_in[8], (const bf16*)d_in[9], (const bf16*)d_in[0], (const bf16*)d_in[4], P);
}
```

```cpp
#include <cuda_runtime.h>
#include <cuda.h>
#include <cuda_bf16.h>
#include <stdio.h>
#include <stdint.h>
typedef __nv_bfloat16 bf16;
__device__ __forceinline__ uint32_t smem_u32(const void* p) { return (uint32_t)__cvta_generic_to_shared(p); }
__device__ __forceinline__ void mbar_init(uint32_t bar, int cnt) { asm volatile("mbarrier.init.shared::cta.b64 [%0], %1;" ::"r"(bar), "r"(cnt) : "memory"); }
__device__ __forceinline__ void mbar_expect(uint32_t bar, int bytes) { asm volatile("mbarrier.arrive.expect_tx.shared::cta.b64 _, [%0], %1;" ::"r"(bar), "r"(bytes) : "memory"); }
__device__ __forceinline__ void mbar_arrive(uint32_t bar) { asm volatile("mbarrier.arrive.shared::cta.b64 _, [%0];" ::"r"(bar) : "memory"); }
__device__ __forceinline__ void mbar_arrive_remote(uint32_t bar) { asm volatile("mbarrier.arrive.relaxed.cluster.shared::cluster.b64 _, [%0];" ::"r"(bar) : "memory"); }
__device__ __forceinline__ uint32_t mapa(uint32_t a, uint32_t cta) { uint32_t r; asm("mapa.shared::cluster.u32 %0, %1, %2;" : "=r"(r) : "r"(a), "r"(cta)); return r; }
__device__ __forceinline__ bool mbar_try(uint32_t bar, int parity) {
  uint32_t ok;
  asm volatile("{\n.reg .pred p;\nmbarrier.try_wait.parity.shared::cta.b64 p, [%1], %2;\nselp.u32 %0, 1, 0, p;\n}" : "=r"(ok) : "r"(bar), "r"(parity) : "memory");
  return ok;
}
__device__ __forceinline__ void mbar_wait(uint32_t bar, int parity) {
#pragma unroll 1
  for (int i = 0; i < (1 << 20); i++) { if (mbar_try(bar, parity)) return; }
  __trap();
}
__device__ __forceinline__ bool elect() {
  uint32_t p;
  asm volatile("{\n.reg .pred P;\nelect.sync _|P, 0xffffffff;\nselp.u32 %0, 1, 0, P;\n}" : "=r"(p));
  return p;
}
__device__ __forceinline__ void tma2d(uint32_t dst, const CUtensorMap* m, int c0, int c1, uint32_t bar) {
  asm volatile("cp.async.bulk.tensor.2d.shared::cluster.global.mbarrier::complete_tx::bytes [%0], [%1, {%3, %4}], [%2];" ::"r"(dst), "l"(m), "r"(bar), "r"(c0), "r"(c1) : "memory");
}
__device__ __forceinline__ void tma3d(uint32_t dst, const CUtensorMap* m, int c0, int c1, int c2, uint32_t bar) {
  asm volatile("cp.async.bulk.tensor.3d.shared::cluster.global.mbarrier::complete_tx::bytes [%0], [%1, {%3, %4, %5}], [%2];" ::"r"(dst), "l"(m), "r"(bar), "r"(c0), "r"(c1), "r"(c2) : "memory");
}
__device__ __forceinline__ void tma4d(uint32_t dst, const CUtensorMap* m, int c0, int c1, int c2, int c3, uint32_t bar) {
  asm volatile("cp.async.bulk.tensor.4d.shared::cluster.global.mbarrier::complete_tx::bytes [%0], [%1, {%3, %4, %5, %6}], [%2];" ::"r"(dst), "l"(m), "r"(bar), "r"(c0), "r"(c1), "r"(c2), "r"(c3) : "memory");
}
__device__ __forceinline__ void tma5d(uint32_t dst, const CUtensorMap* m, int c0, int c1, int c2, int c3, int c4, uint32_t bar) {
  asm volatile("cp.async.bulk.tensor.5d.shared::cluster.global.mbarrier::complete_tx::bytes [%0], [%1, {%3, %4, %5, %6, %7}], [%2];" ::"r"(dst), "l"(m), "r"(bar), "r"(c0), "r"(c1), "r"(c2), "r"(c3), "r"(c4) : "memory");
}
__device__ __forceinline__ void tma_store2d(const CUtensorMap* m, uint32_t src, int c0, int c1) {
  asm volatile("cp.async.bulk.tensor.2d.global.shared::cta.bulk_group [%0, {%2, %3}], [%1];" ::"l"(m), "r"(src), "r"(c0), "r"(c1) : "memory");
}
__device__ __forceinline__ void tma_store4d(const CUtensorMap* m, uint32_t src, int c0, int c1, int c2, int c3) {
  asm volatile("cp.async.bulk.tensor.4d.global.shared::cta.bulk_group [%0, {%2, %3, %4, %5}], [%1];" ::"l"(m), "r"(src), "r"(c0), "r"(c1), "r"(c2), "r"(c3) : "memory");
}
__device__ __forceinline__ void tma_prefetch2d(const CUtensorMap* m, int c0, int c1) {
  asm volatile("cp.async.bulk.prefetch.tensor.2d.L2.global [%0, {%1, %2}];" ::"l"(m), "r"(c0), "r"(c1) : "memory");
}
__device__ __forceinline__ void bulk_g2s(uint32_t dst, const void* src, int bytes, uint32_t bar) {
  asm volatile("cp.async.bulk.shared::cluster.global.mbarrier::complete_tx::bytes [%0], [%1], %2, [%3];" ::"r"(dst), "l"(src), "r"(bytes), "r"(bar) : "memory");
}
__device__ __forceinline__ void bulk_s2g(void* dst, uint32_t src, int bytes) {
  asm volatile("cp.async.bulk.global.shared::cta.bulk_group [%0], [%1], %2;" ::"l"(dst), "r"(src), "r"(bytes) : "memory");
}
__device__ __forceinline__ void cp16(uint32_t dst, const void* src) { asm volatile("cp.async.cg.shared.global [%0], [%1], 16;" ::"r"(dst), "l"(src) : "memory"); }
__device__ __forceinline__ void cp16z(uint32_t dst, const void* src, int n) { asm volatile("cp.async.cg.shared.global [%0], [%1], 16, %2;" ::"r"(dst), "l"(src), "r"(n) : "memory"); }
__device__ __forceinline__ void cp_arrive(uint32_t bar) { asm volatile("cp.async.mbarrier.arrive.noinc.shared::cta.b64 [%0];" ::"r"(bar) : "memory"); }
__device__ __forceinline__ void st_async4(uint32_t dst, const uint32_t* v, uint32_t bar) {
  asm volatile("st.async.weak.shared::cluster.mbarrier::complete_tx::bytes.v4.b32 [%0], {%1, %2, %3, %4}, [%5];" ::"r"(dst), "r"(v[0]), "r"(v[1]), "r"(v[2]), "r"(v[3]), "r"(bar) : "memory");
}
__device__ __forceinline__ void wg_fence() { asm volatile("wgmma.fence.sync.aligned;" ::: "memory"); }
__device__ __forceinline__ void wg_commit() { asm volatile("wgmma.commit_group.sync.aligned;" ::: "memory"); }
template <int N> __device__ __forceinline__ void wg_wait() { asm volatile("wgmma.wait_group.sync.aligned %0;" ::"n"(N) : "memory"); }
__device__ __forceinline__ uint64_t mkdesc(uint32_t addr, uint32_t lbo, uint32_t sbo, uint32_t swz) {
  return (uint64_t)((addr & 0x3FFFF) >> 4) | ((uint64_t)(lbo >> 4) << 16) | ((uint64_t)(sbo >> 4) << 32) | ((uint64_t)swz << 62);
}
__device__ __forceinline__ void ldsm4t(uint32_t* r, uint32_t a) {
  asm volatile("ldmatrix.sync.aligned.m8n8.x4.trans.shared.b16 {%0,%1,%2,%3}, [%4];" : "=r"(r[0]), "=r"(r[1]), "=r"(r[2]), "=r"(r[3]) : "r"(a) : "memory");
}
__device__ __forceinline__ void stsm4(uint32_t a, const uint32_t* r) {
  asm volatile("stmatrix.sync.aligned.m8n8.x4.shared.b16 [%0], {%1,%2,%3,%4};" ::"r"(a), "r"(r[0]), "r"(r[1]), "r"(r[2]), "r"(r[3]) : "memory");
}
__device__ __forceinline__ void bar_sync(int id, int n) { asm volatile("bar.sync %0, %1;" ::"r"(id), "r"(n) : "memory"); }
__device__ __forceinline__ void bar_arrive(int id, int n) { asm volatile("bar.arrive %0, %1;" ::"r"(id), "r"(n) : "memory"); }
__device__ __forceinline__ uint32_t lds32(uint32_t a) { uint32_t v; asm volatile("ld.shared.b32 %0, [%1];" : "=r"(v) : "r"(a) : "memory"); return v; }
__device__ __forceinline__ uint2 lds64(uint32_t a) { uint2 v; asm volatile("ld.shared.v2.b32 {%0,%1}, [%2];" : "=r"(v.x), "=r"(v.y) : "r"(a) : "memory"); return v; }
__device__ __forceinline__ uint4 lds128(uint32_t a) { uint4 v; asm volatile("ld.shared.v4.b32 {%0,%1,%2,%3}, [%4];" : "=r"(v.x), "=r"(v.y), "=r"(v.z), "=r"(v.w) : "r"(a) : "memory"); return v; }
__device__ __forceinline__ void sts16(uint32_t a, uint32_t v) { asm volatile("st.shared.b16 [%0], %1;" ::"r"(a), "h"((uint16_t)v) : "memory"); }
__device__ __forceinline__ void sts32(uint32_t a, uint32_t v) { asm volatile("st.shared.b32 [%0], %1;" ::"r"(a), "r"(v) : "memory"); }
__device__ __forceinline__ void sts64(uint32_t a, uint32_t x, uint32_t y) { asm volatile("st.shared.v2.b32 [%0], {%1,%2};" ::"r"(a), "r"(x), "r"(y) : "memory"); }
__device__ __forceinline__ void sts128(uint32_t a, uint4 v) { asm volatile("st.shared.v4.b32 [%0], {%1,%2,%3,%4};" ::"r"(a), "r"(v.x), "r"(v.y), "r"(v.z), "r"(v.w) : "memory"); }
template<int TB> __device__ __forceinline__ void wgmma_rs_n128(float* d, const uint32_t* a, uint64_t db, int sd) {
  asm volatile("{\n.reg .pred p;\nsetp.ne.b32 p, %69, 0;\n"
    "wgmma.mma_async.sync.aligned.m64n128k16.f32.bf16.bf16 {%0, %1, %2, %3, %4, %5, %6, %7, %8, %9, %10, %11, %12, %13, %14, %15, %16, %17, %18, %19, %20, %21, %22, %23, %24, %25, %26, %27, %28, %29, %30, %31, %32, %33, %34, %35, %36, %37, %38, %39, %40, %41, %42, %43, %44, %45, %46, %47, %48, %49, %50, %51, %52, %53, %54, %55, %56, %57, %58, %59, %60, %61, %62, %63}, {%64, %65, %66, %67}, %68, p, 1, 1, %70;\n}"
    : "+f"(d[0]), "+f"(d[1]), "+f"(d[2]), "+f"(d[3]), "+f"(d[4]), "+f"(d[5]), "+f"(d[6]), "+f"(d[7]), "+f"(d[8]), "+f"(d[9]), "+f"(d[10]), "+f"(d[11]), "+f"(d[12]), "+f"(d[13]), "+f"(d[14]), "+f"(d[15]), "+f"(d[16]), "+f"(d[17]), "+f"(d[18]), "+f"(d[19]), "+f"(d[20]), "+f"(d[21]), "+f"(d[22]), "+f"(d[23]), "+f"(d[24]), "+f"(d[25]), "+f"(d[26]), "+f"(d[27]), "+f"(d[28]), "+f"(d[29]), "+f"(d[30]), "+f"(d[31]), "+f"(d[32]), "+f"(d[33]), "+f"(d[34]), "+f"(d[35]), "+f"(d[36]), "+f"(d[37]), "+f"(d[38]), "+f"(d[39]), "+f"(d[40]), "+f"(d[41]), "+f"(d[42]), "+f"(d[43]), "+f"(d[44]), "+f"(d[45]), "+f"(d[46]), "+f"(d[47]), "+f"(d[48]), "+f"(d[49]), "+f"(d[50]), "+f"(d[51]), "+f"(d[52]), "+f"(d[53]), "+f"(d[54]), "+f"(d[55]), "+f"(d[56]), "+f"(d[57]), "+f"(d[58]), "+f"(d[59]), "+f"(d[60]), "+f"(d[61]), "+f"(d[62]), "+f"(d[63])
    : "r"(a[0]), "r"(a[1]), "r"(a[2]), "r"(a[3]), "l"(db), "r"(sd), "n"(TB));
}

template<int TB> __device__ __forceinline__ void wgmma_rs_n160(float* d, const uint32_t* a, uint64_t db, int sd) {
  asm volatile("{\n.reg .pred p;\nsetp.ne.b32 p, %85, 0;\n"
    "wgmma.mma_async.sync.aligned.m64n160k16.f32.bf16.bf16 {%0, %1, %2, %3, %4, %5, %6, %7, %8, %9, %10, %11, %12, %13, %14, %15, %16, %17, %18, %19, %20, %21, %22, %23, %24, %25, %26, %27, %28, %29, %30, %31, %32, %33, %34, %35, %36, %37, %38, %39, %40, %41, %42, %43, %44, %45, %46, %47, %48, %49, %50, %51, %52, %53, %54, %55, %56, %57, %58, %59, %60, %61, %62, %63, %64, %65, %66, %67, %68, %69, %70, %71, %72, %73, %74, %75, %76, %77, %78, %79}, {%80, %81, %82, %83}, %84, p, 1, 1, %86;\n}"
    : "+f"(d[0]), "+f"(d[1]), "+f"(d[2]), "+f"(d[3]), "+f"(d[4]), "+f"(d[5]), "+f"(d[6]), "+f"(d[7]), "+f"(d[8]), "+f"(d[9]), "+f"(d[10]), "+f"(d[11]), "+f"(d[12]), "+f"(d[13]), "+f"(d[14]), "+f"(d[15]), "+f"(d[16]), "+f"(d[17]), "+f"(d[18]), "+f"(d[19]), "+f"(d[20]), "+f"(d[21]), "+f"(d[22]), "+f"(d[23]), "+f"(d[24]), "+f"(d[25]), "+f"(d[26]), "+f"(d[27]), "+f"(d[28]), "+f"(d[29]), "+f"(d[30]), "+f"(d[31]), "+f"(d[32]), "+f"(d[33]), "+f"(d[34]), "+f"(d[35]), "+f"(d[36]), "+f"(d[37]), "+f"(d[38]), "+f"(d[39]), "+f"(d[40]), "+f"(d[41]), "+f"(d[42]), "+f"(d[43]), "+f"(d[44]), "+f"(d[45]), "+f"(d[46]), "+f"(d[47]), "+f"(d[48]), "+f"(d[49]), "+f"(d[50]), "+f"(d[51]), "+f"(d[52]), "+f"(d[53]), "+f"(d[54]), "+f"(d[55]), "+f"(d[56]), "+f"(d[57]), "+f"(d[58]), "+f"(d[59]), "+f"(d[60]), "+f"(d[61]), "+f"(d[62]), "+f"(d[63]), "+f"(d[64]), "+f"(d[65]), "+f"(d[66]), "+f"(d[67]), "+f"(d[68]), "+f"(d[69]), "+f"(d[70]), "+f"(d[71]), "+f"(d[72]), "+f"(d[73]), "+f"(d[74]), "+f"(d[75]), "+f"(d[76]), "+f"(d[77]), "+f"(d[78]), "+f"(d[79])
    : "r"(a[0]), "r"(a[1]), "r"(a[2]), "r"(a[3]), "l"(db), "r"(sd), "n"(TB));
}

template<int TB> __device__ __forceinline__ void wgmma_rs_n192(float* d, const uint32_t* a, uint64_t db, int sd) {
  asm volatile("{\n.reg .pred p;\nsetp.ne.b32 p, %101, 0;\n"
    "wgmma.mma_async.sync.aligned.m64n192k16.f32.bf16.bf16 {%0, %1, %2, %3, %4, %5, %6, %7, %8, %9, %10, %11, %12, %13, %14, %15, %16, %17, %18, %19, %20, %21, %22, %23, %24, %25, %26, %27, %28, %29, %30, %31, %32, %33, %34, %35, %36, %37, %38, %39, %40, %41, %42, %43, %44, %45, %46, %47, %48, %49, %50, %51, %52, %53, %54, %55, %56, %57, %58, %59, %60, %61, %62, %63, %64, %65, %66, %67, %68, %69, %70, %71, %72, %73, %74, %75, %76, %77, %78, %79, %80, %81, %82, %83, %84, %85, %86, %87, %88, %89, %90, %91, %92, %93, %94, %95}, {%96, %97, %98, %99}, %100, p, 1, 1, %102;\n}"
    : "+f"(d[0]), "+f"(d[1]), "+f"(d[2]), "+f"(d[3]), "+f"(d[4]), "+f"(d[5]), "+f"(d[6]), "+f"(d[7]), "+f"(d[8]), "+f"(d[9]), "+f"(d[10]), "+f"(d[11]), "+f"(d[12]), "+f"(d[13]), "+f"(d[14]), "+f"(d[15]), "+f"(d[16]), "+f"(d[17]), "+f"(d[18]), "+f"(d[19]), "+f"(d[20]), "+f"(d[21]), "+f"(d[22]), "+f"(d[23]), "+f"(d[24]), "+f"(d[25]), "+f"(d[26]), "+f"(d[27]), "+f"(d[28]), "+f"(d[29]), "+f"(d[30]), "+f"(d[31]), "+f"(d[32]), "+f"(d[33]), "+f"(d[34]), "+f"(d[35]), "+f"(d[36]), "+f"(d[37]), "+f"(d[38]), "+f"(d[39]), "+f"(d[40]), "+f"(d[41]), "+f"(d[42]), "+f"(d[43]), "+f"(d[44]), "+f"(d[45]), "+f"(d[46]), "+f"(d[47]), "+f"(d[48]), "+f"(d[49]), "+f"(d[50]), "+f"(d[51]), "+f"(d[52]), "+f"(d[53]), "+f"(d[54]), "+f"(d[55]), "+f"(d[56]), "+f"(d[57]), "+f"(d[58]), "+f"(d[59]), "+f"(d[60]), "+f"(d[61]), "+f"(d[62]), "+f"(d[63]), "+f"(d[64]), "+f"(d[65]), "+f"(d[66]), "+f"(d[67]), "+f"(d[68]), "+f"(d[69]), "+f"(d[70]), "+f"(d[71]), "+f"(d[72]), "+f"(d[73]), "+f"(d[74]), "+f"(d[75]), "+f"(d[76]), "+f"(d[77]), "+f"(d[78]), "+f"(d[79]), "+f"(d[80]), "+f"(d[81]), "+f"(d[82]), "+f"(d[83]), "+f"(d[84]), "+f"(d[85]), "+f"(d[86]), "+f"(d[87]), "+f"(d[88]), "+f"(d[89]), "+f"(d[90]), "+f"(d[91]), "+f"(d[92]), "+f"(d[93]), "+f"(d[94]), "+f"(d[95])
    : "r"(a[0]), "r"(a[1]), "r"(a[2]), "r"(a[3]), "l"(db), "r"(sd), "n"(TB));
}

template<int TB> __device__ __forceinline__ void wgmma_rs_n32(float* d, const uint32_t* a, uint64_t db, int sd) {
  asm volatile("{\n.reg .pred p;\nsetp.ne.b32 p, %21, 0;\n"
    "wgmma.mma_async.sync.aligned.m64n32k16.f32.bf16.bf16 {%0, %1, %2, %3, %4, %5, %6, %7, %8, %9, %10, %11, %12, %13, %14, %15}, {%16, %17, %18, %19}, %20, p, 1, 1, %22;\n}"
    : "+f"(d[0]), "+f"(d[1]), "+f"(d[2]), "+f"(d[3]), "+f"(d[4]), "+f"(d[5]), "+f"(d[6]), "+f"(d[7]), "+f"(d[8]), "+f"(d[9]), "+f"(d[10]), "+f"(d[11]), "+f"(d[12]), "+f"(d[13]), "+f"(d[14]), "+f"(d[15])
    : "r"(a[0]), "r"(a[1]), "r"(a[2]), "r"(a[3]), "l"(db), "r"(sd), "n"(TB));
}

template<int TB> __device__ __forceinline__ void wgmma_rs_n64(float* d, const uint32_t* a, uint64_t db, int sd) {
  asm volatile("{\n.reg .pred p;\nsetp.ne.b32 p, %37, 0;\n"
    "wgmma.mma_async.sync.aligned.m64n64k16.f32.bf16.bf16 {%0, %1, %2, %3, %4, %5, %6, %7, %8, %9, %10, %11, %12, %13, %14, %15, %16, %17, %18, %19, %20, %21, %22, %23, %24, %25, %26, %27, %28, %29, %30, %31}, {%32, %33, %34, %35}, %36, p, 1, 1, %38;\n}"
    : "+f"(d[0]), "+f"(d[1]), "+f"(d[2]), "+f"(d[3]), "+f"(d[4]), "+f"(d[5]), "+f"(d[6]), "+f"(d[7]), "+f"(d[8]), "+f"(d[9]), "+f"(d[10]), "+f"(d[11]), "+f"(d[12]), "+f"(d[13]), "+f"(d[14]), "+f"(d[15]), "+f"(d[16]), "+f"(d[17]), "+f"(d[18]), "+f"(d[19]), "+f"(d[20]), "+f"(d[21]), "+f"(d[22]), "+f"(d[23]), "+f"(d[24]), "+f"(d[25]), "+f"(d[26]), "+f"(d[27]), "+f"(d[28]), "+f"(d[29]), "+f"(d[30]), "+f"(d[31])
    : "r"(a[0]), "r"(a[1]), "r"(a[2]), "r"(a[3]), "l"(db), "r"(sd), "n"(TB));
}

template<int TB> __device__ __forceinline__ void wgmma_rs_n80(float* d, const uint32_t* a, uint64_t db, int sd) {
  asm volatile("{\n.reg .pred p;\nsetp.ne.b32 p, %45, 0;\n"
    "wgmma.mma_async.sync.aligned.m64n80k16.f32.bf16.bf16 {%0, %1, %2, %3, %4, %5, %6, %7, %8, %9, %10, %11, %12, %13, %14, %15, %16, %17, %18, %19, %20, %21, %22, %23, %24, %25, %26, %27, %28, %29, %30, %31, %32, %33, %34, %35, %36, %37, %38, %39}, {%40, %41, %42, %43}, %44, p, 1, 1, %46;\n}"
    : "+f"(d[0]), "+f"(d[1]), "+f"(d[2]), "+f"(d[3]), "+f"(d[4]), "+f"(d[5]), "+f"(d[6]), "+f"(d[7]), "+f"(d[8]), "+f"(d[9]), "+f"(d[10]), "+f"(d[11]), "+f"(d[12]), "+f"(d[13]), "+f"(d[14]), "+f"(d[15]), "+f"(d[16]), "+f"(d[17]), "+f"(d[18]), "+f"(d[19]), "+f"(d[20]), "+f"(d[21]), "+f"(d[22]), "+f"(d[23]), "+f"(d[24]), "+f"(d[25]), "+f"(d[26]), "+f"(d[27]), "+f"(d[28]), "+f"(d[29]), "+f"(d[30]), "+f"(d[31]), "+f"(d[32]), "+f"(d[33]), "+f"(d[34]), "+f"(d[35]), "+f"(d[36]), "+f"(d[37]), "+f"(d[38]), "+f"(d[39])
    : "r"(a[0]), "r"(a[1]), "r"(a[2]), "r"(a[3]), "l"(db), "r"(sd), "n"(TB));
}

template<int TB> __device__ __forceinline__ void wgmma_rs_n96(float* d, const uint32_t* a, uint64_t db, int sd) {
  asm volatile("{\n.reg .pred p;\nsetp.ne.b32 p, %53, 0;\n"
    "wgmma.mma_async.sync.aligned.m64n96k16.f32.bf16.bf16 {%0, %1, %2, %3, %4, %5, %6, %7, %8, %9, %10, %11, %12, %13, %14, %15, %16, %17, %18, %19, %20, %21, %22, %23, %24, %25, %26, %27, %28, %29, %30, %31, %32, %33, %34, %35, %36, %37, %38, %39, %40, %41, %42, %43, %44, %45, %46, %47}, {%48, %49, %50, %51}, %52, p, 1, 1, %54;\n}"
    : "+f"(d[0]), "+f"(d[1]), "+f"(d[2]), "+f"(d[3]), "+f"(d[4]), "+f"(d[5]), "+f"(d[6]), "+f"(d[7]), "+f"(d[8]), "+f"(d[9]), "+f"(d[10]), "+f"(d[11]), "+f"(d[12]), "+f"(d[13]), "+f"(d[14]), "+f"(d[15]), "+f"(d[16]), "+f"(d[17]), "+f"(d[18]), "+f"(d[19]), "+f"(d[20]), "+f"(d[21]), "+f"(d[22]), "+f"(d[23]), "+f"(d[24]), "+f"(d[25]), "+f"(d[26]), "+f"(d[27]), "+f"(d[28]), "+f"(d[29]), "+f"(d[30]), "+f"(d[31]), "+f"(d[32]), "+f"(d[33]), "+f"(d[34]), "+f"(d[35]), "+f"(d[36]), "+f"(d[37]), "+f"(d[38]), "+f"(d[39]), "+f"(d[40]), "+f"(d[41]), "+f"(d[42]), "+f"(d[43]), "+f"(d[44]), "+f"(d[45]), "+f"(d[46]), "+f"(d[47])
    : "r"(a[0]), "r"(a[1]), "r"(a[2]), "r"(a[3]), "l"(db), "r"(sd), "n"(TB));
}

template<int TA, int TB> __device__ __forceinline__ void wgmma_ss_n192(float* d, uint64_t da, uint64_t db, int sd) {
  asm volatile("{\n.reg .pred p;\nsetp.ne.b32 p, %98, 0;\n"
    "wgmma.mma_async.sync.aligned.m64n192k16.f32.bf16.bf16 {%0, %1, %2, %3, %4, %5, %6, %7, %8, %9, %10, %11, %12, %13, %14, %15, %16, %17, %18, %19, %20, %21, %22, %23, %24, %25, %26, %27, %28, %29, %30, %31, %32, %33, %34, %35, %36, %37, %38, %39, %40, %41, %42, %43, %44, %45, %46, %47, %48, %49, %50, %51, %52, %53, %54, %55, %56, %57, %58, %59, %60, %61, %62, %63, %64, %65, %66, %67, %68, %69, %70, %71, %72, %73, %74, %75, %76, %77, %78, %79, %80, %81, %82, %83, %84, %85, %86, %87, %88, %89, %90, %91, %92, %93, %94, %95}, %96, %97, p, 1, 1, %99, %100;\n}"
    : "+f"(d[0]), "+f"(d[1]), "+f"(d[2]), "+f"(d[3]), "+f"(d[4]), "+f"(d[5]), "+f"(d[6]), "+f"(d[7]), "+f"(d[8]), "+f"(d[9]), "+f"(d[10]), "+f"(d[11]), "+f"(d[12]), "+f"(d[13]), "+f"(d[14]), "+f"(d[15]), "+f"(d[16]), "+f"(d[17]), "+f"(d[18]), "+f"(d[19]), "+f"(d[20]), "+f"(d[21]), "+f"(d[22]), "+f"(d[23]), "+f"(d[24]), "+f"(d[25]), "+f"(d[26]), "+f"(d[27]), "+f"(d[28]), "+f"(d[29]), "+f"(d[30]), "+f"(d[31]), "+f"(d[32]), "+f"(d[33]), "+f"(d[34]), "+f"(d[35]), "+f"(d[36]), "+f"(d[37]), "+f"(d[38]), "+f"(d[39]), "+f"(d[40]), "+f"(d[41]), "+f"(d[42]), "+f"(d[43]), "+f"(d[44]), "+f"(d[45]), "+f"(d[46]), "+f"(d[47]), "+f"(d[48]), "+f"(d[49]), "+f"(d[50]), "+f"(d[51]), "+f"(d[52]), "+f"(d[53]), "+f"(d[54]), "+f"(d[55]), "+f"(d[56]), "+f"(d[57]), "+f"(d[58]), "+f"(d[59]), "+f"(d[60]), "+f"(d[61]), "+f"(d[62]), "+f"(d[63]), "+f"(d[64]), "+f"(d[65]), "+f"(d[66]), "+f"(d[67]), "+f"(d[68]), "+f"(d[69]), "+f"(d[70]), "+f"(d[71]), "+f"(d[72]), "+f"(d[73]), "+f"(d[74]), "+f"(d[75]), "+f"(d[76]), "+f"(d[77]), "+f"(d[78]), "+f"(d[79]), "+f"(d[80]), "+f"(d[81]), "+f"(d[82]), "+f"(d[83]), "+f"(d[84]), "+f"(d[85]), "+f"(d[86]), "+f"(d[87]), "+f"(d[88]), "+f"(d[89]), "+f"(d[90]), "+f"(d[91]), "+f"(d[92]), "+f"(d[93]), "+f"(d[94]), "+f"(d[95])
    : "l"(da), "l"(db), "r"(sd), "n"(TA), "n"(TB));
}

template<int TA, int TB> __device__ __forceinline__ void wgmma_ss_n8(float* d, uint64_t da, uint64_t db, int sd) {
  asm volatile("{\n.reg .pred p;\nsetp.ne.b32 p, %6, 0;\n"
    "wgmma.mma_async.sync.aligned.m64n8k16.f32.bf16.bf16 {%0, %1, %2, %3}, %4, %5, p, 1, 1, %7, %8;\n}"
    : "+f"(d[0]), "+f"(d[1]), "+f"(d[2]), "+f"(d[3])
    : "l"(da), "l"(db), "r"(sd), "n"(TA), "n"(TB));
}

constexpr int S_ = 2048, D_ = 640, F_ = 1536;

struct Scr {
  uint32_t flag[32 * 8];
  uint32_t mv[2 * 2048];
  bf16 cimg[8 * 6 * 512];
  uint2 st2[S_];
  bf16 kvT[D_ * S_];
  bf16 zT[D_ * S_];
  bf16 x1T[D_ * S_];
  bf16 AT[D_ * S_];
  uint4 PP[128 * 1280];
};
__device__ __align__(1024) Scr g_scr;
__device__ __forceinline__ uint32_t clk() { uint32_t c; asm volatile("mov.u32 %0, %%clock;" : "=r"(c) :: "memory"); return c; }
#define DEVSM 0
#define STAMP(id)
#define STAMPIF(c, id)
constexpr int FL_X = 5, FL_C = 128;
#define CD 600
#define SD 1000

constexpr int SM_X = 1024, SM_EXT = 21504, SM_SMALL = 29696, SM_STAT = 30720, SM_CB = 32768, SM_RING = 34816, SM_TOTAL = SM_RING + 6 * 32768;
constexpr int SMALL_LN = 224, SMALL_RED = 320, SMALL_DUMMY = 1008, SMALL_E = 1012, SMALL_TS = 160;
constexpr int JOB_SZ = 10880, JOB_V = 5760, R_X = 5 * 32768, R_BOX = R_X + 12288;
constexpr int K1OFF = 4672, KSZ = 9472, CSZ = KSZ + 4224;
enum { B_KJ = 0, B_X = 5, B_FB = 10, B_PEER = 20, B_RECV = 24, B_EXT = 28, B_X1 = 29, B_BOX = 38, B_F = 44, B_ST0 = 45, B_GB = 46,
       B_F1 = 48, B_E1 = 54, B_EB = 60,
       B_Z = 80, B_K = 85, B_EW = 88, B_ST2 = 94, B_XF = 95, B_LN = 96, B_KVS = 98, B_BD = 99,
       B_B = 106, B_S = 112 };
__device__ __forceinline__ uint32_t chan_base(uint32_t sb, int ch) { return sb + SM_RING + (2 + (ch >> 1)) * 32768 + (ch & 1) * CSZ; }

struct Params { CUtensorMap mS, mX, mWm, mK, mV, mG, mU, mD, mO, mO2; };

__device__ __forceinline__ void flag_add(Scr* G, int id) { asm volatile("red.relaxed.gpu.global.add.u32 [%0], 1;" ::"l"(G->flag + id) : "memory"); }
__device__ __forceinline__ uint32_t rdback(const void* p) { uint32_t v; asm volatile("ld.relaxed.gpu.global.u32 %0, [%1];" : "=r"(v) : "l"(p) : "memory"); return v; }
__device__ __forceinline__ void st_tag(uint2* p, uint32_t v, uint32_t t) { asm volatile("st.relaxed.gpu.global.v2.u32 [%0], {%1, %2};" ::"l"(p), "r"(v), "r"(t) : "memory"); }
__device__ __forceinline__ void spin(uint32_t t, uint32_t d) { if (d) while (clk() - t < d); }
__device__ __forceinline__ uint2 ld_tag(const uint2* p) { uint2 v; asm volatile("ld.relaxed.gpu.global.v2.u32 {%0, %1}, [%2];" : "=r"(v.x), "=r"(v.y) : "l"(p) : "memory"); return v; }
__device__ __forceinline__ uint4 ld_tag2(const uint2* p) {
  uint4 v;
  asm volatile("ld.relaxed.gpu.global.v4.u32 {%0, %1, %2, %3}, [%4];" : "=r"(v.x), "=r"(v.y), "=r"(v.z), "=r"(v.w) : "l"(p) : "memory");
  return v;
}
__device__ __forceinline__ void rdwait(uint32_t sb, uint32_t v) { sts32(sb + SM_SMALL + SMALL_DUMMY, v); }
__device__ __forceinline__ void fence_async_s() { asm volatile("fence.proxy.async.shared::cta;" ::: "memory"); }
__device__ __forceinline__ void fence_async_g() { asm volatile("fence.proxy.async.global;" ::: "memory"); }
__device__ __forceinline__ void bulk_done() { asm volatile("cp.async.bulk.commit_group;\n\tcp.async.bulk.wait_group 0;" ::: "memory"); }
__device__ __forceinline__ void flag_wait(Scr* G, int id, uint32_t target) {
  const uint32_t* p = G->flag + id;
#pragma unroll 1
  for (int i = 0; i < (1 << 20); i++) {
    uint32_t v;
    asm volatile("ld.relaxed.gpu.global.u32 %0, [%1];" : "=r"(v) : "l"(p) : "memory");
    if ((int)(v - target) >= 0) return;
  }
  __trap();
}
__device__ __forceinline__ int tbase(int pb) { return 127 - (32 * (pb >> 6) + 8 * (pb & 8) + 4 * ((2 * (pb & 3) - ((pb >> 2) & 1)) & 7) + ((pb >> 4) & 3)); }
__device__ __forceinline__ uint32_t hmul(uint32_t a, uint32_t b) { uint32_t d; asm("mul.rn.bf16x2 %0, %1, %2;" : "=r"(d) : "r"(a), "r"(b)); return d; }
__device__ __forceinline__ uint32_t hadd(uint32_t a, uint32_t b) { uint32_t d; asm("add.rn.bf16x2 %0, %1, %2;" : "=r"(d) : "r"(a), "r"(b)); return d; }
__device__ __forceinline__ uint32_t hsub(uint32_t a, uint32_t b) { uint32_t d; asm("sub.rn.bf16x2 %0, %1, %2;" : "=r"(d) : "r"(a), "r"(b)); return d; }
__device__ __forceinline__ uint32_t hfma(uint32_t a, uint32_t b, uint32_t c) { uint32_t d; asm("fma.rn.bf16x2 %0, %1, %2, %3;" : "=r"(d) : "r"(a), "r"(b), "r"(c)); return d; }
__device__ __forceinline__ uint32_t pack2(float lo, float hi) { uint32_t d; asm("cvt.rn.bf16x2.f32 %0, %1, %2;" : "=r"(d) : "f"(hi), "f"(lo)); return d; }
__device__ __forceinline__ float blo(uint32_t v) { return __uint_as_float(v << 16); }
__device__ __forceinline__ float bhi(uint32_t v) { return __uint_as_float(v & 0xffff0000u); }
__device__ __forceinline__ float rbf(float v) { return blo(pack2(v, 0.f)); }
template <int N> __device__ __forceinline__ void bfly(float* v, int mask, bool up) {
#pragma unroll
  for (int i = 0; i < N / 2; i++) {
    float send = up ? v[i] : v[i + N / 2], keep = up ? v[i + N / 2] : v[i];
    v[i] = keep + __shfl_xor_sync(0xffffffffu, send, mask);
  }
}
__device__ __forceinline__ bool mod_first(int b) { return !(b & 1) || !(b & 6); }
__device__ __forceinline__ int mod_grp(int b, int j) {
  const int m = b >> 3, s = b & 7, t = 16 * s + m, v = j ? (t * 43) >> 10 : s >> 1;
  if (j == 2) return b + 112;
  if (j == 0 && s == 1) return m + (m < 8 ? 152 : 192);
  return v < 4 ? (v == 3 ? 160 : 40 * v) + (j ? 16 + t - 24 * v : m) : t + 24;
}

__device__ __forceinline__ void kv_load(const bf16* gk, const bf16* gv, const bf16* gs, uint32_t sb, int b, int r, int tid) {
  const int row = tid >> 2, col = 128 * r + 32 * (b & 3);
  const uint32_t a = sb + SM_RING + r * JOB_SZ + (row >> 3) * 80 + (tid & 3) * 16, ak = a + (row & 7) * 720, av = a + (row & 7) * 640 + JOB_V;
  const int o = (64 * (b >> 2) + row) * D_ + col + 8 * (tid & 3);
  cp16(ak + 80, gk + o);
  cp16(ak + 400, gk + o + 32 * D_);
  cp16(av, gv + o);
  cp16(av + 320, gv + o + 32 * D_);
  if (tid < 12) cp16z(ak + 3600, gk + (b < 4 ? o : o - 3 * D_), b < 4 ? 0 : 16);
  else if (tid >= 112) cp16(sb + SM_CB + 256 * r + 16 * (tid - 112), gs + 4 * col + 8 * (tid - 112));
}
__device__ __forceinline__ void load_kv(const Params& P, const bf16* gs, uint32_t sb, int b, int r) {
  const uint32_t a = sb + SM_RING + r * JOB_SZ, bar = sb + 8 * (B_B + r);
  const int cg = 4 * r + (b & 3);
  mbar_expect(bar, JOB_SZ + 256);
  tma4d(a, &P.mK, 0, cg, 8 * (b >> 2) - 1, 0, bar);
  tma4d(a + JOB_V, &P.mV, 0, cg, 8 * (b >> 2), 0, bar);
  bulk_g2s(sb + SM_CB + 256 * r, gs + 128 * cg, 256, bar);
}
__device__ __forceinline__ uint4* kv_dst(Scr* G, int b, int r, int tid) {
  return (uint4*)(G->kvT + (128 * r + 32 * (b & 3) + 8 * (tid >> 5) + 2 * (tid & 3)) * S_ + 2040 - 64 * (b >> 2)) - ((tid >> 2) & 7);
}
__device__ __forceinline__ void kv_job(Scr* G, uint32_t sb, int b, int r, int tid) {
  const int cp = 4 * (tid >> 5) + (tid & 3);
  const uint32_t ka = sb + SM_RING + r * JOB_SZ + ((tid >> 2) & 7) * 80 + cp * 4;
  mbar_wait(sb + 8 * (B_B + r), 0);
  STAMPIF(tid == 0, 56 + r);
  const uint4 sk = lds128(sb + SM_CB + 256 * r + 16 * cp);
  const uint32_t s0 = __byte_perm(sk.x, sk.z, 0x5410), s1 = __byte_perm(sk.x, sk.z, 0x7632), s2 = __byte_perm(sk.y, sk.w, 0x5410), s3 = __byte_perm(sk.y, sk.w, 0x7632);
  uint32_t kk[11], o[8];
#pragma unroll
  for (int i = 0; i < 11; i++) kk[i] = lds32(ka + 720 * ((i + 5) & 7) + 80 * ((i + 5) >> 3));
#pragma unroll
  for (int i = 0; i < 8; i++) {
    uint32_t v = lds32(ka + JOB_V + 640 * i);
    o[i] = hmul(hfma(kk[i + 3], s0, hfma(kk[i + 2], s1, hfma(kk[i + 1], s2, hmul(kk[i], s3)))), v);
  }
  uint4* dst = kv_dst(G, b, r, tid);
  dst[0] = make_uint4(__byte_perm(o[7], o[6], 0x5410), __byte_perm(o[5], o[4], 0x5410), __byte_perm(o[3], o[2], 0x5410), __byte_perm(o[1], o[0], 0x5410) | 1);
  dst[256] = make_uint4(__byte_perm(o[7], o[6], 0x7632), __byte_perm(o[5], o[4], 0x7632), __byte_perm(o[3], o[2], 0x7632), __byte_perm(o[1], o[0], 0x7632) | 1);
  if (tid == 0) { sts32(sb + SM_SMALL + SMALL_TS + 4 * r, clk()); mbar_arrive(sb + 8 * (B_KJ + r)); }
}
__device__ __forceinline__ void u_wait(uint4& a, uint4& c, const void* p) {
  asm volatile("{\n.reg .pred p;\n.reg .b32 t, n;\nmov.b32 n, 0;\n"
               "L0:\nlop3.b32 t, %3, %7, 1, 0x80;\nsetp.eq.b32 p, t, 0;\nvote.sync.any.pred p, p, 0xffffffff;\n@!p bra.uni L1;\n"
               "ld.relaxed.gpu.global.v4.u32 {%0, %1, %2, %3}, [%8];\nld.relaxed.gpu.global.v4.u32 {%4, %5, %6, %7}, [%8+2048];\n"
               "add.u32 n, n, 1;\nsetp.lt.u32 p, n, 1000000;\n@p bra.uni L0;\ntrap;\nL1:\n}"
               : "+r"(a.x), "+r"(a.y), "+r"(a.z), "+r"(a.w), "+r"(c.x), "+r"(c.y), "+r"(c.z), "+r"(c.w) : "l"(p) : "memory");
}
__device__ __forceinline__ uint64_t box_a(uint32_t sb) { return mkdesc(sb + SM_RING + R_BOX, 256, 1024, 3); }
__device__ __forceinline__ uint64_t box_b(uint32_t sb) { return mkdesc(sb + SM_STAT, 64, 128, 0); }
__device__ __forceinline__ void mod_put(Scr* G, uint32_t sb, const float* a, int b, int j, uint32_t e1, int tid) {
  const uint32_t red = sb + SM_STAT + 1536;
  if ((tid & 3) == tid >> 6) sts64(red + 32 * ((tid >> 2) & 7) + 8 * (tid >> 5), __float_as_uint((tid & 32) ? a[1] : a[0]), __float_as_uint((tid & 32) ? a[3] : a[2]));
  bar_sync(j ? 4 : 5, 128);
  if (tid < 16) {
    const uint4 u = lds128(red + 32 * (tid & 7)), v = lds128(red + 32 * (tid & 7) + 16);
    asm volatile("" : "+r"(b));
    const int grp = mod_grp(b, j);
    const uint32_t one = (grp >= 40 && grp < 80) || (grp >= 160 && grp < 200) ? 0x3f803f80u : 0u;
    const float lo = __uint_as_float(u.x) + __uint_as_float(u.z) + __uint_as_float(v.x) + __uint_as_float(v.z);
    const float hi = __uint_as_float(u.y) + __uint_as_float(u.w) + __uint_as_float(v.y) + __uint_as_float(v.w);
    asm volatile("st.relaxed.gpu.global.u32 [%0], %1;" ::"l"(G->mv + 8 * grp + 256 * (tid & 8) + (tid & 7)),
                 "r"(((tid >> 3) ^ e1) & 1 ? 0 : ~hadd(pack2(lo, hi), one)) : "memory");
  }
}
__device__ __forceinline__ void mod_box(Scr* G, uint32_t sb, int b, int j, uint32_t e1, int tid) {
  float a[4];
  uint64_t da = box_a(sb), db = box_b(sb);
#pragma unroll
  for (int h = 0; h < 2; h++) {
    mbar_wait(sb + 8 * (B_BOX + 2 * j + h), 0);
    STAMPIF(tid == 0 && j == 0, 71 + h);
    wg_fence();
#pragma unroll
    for (int n = 5 * h; n < 5 * h + 5; n++) wgmma_ss_n8<1, 0>(a, da + 128 * n, db + 8 * n, n != 0);
    wg_commit();
  }
  wg_wait<0>();
#pragma unroll
  for (int i = 0; i < 4; i++) asm volatile("" : "+f"(a[i])::"memory");
  mod_put(G, sb, a, b, j, e1, tid);
}
__device__ __forceinline__ void a_check(uint32_t sa, const void* ga, uint32_t tag) {
  asm volatile("{\n.reg .pred p;\n.reg .b32 t, n, x, y, z;\n.reg .b64 g;\n"
               "ld.shared.b32 t, [%0];\nlop3.b32 t, t, %2, 1, 0x28;\nsetp.ne.b32 p, t, 0;\nvote.sync.any.pred p, p, 0xffffffff;\n@!p bra.uni L1;\nmov.b32 n, 0;\n"
               "L0:\nld.relaxed.gpu.global.b32 t, [%1];\nlop3.b32 t, t, %2, 1, 0x28;\nsetp.ne.b32 p, t, 0;\nvote.sync.any.pred p, p, 0xffffffff;\n@!p bra.uni L2;\n"
               "add.u32 n, n, 1;\nsetp.lt.u32 p, n, 1000000;\n@p bra.uni L0;\ntrap;\nL2:\n"
               "and.b64 g, %1, -32;\nand.b32 n, %0, -32;\n"
               "ld.relaxed.gpu.global.v4.b32 {t, x, y, z}, [g];\nst.shared.v4.b32 [n], {t, x, y, z};\n"
               "ld.relaxed.gpu.global.v4.b32 {t, x, y, z}, [g+16];\nst.shared.v4.b32 [n+16], {t, x, y, z};\n"
               "fence.proxy.async.shared::cta;\nbar.warp.sync 0xffffffff;\nL1:\n}" ::"r"(sa), "l"(ga), "r"(tag) : "memory");
}
__device__ __forceinline__ void z_wait(uint4& a, uint4& c, uint32_t* v, const void* p, const void* q) {
  asm volatile("{\n.reg .pred p;\n.reg .b32 t, n;\nmov.b32 n, 0;\n"
               "L0:\nlop3.b32 t, %3, %7, 1, 0x80;\nmin.u32 t, t, %8;\nmin.u32 t, t, %9;\nmin.u32 t, t, %10;\nmin.u32 t, t, %11;\n"
               "setp.eq.b32 p, t, 0;\nvote.sync.any.pred p, p, 0xffffffff;\n@!p bra.uni L1;\n"
               "ld.relaxed.gpu.global.v4.u32 {%0, %1, %2, %3}, [%12];\nld.relaxed.gpu.global.v4.u32 {%4, %5, %6, %7}, [%12+32768];\n"
               "ld.relaxed.gpu.global.u32 %8, [%13];\nld.relaxed.gpu.global.u32 %9, [%13+1280];\nld.relaxed.gpu.global.u32 %10, [%13+2560];\nld.relaxed.gpu.global.u32 %11, [%13+5120];\n"
               "add.u32 n, n, 1;\nsetp.lt.u32 p, n, 1000000;\n@p bra.uni L0;\ntrap;\nL1:\n}"
               : "+r"(a.x), "+r"(a.y), "+r"(a.z), "+r"(a.w), "+r"(c.x), "+r"(c.y), "+r"(c.z), "+r"(c.w), "+r"(v[0]), "+r"(v[1]), "+r"(v[2]), "+r"(v[3])
               : "l"(p), "l"(q) : "memory");
}
__device__ __forceinline__ void load_x(const Params& P, uint32_t sb, int b, int h) {
  const uint32_t bar = sb + 8 * (B_X + h);
  mbar_expect(bar, 10240);
  tma5d(sb + SM_X + h * 10240, &P.mX, 0, 0, 0, 5 * h, tbase(b), bar);
}
__device__ __forceinline__ uint32_t x_addr(uint32_t sb, int w, int lane) {
  const int rho = 15 - (4 * (lane >> 3) + 2 * (lane & 1) + ((lane >> 1) & 1));
  return sb + SM_X + (w >> 1) * 2048 + rho * 128 + (((2 * (w & 1) + (lane & 4)) ^ (rho & 7)) << 4);
}
__device__ __forceinline__ void ln1_job(uint32_t sb, int tid) {
  const uint32_t xr = sb + SM_X + 16 * tid;
  float pv, s1 = 0.f, s2 = 0.f, s3 = 0.f;
#pragma unroll 1
  for (int h = 0; h < 2; h++) {
    mbar_wait(sb + 8 * (B_X + h), 0);
    STAMPIF(tid == 0, 25);
    pv = blo(lds32(xr & ~127u));
#pragma unroll
    for (int n = 0; n < 5; n++) {
      const uint4 v = lds128(xr + 10240 * h + 2048 * n);
      const uint32_t u[4] = {v.x, v.y, v.z, v.w};
#pragma unroll
      for (int j = 0; j < 4; j++) {
        const float a = blo(u[j]) - pv, c = bhi(u[j]) - pv;
        s1 += a + c; s2 += a * a; s3 += c * c;
      }
    }
  }
  s2 += s3;
#pragma unroll
  for (int o = 1; o < 8; o <<= 1) { s1 += __shfl_xor_sync(0xffffffffu, s1, o); s2 += __shfl_xor_sync(0xffffffffu, s2, o); }
  const float mu = s1 * (1.f / D_), var = fmaxf(s2 * (1.f / D_) - mu * mu, 0.f);
  const float rs = __frcp_rn(rbf(__fsqrt_rn(rbf(rbf(var) + 1e-5f))));
  const int i = 15 - (tid >> 3), j = tid & 7;
  if (j < 2) sts16(sb + SM_SMALL + SMALL_LN + 32 * j + 16 * (i & 1) + (i & 14), pack2(j ? rs : pv + mu, 0.f));
  bar_sync(5, 128);
  STAMPIF(tid == 0, 75);
}
__device__ __forceinline__ void load_box(const Params& P, uint32_t sb, int b, int cls) {
  const uint32_t bar = sb + 8 * (B_BOX + cls);
  mbar_expect(bar, 10240);
  tma3d(sb + SM_RING + R_BOX + 10240 * (cls & 1), &P.mWm, 16 * mod_grp(b, cls >> 1), 0, 5 * (cls & 1), bar);
}
__device__ __forceinline__ void load_ssm(const Params& P, uint32_t sb, int b, int r) {
  const uint32_t bar = sb + 8 * (B_S + r);
  mbar_expect(bar, 16 * 288);
  tma3d(chan_base(sb, r) + 128, &P.mS, 0, 0, 128 * r + b, bar);
}
__device__ __forceinline__ void k1_job(uint32_t sb, int r, int tid, uint32_t dv) {
  const uint32_t a0 = chan_base(sb, r) + 128 + 16 * tid + 32 * (tid >> 4);
  mbar_wait(sb + 8 * (B_S + r), 0);
#pragma unroll
  for (int n = 0; n < 2; n++) {
    const uint32_t a = a0 + 2304 * n;
    uint4 v = lds128(a);
    if (n == 0 && tid == 0) { v.x = hadd(v.x, dv); sts32(a, v.x); }
    const uint32_t pv = lds32(a - ((tid & 15) ? 4 : 36));
    sts128(a + K1OFF, make_uint4(__byte_perm(pv, v.x, 0x5432), __byte_perm(v.x, v.y, 0x5432), __byte_perm(v.y, v.z, 0x5432), __byte_perm(v.z, v.w, 0x5432)));
  }
}

__device__ __forceinline__ uint4 pp_pack(const float* a) { return make_uint4(pack2(a[0], a[1]), pack2(a[2], a[3]), pack2(a[4], a[5]), pack2(a[6], a[7])); }
template <int ST> __device__ __forceinline__ void pp_send(uint4* p, const float* a, uint32_t tag) {
#pragma unroll
  for (int i = 0; i < 5; i++) {
    uint4 v = pp_pack(a + 8 * i);
    v.w = (v.w & ~1u) | tag;
    p[ST * i] = v;
  }
}
template <int ST> __device__ __forceinline__ void pp_load(uint4* f, const uint4* p) {
#pragma unroll
  for (int i = 0; i < 5; i++) f[i] = ld_tag2((const uint2*)(p + ST * i));
}
template <int ST> __device__ __forceinline__ void pp_wait(uint4* f, const uint4* p, uint32_t tag) {
  asm volatile("{\n.reg .pred p;\n.reg .b32 t, n;\nmov.b32 n, 0;\n"
               "L0:\nxor.b32 t, %3, %21;\nlop3.b32 t, t, %7, %21, 0xf6;\nlop3.b32 t, t, %11, %21, 0xf6;\nlop3.b32 t, t, %15, %21, 0xf6;\nlop3.b32 t, t, %19, %21, 0xf6;\n"
               "and.b32 t, t, 1;\nsetp.ne.b32 p, t, 0;\nvote.sync.any.pred p, p, 0xffffffff;\n@!p bra.uni L1;\n"
               "ld.relaxed.gpu.global.v4.u32 {%0, %1, %2, %3}, [%20];\nld.relaxed.gpu.global.v4.u32 {%4, %5, %6, %7}, [%20+%22];\n"
               "ld.relaxed.gpu.global.v4.u32 {%8, %9, %10, %11}, [%20+%23];\nld.relaxed.gpu.global.v4.u32 {%12, %13, %14, %15}, [%20+%24];\n"
               "ld.relaxed.gpu.global.v4.u32 {%16, %17, %18, %19}, [%20+%25];\n"
               "add.u32 n, n, 1;\nsetp.lt.u32 p, n, 1000000;\n@p bra.uni L0;\ntrap;\nL1:\n}"
               : "+r"(f[0].x), "+r"(f[0].y), "+r"(f[0].z), "+r"(f[0].w), "+r"(f[1].x), "+r"(f[1].y), "+r"(f[1].z), "+r"(f[1].w), "+r"(f[2].x), "+r"(f[2].y),
                 "+r"(f[2].z), "+r"(f[2].w), "+r"(f[3].x), "+r"(f[3].y), "+r"(f[3].z), "+r"(f[3].w), "+r"(f[4].x), "+r"(f[4].y), "+r"(f[4].z), "+r"(f[4].w)
               : "l"(p), "r"(tag), "n"(16 * ST), "n"(32 * ST), "n"(48 * ST), "n"(64 * ST) : "memory");
}
__device__ __forceinline__ void pp_add(uint4& f, const uint4 e) { f = make_uint4(hadd(f.x, e.x), hadd(f.y, e.y), hadd(f.z, e.z), hadd(f.w, e.w)); }
__device__ __forceinline__ int out_col(int s, int n) { return 320 * (s & 1) + (n < 4 ? 32 * (s & 6) + 16 * n : 256 + 8 * (s & 6)); }
__device__ __forceinline__ void l2_prefetch(const void* p, int bytes) { asm volatile("cp.async.bulk.prefetch.L2.global [%0], %1;" ::"l"(p), "r"(bytes) : "memory"); }
__device__ __forceinline__ void pf_line(const void* p) { asm volatile("prefetch.global.L2 [%0];" ::"l"(p) : "memory"); }
__device__ __forceinline__ int role(int bx) {
  const int c = bx >> 1, d = c - 36, q = (d * 37) >> 8, k = d - 7 * q;
  const int rank = c < 4 ? 12 + c : c < 36 ? ((c - 4) & 7) * 8 + ((c - 4) >> 3) : (k ? k + 1 : 0) * 8 + 4 + q;
  return 8 * (rank & 15) + 2 * (rank >> 4) + (bx & 1);
}
enum { K_KV, K_SSM, K_BOX, K_PW, K_PD, K_PKV, K_PSSM, K_PBOX, K_W, K_X, K_ST, K_END = 15 };
#define E(t, bar, kind, r) ((t) << 16 | (bar) << 8 | (kind) << 4 | (r))
#define SCHED E(2800, 255, K_BOX, 0), E(0, 255, K_BOX, 1), E(3700, 255, K_KV, 2), E(4400, 255, K_SSM, 2), E(4800, 255, K_KV, 3), E(5500, 255, K_X, 0), \
              E(6400, 255, K_KV, 4), E(7100, 255, K_X, 1), E(7900, 255, K_SSM, 3), E(8300, 255, K_SSM, 4), E(8600, 255, K_BOX, 2), E(9500, 255, K_PW, 0), \
              E(10100, 255, K_BOX, 3)
#define XPF 2
#define XBOTH 0
#define AUXP 0xfedcb0217ull
constexpr int aux_last(int mask) { int r = 0; for (uint64_t p = AUXP; p; p >>= 4) if ((mask >> (p & 15)) & 1) r = p & 15; return r; }
constexpr int kLastKv = aux_last(0x0e);
#define XI 8
#define XW 0
#define PWM 0x3c
#define STM 0x7c0
#define PDM 0x3800
#define KV4C 3
#define KV1L 0
#define CVT 1
#define UPOS 4
#define UD 1000
#define PL1 12
#define PL2 13
#define P3E 0
#define SJ(h) (3 * (h))
constexpr uint32_t kSched[] = {SCHED, E(0, 255, K_END, 0)};
struct In { const bf16 *k, *v, *sk, *Wg, *Wu, *Wd, *ss; };
__device__ __forceinline__ void load_w(const Params& P, uint32_t sb, int s, int it) {
  const int st = it % 5;
  mbar_wait(sb + 8 * (B_E1 + st), (it / 5) & 1);
  const uint32_t a = sb + SM_RING + st * 32768 + 8192, fb = sb + 8 * (B_F1 + st);
  mbar_expect(fb, 24576);
#pragma unroll
  for (int j = 0; j < 3; j++) {
    tma2d(a + 8192 * j, &P.mG, 192 * s + 64 * j, 32 * it, fb);
    tma2d(a + 8192 * j + 4096, &P.mU, 192 * s + 64 * j, 32 * it, fb);
  }
}

template <int I> __device__ __forceinline__ int sched_run(const Params& P, const In& in, uint32_t sb, int b, int lane, uint32_t t_0) {
  constexpr uint32_t e = kSched[I];
  constexpr int kind = (e >> 4) & 15, r = e & 15, bar = (e >> 8) & 255;
  if constexpr (kind == K_END) return 0;
  else {
    if constexpr ((e >> 16) != 0) while (clk() - t_0 < (e >> 16));
    if (bar != 255) mbar_wait(sb + 8 * bar, 0);
    if (kind == K_BOX && r == 2) mbar_wait(sb + 8 * B_BD, 0);
    if (kind == K_PKV) {
      const bf16* kvp = (lane < 16 ? in.k : in.v) + (16 * b + (lane & 15)) * D_ + 128 * r;
      pf_line(kvp); pf_line(kvp + 64);
    } else {
      if (elect()) {
        if (kind == K_KV) load_kv(P, in.sk, sb, b, r);
        if (kind == K_X) load_x(P, sb, b, r);
        if (kind == K_SSM) load_ssm(P, sb, b, r);
        if (kind == K_BOX && (r > 1 || mod_first(b))) load_box(P, sb, b, r);
        if (kind == K_PW) { l2_prefetch(in.Wg + (128 * r + b) * F_, 2 * F_); l2_prefetch(in.Wu + (128 * r + b) * F_, 2 * F_); }
        if (kind == K_PSSM) l2_prefetch(in.ss + (128 * r + b) * S_, 4096);
      }
      __syncwarp();
    }
    return sched_run<I + 1>(P, in, sb, b, lane, t_0) + (kind == K_PW);
  }
}

__global__ void __launch_bounds__(512, 1) fused_kernel(const bf16* __restrict__ gk, const bf16* __restrict__ gv, const bf16* __restrict__ gsk,
                                                       const bf16* __restrict__ gD, const bf16* __restrict__ gc, Scr* G, const bf16* gWg, const bf16* gWu,
                                                       const bf16* gWd, bf16* gout, const bf16* gss, const __grid_constant__ Params P) {
  extern __shared__ __align__(1024) char smem_raw[];
  const uint32_t sb = smem_u32(smem_raw), ring = sb + SM_RING;
  const int b = role(blockIdx.x), m = b >> 3, s = b & 7;
  const uint32_t t_0 = clk();
  const int wg = __shfl_sync(0xffffffffu, threadIdx.x >> 7, 0);
  const int tid = threadIdx.x & 127, lane = tid & 31;
  const int w = __shfl_sync(0xffffffffu, tid >> 5, 0);
  if (wg < 2) {
    if (!KV1L || wg == 0) kv_load(gk, gv, gsk, sb, b, wg, tid);
  } else {
    if (wg == 2) {
      if (tid < 40) {
        int c = tid & 7;
        sts128(chan_base(sb, tid >> 3) + (c < 2 ? 80 + c * K1OFF : KSZ + 4096 + (c - 2) * 16), make_uint4(0, 0, 0, 0));
      }
    }
    if (elect()) {
      const int j = 4 * (3 - wg) + w - 1;
      if (j < 4) asm volatile("prefetch.tensormap [%0];" ::"l"(&P.mX + j) : "memory");
      if (j < 0) {
#pragma unroll
        for (int i = 0; i < 5; i++) mbar_init(sb + 8 * (B_S + i), 1);
        fence_async_s();
        if (XPF > 0) load_ssm(P, sb, b, 0);
        if (XPF > 1) load_ssm(P, sb, b, 1);
      } else {
        const int c = j < 3 ? 1 : j < 5 ? 2 : 4;
#pragma unroll
        for (int i = 0; i < 16; i++) mbar_init(sb + 128 * j + 8 * i, i < 10 || j < 6 ? c : i < 12 ? 128 : 1);
      }
    }
    fence_async_s();
  }
  __syncthreads();
  STAMPIF(threadIdx.x == 0, 55);

  if (wg < 2) {
    if (KV1L && wg == 1) kv_load(gk, gv, gsk, sb, b, wg, tid);
    cp_arrive(sb + 8 * (B_B + wg));
    asm volatile("setmaxnreg.inc.sync.aligned.u32 224;");
    STAMPIF(threadIdx.x == 0, 82);
    const int g = lane >> 2, q = lane & 3;
    if (wg == 1) bar_arrive(1, 256);
    const uint32_t dv = *(const uint16_t*)(gD + 128 * wg + b);
    {
      const int b0 = (g >> 1) & 1, b1 = g >> 2, u = q + 4 * b0 - w;
      const uint32_t fo = 128 + (g & 1) * K1OFF + 288 * b1 + 4 * u, fo0 = fo - (u < 0 ? 32 : 0);
      const bool wrap = b0 && q == 0;
      const int src1 = b0 ? ((lane & 20) | ((q - 1) & 3)) : (lane | 8);
      const uint2* pu = (const uint2*)(G->kvT + (128 * wg + b) * S_ + 8 * tid);
      uint4 u0 = make_uint4(0, 0, 0, 0), u1 = u0;
      if (UPOS & 1) { u0 = ld_tag2(pu); u1 = ld_tag2(pu + 256); }
#pragma unroll 1
      for (int ch = wg; ch < 5; ch += 2) {
        const uint32_t base = chan_base(sb, ch);
        if (ch < 2 || ch == KV4C) {
          kv_job(G, sb, b, ch < 2 ? ch : 4, tid);
          STAMPIF(tid == 0, ch < 2 ? 1 + ch : 24);
        }
        if (ch < 2) {
          k1_job(sb, wg, tid, dv);
          bar_sync(3 + wg, 128);
        } else {
          mbar_wait(sb + 8 * (B_K + ch - 2), 0);
          if (UPOS & 4) { u0 = ld_tag2(pu); u1 = ld_tag2(pu + 256); }
          mbar_wait(sb + 8 * (B_S + ch), 0);
        }
        const uint32_t fa = base + fo, fa0 = base + fo0;
        uint32_t af[16][4];
#pragma unroll
        for (int j = 0; j < 16; j++) {
          const int o = 64 * (j & 1) + 576 * (j >> 1);
          af[j][0] = lds32(((j & 1) ? fa : fa0) + o); af[j][1] = lds32(fa + o + 128); af[j][2] = lds32(fa + o + 32); af[j][3] = lds32(fa + o + 160);
        }
        STAMPIF(tid == 0, 40 + ch);
        u_wait(u0, u1, pu);
        sts128(base + KSZ + 16 * tid, u0);
        sts128(base + KSZ + 2048 + 16 * tid, u1);
        fence_async_s();
        pu += 128 * S_ / 2;
        float acc[128];
        const uint64_t db = mkdesc(base + KSZ, 32, 128, 0);
        bar_sync(1 + wg, 256);
        wg_fence();
        wgmma_rs_n64<0>(acc + 96, af[0], db + 192, 0);
        wgmma_rs_n192<0>(acc, af[0], db, 0);
        wgmma_rs_n64<0>(acc + 96, af[1], db + 196, 1);
        wgmma_rs_n192<0>(acc, af[1], db + 4, 1);
        wgmma_rs_n32<0>(acc + 96, af[2], db + 224, 1);
        wgmma_rs_n192<0>(acc, af[2], db + 32, 1);
        wgmma_rs_n32<0>(acc + 96, af[3], db + 228, 1);
        wgmma_rs_n192<0>(acc, af[3], db + 36, 1);
        wgmma_rs_n192<0>(acc, af[4], db + 64, 1);
        wgmma_rs_n192<0>(acc, af[5], db + 68, 1);
        wgmma_rs_n160<0>(acc, af[6], db + 96, 1);
        wgmma_rs_n160<0>(acc, af[7], db + 100, 1);
        if (CVT == 2) wg_commit();
        wgmma_rs_n128<0>(acc, af[8], db + 128, 1);
        wgmma_rs_n128<0>(acc, af[9], db + 132, 1);
        if (CVT == 1) wg_commit();
        wgmma_rs_n96<0>(acc, af[10], db + 160, 1);
        wgmma_rs_n96<0>(acc, af[11], db + 164, 1);
        if (CVT == 0) bar_arrive(2 - wg, 256);
        wgmma_rs_n64<0>(acc, af[12], db + 192, 1);
        wgmma_rs_n64<0>(acc, af[13], db + 196, 1);
        wgmma_rs_n32<0>(acc, af[14], db + 224, 1);
        wgmma_rs_n32<0>(acc, af[15], db + 228, 1);
        wg_commit();
        if (tid < 2 && ch == (wg == (KV4C & 1) && KV4C < 5 ? KV4C : wg)) mbar_arrive(sb + 8 * (B_E1 + tid));
        if (CVT) { wg_wait<1>(); if (ch < 4) bar_arrive(2 - wg, 256); }
        STAMPIF(tid == 0, 3 + ch);
        wg_wait<0>();
#pragma unroll
        for (int i = 0; i < 128; i++) asm volatile("" : "+f"(acc[i])::"memory");
        bar_sync(3 + wg, 128);
        if (tid <= (ch >> 2)) mbar_arrive(sb + 8 * (B_E1 + 2 + (ch >> 1)));
        if (ch < 3 && !(UPOS & 14)) { u0 = ld_tag2(pu); u1 = ld_tag2(pu + 256); }
        float S0[33], T[34];
#pragma unroll
        for (int i = 0; i < 31; i++) S0[i] = acc[4 * i] + acc[4 * i + 6];
        S0[31] = acc[124]; S0[32] = 0.f;
#pragma unroll
        for (int i = 0; i < 32; i++) {
          float s1 = i < 31 ? acc[4 * i + 1] + acc[4 * i + 7] : acc[125];
          T[i] = (wrap ? S0[i + 1] : S0[i]) + __shfl_sync(0xffffffffu, s1, src1);
        }
        T[32] = 0.f; T[33] = 0.f;
        uint4* pz = (uint4*)(G->zT + (128 * ch + b) * S_) + ((tid & 120) | (2 * q) | (g & 1));
#pragma unroll
        for (int h = 0; h < 2; h++) {
          float y[8];
#pragma unroll
          for (int mu = 0; mu < 8; mu++) y[mu] = (b1 ? T[4 * mu + 4 + h] : T[4 * mu + h]) + __shfl_xor_sync(0xffffffffu, T[4 * mu + 2 + h], 16);
          pz[128 * h] = make_uint4(pack2(y[0], y[1]), pack2(y[2], y[3]), pack2(y[4], y[5]), pack2(y[6], y[7]) | 1);
        }
        if (ch < 3 && (UPOS & 2)) { u0 = ld_tag2(pu); u1 = ld_tag2(pu + 256); }
        if (UPOS & 8) u0.w = 0;
        __syncwarp();
        if (lane == 0) mbar_arrive(sb + 8 * (B_Z + ch));
        STAMPIF(tid == 0, 8 + ch);
      }
    }
    uint32_t hh[96];
    {
      float ga[192];
      float* ua = ga + 96;
      const uint64_t da0 = mkdesc(ring + wg * 2048, 512, 256, 3), db0 = mkdesc(ring + 8192, 4096, 1024, 1);
      int st = 0, ph = 0;
      mbar_wait(sb + 8 * B_BD, 0);
      const uint32_t e1 = lds32(sb + SM_SMALL + SMALL_E);
      if (wg) {
        mod_box(G, sb, b, 1, e1, tid);
        __syncwarp();
        if (lane == 0) mbar_arrive(sb + 8 * (B_BD + 1));
        STAMPIF(tid == 0, 73);
      }
      const int ao = 256 * (lane & 16) + 16 * (threadIdx.x & 224) + 32 * (lane & 15) + 4 * (lane & 4) + (lane & 8) + 4;
      const bool cs = b < 96;
      const int x0 = wg ? XI : 99, x1 = x0 + (cs ? 4 : 2), xs = cs ? 4 : 8;
      uint64_t xa = cs ? mkdesc(sb + SM_EXT, 4096, 1024, 1) : box_a(sb), xb = cs ? mkdesc(sb + SM_CB, 32, 128, 0) : box_b(sb);
      uint64_t ya = xa + (cs ? (SM_RING + R_X - SM_EXT) / 16 : 256), yb = xb + 16;
      float bx[4];
#pragma unroll 1
      for (int it = 0; it < 20; it++) {
        if (it == x0) {
          mbar_wait(sb + 8 * (cs ? B_F : B_BOX + 4), 0);
          mbar_wait(sb + 8 * (cs ? B_ST0 : B_BOX + 5), 0);
          STAMPIF(tid == 0, 76);
        }
        if (it == x1 + XW) {
          wg_wait<XW>();
#pragma unroll
          for (int i = 0; i < 4; i++) asm volatile("" : "+f"(bx[i])::"memory");
          if (!cs) mod_put(G, sb, bx, b, 2, e1, tid);
          else {
            const int row = (m < 6 ? 0 : 4) + q;
            uint16_t* dst = (uint16_t*)G->cimg + s * 3072 + (m % 6) * 512 + row * 64 + g;
#pragma unroll
            for (int j = 0; j < 2; j++) {
              const float c1 = __shfl_sync(0xffffffffu, bx[2 * j], lane & 28), c2 = __shfl_sync(0xffffffffu, bx[2 * j + 1], lane & 28);
              const float t = (lane & 2) ? c2 : c1, hi = rbf(t);
              dst[((2 * w + j) ^ row) << 3] = (uint16_t)pack2((lane & 1) ? t - hi : hi, 0.f);
            }
          }
          __syncwarp();
          if (lane == 0) mbar_arrive(sb + 8 * (B_BD + 2));
          STAMPIF(tid == 0, 77);
        }
        mbar_wait(sb + 8 * (B_F1 + st), ph);
        a_check(ring + st * 32768 + ao, (const char*)G->AT + (20 * m + it) * 8192 + ao, e1);
        STAMPIF(tid == 0 && it == 0, 13 + wg);
        STAMPIF(threadIdx.x == 0, 100 + it);
        const uint64_t da = da0 + st * 2048, db = db0 + st * 2048;
        if (it >= x0 && it < x1) {
          wg_fence();
          wgmma_ss_n8<1, 0>(bx, xa, xb, it != x0);
          wgmma_ss_n192<1, 1>(ga, da, db, 1);
          wgmma_ss_n8<1, 0>(bx, ya, yb, 1);
          wgmma_ss_n192<1, 1>(ua, da, db + 768, 1);
          wgmma_ss_n8<1, 0>(bx, ya + 128, yb + xs, 1);
          wgmma_ss_n192<1, 1>(ga, da + 256, db + 128, 1);
          wgmma_ss_n8<1, 0>(bx, ya + 256, yb + 2 * xs, 1);
          wgmma_ss_n192<1, 1>(ua, da + 256, db + 128 + 768, 1);
          wgmma_ss_n8<1, 0>(bx, ya + 384, yb + 3 * xs, 1);
          wg_commit();
          xa += 128; xb += xs; ya += 512; yb += 4 * xs;
        } else {
          wg_fence();
          wgmma_ss_n192<1, 1>(ga, da, db, it != 0);
          wgmma_ss_n192<1, 1>(ua, da, db + 768, it != 0);
          wgmma_ss_n192<1, 1>(ga, da + 256, db + 128, 1);
          wgmma_ss_n192<1, 1>(ua, da + 256, db + 128 + 768, 1);
          wg_commit();
        }
        wg_wait<1>();
        if (it > 0 && tid == 0) mbar_arrive(sb + 8 * (B_E1 + (st == 0 ? 4 : st - 1)));
        if (++st == 5) { st = 0; ph ^= 1; }
      }
      STAMPIF(threadIdx.x == 0, 61);
      if (tid == 0) {
        mbar_wait(sb + 8 * (B_E1 + 5), 0);
        mbar_arrive_remote(mapa(sb + 8 * (B_PEER + 2 * wg), (b & 1) ^ 1));
      }
      mbar_wait(sb + 8 * B_EXT, 0);
      mbar_wait(sb + 8 * B_ST2, 0);
      const uint64_t de = mkdesc(sb + SM_EXT, 1024, 0, 1), ds = mkdesc(sb + SM_STAT + wg * 1024, 0, 128, 0);
      wg_fence();
      wgmma_ss_n192<0, 1>(ga, ds, de, 1);
      wgmma_ss_n192<0, 1>(ua, ds, de + 192, 1);
      wg_commit();
      wg_wait<1>();
      if (tid == 0) {
        mbar_arrive(sb + 8 * (B_E1 + 4));
        mbar_arrive_remote(mapa(sb + 8 * (B_PEER + 2 * wg + 1), (b & 1) ^ 1));
      }
      wg_wait<0>();
#pragma unroll
      for (int i = 0; i < 192; i++) asm volatile("" : "+f"(ga[i])::"memory");
      STAMPIF(tid == 0, 15 + wg);
#pragma unroll
      for (int i = 0; i < 48; i++) {
        const int j = 64 * (i >> 4) + 2 * (i & 15);
        hh[i] = pack2(ga[j] * ga[j + 32], ga[j + 1] * ga[j + 33]);
        asm volatile("" : "+r"(hh[i])::"memory");
      }
    }
    float acc[80];
    uint4 pf[15];
    const uint32_t tag = lds32(sb + SM_SMALL + SMALL_E) & 1;
    const uint32_t obuf = ring + w * 32768 + wg * 4096;
    uint4* const pp[3] = {G->PP + 10240 * m + threadIdx.x, (uint4*)G->zT + 16 * m + 256 * (threadIdx.x >> 4) + (tid & 15), (uint4*)G->kvT + 10240 * m + threadIdx.x};
    {
      const uint32_t la = ring + wg * 2048 + tid * 16, ra = mapa(la, (b & 1) ^ 1), rb = mapa(sb + 8 * (B_RECV + 2 * wg), (b & 1) ^ 1);
#pragma unroll
      for (int h = 0; h < 16; h++) {
        const int gr = h >> 1, pe = gr < 4 ? gr >> 1 : gr & 1, ac = gr < 4 ? gr & 1 : gr / 6, d = gr < 4 ? ac + 1 : ac + 3;
        if (h == 0) mbar_wait(sb + 8 * B_FB, 0);
        if (h == 4) mbar_wait(sb + 8 * (B_FB + 5), 0);
        if (!(h & 1)) mbar_wait(sb + 8 * (B_FB + gr + (gr < 4 ? 1 : 2)), 0);
        if (gr == 2) {
          mbar_wait(sb + 8 * (B_RECV + 2 * wg + (h & 1)), 0);
#pragma unroll
          for (int j = 6 * (h & 1); j < 6 * (h & 1) + 6; j++) {
            const uint4 v = lds128(la + (j < 2 ? 5 : (j >> 1) - 1) * 32768 + (j & 1) * 4096);
            hh[48 + 4 * j] = v.x; hh[49 + 4 * j] = v.y; hh[50 + 4 * j] = v.z; hh[51 + 4 * j] = v.w;
          }
        }
        STAMPIF(tid == 0 && h % 4 == 0, (wg ? 89 : 121) + h / 4);
        const uint64_t db = mkdesc(ring + (gr & 3) * 32768 + 8192, (5 - pe - (gr & 3)) * 32768 + 16 * ((s + 2 * d) & 6), 1024, 1);
        wg_fence();
#pragma unroll
        for (int j = 6 * (h & 1); j < 6 * (h & 1) + 6; j++) wgmma_rs_n80<1>(acc + 40 * ac, hh + 48 * pe + 4 * j, db + 128 * j, pe || j);
        wg_commit();
        if (h < 4) {
#pragma unroll
          for (int j = SJ(h); j < SJ(h + 1); j++) {
            if (j == 0 || j == 10) mbar_wait(sb + 8 * (B_PEER + 2 * wg + j / 10), 0);
            st_async4(ra + (j < 2 ? 5 : (j >> 1) - 1) * 32768 + (j & 1) * 4096, hh + 4 * j, rb + 8 * (j / 6));
          }
          STAMPIF(tid == 0 && h == 3, 81);
        }
        if (h == PL1) pp_load<256>(pf, pp[0] + s * 1280);
        if (h == 2 || h == 4 || h == 6 || h == 8 || h == 12) {
          wg_wait<1>();
          if (h < 12 && tid == 0) mbar_arrive(sb + 8 * (B_EB + gr - 1));
          if (h >= 6) {
            const int i = h == 6 ? 1 : h == 8 ? 2 : 3;
            float* a = acc + 40 * (1 - ac);
#pragma unroll
            for (int j = 0; j < 40; j++) asm volatile("" : "+f"(a[j])::"memory");
            if (i == 2) pp_send<4096>(pp[1] + (s ^ 4) * 20480, a, 0);
            else pp_send<256>(pp[i - 1] + ((s + 2 * i) & 7) * 1280, a, i == 1 ? tag : 0);
            STAMPIF(threadIdx.x == 0, 50 + i);
          }
        }
        if (h == 5) bar_sync(3 + wg, 128);
        if (h == PL2) pp_load<4096>(pf + 5, pp[1] + s * 20480);
        if (h == 14) wg_wait<1>();
        STAMPIF(tid == 0 && h == 14, wg ? 97 : 96);
      }
    }
    STAMPIF(tid == 0, wg ? 95 : 93);
    if (!P3E) {
      pp_wait<256>(pf, pp[0] + s * 1280, tag);
      pp_wait<4096>(pf + 5, pp[1] + s * 20480, 0);
      STAMPIF(tid == 0, wg ? 36 : 98);
#pragma unroll
      for (int i = 0; i < 5; i++) {
        pp_add(pf[i], pf[5 + i]);
        asm volatile("" : "+r"(pf[i].x), "+r"(pf[i].y), "+r"(pf[i].z), "+r"(pf[i].w)::"memory");
      }
    }
    mbar_wait(sb + 8 * B_X1, 0);
    pp_load<256>(pf + 10, pp[2] + s * 1280);
    STAMPIF(tid == 0, wg ? 20 : 17);
    uint32_t xr[20], gr[20], ln;
    mbar_wait(sb + 8 * B_GB, 0);
    STAMPIF(tid == 0, 84 + wg);
    asm volatile("mov.u32 %0, %%laneid;" : "=r"(ln));
    {
      const uint32_t la = sb + SM_X + (4 * wg + w) * 512 + ((ln >> 1) & 8) * 32 + (ln & 7) * 32 + (((ln << 1) ^ (ln << 2)) & 16), lg = sb + SM_CB + 1280 + 4 * (ln & 3);
      uint32_t rh[2], rl[2];
#pragma unroll
      for (int i = 0; i < 2; i++) {
        const float t = blo(lds32(sb + SM_STAT + (4 * wg + w) * 256 + (ln & 28) * 4 + 128 * i + 4)), r = __fdividef(0.25f, t * t);
        rh[i] = pack2(r, r);
        rl[i] = pack2(r - blo(rh[i]), r - blo(rh[i]));
      }
#pragma unroll
      for (int i = 0; i < 10; i++) {
        const uint32_t t = lds32(lg + 32 * i);
        gr[2 * i] = hfma(t, rh[0], hmul(t, rl[0])); gr[2 * i + 1] = hfma(t, rh[1], hmul(t, rl[1]));
        asm volatile("" : "+r"(gr[2 * i]), "+r"(gr[2 * i + 1]));
      }
#pragma unroll
      for (int i = 0; i < 5; i++) ldsm4t(xr + 4 * i, la + i * 4096);
    }
    uint32_t os = obuf + (ln & 15) * 176 + (ln & 16), ol = obuf + (ln >> 3) * 48 + ln * 16, ol1 = obuf + (ln >> 1) * 144 + 128 + ln * 16;
    const char* po = (const char*)(gout + (1793 + 2 * tbase(8 * m + 4 * wg + w)) * D_);
    const char* p0 = po + (int)(2 * out_col(s, 0) + 16 * ln - (ln >> 3) * (512 * D_ + 128));
    const char* p1 = po + (int)(2 * out_col(s, 4) + 16 * (ln & 1) - ((ln & 14) * 128 + (ln >> 4)) * 2 * D_);
    asm volatile("" : "+r"(os), "+r"(ol), "+r"(ol1), "+l"(p0), "+l"(p1));
    wg_wait<0>();
#pragma unroll
    for (int i = 40; i < 80; i++) asm volatile("" : "+f"(acc[i])::"memory");
    STAMPIF(tid == 0, wg ? 50 : 18);
    uint4 po_[5];
#pragma unroll
    for (int i = 0; i < 5; i++) {
      po_[i] = pp_pack(acc + 40 + 8 * i);
      if (!P3E) pp_add(po_[i], pf[i]);
      asm volatile("" : "+r"(po_[i].x), "+r"(po_[i].y), "+r"(po_[i].z), "+r"(po_[i].w)::"memory");
    }
    STAMPIF(tid == 0, wg ? 37 : 99);
    if (P3E) {
      pp_wait<256>(pf, pp[0] + s * 1280, tag);
      pp_wait<4096>(pf + 5, pp[1] + s * 20480, 0);
    }
    pp_wait<256>(pf + 10, pp[2] + s * 1280, 0);
    STAMPIF(tid == 0, wg ? 38 : 125);
#pragma unroll
    for (int i = 0; i < 5; i++) {
      if (P3E) { pp_add(po_[i], pf[i]); pp_add(pf[10 + i], pf[5 + i]); }
      pp_add(po_[i], pf[10 + i]);
      const uint32_t ov[4] = {hfma(gr[4 * i], po_[i].x, xr[4 * i]), hfma(gr[4 * i + 1], po_[i].y, xr[4 * i + 1]), hfma(gr[4 * i + 2], po_[i].z, xr[4 * i + 2]),
                              hfma(gr[4 * i + 3], po_[i].w, xr[4 * i + 3])};
      stsm4(os + 32 * i, ov);
    }
    __syncwarp();
#pragma unroll
    for (int i = 0; i < 5; i++) pf[i] = lds128(i < 4 ? ol + 704 * i : ol1);
#pragma unroll
    for (int i = 0; i < 5; i++)
      asm volatile("st.global.v4.b32 [%0], {%1, %2, %3, %4};" ::"l"(i < 4 ? p0 - (i & 1) * 2048 * D_ - (i >> 1) * 2 * D_ : p1), "r"(pf[i].x), "r"(pf[i].y), "r"(pf[i].z), "r"(pf[i].w) : "memory");
  } else if (wg == 2) {
    asm volatile("setmaxnreg.dec.sync.aligned.u32 40;");
    const uint32_t e1 = (rdback(G->flag + 8 * m + 4) >> 5) + 1;
    if (tid < 80) {
      uint4 c = ((const uint4*)gc)[tid];
#pragma unroll 1
      for (int i = 0; i < 4; i++) {
        const float lo = blo(c.x), hi = bhi(c.x);
        sts32(sb + SM_STAT + 16 * tid + 4 * i, pack2(__fdividef(lo, 1.f + __expf(-lo)), __fdividef(hi, 1.f + __expf(-hi))));
        c.x = c.y; c.y = c.z; c.z = c.w;
      }
    }
    if (tid == 0) sts32(sb + SM_SMALL + SMALL_E, e1);
    fence_async_s();
    bar_sync(5, 128);
    int tl = tid;
#pragma unroll 1
    for (uint64_t pr = AUXP; pr; pr >>= 4) {
      asm volatile("" : "+r"(tl));
      const int op = pr & 15, tid = tl, lane = tid & 31;
      if (op == 0) {
        ln1_job(sb, tid);
      } else if (op < 4) {
        kv_job(G, sb, b, op + 1, tid);
        STAMPIF(tid == 0, 21 + op);
      } else if (op < 11) {
        if (mod_first(b)) mod_box(G, sb, b, 0, e1, tid);
        __syncwarp();
        if (lane == 0) mbar_arrive(sb + 8 * B_BD);
        STAMPIF(tid == 0, 27);
      } else {
        const int r = op - 11, cg = 8 * r + 4 * (w >> 1) + (lane & 2) + (w & 1), g = lane >> 2;
        const uint2* pz = (const uint2*)(G->zT + (16 * cg + g) * S_ + 16 * b + 8 * (lane & 1));
        const uint32_t* pc = G->mv + 2048 * (e1 & 1) + 8 * cg + g;
        mbar_wait(sb + 8 * (B_BD + (r > 1)), 0);
        mbar_wait(sb + 8 * (B_Z + r), 0);
        STAMPIF(tid == 0 && r == 0, 28);
        uint4 z[2] = {ld_tag2(pz), ld_tag2(pz + 4096)};
        uint32_t c[4] = {rdback(pc), rdback(pc + 320), rdback(pc + 640), rdback(pc + 1280)}, xv[8];
        const uint32_t xa = x_addr(sb, w, lane) + 4096 * r, la = sb + SM_SMALL + SMALL_LN + 16 * (lane & 1);
        const uint4 m4 = lds128(la), s4 = lds128(la + 32);
        const uint32_t m_[4] = {m4.x, m4.y, m4.z, m4.w}, s_[4] = {s4.x, s4.y, s4.z, s4.w};
        ldsm4t(xv, xa);
        ldsm4t(xv + 4, xa ^ 16);
        z_wait(z[0], z[1], c, pz, pc);
        STAMPIF(tid == 0 && r == 0, 83);
        uint4* pa = (uint4*)G->AT + ((40 * m + cg) * 8 + s) * 32 + 2 * g + ((lane ^ (lane >> 4)) & 1);
#pragma unroll
        for (int j = 0; j < 4; j++) c[j] = ~c[j];
#pragma unroll
        for (int n = 0; n < 2; n++) {
          const uint32_t z_[4] = {z[n].x, z[n].y, z[n].z, z[n].w}, sel = n ? 0x3232 : 0x1010;
          const uint32_t sa = __byte_perm(c[0], 0, sel), ca1 = __byte_perm(c[1], 0, sel), ga = __byte_perm(c[2], 0, sel), cb1 = __byte_perm(c[3], 0, sel);
          uint32_t o[4], a[4];
#pragma unroll
          for (int j = 0; j < 4; j++) {
            o[j] = hfma(ga, hmul(hfma(hmul(hsub(xv[4 * n + j], m_[j]), s_[j]), ca1, sa), z_[j]), xv[4 * n + j]);
            a[j] = hmul(o[j], cb1);
          }
          a[2 * n + 1] = (a[2 * n + 1] & ~1u) | (e1 & 1);
          pa[16 * n] = make_uint4(a[0], a[1], a[2], a[3]);
          if (n) { __syncwarp(); if (lane == 0) flag_add(G, 8 * m + r); }
          pa[16 * n - D_ * S_ / 8] = make_uint4(o[0], o[1], o[2], o[3]);
          sts128(xa ^ (16 * n), make_uint4(o[0], o[1], o[2], o[3]));
        }
        __syncwarp();
        if (lane == 0) mbar_arrive(sb + 8 * (B_EW + r));
        STAMPIF(tid == 0, 29 + r);
      }
      if (op == kLastKv) { __syncwarp(); if (lane == 0) mbar_arrive(sb + 8 * B_KVS); }
    }
    {
      const uint4 m4 = lds128(sb + SM_SMALL + SMALL_LN + 16 * (lane & 1));
      const uint32_t m_[4] = {m4.x, m4.y, m4.z, m4.w}, xa = x_addr(sb, w, lane);
      float a[16];
#pragma unroll
      for (int i = 0; i < 16; i++) a[i] = 0.f;
#pragma unroll 2
      for (int n = 0; n < 10; n++) {
        const uint4 x4 = lds128((xa ^ (16 * (n & 1))) + 2048 * (n & 14));
        const uint32_t x_[4] = {x4.x, x4.y, x4.z, x4.w};
#pragma unroll
        for (int i = 0; i < 4; i++) {
          const float d0 = blo(x_[i]) - blo(m_[i]), d1 = bhi(x_[i]) - bhi(m_[i]);
          a[4 * i] += d0; a[4 * i + 1] += d0 * d0; a[4 * i + 2] += d1; a[4 * i + 3] += d1 * d1;
        }
      }
      STAMPIF(lane == 0, 67 + (w & 1) + 11 * (w >> 1));
      bfly<16>(a, 16, lane & 16); bfly<8>(a, 8, lane & 8); bfly<4>(a, 4, lane & 4); bfly<2>(a, 2, lane & 2);
      if (lane == 0) mbar_arrive(sb + 8 * B_XF);
      STAMPIF(tid == 0, 88);
      sts32(sb + SM_SMALL + SMALL_RED + 16 * lane + 4 * w, __float_as_uint(a[0]));
      bar_sync(5, 128);
      if (w == 0) {
        const uint4 v = lds128(sb + SM_SMALL + SMALL_RED + 16 * lane);
        const float s1 = __uint_as_float(v.x) + __uint_as_float(v.y) + __uint_as_float(v.z) + __uint_as_float(v.w), s2 = __shfl_xor_sync(0xffffffffu, s1, 2);
        const int p = 8 * (lane & 1) + (lane >> 2);
        const float pv = blo(lds32(sb + SM_SMALL + SMALL_LN + 4 * (p >> 1)) >> (16 * (p & 1)));
        const float mu = s1 * (1.f / D_), var = fmaxf(s2 * (1.f / D_) - mu * mu, 0.f);
        const float sd = rbf(__fsqrt_rn(rbf(rbf(var) + 1e-5f)));
        if (!(lane & 2)) st_tag(G->st2 + 16 * b + p, pack2(-0.5f * (pv + mu), 0.5f * sd), e1);
      }
      STAMPIF(tid == 0, 87);
    }
    {
      uint2 v;
      spin(clk(), SD);
      mbar_wait(sb + 8 * (B_BD + 2), 0);
#pragma unroll 1
      for (int i = 0;; i++) {
        v = ld_tag(G->st2 + 128 * m + tid);
        if (__all_sync(0xffffffffu, v.y == e1)) break;
        if (i > (1 << 20)) __trap();
      }
      const uint32_t hm = __byte_perm(v.x, 0, 0x1010), hs = __byte_perm(v.x, 0, 0x3232);
      sts128(sb + SM_STAT + 16 * tid, make_uint4(hm, hs, hm, hs));
      fence_async_s();
      __syncwarp();
      if (lane == 0) mbar_arrive(sb + 8 * B_ST2);
      STAMPIF(tid == 0, 21);
    }
  } else {
    asm volatile("setmaxnreg.dec.sync.aligned.u32 24;");
    if (w != 0) {
    if (w == 2 && lane < 5) asm volatile("prefetch.tensormap [%0];" ::"l"(&P.mG + lane) : "memory");
    if (w & 1) {
#pragma unroll 1
      for (int j = 4; j < 10; j++) {
        k1_job(sb, j >> 1, 64 * (j & 1) + 16 * (w & 2) + lane, *(const uint16_t*)(gD + 64 * (j & 14) + b));
        if (UD && w == 1 && (j & 1)) {
          mbar_wait(sb + 8 * (B_KJ + (j >> 1)), 0);
          const uint32_t t = lds32(sb + SM_SMALL + SMALL_TS + 4 * (j >> 1));
          while (clk() - t < UD);
        }
        __syncwarp();
        if (lane == 0) mbar_arrive(sb + 8 * (B_K + (j >> 1) - 2));
      }
      STAMPIF(tid == 32, 74);
    }
    if (w == 1) {
     {
      if (elect()) {
        mbar_wait(sb + 8 * B_KVS, 0);
        mbar_wait(sb + 8 * B_EW, 0);
        const uint32_t e1 = lds32(sb + SM_SMALL + SMALL_E);
#pragma unroll 1
        for (int it = 0; it < 20; it++) {
          int st = it % 5;
          if ((it & 3) == 0) { flag_wait(G, 8 * m + (it >> 2), e1 * 32); STAMP(45 + (it >> 2)); }
          mbar_wait(sb + 8 * (B_E1 + st), (it / 5) & 1);
          uint32_t fb = sb + 8 * (B_F1 + st);
          mbar_expect(fb, 8192);
          bulk_g2s(ring + st * 32768, G->AT + (20 * m + it) * 4096, 8192, fb);
        }
        mbar_wait(sb + 8 * B_XF, 0);
        flag_wait(G, 8 * m + FL_X, e1 * 8);
        fence_async_g();
        mbar_expect(sb + 8 * B_X1, 20480);
        bulk_g2s(sb + SM_X, G->x1T + (640 * m + out_col(s, 0)) * 128, 16384, sb + 8 * B_X1);
        bulk_g2s(sb + SM_X + 16384, G->x1T + (640 * m + out_col(s, 4)) * 128, 4096, sb + 8 * B_X1);
        STAMP(86);
      }
     }
    } else if (w == 2) {
      if (lane < 4) mbar_expect(sb + 8 * (B_RECV + lane), 12288);
      mbar_wait(sb + 8 * (B_EW + 4), 0);
      const uint32_t e1 = lds32(sb + SM_SMALL + SMALL_E);
      {
        const bf16* p = G->x1T + ((40 * m + (lane >> 2)) * 8 + s) * 256 + 64 * (lane & 3);
        uint32_t v = 0;
#pragma unroll
        for (int r = 0; r < 5; r++) v ^= rdback(p + 16384 * r);
        rdwait(sb, v);
        __syncwarp();
        if (lane == 0) flag_add(G, 8 * m + FL_X);
        STAMPIF(lane == 0, 94);
      }
      mbar_wait(sb + 8 * (B_BD + 2), 0);
      if (lane < 2) mbar_arrive(sb + 8 * (B_E1 + 5));
      if (m < 12) {
        rdwait(sb, rdback(G->cimg + s * 3072 + (m % 6) * 512 + (m < 6 ? 0 : 256) + 64 * (lane & 3)));
        __syncwarp();
        if (lane == 0) flag_add(G, FL_C + 8 * s);
        STAMPIF(lane == 0, 35);
      }
      if (elect()) {
        flag_wait(G, FL_C + 8 * s, e1 * 12);
        fence_async_g();
        STAMP(54);
        mbar_expect(sb + 8 * B_EXT, 6144);
        bulk_g2s(sb + SM_EXT, G->cimg + s * 3072, 6144, sb + 8 * B_EXT);
      }
    } else {
      mbar_wait(sb + 8 * B_KVS, 0);
      mbar_wait(sb + 8 * (B_BD + 1), 0);
      if (b >= 96 && elect()) { load_box(P, sb, b, 4); load_box(P, sb, b, 5); }
      spin(clk(), CD);
      __syncwarp();
      const uint32_t* p = G->mv + 2048 * (lds32(sb + SM_SMALL + SMALL_E) & 1) + 4 * (lane & 1);
#pragma unroll 1
      for (int n = 0; n < 4; n++) {
        if (n == 3) {
          fence_async_s();
          __syncwarp();
          if (lane == 0) mbar_arrive(sb + 8 * B_F);
          STAMPIF(lane == 0, 34);
          mbar_wait(sb + 8 * B_ST2, 0);
        }
        const int j = n < 3 ? min(16 * n + (lane >> 1), 39) : min(40 + (lane >> 1), 44), k = j < 20 ? j : j - 20;
        const uint2* pj = (const uint2*)(p + (j < 40 ? 8 * (k + (j < 20 ? 160 : 120) + (m < 6 ? 0 : 20)) : 1600 + out_col(s, k - 20) / 2));
        uint4 a;
#pragma unroll 1
        for (int i = 0;; i++) {
          a = ld_tag2(pj);
          if (__all_sync(0xffffffffu, a.x != 0)) break;
          if (i > (1 << 20)) __trap();
        }
        const uint32_t d = sb + SM_CB + 64 * k + 8 * (lane & 1) + (j >= 20 && j < 40 ? 16 : 0);
        sts64(d, ~__byte_perm(a.x, a.y, 0x5410), ~__byte_perm(a.z, a.w, 0x5410));
        sts64(d + 32, ~__byte_perm(a.x, a.y, 0x7632), ~__byte_perm(a.z, a.w, 0x7632));
      }
      __syncwarp();
      if (lane == 0) mbar_arrive(sb + 8 * B_GB);
      STAMPIF(lane == 0, 39);
    }
    } else {
      STAMPIF(lane == 0, 62);
      int rw = sched_run<0>(P, In{gk, gv, gsk, gWg, gWu, gWd, gss}, sb, b, lane, __shfl_sync(0xffffffffu, t_0, 0));
      if (elect()) {
        STAMP(69);
        mbar_wait(sb + 8 * B_KVS, 0);
        STAMP(70);
        int rd = 0, c = 0;
#pragma unroll 1
        for (int it = 0; it < 20; it++) {
          load_w(P, sb, s, it);
          if ((PWM >> it) & 1) { l2_prefetch(gWg + (128 * rw + b) * F_, 2 * F_); l2_prefetch(gWu + (128 * rw + b) * F_, 2 * F_); rw++; }
          if ((PDM >> it) & 1) { l2_prefetch(gWd + (512 * rd + 4 * b) * D_, 8 * D_); rd++; }
          if (((STM >> it) & 1) && b < 96) {
            const int grp = m % 6;
            if (c == 4) mbar_wait(sb + 8 * (B_BD + 1), 0);
            if (c == 0) mbar_expect(sb + 8 * B_ST0, 40960);
#pragma unroll
            for (int j = 0; j < 2; j++, c++)
              tma2d(sb + (c < 2 ? SM_EXT : SM_RING + R_X - 8192) + 4096 * c, &P.mG + (grp & 1), 192 * s + 64 * (grp >> 1), (m < 6 ? 0 : 320) + 32 * c, sb + 8 * B_ST0);
          }
        }
#pragma unroll
        for (int k = 0; k < 10; k++) {
          const int st = k == 0 ? 5 : (k - 1) % 5, pe = k < 6 ? k / 3 : k & 1, d = k < 6 ? 2 - (k & 1) : k >> 1;
          mbar_wait(sb + 8 * (k < 6 ? B_E1 + st : B_EB + st), 0);
          mbar_expect(sb + 8 * (B_FB + k), 24576);
          tma2d(ring + st * 32768 + 8192, &P.mD, 320 * (s & 1) + (st > 3 ? 256 : 32 * ((s + 2 * d) & 6)), 192 * (s ^ pe), sb + 8 * (B_FB + k));
        }
      }
    }
  }
}

typedef CUresult (*EncFn)(CUtensorMap*, CUtensorMapDataType, cuuint32_t, void*, const cuuint64_t*, const cuuint64_t*, const cuuint32_t*, const cuuint32_t*,
                          CUtensorMapInterleave, CUtensorMapSwizzle, CUtensorMapL2promotion, CUtensorMapFloatOOBfill);
static void mkmap(EncFn enc, CUtensorMap* m, const void* p, int rank, const cuuint64_t* dims, const cuuint64_t* strides, const cuuint32_t* box, CUtensorMapSwizzle sw) {
  cuuint32_t es[5] = {1, 1, 1, 1, 1};
  CUresult r = enc(m, CU_TENSOR_MAP_DATA_TYPE_BFLOAT16, rank, (void*)p, dims, strides, box, es, CU_TENSOR_MAP_INTERLEAVE_NONE, sw,
                   CU_TENSOR_MAP_L2_PROMOTION_L2_128B, CU_TENSOR_MAP_FLOAT_OOB_FILL_NONE);
  if (r != CUDA_SUCCESS) fprintf(stderr, "tensor map encode failed: %d\n", (int)r);
}

extern "C" void kernel_launch(void* const* d_in, const int* in_sizes, int n_in, void* d_out, int out_size) {
  void* fn = nullptr;
  cudaDriverEntryPointQueryResult qr;
  cudaGetDriverEntryPoint("cuTensorMapEncodeTiled", &fn, cudaEnableDefault, &qr);
  EncFn enc = (EncFn)fn;
  Scr* G;
  cudaGetSymbolAddress((void**)&G, g_scr);
  Params P;
  { cuuint64_t d[] = {128, 16, 640}, st[] = {256, 4096}; cuuint32_t bx[] = {144, 16, 1}; mkmap(enc, &P.mS, d_in[4], 3, d, st, bx, CU_TENSOR_MAP_SWIZZLE_NONE); }
  { cuuint64_t d[] = {3840, 64, 10}, st[] = {7680, 64 * 7680}; cuuint32_t bx[] = {16, 64, 5}; mkmap(enc, &P.mWm, d_in[11], 3, d, st, bx, CU_TENSOR_MAP_SWIZZLE_32B); }
  { cuuint64_t d[] = {32, 20, 256, 8}, st[] = {64, 10240, 1280}; cuuint32_t bx[] = {40, 1, 9, 8}, bx2[] = {40, 1, 8, 8};
    mkmap(enc, &P.mK, d_in[1], 4, d, st, bx, CU_TENSOR_MAP_SWIZZLE_NONE); mkmap(enc, &P.mV, d_in[2], 4, d, st, bx2, CU_TENSOR_MAP_SWIZZLE_NONE); }
  { cuuint64_t d[] = {1536, 640}, st[] = {3072}; cuuint32_t bx[] = {64, 32};
    mkmap(enc, &P.mG, d_in[7], 2, d, st, bx, CU_TENSOR_MAP_SWIZZLE_128B); mkmap(enc, &P.mU, d_in[8], 2, d, st, bx, CU_TENSOR_MAP_SWIZZLE_128B); }
  { cuuint64_t d[] = {640, 1536}, st[] = {1280}; cuuint32_t bx[] = {64, 192}; mkmap(enc, &P.mD, d_in[9], 2, d, st, bx, CU_TENSOR_MAP_SWIZZLE_128B); }
  { cuuint64_t d[] = {64, 2, 8, 10, 128}, st[] = {1280, 256 * 1280, 128, 2560}; cuuint32_t bx[] = {64, 2, 8, 5, 1}; mkmap(enc, &P.mX, d_in[0], 5, d, st, bx, CU_TENSOR_MAP_SWIZZLE_128B); }
  { cuuint64_t d[] = {640, 8, 2, 128}, st[] = {256 * 1280, 1280, 2560}; cuuint32_t bx[] = {64, 8, 2, 1}, bx2[] = {16, 8, 2, 1};
    mkmap(enc, &P.mO, d_out, 4, d, st, bx, CU_TENSOR_MAP_SWIZZLE_128B); mkmap(enc, &P.mO2, d_out, 4, d, st, bx2, CU_TENSOR_MAP_SWIZZLE_NONE); }
  cudaFuncSetAttribute(fused_kernel, cudaFuncAttributeMaxDynamicSharedMemorySize, SM_TOTAL + DEVSM);
  cudaLaunchConfig_t cfg = {};
  cfg.gridDim = dim3(128); cfg.blockDim = dim3(512); cfg.dynamicSmemBytes = SM_TOTAL + DEVSM; cfg.stream = cudaStreamPerThread;
  cudaLaunchAttribute at[1];
  at[0].id = cudaLaunchAttributeClusterDimension; at[0].val.clusterDim.x = 2; at[0].val.clusterDim.y = 1; at[0].val.clusterDim.z = 1;
  cfg.attrs = at; cfg.numAttrs = 1;
  cudaLaunchKernelEx(&cfg, fused_kernel, (const bf16*)d_in[1], (const bf16*)d_in[2], (const bf16*)d_in[3], (const bf16*)d_in[5], (const bf16*)d_in[10], G,
                     (const bf16*)d_in[7], (const bf16*)d_in[8], (const bf16*)d_in[9], (bf16*)d_out, (const bf16*)d_in[4], P);
}
```

```cpp
#include <cuda_runtime.h>
#include <cuda.h>
#include <cuda_bf16.h>
#include <stdio.h>
#include <stdint.h>
typedef __nv_bfloat16 bf16;
__device__ __forceinline__ uint32_t smem_u32(const void* p) { return (uint32_t)__cvta_generic_to_shared(p); }
__device__ __forceinline__ void mbar_init(uint32_t bar, int cnt) { asm volatile("mbarrier.init.shared::cta.b64 [%0], %1;" ::"r"(bar), "r"(cnt) : "memory"); }
__device__ __forceinline__ void mbar_expect(uint32_t bar, int bytes) { asm volatile("mbarrier.arrive.expect_tx.shared::cta.b64 _, [%0], %1;" ::"r"(bar), "r"(bytes) : "memory"); }
__device__ __forceinline__ void mbar_arrive(uint32_t bar) { asm volatile("mbarrier.arrive.shared::cta.b64 _, [%0];" ::"r"(bar) : "memory"); }
__device__ __forceinline__ void mbar_arrive_remote(uint32_t bar) { asm volatile("mbarrier.arrive.relaxed.cluster.shared::cluster.b64 _, [%0];" ::"r"(bar) : "memory"); }
__device__ __forceinline__ uint32_t mapa(uint32_t a, uint32_t cta) { uint32_t r; asm("mapa.shared::cluster.u32 %0, %1, %2;" : "=r"(r) : "r"(a), "r"(cta)); return r; }
__device__ __forceinline__ bool mbar_try(uint32_t bar, int parity) {
  uint32_t ok;
  asm volatile("{\n.reg .pred p;\nmbarrier.try_wait.parity.shared::cta.b64 p, [%1], %2;\nselp.u32 %0, 1, 0, p;\n}" : "=r"(ok) : "r"(bar), "r"(parity) : "memory");
  return ok;
}
__device__ __forceinline__ void mbar_wait(uint32_t bar, int parity) {
#pragma unroll 1
  for (int i = 0; i < (1 << 20); i++) { if (mbar_try(bar, parity)) return; }
  __trap();
}
__device__ __forceinline__ bool elect() {
  uint32_t p;
  asm volatile("{\n.reg .pred P;\nelect.sync _|P, 0xffffffff;\nselp.u32 %0, 1, 0, P;\n}" : "=r"(p));
  return p;
}
__device__ __forceinline__ void tma2d(uint32_t dst, const CUtensorMap* m, int c0, int c1, uint32_t bar) {
  asm volatile("cp.async.bulk.tensor.2d.shared::cluster.global.mbarrier::complete_tx::bytes [%0], [%1, {%3, %4}], [%2];" ::"r"(dst), "l"(m), "r"(bar), "r"(c0), "r"(c1) : "memory");
}
__device__ __forceinline__ void tma3d(uint32_t dst, const CUtensorMap* m, int c0, int c1, int c2, uint32_t bar) {
  asm volatile("cp.async.bulk.tensor.3d.shared::cluster.global.mbarrier::complete_tx::bytes [%0], [%1, {%3, %4, %5}], [%2];" ::"r"(dst), "l"(m), "r"(bar), "r"(c0), "r"(c1), "r"(c2) : "memory");
}
__device__ __forceinline__ void tma4d(uint32_t dst, const CUtensorMap* m, int c0, int c1, int c2, int c3, uint32_t bar) {
  asm volatile("cp.async.bulk.tensor.4d.shared::cluster.global.mbarrier::complete_tx::bytes [%0], [%1, {%3, %4, %5, %6}], [%2];" ::"r"(dst), "l"(m), "r"(bar), "r"(c0), "r"(c1), "r"(c2), "r"(c3) : "memory");
}
__device__ __forceinline__ void tma5d(uint32_t dst, const CUtensorMap* m, int c0, int c1, int c2, int c3, int c4, uint32_t bar) {
  asm volatile("cp.async.bulk.tensor.5d.shared::cluster.global.mbarrier::complete_tx::bytes [%0], [%1, {%3, %4, %5, %6, %7}], [%2];" ::"r"(dst), "l"(m), "r"(bar), "r"(c0), "r"(c1), "r"(c2), "r"(c3), "r"(c4) : "memory");
}
__device__ __forceinline__ void tma_store2d(const CUtensorMap* m, uint32_t src, int c0, int c1) {
  asm volatile("cp.async.bulk.tensor.2d.global.shared::cta.bulk_group [%0, {%2, %3}], [%1];" ::"l"(m), "r"(src), "r"(c0), "r"(c1) : "memory");
}
__device__ __forceinline__ void tma_store4d(const CUtensorMap* m, uint32_t src, int c0, int c1, int c2, int c3) {
  asm volatile("cp.async.bulk.tensor.4d.global.shared::cta.bulk_group [%0, {%2, %3, %4, %5}], [%1];" ::"l"(m), "r"(src), "r"(c0), "r"(c1), "r"(c2), "r"(c3) : "memory");
}
__device__ __forceinline__ void tma_prefetch2d(const CUtensorMap* m, int c0, int c1) {
  asm volatile("cp.async.bulk.prefetch.tensor.2d.L2.global [%0, {%1, %2}];" ::"l"(m), "r"(c0), "r"(c1) : "memory");
}
__device__ __forceinline__ void bulk_g2s(uint32_t dst, const void* src, int bytes, uint32_t bar) {
  asm volatile("cp.async.bulk.shared::cluster.global.mbarrier::complete_tx::bytes [%0], [%1], %2, [%3];" ::"r"(dst), "l"(src), "r"(bytes), "r"(bar) : "memory");
}
__device__ __forceinline__ void bulk_s2g(void* dst, uint32_t src, int bytes) {
  asm volatile("cp.async.bulk.global.shared::cta.bulk_group [%0], [%1], %2;" ::"l"(dst), "r"(src), "r"(bytes) : "memory");
}
__device__ __forceinline__ void cp16(uint32_t dst, const void* src) { asm volatile("cp.async.cg.shared.global [%0], [%1], 16;" ::"r"(dst), "l"(src) : "memory"); }
__device__ __forceinline__ void cp16z(uint32_t dst, const void* src, int n) { asm volatile("cp.async.cg.shared.global [%0], [%1], 16, %2;" ::"r"(dst), "l"(src), "r"(n) : "memory"); }
__device__ __forceinline__ void cp_arrive(uint32_t bar) { asm volatile("cp.async.mbarrier.arrive.noinc.shared::cta.b64 [%0];" ::"r"(bar) : "memory"); }
__device__ __forceinline__ void st_async4(uint32_t dst, const uint32_t* v, uint32_t bar) {
  asm volatile("st.async.weak.shared::cluster.mbarrier::complete_tx::bytes.v4.b32 [%0], {%1, %2, %3, %4}, [%5];" ::"r"(dst), "r"(v[0]), "r"(v[1]), "r"(v[2]), "r"(v[3]), "r"(bar) : "memory");
}
__device__ __forceinline__ void wg_fence() { asm volatile("wgmma.fence.sync.aligned;" ::: "memory"); }
__device__ __forceinline__ void wg_commit() { asm volatile("wgmma.commit_group.sync.aligned;" ::: "memory"); }
template <int N> __device__ __forceinline__ void wg_wait() { asm volatile("wgmma.wait_group.sync.aligned %0;" ::"n"(N) : "memory"); }
__device__ __forceinline__ uint64_t mkdesc(uint32_t addr, uint32_t lbo, uint32_t sbo, uint32_t swz) {
  return (uint64_t)((addr & 0x3FFFF) >> 4) | ((uint64_t)(lbo >> 4) << 16) | ((uint64_t)(sbo >> 4) << 32) | ((uint64_t)swz << 62);
}
__device__ __forceinline__ void ldsm4t(uint32_t* r, uint32_t a) {
  asm volatile("ldmatrix.sync.aligned.m8n8.x4.trans.shared.b16 {%0,%1,%2,%3}, [%4];" : "=r"(r[0]), "=r"(r[1]), "=r"(r[2]), "=r"(r[3]) : "r"(a) : "memory");
}
__device__ __forceinline__ void stsm4(uint32_t a, const uint32_t* r) {
  asm volatile("stmatrix.sync.aligned.m8n8.x4.shared.b16 [%0], {%1,%2,%3,%4};" ::"r"(a), "r"(r[0]), "r"(r[1]), "r"(r[2]), "r"(r[3]) : "memory");
}
__device__ __forceinline__ void stsm4t(uint32_t a, const uint32_t* r) {
  asm volatile("stmatrix.sync.aligned.m8n8.x4.trans.shared.b16 [%0], {%1,%2,%3,%4};" ::"r"(a), "r"(r[0]), "r"(r[1]), "r"(r[2]), "r"(r[3]) : "memory");
}
__device__ __forceinline__ void bar_sync(int id, int n) { asm volatile("bar.sync %0, %1;" ::"r"(id), "r"(n) : "memory"); }
__device__ __forceinline__ void bar_arrive(int id, int n) { asm volatile("bar.arrive %0, %1;" ::"r"(id), "r"(n) : "memory"); }
__device__ __forceinline__ uint32_t lds32(uint32_t a) { uint32_t v; asm volatile("ld.shared.b32 %0, [%1];" : "=r"(v) : "r"(a) : "memory"); return v; }
__device__ __forceinline__ uint2 lds64(uint32_t a) { uint2 v; asm volatile("ld.shared.v2.b32 {%0,%1}, [%2];" : "=r"(v.x), "=r"(v.y) : "r"(a) : "memory"); return v; }
__device__ __forceinline__ uint4 lds128(uint32_t a) { uint4 v; asm volatile("ld.shared.v4.b32 {%0,%1,%2,%3}, [%4];" : "=r"(v.x), "=r"(v.y), "=r"(v.z), "=r"(v.w) : "r"(a) : "memory"); return v; }
__device__ __forceinline__ void sts16(uint32_t a, uint32_t v) { asm volatile("st.shared.b16 [%0], %1;" ::"r"(a), "h"((uint16_t)v) : "memory"); }
__device__ __forceinline__ void sts32(uint32_t a, uint32_t v) { asm volatile("st.shared.b32 [%0], %1;" ::"r"(a), "r"(v) : "memory"); }
__device__ __forceinline__ void sts64(uint32_t a, uint32_t x, uint32_t y) { asm volatile("st.shared.v2.b32 [%0], {%1,%2};" ::"r"(a), "r"(x), "r"(y) : "memory"); }
__device__ __forceinline__ void sts128(uint32_t a, uint4 v) { asm volatile("st.shared.v4.b32 [%0], {%1,%2,%3,%4};" ::"r"(a), "r"(v.x), "r"(v.y), "r"(v.z), "r"(v.w) : "memory"); }
template<int TB> __device__ __forceinline__ void wgmma_rs_n128(float* d, const uint32_t* a, uint64_t db, int sd) {
  asm volatile("{\n.reg .pred p;\nsetp.ne.b32 p, %69, 0;\n"
    "wgmma.mma_async.sync.aligned.m64n128k16.f32.bf16.bf16 {%0, %1, %2, %3, %4, %5, %6, %7, %8, %9, %10, %11, %12, %13, %14, %15, %16, %17, %18, %19, %20, %21, %22, %23, %24, %25, %26, %27, %28, %29, %30, %31, %32, %33, %34, %35, %36, %37, %38, %39, %40, %41, %42, %43, %44, %45, %46, %47, %48, %49, %50, %51, %52, %53, %54, %55, %56, %57, %58, %59, %60, %61, %62, %63}, {%64, %65, %66, %67}, %68, p, 1, 1, %70;\n}"
    : "+f"(d[0]), "+f"(d[1]), "+f"(d[2]), "+f"(d[3]), "+f"(d[4]), "+f"(d[5]), "+f"(d[6]), "+f"(d[7]), "+f"(d[8]), "+f"(d[9]), "+f"(d[10]), "+f"(d[11]), "+f"(d[12]), "+f"(d[13]), "+f"(d[14]), "+f"(d[15]), "+f"(d[16]), "+f"(d[17]), "+f"(d[18]), "+f"(d[19]), "+f"(d[20]), "+f"(d[21]), "+f"(d[22]), "+f"(d[23]), "+f"(d[24]), "+f"(d[25]), "+f"(d[26]), "+f"(d[27]), "+f"(d[28]), "+f"(d[29]), "+f"(d[30]), "+f"(d[31]), "+f"(d[32]), "+f"(d[33]), "+f"(d[34]), "+f"(d[35]), "+f"(d[36]), "+f"(d[37]), "+f"(d[38]), "+f"(d[39]), "+f"(d[40]), "+f"(d[41]), "+f"(d[42]), "+f"(d[43]), "+f"(d[44]), "+f"(d[45]), "+f"(d[46]), "+f"(d[47]), "+f"(d[48]), "+f"(d[49]), "+f"(d[50]), "+f"(d[51]), "+f"(d[52]), "+f"(d[53]), "+f"(d[54]), "+f"(d[55]), "+f"(d[56]), "+f"(d[57]), "+f"(d[58]), "+f"(d[59]), "+f"(d[60]), "+f"(d[61]), "+f"(d[62]), "+f"(d[63])
    : "r"(a[0]), "r"(a[1]), "r"(a[2]), "r"(a[3]), "l"(db), "r"(sd), "n"(TB));
}

template<int TB> __device__ __forceinline__ void wgmma_rs_n160(float* d, const uint32_t* a, uint64_t db, int sd) {
  asm volatile("{\n.reg .pred p;\nsetp.ne.b32 p, %85, 0;\n"
    "wgmma.mma_async.sync.aligned.m64n160k16.f32.bf16.bf16 {%0, %1, %2, %3, %4, %5, %6, %7, %8, %9, %10, %11, %12, %13, %14, %15, %16, %17, %18, %19, %20, %21, %22, %23, %24, %25, %26, %27, %28, %29, %30, %31, %32, %33, %34, %35, %36, %37, %38, %39, %40, %41, %42, %43, %44, %45, %46, %47, %48, %49, %50, %51, %52, %53, %54, %55, %56, %57, %58, %59, %60, %61, %62, %63, %64, %65, %66, %67, %68, %69, %70, %71, %72, %73, %74, %75, %76, %77, %78, %79}, {%80, %81, %82, %83}, %84, p, 1, 1, %86;\n}"
    : "+f"(d[0]), "+f"(d[1]), "+f"(d[2]), "+f"(d[3]), "+f"(d[4]), "+f"(d[5]), "+f"(d[6]), "+f"(d[7]), "+f"(d[8]), "+f"(d[9]), "+f"(d[10]), "+f"(d[11]), "+f"(d[12]), "+f"(d[13]), "+f"(d[14]), "+f"(d[15]), "+f"(d[16]), "+f"(d[17]), "+f"(d[18]), "+f"(d[19]), "+f"(d[20]), "+f"(d[21]), "+f"(d[22]), "+f"(d[23]), "+f"(d[24]), "+f"(d[25]), "+f"(d[26]), "+f"(d[27]), "+f"(d[28]), "+f"(d[29]), "+f"(d[30]), "+f"(d[31]), "+f"(d[32]), "+f"(d[33]), "+f"(d[34]), "+f"(d[35]), "+f"(d[36]), "+f"(d[37]), "+f"(d[38]), "+f"(d[39]), "+f"(d[40]), "+f"(d[41]), "+f"(d[42]), "+f"(d[43]), "+f"(d[44]), "+f"(d[45]), "+f"(d[46]), "+f"(d[47]), "+f"(d[48]), "+f"(d[49]), "+f"(d[50]), "+f"(d[51]), "+f"(d[52]), "+f"(d[53]), "+f"(d[54]), "+f"(d[55]), "+f"(d[56]), "+f"(d[57]), "+f"(d[58]), "+f"(d[59]), "+f"(d[60]), "+f"(d[61]), "+f"(d[62]), "+f"(d[63]), "+f"(d[64]), "+f"(d[65]), "+f"(d[66]), "+f"(d[67]), "+f"(d[68]), "+f"(d[69]), "+f"(d[70]), "+f"(d[71]), "+f"(d[72]), "+f"(d[73]), "+f"(d[74]), "+f"(d[75]), "+f"(d[76]), "+f"(d[77]), "+f"(d[78]), "+f"(d[79])
    : "r"(a[0]), "r"(a[1]), "r"(a[2]), "r"(a[3]), "l"(db), "r"(sd), "n"(TB));
}

template<int TB> __device__ __forceinline__ void wgmma_rs_n192(float* d, const uint32_t* a, uint64_t db, int sd) {
  asm volatile("{\n.reg .pred p;\nsetp.ne.b32 p, %101, 0;\n"
    "wgmma.mma_async.sync.aligned.m64n192k16.f32.bf16.bf16 {%0, %1, %2, %3, %4, %5, %6, %7, %8, %9, %10, %11, %12, %13, %14, %15, %16, %17, %18, %19, %20, %21, %22, %23, %24, %25, %26, %27, %28, %29, %30, %31, %32, %33, %34, %35, %36, %37, %38, %39, %40, %41, %42, %43, %44, %45, %46, %47, %48, %49, %50, %51, %52, %53, %54, %55, %56, %57, %58, %59, %60, %61, %62, %63, %64, %65, %66, %67, %68, %69, %70, %71, %72, %73, %74, %75, %76, %77, %78, %79, %80, %81, %82, %83, %84, %85, %86, %87, %88, %89, %90, %91, %92, %93, %94, %95}, {%96, %97, %98, %99}, %100, p, 1, 1, %102;\n}"
    : "+f"(d[0]), "+f"(d[1]), "+f"(d[2]), "+f"(d[3]), "+f"(d[4]), "+f"(d[5]), "+f"(d[6]), "+f"(d[7]), "+f"(d[8]), "+f"(d[9]), "+f"(d[10]), "+f"(d[11]), "+f"(d[12]), "+f"(d[13]), "+f"(d[14]), "+f"(d[15]), "+f"(d[16]), "+f"(d[17]), "+f"(d[18]), "+f"(d[19]), "+f"(d[20]), "+f"(d[21]), "+f"(d[22]), "+f"(d[23]), "+f"(d[24]), "+f"(d[25]), "+f"(d[26]), "+f"(d[27]), "+f"(d[28]), "+f"(d[29]), "+f"(d[30]), "+f"(d[31]), "+f"(d[32]), "+f"(d[33]), "+f"(d[34]), "+f"(d[35]), "+f"(d[36]), "+f"(d[37]), "+f"(d[38]), "+f"(d[39]), "+f"(d[40]), "+f"(d[41]), "+f"(d[42]), "+f"(d[43]), "+f"(d[44]), "+f"(d[45]), "+f"(d[46]), "+f"(d[47]), "+f"(d[48]), "+f"(d[49]), "+f"(d[50]), "+f"(d[51]), "+f"(d[52]), "+f"(d[53]), "+f"(d[54]), "+f"(d[55]), "+f"(d[56]), "+f"(d[57]), "+f"(d[58]), "+f"(d[59]), "+f"(d[60]), "+f"(d[61]), "+f"(d[62]), "+f"(d[63]), "+f"(d[64]), "+f"(d[65]), "+f"(d[66]), "+f"(d[67]), "+f"(d[68]), "+f"(d[69]), "+f"(d[70]), "+f"(d[71]), "+f"(d[72]), "+f"(d[73]), "+f"(d[74]), "+f"(d[75]), "+f"(d[76]), "+f"(d[77]), "+f"(d[78]), "+f"(d[79]), "+f"(d[80]), "+f"(d[81]), "+f"(d[82]), "+f"(d[83]), "+f"(d[84]), "+f"(d[85]), "+f"(d[86]), "+f"(d[87]), "+f"(d[88]), "+f"(d[89]), "+f"(d[90]), "+f"(d[91]), "+f"(d[92]), "+f"(d[93]), "+f"(d[94]), "+f"(d[95])
    : "r"(a[0]), "r"(a[1]), "r"(a[2]), "r"(a[3]), "l"(db), "r"(sd), "n"(TB));
}

template<int TB> __device__ __forceinline__ void wgmma_rs_n32(float* d, const uint32_t* a, uint64_t db, int sd) {
  asm volatile("{\n.reg .pred p;\nsetp.ne.b32 p, %21, 0;\n"
    "wgmma.mma_async.sync.aligned.m64n32k16.f32.bf16.bf16 {%0, %1, %2, %3, %4, %5, %6, %7, %8, %9, %10, %11, %12, %13, %14, %15}, {%16, %17, %18, %19}, %20, p, 1, 1, %22;\n}"
    : "+f"(d[0]), "+f"(d[1]), "+f"(d[2]), "+f"(d[3]), "+f"(d[4]), "+f"(d[5]), "+f"(d[6]), "+f"(d[7]), "+f"(d[8]), "+f"(d[9]), "+f"(d[10]), "+f"(d[11]), "+f"(d[12]), "+f"(d[13]), "+f"(d[14]), "+f"(d[15])
    : "r"(a[0]), "r"(a[1]), "r"(a[2]), "r"(a[3]), "l"(db), "r"(sd), "n"(TB));
}

template<int TB> __device__ __forceinline__ void wgmma_rs_n64(float* d, const uint32_t* a, uint64_t db, int sd) {
  asm volatile("{\n.reg .pred p;\nsetp.ne.b32 p, %37, 0;\n"
    "wgmma.mma_async.sync.aligned.m64n64k16.f32.bf16.bf16 {%0, %1, %2, %3, %4, %5, %6, %7, %8, %9, %10, %11, %12, %13, %14, %15, %16, %17, %18, %19, %20, %21, %22, %23, %24, %25, %26, %27, %28, %29, %30, %31}, {%32, %33, %34, %35}, %36, p, 1, 1, %38;\n}"
    : "+f"(d[0]), "+f"(d[1]), "+f"(d[2]), "+f"(d[3]), "+f"(d[4]), "+f"(d[5]), "+f"(d[6]), "+f"(d[7]), "+f"(d[8]), "+f"(d[9]), "+f"(d[10]), "+f"(d[11]), "+f"(d[12]), "+f"(d[13]), "+f"(d[14]), "+f"(d[15]), "+f"(d[16]), "+f"(d[17]), "+f"(d[18]), "+f"(d[19]), "+f"(d[20]), "+f"(d[21]), "+f"(d[22]), "+f"(d[23]), "+f"(d[24]), "+f"(d[25]), "+f"(d[26]), "+f"(d[27]), "+f"(d[28]), "+f"(d[29]), "+f"(d[30]), "+f"(d[31])
    : "r"(a[0]), "r"(a[1]), "r"(a[2]), "r"(a[3]), "l"(db), "r"(sd), "n"(TB));
}

template<int TB> __device__ __forceinline__ void wgmma_rs_n96(float* d, const uint32_t* a, uint64_t db, int sd) {
  asm volatile("{\n.reg .pred p;\nsetp.ne.b32 p, %53, 0;\n"
    "wgmma.mma_async.sync.aligned.m64n96k16.f32.bf16.bf16 {%0, %1, %2, %3, %4, %5, %6, %7, %8, %9, %10, %11, %12, %13, %14, %15, %16, %17, %18, %19, %20, %21, %22, %23, %24, %25, %26, %27, %28, %29, %30, %31, %32, %33, %34, %35, %36, %37, %38, %39, %40, %41, %42, %43, %44, %45, %46, %47}, {%48, %49, %50, %51}, %52, p, 1, 1, %54;\n}"
    : "+f"(d[0]), "+f"(d[1]), "+f"(d[2]), "+f"(d[3]), "+f"(d[4]), "+f"(d[5]), "+f"(d[6]), "+f"(d[7]), "+f"(d[8]), "+f"(d[9]), "+f"(d[10]), "+f"(d[11]), "+f"(d[12]), "+f"(d[13]), "+f"(d[14]), "+f"(d[15]), "+f"(d[16]), "+f"(d[17]), "+f"(d[18]), "+f"(d[19]), "+f"(d[20]), "+f"(d[21]), "+f"(d[22]), "+f"(d[23]), "+f"(d[24]), "+f"(d[25]), "+f"(d[26]), "+f"(d[27]), "+f"(d[28]), "+f"(d[29]), "+f"(d[30]), "+f"(d[31]), "+f"(d[32]), "+f"(d[33]), "+f"(d[34]), "+f"(d[35]), "+f"(d[36]), "+f"(d[37]), "+f"(d[38]), "+f"(d[39]), "+f"(d[40]), "+f"(d[41]), "+f"(d[42]), "+f"(d[43]), "+f"(d[44]), "+f"(d[45]), "+f"(d[46]), "+f"(d[47])
    : "r"(a[0]), "r"(a[1]), "r"(a[2]), "r"(a[3]), "l"(db), "r"(sd), "n"(TB));
}

template<int TA, int TB> __device__ __forceinline__ void wgmma_ss_n192(float* d, uint64_t da, uint64_t db, int sd) {
  asm volatile("{\n.reg .pred p;\nsetp.ne.b32 p, %98, 0;\n"
    "wgmma.mma_async.sync.aligned.m64n192k16.f32.bf16.bf16 {%0, %1, %2, %3, %4, %5, %6, %7, %8, %9, %10, %11, %12, %13, %14, %15, %16, %17, %18, %19, %20, %21, %22, %23, %24, %25, %26, %27, %28, %29, %30, %31, %32, %33, %34, %35, %36, %37, %38, %39, %40, %41, %42, %43, %44, %45, %46, %47, %48, %49, %50, %51, %52, %53, %54, %55, %56, %57, %58, %59, %60, %61, %62, %63, %64, %65, %66, %67, %68, %69, %70, %71, %72, %73, %74, %75, %76, %77, %78, %79, %80, %81, %82, %83, %84, %85, %86, %87, %88, %89, %90, %91, %92, %93, %94, %95}, %96, %97, p, 1, 1, %99, %100;\n}"
    : "+f"(d[0]), "+f"(d[1]), "+f"(d[2]), "+f"(d[3]), "+f"(d[4]), "+f"(d[5]), "+f"(d[6]), "+f"(d[7]), "+f"(d[8]), "+f"(d[9]), "+f"(d[10]), "+f"(d[11]), "+f"(d[12]), "+f"(d[13]), "+f"(d[14]), "+f"(d[15]), "+f"(d[16]), "+f"(d[17]), "+f"(d[18]), "+f"(d[19]), "+f"(d[20]), "+f"(d[21]), "+f"(d[22]), "+f"(d[23]), "+f"(d[24]), "+f"(d[25]), "+f"(d[26]), "+f"(d[27]), "+f"(d[28]), "+f"(d[29]), "+f"(d[30]), "+f"(d[31]), "+f"(d[32]), "+f"(d[33]), "+f"(d[34]), "+f"(d[35]), "+f"(d[36]), "+f"(d[37]), "+f"(d[38]), "+f"(d[39]), "+f"(d[40]), "+f"(d[41]), "+f"(d[42]), "+f"(d[43]), "+f"(d[44]), "+f"(d[45]), "+f"(d[46]), "+f"(d[47]), "+f"(d[48]), "+f"(d[49]), "+f"(d[50]), "+f"(d[51]), "+f"(d[52]), "+f"(d[53]), "+f"(d[54]), "+f"(d[55]), "+f"(d[56]), "+f"(d[57]), "+f"(d[58]), "+f"(d[59]), "+f"(d[60]), "+f"(d[61]), "+f"(d[62]), "+f"(d[63]), "+f"(d[64]), "+f"(d[65]), "+f"(d[66]), "+f"(d[67]), "+f"(d[68]), "+f"(d[69]), "+f"(d[70]), "+f"(d[71]), "+f"(d[72]), "+f"(d[73]), "+f"(d[74]), "+f"(d[75]), "+f"(d[76]), "+f"(d[77]), "+f"(d[78]), "+f"(d[79]), "+f"(d[80]), "+f"(d[81]), "+f"(d[82]), "+f"(d[83]), "+f"(d[84]), "+f"(d[85]), "+f"(d[86]), "+f"(d[87]), "+f"(d[88]), "+f"(d[89]), "+f"(d[90]), "+f"(d[91]), "+f"(d[92]), "+f"(d[93]), "+f"(d[94]), "+f"(d[95])
    : "l"(da), "l"(db), "r"(sd), "n"(TA), "n"(TB));
}

template<int TA, int TB> __device__ __forceinline__ void wgmma_ss_n8(float* d, uint64_t da, uint64_t db, int sd) {
  asm volatile("{\n.reg .pred p;\nsetp.ne.b32 p, %6, 0;\n"
    "wgmma.mma_async.sync.aligned.m64n8k16.f32.bf16.bf16 {%0, %1, %2, %3}, %4, %5, p, 1, 1, %7, %8;\n}"
    : "+f"(d[0]), "+f"(d[1]), "+f"(d[2]), "+f"(d[3])
    : "l"(da), "l"(db), "r"(sd), "n"(TA), "n"(TB));
}

constexpr int S_ = 2048, D_ = 640, F_ = 1536;

struct Scr {
  uint32_t flag[32 * 8];
  uint32_t mv[2 * 2048];
  bf16 cimg[8 * 6 * 512];
  uint2 st2[S_];
  bf16 kvT[D_ * S_];
  bf16 zT[D_ * S_];
  bf16 AT[D_ * S_];
};
__device__ __align__(1024) Scr g_scr;
__device__ __forceinline__ uint32_t clk() { uint32_t c; asm volatile("mov.u32 %0, %%clock;" : "=r"(c) :: "memory"); return c; }
#define DEVSM 0
#define STAMP(id)
#define STAMPIF(c, id)
constexpr int FL_X = 5, FL_C = 128;
#define CD 600
#define SD 1000

constexpr int SM_X = 1024, SM_EXT = 21504, SM_SMALL = 29696, SM_STAT = 30720, SM_CB = 32768, SM_RING = 34816, SM_TOTAL = SM_RING + 6 * 32768;
constexpr int SMALL_LN = 224, SMALL_RED = 320, SMALL_DUMMY = 1008, SMALL_E = 1012, SMALL_TS = 160;
constexpr int JOB_SZ = 10880, JOB_V = 5760, R_X = 5 * 32768, R_BOX = R_X + 12288;
constexpr int K1OFF = 4672, KSZ = 9472, CSZ = KSZ + 4224;
enum { B_KJ = 0, B_X = 5, B_FB = 10, B_PEER = 20, B_RECV = 24, B_EXT = 28, B_X1 = 29, B_A = 30, B_E0 = 35, B_BOX = 38, B_F = 44, B_ST0 = 45, B_GB = 46,
       B_F1 = 48, B_E1 = 54, B_EB = 60,
       B_Z = 80, B_K = 85, B_EW = 88, B_ST2 = 94, B_XF = 95, B_LN = 96, B_KVS = 98, B_BD = 99,
       B_B = 106, B_S = 112 };
__device__ __forceinline__ uint32_t chan_base(uint32_t sb, int ch) { return sb + SM_RING + (2 + (ch >> 1)) * 32768 + (ch & 1) * CSZ; }

struct Params { CUtensorMap mS, mX, mWm, mK, mV, mG, mU, mD; };

__device__ __forceinline__ void flag_add(Scr* G, int id) { asm volatile("red.relaxed.gpu.global.add.u32 [%0], 1;" ::"l"(G->flag + id) : "memory"); }
__device__ __forceinline__ uint32_t rdback(const void* p) { uint32_t v; asm volatile("ld.relaxed.gpu.global.u32 %0, [%1];" : "=r"(v) : "l"(p) : "memory"); return v; }
__device__ __forceinline__ void st_tag(uint2* p, uint32_t v, uint32_t t) { asm volatile("st.relaxed.gpu.global.v2.u32 [%0], {%1, %2};" ::"l"(p), "r"(v), "r"(t) : "memory"); }
__device__ __forceinline__ void spin(uint32_t t, uint32_t d) { if (d) while (clk() - t < d); }
__device__ __forceinline__ uint2 ld_tag(const uint2* p) { uint2 v; asm volatile("ld.relaxed.gpu.global.v2.u32 {%0, %1}, [%2];" : "=r"(v.x), "=r"(v.y) : "l"(p) : "memory"); return v; }
__device__ __forceinline__ uint4 ld_tag2(const uint2* p) {
  uint4 v;
  asm volatile("ld.relaxed.gpu.global.v4.u32 {%0, %1, %2, %3}, [%4];" : "=r"(v.x), "=r"(v.y), "=r"(v.z), "=r"(v.w) : "l"(p) : "memory");
  return v;
}
__device__ __forceinline__ void stg128(void* p, uint4 v) { asm volatile("st.global.v4.b32 [%0], {%1, %2, %3, %4};" ::"l"(p), "r"(v.x), "r"(v.y), "r"(v.z), "r"(v.w) : "memory"); }
__device__ __forceinline__ uint32_t epoch(uint32_t sb) { return lds32(sb + SM_SMALL + SMALL_E); }
__device__ __forceinline__ void rdwait(uint32_t sb, uint32_t v) { sts32(sb + SM_SMALL + SMALL_DUMMY, v); }
__device__ __forceinline__ void fence_async_s() { asm volatile("fence.proxy.async.shared::cta;" ::: "memory"); }
__device__ __forceinline__ void fence_async_g() { asm volatile("fence.proxy.async.global;" ::: "memory"); }
__device__ __forceinline__ void bulk_done() { asm volatile("cp.async.bulk.commit_group;\n\tcp.async.bulk.wait_group 0;" ::: "memory"); }
__device__ __forceinline__ void flag_wait(Scr* G, int id, uint32_t target) {
  const uint32_t* p = G->flag + id;
#pragma unroll 1
  for (int i = 0; i < (1 << 20); i++) {
    uint32_t v;
    asm volatile("ld.relaxed.gpu.global.u32 %0, [%1];" : "=r"(v) : "l"(p) : "memory");
    if ((int)(v - target) >= 0) return;
  }
  __trap();
}
__device__ __forceinline__ int tbase(int pb) { return 127 - (32 * (pb >> 6) + 8 * (pb & 8) + 4 * ((2 * (pb & 3) - ((pb >> 2) & 1)) & 7) + ((pb >> 4) & 3)); }
__device__ __forceinline__ uint32_t hmul(uint32_t a, uint32_t b) { uint32_t d; asm("mul.rn.bf16x2 %0, %1, %2;" : "=r"(d) : "r"(a), "r"(b)); return d; }
__device__ __forceinline__ uint32_t hadd(uint32_t a, uint32_t b) { uint32_t d; asm("add.rn.bf16x2 %0, %1, %2;" : "=r"(d) : "r"(a), "r"(b)); return d; }
__device__ __forceinline__ uint32_t hsub(uint32_t a, uint32_t b) { uint32_t d; asm("sub.rn.bf16x2 %0, %1, %2;" : "=r"(d) : "r"(a), "r"(b)); return d; }
__device__ __forceinline__ uint32_t hfma(uint32_t a, uint32_t b, uint32_t c) { uint32_t d; asm("fma.rn.bf16x2 %0, %1, %2, %3;" : "=r"(d) : "r"(a), "r"(b), "r"(c)); return d; }
__device__ __forceinline__ uint32_t pack2(float lo, float hi) { uint32_t d; asm("cvt.rn.bf16x2.f32 %0, %1, %2;" : "=r"(d) : "f"(hi), "f"(lo)); return d; }
__device__ __forceinline__ float blo(uint32_t v) { return __uint_as_float(v << 16); }
__device__ __forceinline__ float bhi(uint32_t v) { return __uint_as_float(v & 0xffff0000u); }
__device__ __forceinline__ uint32_t tagged(uint32_t v, uint32_t e1) { return (v & ~1u) | (e1 & 1); }
__device__ __forceinline__ float rbf(float v) { return blo(pack2(v, 0.f)); }
template <int N> __device__ __forceinline__ void bfly(float* v, int mask, bool up) {
#pragma unroll
  for (int i = 0; i < N / 2; i++) {
    float send = up ? v[i] : v[i + N / 2], keep = up ? v[i + N / 2] : v[i];
    v[i] = keep + __shfl_xor_sync(0xffffffffu, send, mask);
  }
}
__device__ __forceinline__ bool mod_first(int b) { return !(b & 1) || !(b & 6); }
__device__ __forceinline__ int mod_grp(int b, int j) {
  const int m = b >> 3, s = b & 7, t = 16 * s + m, v = j ? (t * 43) >> 10 : s >> 1;
  if (j == 2) return b + 112;
  if (j == 0 && s == 1) return m + (m < 8 ? 152 : 192);
  return v < 4 ? (v == 3 ? 160 : 40 * v) + (j ? 16 + t - 24 * v : m) : t + 24;
}

__device__ __forceinline__ void kv_load(const bf16* gk, const bf16* gv, const bf16* gs, uint32_t sb, int b, int r, int tid) {
  const int row = tid >> 2, col = 128 * r + 32 * (b & 3);
  const uint32_t a = sb + SM_RING + r * JOB_SZ + (row >> 3) * 80 + (tid & 3) * 16, ak = a + (row & 7) * 720, av = a + (row & 7) * 640 + JOB_V;
  const int o = (64 * (b >> 2) + row) * D_ + col + 8 * (tid & 3);
  cp16(ak + 80, gk + o);
  cp16(ak + 400, gk + o + 32 * D_);
  cp16(av, gv + o);
  cp16(av + 320, gv + o + 32 * D_);
  if (tid < 12) cp16z(ak + 3600, gk + (b < 4 ? o : o - 3 * D_), b < 4 ? 0 : 16);
  else if (tid >= 112) cp16(sb + SM_CB + 256 * r + 16 * (tid - 112), gs + 4 * col + 8 * (tid - 112));
}
__device__ __forceinline__ void load_kv(const Params& P, const bf16* gs, uint32_t sb, int b, int r) {
  const uint32_t a = sb + SM_RING + r * JOB_SZ, bar = sb + 8 * (B_B + r);
  const int cg = 4 * r + (b & 3);
  mbar_expect(bar, JOB_SZ + 256);
  tma4d(a, &P.mK, 0, cg, 8 * (b >> 2) - 1, 0, bar);
  tma4d(a + JOB_V, &P.mV, 0, cg, 8 * (b >> 2), 0, bar);
  bulk_g2s(sb + SM_CB + 256 * r, gs + 128 * cg, 256, bar);
}
__device__ __forceinline__ uint4* kv_dst(Scr* G, int b, int r, int tid) {
  return (uint4*)(G->kvT + (128 * r + 32 * (b & 3) + 8 * (tid >> 5) + 2 * (tid & 3)) * S_ + 2040 - 64 * (b >> 2)) - ((tid >> 2) & 7);
}
__device__ __forceinline__ void kv_job(Scr* G, uint32_t sb, int b, int r, int tid) {
  const int cp = 4 * (tid >> 5) + (tid & 3);
  const uint32_t ka = sb + SM_RING + r * JOB_SZ + ((tid >> 2) & 7) * 80 + cp * 4;
  mbar_wait(sb + 8 * (B_B + r), 0);
  STAMPIF(tid == 0, 56 + r);
  const uint4 sk = lds128(sb + SM_CB + 256 * r + 16 * cp);
  const uint32_t s0 = __byte_perm(sk.x, sk.z, 0x5410), s1 = __byte_perm(sk.x, sk.z, 0x7632), s2 = __byte_perm(sk.y, sk.w, 0x5410), s3 = __byte_perm(sk.y, sk.w, 0x7632);
  uint32_t kk[11], o[8];
#pragma unroll
  for (int i = 0; i < 11; i++) kk[i] = lds32(ka + 720 * ((i + 5) & 7) + 80 * ((i + 5) >> 3));
#pragma unroll
  for (int i = 0; i < 8; i++) {
    uint32_t v = lds32(ka + JOB_V + 640 * i);
    o[i] = hmul(hfma(kk[i + 3], s0, hfma(kk[i + 2], s1, hfma(kk[i + 1], s2, hmul(kk[i], s3)))), v);
  }
  uint4* dst = kv_dst(G, b, r, tid);
  dst[0] = make_uint4(__byte_perm(o[7], o[6], 0x5410), __byte_perm(o[5], o[4], 0x5410), __byte_perm(o[3], o[2], 0x5410), __byte_perm(o[1], o[0], 0x5410) | 1);
  dst[256] = make_uint4(__byte_perm(o[7], o[6], 0x7632), __byte_perm(o[5], o[4], 0x7632), __byte_perm(o[3], o[2], 0x7632), __byte_perm(o[1], o[0], 0x7632) | 1);
  if (tid == 0) { sts32(sb + SM_SMALL + SMALL_TS + 4 * r, clk()); mbar_arrive(sb + 8 * (B_KJ + r)); }
}
__device__ __forceinline__ void u_wait(uint4& a, uint4& c, const void* p) {
  asm volatile("{\n.reg .pred p;\n.reg .b32 t, n;\nmov.b32 n, 0;\n"
               "L0:\nlop3.b32 t, %3, %7, 1, 0x80;\nsetp.eq.b32 p, t, 0;\nvote.sync.any.pred p, p, 0xffffffff;\n@!p bra.uni L1;\n"
               "ld.relaxed.gpu.global.v4.u32 {%0, %1, %2, %3}, [%8];\nld.relaxed.gpu.global.v4.u32 {%4, %5, %6, %7}, [%8+2048];\n"
               "add.u32 n, n, 1;\nsetp.lt.u32 p, n, 1000000;\n@p bra.uni L0;\ntrap;\nL1:\n}"
               : "+r"(a.x), "+r"(a.y), "+r"(a.z), "+r"(a.w), "+r"(c.x), "+r"(c.y), "+r"(c.z), "+r"(c.w) : "l"(p) : "memory");
}
__device__ __forceinline__ uint64_t box_a(uint32_t sb) { return mkdesc(sb + SM_RING + R_BOX, 256, 1024, 3); }
__device__ __forceinline__ uint64_t box_b(uint32_t sb) { return mkdesc(sb + SM_STAT, 64, 128, 0); }
__device__ __forceinline__ void mod_put(Scr* G, uint32_t sb, const float* a, int b, int j, uint32_t e1, int tid) {
  const uint32_t red = sb + SM_STAT + 1536;
  if ((tid & 3) == tid >> 6) sts64(red + 32 * ((tid >> 2) & 7) + 8 * (tid >> 5), __float_as_uint((tid & 32) ? a[1] : a[0]), __float_as_uint((tid & 32) ? a[3] : a[2]));
  bar_sync(j ? 4 : 5, 128);
  if (tid < 16) {
    const uint4 u = lds128(red + 32 * (tid & 7)), v = lds128(red + 32 * (tid & 7) + 16);
    asm volatile("" : "+r"(b));
    const int grp = mod_grp(b, j);
    const uint32_t one = (grp >= 40 && grp < 80) || (grp >= 160 && grp < 200) ? 0x3f803f80u : 0u;
    const float lo = __uint_as_float(u.x) + __uint_as_float(u.z) + __uint_as_float(v.x) + __uint_as_float(v.z);
    const float hi = __uint_as_float(u.y) + __uint_as_float(u.w) + __uint_as_float(v.y) + __uint_as_float(v.w);
    asm volatile("st.relaxed.gpu.global.u32 [%0], %1;" ::"l"(G->mv + 8 * grp + 256 * (tid & 8) + (tid & 7)),
                 "r"(((tid >> 3) ^ e1) & 1 ? 0 : ~hadd(pack2(lo, hi), one)) : "memory");
  }
}
__device__ __forceinline__ void mod_box(Scr* G, uint32_t sb, int b, int j, uint32_t e1, int tid) {
  float a[4];
  uint64_t da = box_a(sb), db = box_b(sb);
#pragma unroll
  for (int h = 0; h < 2; h++) {
    mbar_wait(sb + 8 * (B_BOX + 2 * j + h), 0);
    STAMPIF(tid == 0 && j == 0, 71 + h);
    wg_fence();
#pragma unroll
    for (int n = 5 * h; n < 5 * h + 5; n++) wgmma_ss_n8<1, 0>(a, da + 128 * n, db + 8 * n, n != 0);
    wg_commit();
  }
  wg_wait<0>();
#pragma unroll
  for (int i = 0; i < 4; i++) asm volatile("" : "+f"(a[i])::"memory");
  mod_put(G, sb, a, b, j, e1, tid);
}
__device__ __forceinline__ void a_check(uint32_t sa, const void* ga, uint32_t tag) {
  asm volatile("{\n.reg .pred p;\n.reg .b32 t, n, x, y, z;\n.reg .b64 g;\n"
               "ld.shared.b32 t, [%0];\nlop3.b32 t, t, %2, 1, 0x28;\nsetp.ne.b32 p, t, 0;\nvote.sync.any.pred p, p, 0xffffffff;\n@!p bra.uni L1;\nmov.b32 n, 0;\n"
               "L0:\nld.relaxed.gpu.global.b32 t, [%1];\nlop3.b32 t, t, %2, 1, 0x28;\nsetp.ne.b32 p, t, 0;\nvote.sync.any.pred p, p, 0xffffffff;\n@!p bra.uni L2;\n"
               "add.u32 n, n, 1;\nsetp.lt.u32 p, n, 1000000;\n@p bra.uni L0;\ntrap;\nL2:\n"
               "and.b64 g, %1, -32;\nand.b32 n, %0, -32;\n"
               "ld.relaxed.gpu.global.v4.b32 {t, x, y, z}, [g];\nst.shared.v4.b32 [n], {t, x, y, z};\n"
               "ld.relaxed.gpu.global.v4.b32 {t, x, y, z}, [g+16];\nst.shared.v4.b32 [n+16], {t, x, y, z};\n"
               "fence.proxy.async.shared::cta;\nbar.warp.sync 0xffffffff;\nL1:\n}" ::"r"(sa), "l"(ga), "r"(tag) : "memory");
}
__device__ __forceinline__ void z_wait(uint4& a, uint4& c, uint32_t* v, const void* p, const void* q, uint32_t e1) {
  asm volatile("{\n.reg .pred p;\n.reg .b32 t, n;\nmov.b32 n, 0;\n"
               "L0:\nlop3.b32 t, %3, %7, %14, 0x81;\nand.b32 t, t, 1;\nmin.u32 t, t, %8;\nmin.u32 t, t, %9;\nmin.u32 t, t, %10;\nmin.u32 t, t, %11;\n"
               "setp.eq.b32 p, t, 0;\nvote.sync.any.pred p, p, 0xffffffff;\n@!p bra.uni L1;\n"
               "ld.relaxed.gpu.global.v4.u32 {%0, %1, %2, %3}, [%12];\nld.relaxed.gpu.global.v4.u32 {%4, %5, %6, %7}, [%12+32768];\n"
               "ld.relaxed.gpu.global.u32 %8, [%13];\nld.relaxed.gpu.global.u32 %9, [%13+1280];\nld.relaxed.gpu.global.u32 %10, [%13+2560];\nld.relaxed.gpu.global.u32 %11, [%13+5120];\n"
               "add.u32 n, n, 1;\nsetp.lt.u32 p, n, 1000000;\n@p bra.uni L0;\ntrap;\nL1:\n}"
               : "+r"(a.x), "+r"(a.y), "+r"(a.z), "+r"(a.w), "+r"(c.x), "+r"(c.y), "+r"(c.z), "+r"(c.w), "+r"(v[0]), "+r"(v[1]), "+r"(v[2]), "+r"(v[3])
               : "l"(p), "l"(q), "r"(e1) : "memory");
}
__device__ __forceinline__ void load_x(const Params& P, uint32_t sb, int b, int h) {
  const uint32_t bar = sb + 8 * (B_X + h);
  mbar_expect(bar, 10240);
  tma5d(sb + SM_X + h * 10240, &P.mX, 0, 0, 0, 5 * h, tbase(b), bar);
}
__device__ __forceinline__ uint32_t x_addr(uint32_t sb, int w, int lane) {
  const int rho = 15 - (4 * (lane >> 3) + 2 * (lane & 1) + ((lane >> 1) & 1));
  return sb + SM_X + (w >> 1) * 2048 + rho * 128 + (((2 * (w & 1) + (lane & 4)) ^ (rho & 7)) << 4);
}
__device__ __forceinline__ void ln1_job(uint32_t sb, int tid) {
  const uint32_t xr = sb + SM_X + 16 * tid;
  float pv, s1 = 0.f, s2 = 0.f, s3 = 0.f;
#pragma unroll 1
  for (int h = 0; h < 2; h++) {
    mbar_wait(sb + 8 * (B_X + h), 0);
    STAMPIF(tid == 0, 25);
    pv = blo(lds32(xr & ~127u));
#pragma unroll
    for (int n = 0; n < 5; n++) {
      const uint4 v = lds128(xr + 10240 * h + 2048 * n);
      const uint32_t u[4] = {v.x, v.y, v.z, v.w};
#pragma unroll
      for (int j = 0; j < 4; j++) {
        const float a = blo(u[j]) - pv, c = bhi(u[j]) - pv;
        s1 += a + c; s2 += a * a; s3 += c * c;
      }
    }
  }
  s2 += s3;
#pragma unroll
  for (int o = 1; o < 8; o <<= 1) { s1 += __shfl_xor_sync(0xffffffffu, s1, o); s2 += __shfl_xor_sync(0xffffffffu, s2, o); }
  const float mu = s1 * (1.f / D_), var = fmaxf(s2 * (1.f / D_) - mu * mu, 0.f);
  const float rs = __frcp_rn(rbf(__fsqrt_rn(rbf(rbf(var) + 1e-5f))));
  const int i = 15 - (tid >> 3), j = tid & 7;
  if (j < 2) sts16(sb + SM_SMALL + SMALL_LN + 32 * j + 16 * (i & 1) + (i & 14), pack2(j ? rs : pv + mu, 0.f));
  bar_sync(5, 128);
  STAMPIF(tid == 0, 75);
}
__device__ __forceinline__ void load_box(const Params& P, uint32_t sb, int b, int cls) {
  const uint32_t bar = sb + 8 * (B_BOX + cls);
  mbar_expect(bar, 10240);
  tma3d(sb + SM_RING + R_BOX + 10240 * (cls & 1), &P.mWm, 16 * mod_grp(b, cls >> 1), 0, 5 * (cls & 1), bar);
}
__device__ __forceinline__ void load_ssm(const Params& P, uint32_t sb, int b, int r) {
  const uint32_t bar = sb + 8 * (B_S + r);
  mbar_expect(bar, 16 * 288);
  tma3d(chan_base(sb, r) + 128, &P.mS, 0, 0, 128 * r + b, bar);
}
__device__ __forceinline__ void k1_job(uint32_t sb, int r, int tid, uint32_t dv) {
  const uint32_t a0 = chan_base(sb, r) + 128 + 16 * tid + 32 * (tid >> 4);
  mbar_wait(sb + 8 * (B_S + r), 0);
#pragma unroll
  for (int n = 0; n < 2; n++) {
    const uint32_t a = a0 + 2304 * n;
    uint4 v = lds128(a);
    if (n == 0 && tid == 0) { v.x = hadd(v.x, dv); sts32(a, v.x); }
    const uint32_t pv = lds32(a - ((tid & 15) ? 4 : 36));
    sts128(a + K1OFF, make_uint4(__byte_perm(pv, v.x, 0x5432), __byte_perm(v.x, v.y, 0x5432), __byte_perm(v.y, v.z, 0x5432), __byte_perm(v.z, v.w, 0x5432)));
  }
}

__device__ __forceinline__ int out_blk(int s, int p) { const int t = p + (s >> 1); return t < 5 ? t : t - 5; }
__device__ __forceinline__ void l2_prefetch(const void* p, int bytes) { asm volatile("cp.async.bulk.prefetch.L2.global [%0], %1;" ::"l"(p), "r"(bytes) : "memory"); }
__device__ __forceinline__ void pf_line(const void* p) { asm volatile("prefetch.global.L2 [%0];" ::"l"(p) : "memory"); }
__device__ __forceinline__ int role(int bx) {
  const int c = bx >> 1, d = c - 36, q = (d * 37) >> 8, k = d - 7 * q;
  const int rank = c < 4 ? 12 + c : c < 36 ? ((c - 4) & 7) * 8 + ((c - 4) >> 3) : (k ? k + 1 : 0) * 8 + 4 + q;
  return 8 * (rank & 15) + 2 * (rank >> 4) + (bx & 1);
}
enum { K_KV, K_SSM, K_BOX, K_PW, K_PD, K_PKV, K_PSSM, K_PBOX, K_W, K_X, K_ST, K_END = 15 };
#define E(t, bar, kind, r) ((t) << 16 | (bar) << 8 | (kind) << 4 | (r))
#define SCHED E(2800, 255, K_BOX, 0), E(0, 255, K_BOX, 1), E(3700, 255, K_KV, 2), E(4400, 255, K_SSM, 2), E(4800, 255, K_KV, 3), E(5500, 255, K_X, 0), \
              E(6400, 255, K_KV, 4), E(7100, 255, K_X, 1), E(7900, 255, K_SSM, 3), E(8300, 255, K_SSM, 4), E(8600, 255, K_BOX, 2), E(9500, 255, K_PW, 0), \
              E(10100, 255, K_BOX, 3)
#define XPF 2
#define XBOTH 0
#define AUXP 0xfedcb0217ull
constexpr int aux_last(int mask) { int r = 0; for (uint64_t p = AUXP; p; p >>= 4) if ((mask >> (p & 15)) & 1) r = p & 15; return r; }
constexpr int kLastKv = aux_last(0x0e);
#define XI 8
#define XW 0
#define PWM 0x3c
#define STM 0x7c0
#define PDM 0x3800
#define KV4C 3
#define CVT 1
#define UPOS 4
#define UD 1000
#define UD0 0
#define UD1 0
#define ZP 0
#define ITW 0
#define SJ(h) (3 * (h))
constexpr uint32_t kSched[] = {SCHED, E(0, 255, K_END, 0)};
struct In { const bf16 *k, *v, *sk, *Wg, *Wu, *Wd, *ss; };
__device__ __forceinline__ void load_w(const Params& P, uint32_t sb, int s, int it) {
  const int st = it % 5;
  mbar_wait(sb + 8 * (B_E1 + st), (it / 5) & 1);
  const uint32_t a = sb + SM_RING + st * 32768 + 8192, fb = sb + 8 * (B_F1 + st);
  mbar_expect(fb, 24576);
#pragma unroll
  for (int j = 0; j < 3; j++) {
    tma2d(a + 8192 * j, &P.mG, 192 * s + 64 * j, 32 * it, fb);
    tma2d(a + 8192 * j + 4096, &P.mU, 192 * s + 64 * j, 32 * it, fb);
  }
}

template <int I> __device__ __forceinline__ int sched_run(const Params& P, const In& in, uint32_t sb, int b, int lane, uint32_t t_0) {
  constexpr uint32_t e = kSched[I];
  constexpr int kind = (e >> 4) & 15, r = e & 15, bar = (e >> 8) & 255;
  if constexpr (kind == K_END) return 0;
  else {
    if constexpr ((e >> 16) != 0) while (clk() - t_0 < (e >> 16));
    if (bar != 255) mbar_wait(sb + 8 * bar, 0);
    if (kind == K_BOX && r == 2) mbar_wait(sb + 8 * B_BD, 0);
    if (kind == K_PKV) {
      const bf16* kvp = (lane < 16 ? in.k : in.v) + (16 * b + (lane & 15)) * D_ + 128 * r;
      pf_line(kvp); pf_line(kvp + 64);
    } else {
      if (elect()) {
        if (kind == K_KV) load_kv(P, in.sk, sb, b, r);
        if (kind == K_X) load_x(P, sb, b, r);
        if (kind == K_SSM) load_ssm(P, sb, b, r);
        if (kind == K_BOX && (r > 1 || mod_first(b))) load_box(P, sb, b, r);
        if (kind == K_PW) { l2_prefetch(in.Wg + (128 * r + b) * F_, 2 * F_); l2_prefetch(in.Wu + (128 * r + b) * F_, 2 * F_); }
        if (kind == K_PSSM) l2_prefetch(in.ss + (128 * r + b) * S_, 4096);
      }
      __syncwarp();
    }
    return sched_run<I + 1>(P, in, sb, b, lane, t_0) + (kind == K_PW);
  }
}

__global__ void __launch_bounds__(512, 1) fused_kernel(const bf16* __restrict__ gk, const bf16* __restrict__ gv, const bf16* __restrict__ gsk,
                                                       const bf16* __restrict__ gD, const bf16* __restrict__ gc, Scr* G, const bf16* gWg, const bf16* gWu,
                                                       const bf16* gWd, bf16* gout, const bf16* gss, const __grid_constant__ Params P) {
  extern __shared__ __align__(1024) char smem_raw[];
  const uint32_t sb = smem_u32(smem_raw), ring = sb + SM_RING;
  const int b = role(blockIdx.x), m = b >> 3, s = b & 7;
  const uint32_t t_0 = clk();
  const int wg = __shfl_sync(0xffffffffu, threadIdx.x >> 7, 0);
  const int tid = threadIdx.x & 127, lane = tid & 31;
  const int w = __shfl_sync(0xffffffffu, tid >> 5, 0);
  if (wg < 2) {
    kv_load(gk, gv, gsk, sb, b, wg, tid);
  } else {
    if (wg == 2) {
      if (tid < 40) {
        int c = tid & 7;
        sts128(chan_base(sb, tid >> 3) + (c < 2 ? 80 + c * K1OFF : KSZ + 4096 + (c - 2) * 16), make_uint4(0, 0, 0, 0));
      }
    }
    if (elect()) {
      const int j = 4 * (3 - wg) + w - 1;
      if (j < 4) asm volatile("prefetch.tensormap [%0];" ::"l"(&P.mX + j) : "memory");
      if (j < 0) {
#pragma unroll
        for (int i = 0; i < 5; i++) mbar_init(sb + 8 * (B_S + i), 1);
        fence_async_s();
        if (XPF > 0) load_ssm(P, sb, b, 0);
        if (XPF > 1) load_ssm(P, sb, b, 1);
      } else {
        const int c = j < 3 ? 1 : j < 5 ? 2 : 4;
#pragma unroll
        for (int i = 0; i < 16; i++) mbar_init(sb + 128 * j + 8 * i, i < 10 || j < 6 ? c : i < 12 ? 128 : 1);
      }
    }
    fence_async_s();
  }
  __syncthreads();
  STAMPIF(threadIdx.x == 0, 55);

  if (wg < 2) {
    cp_arrive(sb + 8 * (B_B + wg));
    asm volatile("setmaxnreg.inc.sync.aligned.u32 224;");
    STAMPIF(threadIdx.x == 0, 82);
    const int g = lane >> 2, q = lane & 3;
    if (wg == 1) bar_arrive(1, 256);
    const uint32_t dv = *(const uint16_t*)(gD + 128 * wg + b);
    {
      const int b0 = (g >> 1) & 1, b1 = g >> 2, u = q + 4 * b0 - w;
      const uint32_t fo = 128 + (g & 1) * K1OFF + 288 * b1 + 4 * u, fo0 = fo - (u < 0 ? 32 : 0);
      const bool wrap = b0 && q == 0;
      const int src1 = b0 ? ((lane & 20) | ((q - 1) & 3)) : (lane | 8);
      const uint2* pu = (const uint2*)(G->kvT + (128 * wg + b) * S_ + 8 * tid);
      uint4 u0 = make_uint4(0, 0, 0, 0), u1 = u0;
      if (UPOS & 1) { u0 = ld_tag2(pu); u1 = ld_tag2(pu + 256); }
#pragma unroll 1
      for (int ch = wg; ch < 5; ch += 2) {
        const uint32_t base = chan_base(sb, ch);
        if (ch < 2 || ch == KV4C) {
          kv_job(G, sb, b, ch < 2 ? ch : 4, tid);
          STAMPIF(tid == 0, ch < 2 ? 1 + ch : 24);
        }
        if (ch < 2) {
          k1_job(sb, wg, tid, dv);
          bar_sync(3 + wg, 128);
        } else {
          mbar_wait(sb + 8 * (B_K + ch - 2), 0);
          if (UPOS & 4) { u0 = ld_tag2(pu); u1 = ld_tag2(pu + 256); }
          mbar_wait(sb + 8 * (B_S + ch), 0);
        }
        const uint32_t fa = base + fo, fa0 = base + fo0;
        uint32_t af[16][4];
#pragma unroll
        for (int j = 0; j < 16; j++) {
          const int o = 64 * (j & 1) + 576 * (j >> 1);
          af[j][0] = lds32(((j & 1) ? fa : fa0) + o); af[j][1] = lds32(fa + o + 128); af[j][2] = lds32(fa + o + 32); af[j][3] = lds32(fa + o + 160);
        }
        STAMPIF(tid == 0, 40 + ch);
        mbar_wait(sb + 8 * B_E0, 0);
        const uint32_t e1 = epoch(sb);
        if (UD0 && ch < 2) spin(t_0, UD0 + UD1 * wg);
        u_wait(u0, u1, pu);
        sts128(base + KSZ + 16 * tid, u0);
        sts128(base + KSZ + 2048 + 16 * tid, u1);
        fence_async_s();
        float acc[128];
        const uint64_t db = mkdesc(base + KSZ, 32, 128, 0);
        bar_sync(1 + wg, 256);
        wg_fence();
        wgmma_rs_n64<0>(acc + 96, af[0], db + 192, 0);
        wgmma_rs_n192<0>(acc, af[0], db, 0);
        wgmma_rs_n64<0>(acc + 96, af[1], db + 196, 1);
        wgmma_rs_n192<0>(acc, af[1], db + 4, 1);
        wgmma_rs_n32<0>(acc + 96, af[2], db + 224, 1);
        wgmma_rs_n192<0>(acc, af[2], db + 32, 1);
        wgmma_rs_n32<0>(acc + 96, af[3], db + 228, 1);
        wgmma_rs_n192<0>(acc, af[3], db + 36, 1);
        wgmma_rs_n192<0>(acc, af[4], db + 64, 1);
        wgmma_rs_n192<0>(acc, af[5], db + 68, 1);
        wgmma_rs_n160<0>(acc, af[6], db + 96, 1);
        wgmma_rs_n160<0>(acc, af[7], db + 100, 1);
        if (CVT == 2) wg_commit();
        wgmma_rs_n128<0>(acc, af[8], db + 128, 1);
        wgmma_rs_n128<0>(acc, af[9], db + 132, 1);
        if (CVT == 1) wg_commit();
        wgmma_rs_n96<0>(acc, af[10], db + 160, 1);
        wgmma_rs_n96<0>(acc, af[11], db + 164, 1);
        if (CVT == 0) bar_arrive(2 - wg, 256);
        wgmma_rs_n64<0>(acc, af[12], db + 192, 1);
        wgmma_rs_n64<0>(acc, af[13], db + 196, 1);
        wgmma_rs_n32<0>(acc, af[14], db + 224, 1);
        wgmma_rs_n32<0>(acc, af[15], db + 228, 1);
        wg_commit();
        if (ZP == 0) {
          stg128((void*)pu, make_uint4(0, 0, 0, 0));
          stg128((void*)(pu + 256), make_uint4(0, 0, 0, 0));
        }
        if (tid < 2 && ch == (wg == (KV4C & 1) && KV4C < 5 ? KV4C : wg)) mbar_arrive(sb + 8 * (B_E1 + tid));
        if (CVT) { wg_wait<1>(); if (ch < 4) bar_arrive(2 - wg, 256); }
        STAMPIF(tid == 0, 3 + ch);
        if (ZP == 1) {
          stg128((void*)pu, make_uint4(0, 0, 0, 0));
          stg128((void*)(pu + 256), make_uint4(0, 0, 0, 0));
        }
        wg_wait<0>();
#pragma unroll
        for (int i = 0; i < 128; i++) asm volatile("" : "+f"(acc[i])::"memory");
        bar_sync(3 + wg, 128);
        if (tid <= (ch >> 2)) mbar_arrive(sb + 8 * (B_E1 + 2 + (ch >> 1)));
        float S0[33], T[34];
#pragma unroll
        for (int i = 0; i < 31; i++) S0[i] = acc[4 * i] + acc[4 * i + 6];
        S0[31] = acc[124]; S0[32] = 0.f;
#pragma unroll
        for (int i = 0; i < 32; i++) {
          float s1 = i < 31 ? acc[4 * i + 1] + acc[4 * i + 7] : acc[125];
          T[i] = (wrap ? S0[i + 1] : S0[i]) + __shfl_sync(0xffffffffu, s1, src1);
        }
        T[32] = 0.f; T[33] = 0.f;
        uint4* pz = (uint4*)(G->zT + (128 * ch + b) * S_) + ((tid & 120) | (2 * q) | (g & 1));
#pragma unroll
        for (int h = 0; h < 2; h++) {
          float y[8];
#pragma unroll
          for (int mu = 0; mu < 8; mu++) y[mu] = (b1 ? T[4 * mu + 4 + h] : T[4 * mu + h]) + __shfl_xor_sync(0xffffffffu, T[4 * mu + 2 + h], 16);
          pz[128 * h] = make_uint4(pack2(y[0], y[1]), pack2(y[2], y[3]), pack2(y[4], y[5]), tagged(pack2(y[6], y[7]), e1));
        }
        __syncwarp();
        if (lane == 0) mbar_arrive(sb + 8 * (B_Z + ch));
        if (ZP == 2) {
          stg128((void*)pu, make_uint4(0, 0, 0, 0));
          stg128((void*)(pu + 256), make_uint4(0, 0, 0, 0));
        }
        pu += 128 * S_ / 2;
        STAMPIF(tid == 0, 8 + ch);
      }
    }
    uint32_t hh[96];
    {
      float ga[192];
      float* ua = ga + 96;
      const uint64_t da0 = mkdesc(ring + wg * 2048, 512, 256, 3), db0 = mkdesc(ring + 8192, 4096, 1024, 1);
      int st = 0, ph = 0;
      mbar_wait(sb + 8 * B_BD, 0);
      const uint32_t e1 = epoch(sb);
      if (wg) {
        mod_box(G, sb, b, 1, e1, tid);
        __syncwarp();
        if (lane == 0) mbar_arrive(sb + 8 * (B_BD + 1));
        STAMPIF(tid == 0, 73);
      }
      const bool cs = b < 96;
      const int x0 = wg ? XI : 99,
                x1 = x0 + (cs ? 4 : 2), xs = cs ? 4 : 8;
      uint64_t xa = cs ? mkdesc(sb + SM_EXT, 4096, 1024, 1) : box_a(sb), xb = cs ? mkdesc(sb + SM_CB, 32, 128, 0) : box_b(sb);
      uint64_t ya = xa + (cs ? (SM_RING + R_X - SM_EXT) / 16 : 256), yb = xb + 16;
      float bx[4];
#pragma unroll 1
      for (int it = 0; it < 20; it++) {
        if (it == x0) {
          mbar_wait(sb + 8 * (cs ? B_F : B_BOX + 4), 0);
          mbar_wait(sb + 8 * (cs ? B_ST0 : B_BOX + 5), 0);
          STAMPIF(tid == 0, 76);
        }
        if (it == x1 + XW) {
          wg_wait<XW>();
#pragma unroll
          for (int i = 0; i < 4; i++) asm volatile("" : "+f"(bx[i])::"memory");
          if (!cs) mod_put(G, sb, bx, b, 2, e1, tid);
          else {
            const int row = (m < 6 ? 0 : 4) + q;
            uint16_t* dst = (uint16_t*)G->cimg + s * 3072 + (m % 6) * 512 + row * 64 + g;
#pragma unroll
            for (int j = 0; j < 2; j++) {
              const float c1 = __shfl_sync(0xffffffffu, bx[2 * j], lane & 28), c2 = __shfl_sync(0xffffffffu, bx[2 * j + 1], lane & 28);
              const float t = (lane & 2) ? c2 : c1, hi = rbf(t);
              dst[((2 * w + j) ^ row) << 3] = (uint16_t)pack2((lane & 1) ? t - hi : hi, 0.f);
            }
          }
          __syncwarp();
          if (lane == 0) mbar_arrive(sb + 8 * (B_BD + 2));
          STAMPIF(tid == 0, 77);
        }
        mbar_wait(sb + 8 * (B_F1 + st), ph);
        STAMPIF(tid == 0 && it == 0, 13 + wg);
        if (ITW == 1) STAMPIF(tid == 0 && it >= 10, 90 + it + 10 * wg);
        else if (ITW == 2) STAMPIF(tid == 0 && it < 10, 100 + it + 10 * wg);
        else STAMPIF(threadIdx.x == ITW, 100 + it);
        const uint64_t da = da0 + st * 2048, db = db0 + st * 2048;
        if (it >= x0 && it < x1) {
          wg_fence();
          wgmma_ss_n8<1, 0>(bx, xa, xb, it != x0);
          wgmma_ss_n192<1, 1>(ga, da, db, 1);
          wgmma_ss_n8<1, 0>(bx, ya, yb, 1);
          wgmma_ss_n192<1, 1>(ua, da, db + 768, 1);
          wgmma_ss_n8<1, 0>(bx, ya + 128, yb + xs, 1);
          wgmma_ss_n192<1, 1>(ga, da + 256, db + 128, 1);
          wgmma_ss_n8<1, 0>(bx, ya + 256, yb + 2 * xs, 1);
          wgmma_ss_n192<1, 1>(ua, da + 256, db + 128 + 768, 1);
          wgmma_ss_n8<1, 0>(bx, ya + 384, yb + 3 * xs, 1);
          wg_commit();
          xa += 128; xb += xs; ya += 512; yb += 4 * xs;
        } else {
          wg_fence();
          wgmma_ss_n192<1, 1>(ga, da, db, it != 0);
          wgmma_ss_n192<1, 1>(ua, da, db + 768, it != 0);
          wgmma_ss_n192<1, 1>(ga, da + 256, db + 128, 1);
          wgmma_ss_n192<1, 1>(ua, da + 256, db + 128 + 768, 1);
          wg_commit();
        }
        wg_wait<1>();
        if (it > 0 && tid == 0) mbar_arrive(sb + 8 * (B_E1 + (st == 0 ? 4 : st - 1)));
        if (++st == 5) { st = 0; ph ^= 1; }
      }
      STAMPIF(threadIdx.x == 0, 61);
      if (tid == 0) {
        mbar_wait(sb + 8 * (B_E1 + 5), 0);
        mbar_arrive_remote(mapa(sb + 8 * (B_PEER + 2 * wg), (b & 1) ^ 1));
      }
      mbar_wait(sb + 8 * B_EXT, 0);
      mbar_wait(sb + 8 * B_ST2, 0);
      const uint64_t de = mkdesc(sb + SM_EXT, 1024, 0, 1), ds = mkdesc(sb + SM_STAT + wg * 1024, 0, 128, 0);
      wg_fence();
      wgmma_ss_n192<0, 1>(ga, ds, de, 1);
      wgmma_ss_n192<0, 1>(ua, ds, de + 192, 1);
      wg_commit();
      wg_wait<1>();
      if (tid == 0) {
        mbar_arrive(sb + 8 * (B_E1 + 4));
        mbar_arrive_remote(mapa(sb + 8 * (B_PEER + 2 * wg + 1), (b & 1) ^ 1));
      }
      wg_wait<0>();
#pragma unroll
      for (int i = 0; i < 192; i++) asm volatile("" : "+f"(ga[i])::"memory");
      STAMPIF(tid == 0, 15 + wg);
#pragma unroll
      for (int i = 0; i < 48; i++) {
        const int j = 64 * (i >> 4) + 2 * (i & 15);
        hh[i] = pack2(ga[j] * ga[j + 32], ga[j + 1] * ga[j + 33]);
        asm volatile("" : "+r"(hh[i])::"memory");
      }
    }
    {
      float acc[64], rs[2] = {};
      uint4 pf[4], gb = {};
      uint32_t ln, os, ol, og;
      const char *po, *pq;
      const uint32_t la = ring + wg * 2048 + tid * 16, ra = mapa(la, (b & 1) ^ 1), rb = mapa(sb + 8 * (B_RECV + 2 * wg), (b & 1) ^ 1);
      auto stage = [&](const float* a, int i) {
        const uint32_t v[4] = {pack2(a[8 * i] * rs[0], a[8 * i + 1] * rs[0]), pack2(a[8 * i + 2] * rs[1], a[8 * i + 3] * rs[1]),
                               pack2(a[8 * i + 4] * rs[0], a[8 * i + 5] * rs[0]), pack2(a[8 * i + 6] * rs[1], a[8 * i + 7] * rs[1])};
        stsm4(os + 32 * i, v);
      };
      auto fetch = [&](int p) {
        __syncwarp();
#pragma unroll
        for (int i = 0; i < 4; i++) pf[i] = lds128(ol + 576 * i);
      };
      auto next = [&](int p) {
        gb = lds128(og + 256 * out_blk(s, p));
        pq = po + 128 * out_blk(s, p);
        asm volatile("" : "+l"(pq));
      };
      auto add = [&](int p, int i) {
        asm volatile("red.relaxed.gpu.global.add.noftz.v4.bf16x2 [%0], {%1, %2, %3, %4};" ::"l"(pq - (i & 1) * 2048 * D_ - (i >> 1) * 2 * D_),
                     "r"(hmul(pf[i].x, gb.x)), "r"(hmul(pf[i].y, gb.y)), "r"(hmul(pf[i].z, gb.z)), "r"(hmul(pf[i].w, gb.w)) : "memory");
      };
#pragma unroll
      for (int h = 0; h < 20; h++) {
        const int gr = h >> 1, pe = gr < 4 ? gr >> 1 : gr & 1, ac = (gr < 4 ? gr : gr >> 1) & 1;
        const int ep = h == 7 || h == 8 ? 0 : h > 8 && (h & 3) == 1 || h > 8 && (h & 3) == 2 ? (h >> 2) - 1 : -1;
        if (!(h & 1)) mbar_wait(sb + 8 * (B_FB + gr), 0);
        if (gr == 2) {
          mbar_wait(sb + 8 * (B_RECV + 2 * wg + (h & 1)), 0);
#pragma unroll
          for (int j = 6 * (h & 1); j < 6 * (h & 1) + 6; j++) {
            const uint4 v = lds128(la + (j < 2 ? 5 : (j >> 1) - 1) * 32768 + (j & 1) * 4096);
            hh[48 + 4 * j] = v.x; hh[49 + 4 * j] = v.y; hh[50 + 4 * j] = v.z; hh[51 + 4 * j] = v.w;
          }
        }
        if (h == 6) {
          mbar_wait(sb + 8 * B_X1, 0);
          mbar_wait(sb + 8 * B_GB, 0);
          asm volatile("mov.u32 %0, %%laneid;" : "=r"(ln));
#pragma unroll
          for (int i = 0; i < 2; i++) rs[i] = blo(lds32(sb + SM_STAT + (4 * wg + w) * 256 + (ln & 28) * 4 + 128 * i + 4));
        }
        STAMPIF(tid == 0 && h % 4 == 0 && h < 16, (wg ? 89 : 121) + h / 4);
        STAMPIF(tid == 0 && h == 16, wg ? 97 : 96);
        const uint64_t db = mkdesc(ring + ((gr + 5) % 6) * 32768 + 8192, 16 * gr + 16, 1024, 1);
        wg_fence();
#pragma unroll
        for (int j = 0; j < 6; j++) {
          const int k = 6 * (h & 1) + j;
          wgmma_rs_n64<1>(acc + 32 * ac, hh + 48 * pe + 4 * k, db + 128 * k, pe || k);
          if (ep >= 0 && (h & 1)) {
            if (j < 4) stage(acc + 32 * (1 - ac), j);
            if (j == 4) fetch(ep);
          }
          if (ep >= 0 && !(h & 1) && j > 0 && j < 5) add(ep, j - 1);
          if (ep >= 0 && !(h & 1) && j == 5) next(ep + 1);
        }
        wg_commit();
        if (h < 4) {
#pragma unroll
          for (int j = SJ(h); j < SJ(h + 1); j++) {
            if (j == 0 || j == 10) mbar_wait(sb + 8 * (B_PEER + 2 * wg + j / 10), 0);
            st_async4(ra + (j < 2 ? 5 : (j >> 1) - 1) * 32768 + (j & 1) * 4096, hh + 4 * j, rb + 8 * (j / 6));
          }
          STAMPIF(tid == 0 && h == 3, 81);
        }
        if (h == 6) {
#pragma unroll
          for (int i = 0; i < 2; i++) rs[i] = __fdividef(0.25f, rs[i] * rs[i]);
          const uint32_t ob = sb + SM_X + (4 * wg + w) * 2304;
          os = ob + (ln & 15) * 144 + (ln & 16); ol = ob + (ln >> 3) * 16 + ln * 16;
          po = (const char*)(gout + (1793 + 2 * tbase(8 * m + 4 * wg + w)) * D_) + (int)(640 * (s & 1) + 16 * ln - (ln >> 3) * (512 * D_ + 128));
          og = sb + SM_CB + 32 * (ln & 7);
          asm volatile("" : "+r"(os), "+r"(ol), "+r"(og), "+l"(po));
          next(0);
        }
        if (h == 2 || h == 4 || h == 6 || h == 8 || h == 12 || h == 16) {
          wg_wait<1>();
          if (h < 12 && tid == 0) mbar_arrive(sb + 8 * (B_EB + gr - 1));
          if (h >= 6) {
#pragma unroll
            for (int j = 0; j < 32; j++) asm volatile("" : "+f"(acc[32 * (1 - ac) + j])::"memory");
          }
        }
      }
      STAMPIF(tid == 0, wg ? 95 : 93);
      wg_wait<0>();
#pragma unroll
      for (int i = 0; i < 32; i++) asm volatile("" : "+f"(acc[i])::"memory");
      STAMPIF(tid == 0, wg ? 50 : 18);
#pragma unroll
      for (int i = 0; i < 4; i++) stage(acc, i);
      fetch(4);
#pragma unroll
      for (int i = 0; i < 4; i++) add(4, i);
    }
  } else if (wg == 2) {
    asm volatile("setmaxnreg.dec.sync.aligned.u32 40;");
    const uint32_t e1 = (rdback(G->flag + 8 * m + 4) >> 5) + 1;
    if (tid < 80) {
      uint4 c = ((const uint4*)gc)[tid];
#pragma unroll 1
      for (int i = 0; i < 4; i++) {
        const float lo = blo(c.x), hi = bhi(c.x);
        sts32(sb + SM_STAT + 16 * tid + 4 * i, pack2(__fdividef(lo, 1.f + __expf(-lo)), __fdividef(hi, 1.f + __expf(-hi))));
        c.x = c.y; c.y = c.z; c.z = c.w;
      }
    }
    if (tid == 0) { sts32(sb + SM_SMALL + SMALL_E, e1); mbar_arrive(sb + 8 * B_E0); }
    fence_async_s();
    bar_sync(5, 128);
    int tl = tid;
#pragma unroll 1
    for (uint64_t pr = AUXP; pr; pr >>= 4) {
      asm volatile("" : "+r"(tl));
      const int op = pr & 15, tid = tl, lane = tid & 31;
      if (op == 0) {
        ln1_job(sb, tid);
      } else if (op < 4) {
        kv_job(G, sb, b, op + 1, tid);
        STAMPIF(tid == 0, 21 + op);
      } else if (op < 11) {
        if (mod_first(b)) mod_box(G, sb, b, 0, e1, tid);
        __syncwarp();
        if (lane == 0) mbar_arrive(sb + 8 * B_BD);
        STAMPIF(tid == 0, 27);
      } else {
        const int r = op - 11, cg = 8 * r + 4 * (w >> 1) + (lane & 2) + (w & 1), g = lane >> 2;
        const uint2* pz = (const uint2*)(G->zT + (16 * cg + g) * S_ + 16 * b + 8 * (lane & 1));
        const uint32_t* pc = G->mv + 2048 * (e1 & 1) + 8 * cg + g;
        const uint32_t la = sb + SM_SMALL + SMALL_LN + 16 * (lane & 1);
        uint32_t xa = x_addr(sb, w, lane) + 4096 * r, ao = ((40 * m + cg) * 8 + s) * 32 + 2 * g + ((lane ^ (lane >> 4)) & 1), xn[8], xv[8];
        const uint4 m4 = lds128(la), s4 = lds128(la + 32);
        const uint32_t m_[4] = {m4.x, m4.y, m4.z, m4.w}, s_[4] = {s4.x, s4.y, s4.z, s4.w};
        ldsm4t(xv, xa);
        ldsm4t(xv + 4, xa ^ 16);
#pragma unroll
        for (int j = 0; j < 8; j++) {
          xn[j] = hmul(hsub(xv[j], m_[j & 3]), s_[j & 3]);
          asm volatile("" : "+r"(xn[j]));
        }
        asm volatile("" : "+r"(ao));
        mbar_wait(sb + 8 * (B_BD + (r > 1)), 0);
        mbar_wait(sb + 8 * (B_Z + r), 0);
        STAMPIF(tid == 0 && r == 0, 28);
        uint4 z[2] = {ld_tag2(pz), ld_tag2(pz + 4096)};
        uint32_t c[4] = {rdback(pc), rdback(pc + 320), rdback(pc + 640), rdback(pc + 1280)};
        z_wait(z[0], z[1], c, pz, pc, e1);
        asm volatile("" : "+r"(xa));
        STAMPIF(tid == 0 && r == 0, 83);
        uint4* pa = (uint4*)G->AT + ao;
#pragma unroll
        for (int j = 0; j < 4; j++) c[j] = ~c[j];
#pragma unroll
        for (int n = 0; n < 2; n++) {
          const uint32_t z_[4] = {z[n].x, z[n].y, z[n].z, z[n].w}, sel = n ? 0x3232 : 0x1010;
          const uint32_t sa = __byte_perm(c[0], 0, sel), ca1 = __byte_perm(c[1], 0, sel), ga = __byte_perm(c[2], 0, sel), cb1 = __byte_perm(c[3], 0, sel);
          uint32_t o[4], a[4];
#pragma unroll
          for (int j = 0; j < 4; j++) {
            o[j] = hfma(ga, hmul(hfma(xn[4 * n + j], ca1, sa), z_[j]), xv[4 * n + j]);
            a[j] = hmul(o[j], cb1);
          }
          a[2 * n + 1] = tagged(a[2 * n + 1], e1);
          pa[16 * n] = make_uint4(a[0], a[1], a[2], a[3]);
          if (n) { __syncwarp(); if (elect()) flag_add(G, 8 * m + r); }
          stsm4t(xa ^ (16 * n), o);
        }
        __syncwarp();
        {
          int lane;
          asm volatile("mov.u32 %0, %%laneid;" : "=r"(lane));
          const int c = 2 * (w & 1) + (lane & 1) + 2 * (lane & 2), g = lane >> 2;
          const uint32_t a = sb + SM_X + 4096 * r + (w >> 1) * 2048 + g * 128 + ((c ^ g) << 4);
          const uint4 v0 = lds128(a), v1 = lds128(a + 1024);
          char* po = (char*)gout + (2 * tbase(b) + 128 * (g & 6) + (g & 1)) * 2 * D_ + 256 * r + 64 * (w & 2) + 16 * c;
          stg128(po, v0);
          stg128(po + 2048 * D_, v1);
        }
        __syncwarp();
        if (elect()) mbar_arrive(sb + 8 * (B_EW + r));
        STAMPIF(tid == 0, 29 + r);
      }
      if (op == kLastKv) { __syncwarp(); if (elect()) mbar_arrive(sb + 8 * B_KVS); }
    }
    {
      const uint4 m4 = lds128(sb + SM_SMALL + SMALL_LN + 16 * (lane & 1));
      const uint32_t m_[4] = {m4.x, m4.y, m4.z, m4.w}, xa = x_addr(sb, w, lane);
      float a[16];
#pragma unroll
      for (int i = 0; i < 16; i++) a[i] = 0.f;
#pragma unroll 2
      for (int n = 0; n < 10; n++) {
        uint32_t x_[4];
        ldsm4t(x_, (xa ^ (16 * (n & 1))) + 2048 * (n & 14));
#pragma unroll
        for (int i = 0; i < 4; i++) {
          const float d0 = blo(x_[i]) - blo(m_[i]), d1 = bhi(x_[i]) - bhi(m_[i]);
          a[4 * i] += d0; a[4 * i + 1] += d0 * d0; a[4 * i + 2] += d1; a[4 * i + 3] += d1 * d1;
        }
      }
      STAMPIF(lane == 0, 67 + (w & 1) + 11 * (w >> 1));
      bfly<16>(a, 16, lane & 16); bfly<8>(a, 8, lane & 8); bfly<4>(a, 4, lane & 4); bfly<2>(a, 2, lane & 2);
      if (lane == 0) mbar_arrive(sb + 8 * B_XF);
      STAMPIF(tid == 0, 88);
      sts32(sb + SM_SMALL + SMALL_RED + 16 * lane + 4 * w, __float_as_uint(a[0]));
      bar_sync(5, 128);
      if (w == 0) {
        const uint4 v = lds128(sb + SM_SMALL + SMALL_RED + 16 * lane);
        const float s1 = __uint_as_float(v.x) + __uint_as_float(v.y) + __uint_as_float(v.z) + __uint_as_float(v.w), s2 = __shfl_xor_sync(0xffffffffu, s1, 2);
        const int p = 8 * (lane & 1) + (lane >> 2);
        const float pv = blo(lds32(sb + SM_SMALL + SMALL_LN + 4 * (p >> 1)) >> (16 * (p & 1)));
        const float mu = s1 * (1.f / D_), var = fmaxf(s2 * (1.f / D_) - mu * mu, 0.f);
        const float sd = rbf(__fsqrt_rn(rbf(rbf(var) + 1e-5f)));
        if (!(lane & 2)) st_tag(G->st2 + 16 * b + p, pack2(-0.5f * (pv + mu), 0.5f * sd), e1);
      }
      STAMPIF(tid == 0, 87);
    }
    {
      uint2 v;
      spin(clk(), SD);
      mbar_wait(sb + 8 * (B_BD + 2), 0);
#pragma unroll 1
      for (int i = 0;; i++) {
        v = ld_tag(G->st2 + 128 * m + tid);
        if (__all_sync(0xffffffffu, v.y == e1)) break;
        if (i > (1 << 20)) __trap();
      }
      const uint32_t hm = __byte_perm(v.x, 0, 0x1010), hs = __byte_perm(v.x, 0, 0x3232);
      sts128(sb + SM_STAT + 16 * tid, make_uint4(hm, hs, hm, hs));
      fence_async_s();
      __syncwarp();
      if (lane == 0) mbar_arrive(sb + 8 * B_ST2);
      STAMPIF(tid == 0, 21);
    }
  } else {
    asm volatile("setmaxnreg.dec.sync.aligned.u32 24;");
    if (w != 0) {
    if (w == 2 && lane < 3) asm volatile("prefetch.tensormap [%0];" ::"l"(&P.mG + lane) : "memory");
    if (w & 1) {
#pragma unroll 1
      for (int j = 4; j < 10; j++) {
        k1_job(sb, j >> 1, 64 * (j & 1) + 16 * (w & 2) + lane, *(const uint16_t*)(gD + 64 * (j & 14) + b));
        if (UD && w == 1 && (j & 1)) {
          mbar_wait(sb + 8 * (B_KJ + (j >> 1)), 0);
          const uint32_t t = lds32(sb + SM_SMALL + SMALL_TS + 4 * (j >> 1));
          while (clk() - t < UD);
        }
        __syncwarp();
        if (lane == 0) mbar_arrive(sb + 8 * (B_K + (j >> 1) - 2));
      }
      STAMPIF(tid == 32, 74);
    }
    if (w == 1) {
     {
      mbar_wait(sb + 8 * B_KVS, 0);
      const uint32_t e1 = epoch(sb);
      if (elect()) {
        mbar_wait(sb + 8 * B_EW, 0);
#pragma unroll 1
        for (int it = 0; it < 20; it++) {
          int st = it % 5;
          if ((it & 3) == 0) { flag_wait(G, 8 * m + (it >> 2), e1 * 32); STAMP(45 + (it >> 2)); }
          mbar_wait(sb + 8 * (B_E1 + st), (it / 5) & 1);
          uint32_t fb = sb + 8 * (B_A + st);
          mbar_expect(fb, 8192);
          bulk_g2s(ring + st * 32768, G->AT + (20 * m + it) * 4096, 8192, fb);
        }
        mbar_wait(sb + 8 * B_XF, 0);
        flag_wait(G, 8 * m + FL_X, e1 * 8);
        mbar_arrive(sb + 8 * B_X1);
        STAMP(86);
      }
     }
    } else if (w == 2) {
      if (lane < 4) mbar_expect(sb + 8 * (B_RECV + lane), 12288);
      mbar_wait(sb + 8 * B_BD, 0);
      const uint32_t e1 = epoch(sb), ao = 256 * (lane & 16) + 32 * (lane & 15) + 4 * (lane & 4) + (lane & 8) + 4;
#pragma unroll 1
      for (int it = 0; it < 20; it++) {
        const int st = it % 5;
        const uint32_t a = ring + st * 32768 + ao;
        mbar_wait(sb + 8 * (B_A + st), (it / 5) & 1);
        uint32_t t = 0;
#pragma unroll
        for (int j = 0; j < 8; j++) t |= lds32(a + 512 * j) ^ e1;
        if (__any_sync(0xffffffffu, t & 1)) {
#pragma unroll 1
          for (int j = 0; j < 8; j++) a_check(a + 512 * j, (const char*)G->AT + (20 * m + it) * 8192 + ao + 512 * j, e1);
        }
        if (lane == 0) mbar_arrive(sb + 8 * (B_F1 + st));
      }
    } else {
      mbar_wait(sb + 8 * B_KVS, 0);
      mbar_wait(sb + 8 * (B_BD + 1), 0);
      if (b >= 96 && elect()) { load_box(P, sb, b, 4); load_box(P, sb, b, 5); }
      spin(clk(), CD);
      __syncwarp();
      const uint32_t e1 = epoch(sb);
#pragma unroll 1
      for (int n = 0; n < 5; n++) {
        int lane;
        asm volatile("mov.u32 %0, %%laneid;" : "=r"(lane));
        if (n == 3) {
          fence_async_s();
          __syncwarp();
          if (lane == 0) mbar_arrive(sb + 8 * B_F);
          STAMPIF(lane == 0, 34);
          {
            mbar_wait(sb + 8 * (B_EW + 4), 0);
            const char* po = (char*)gout + (2 * tbase(b) + 64 * (lane & 28) + ((lane >> 1) & 1)) * 2 * D_ + (lane & 1) * 640;
            uint32_t v = 0;
#pragma unroll
            for (int r = 0; r < 5; r++) v ^= rdback(po + 128 * r);
            rdwait(sb, v);
            __syncwarp();
            if (lane == 0) flag_add(G, 8 * m + FL_X);
            STAMPIF(lane == 0, 94);
          }
          mbar_wait(sb + 8 * (B_BD + 2), 0);
          if (lane < 2) mbar_arrive(sb + 8 * (B_E1 + 5));
          if (m < 12) {
            rdwait(sb, rdback(G->cimg + s * 3072 + (m % 6) * 512 + (m < 6 ? 0 : 256) + 64 * (lane & 3)));
            __syncwarp();
            if (lane == 0) flag_add(G, FL_C + 8 * s);
            STAMPIF(lane == 0, 35);
          }
          if (elect()) {
            flag_wait(G, FL_C + 8 * s, e1 * 12);
            fence_async_g();
            STAMP(54);
            mbar_expect(sb + 8 * B_EXT, 6144);
            bulk_g2s(sb + SM_EXT, G->cimg + s * 3072, 6144, sb + 8 * B_EXT);
          }
          __syncwarp();
          mbar_wait(sb + 8 * B_ST2, 0);
        }
        const int j = n < 3 ? min(16 * n + (lane >> 1), 39) : min(16 * n - 8 + (lane >> 1), 59), k = j < 20 ? j : j < 40 ? j - 20 : j - 40;
        const uint2* pj = (const uint2*)(G->mv + 2048 * (e1 & 1) + 4 * (lane & 1) + 8 * (k + (j < 40 ? (j < 20 ? 160 : 120) + (m < 6 ? 0 : 20) : 200 + 20 * (s & 1))));
        uint4 a;
#pragma unroll 1
        for (int i = 0;; i++) {
          a = ld_tag2(pj);
          if (__all_sync(0xffffffffu, a.x != 0)) break;
          if (i > (1 << 20)) __trap();
        }
        const uint32_t d = sb + SM_CB + 64 * k + 8 * (lane & 1) + (j >= 20 && j < 40 ? 16 : 0);
        sts64(d, ~__byte_perm(a.x, a.y, 0x5410), ~__byte_perm(a.z, a.w, 0x5410));
        sts64(d + 32, ~__byte_perm(a.x, a.y, 0x7632), ~__byte_perm(a.z, a.w, 0x7632));
      }
      __syncwarp();
      if (lane == 0) mbar_arrive(sb + 8 * B_GB);
      STAMPIF(lane == 0, 39);
    }
    } else {
      STAMPIF(lane == 0, 62);
      int rw = sched_run<0>(P, In{gk, gv, gsk, gWg, gWu, gWd, gss}, sb, b, lane, __shfl_sync(0xffffffffu, t_0, 0));
      if (elect()) {
        STAMP(69);
        mbar_wait(sb + 8 * B_KVS, 0);
        STAMP(70);
        int rd = 0, c = 0;
#pragma unroll 1
        for (int it = 0; it < 20; it++) {
          load_w(P, sb, s, it);
          if ((PWM >> it) & 1) { l2_prefetch(gWg + (128 * rw + b) * F_, 2 * F_); l2_prefetch(gWu + (128 * rw + b) * F_, 2 * F_); rw++; }
          if ((PDM >> it) & 1) { l2_prefetch(gWd + (512 * rd + 4 * b) * D_, 8 * D_); rd++; }
          if (((STM >> it) & 1) && b < 96) {
            const int grp = m % 6;
            if (c == 4) mbar_wait(sb + 8 * (B_BD + 1), 0);
            if (c == 0) mbar_expect(sb + 8 * B_ST0, 40960);
#pragma unroll
            for (int j = 0; j < 2; j++, c++)
              tma2d(sb + (c < 2 ? SM_EXT : SM_RING + R_X - 8192) + 4096 * c, &P.mG + (grp & 1), 192 * s + 64 * (grp >> 1), (m < 6 ? 0 : 320) + 32 * c, sb + 8 * B_ST0);
          }
        }
#pragma unroll
        for (int k = 0; k < 10; k++) {
          const int st = (k + 5) % 6, pe = k < 4 ? k >> 1 : k & 1, ps = k < 4 ? k & 1 : k >> 1;
          mbar_wait(sb + 8 * (k < 6 ? B_E1 + st : B_EB + k - 6), 0);
          mbar_expect(sb + 8 * (B_FB + k), 24576);
          tma2d(ring + st * 32768 + 8192, &P.mD, 320 * (s & 1) + 64 * out_blk(s, ps), 192 * (s ^ pe), sb + 8 * (B_FB + k));
        }
      }
    }
  }
}

typedef CUresult (*EncFn)(CUtensorMap*, CUtensorMapDataType, cuuint32_t, void*, const cuuint64_t*, const cuuint64_t*, const cuuint32_t*, const cuuint32_t*,
                          CUtensorMapInterleave, CUtensorMapSwizzle, CUtensorMapL2promotion, CUtensorMapFloatOOBfill);
static void mkmap(EncFn enc, CUtensorMap* m, const void* p, int rank, const cuuint64_t* dims, const cuuint64_t* strides, const cuuint32_t* box, CUtensorMapSwizzle sw) {
  cuuint32_t es[5] = {1, 1, 1, 1, 1};
  CUresult r = enc(m, CU_TENSOR_MAP_DATA_TYPE_BFLOAT16, rank, (void*)p, dims, strides, box, es, CU_TENSOR_MAP_INTERLEAVE_NONE, sw,
                   CU_TENSOR_MAP_L2_PROMOTION_L2_128B, CU_TENSOR_MAP_FLOAT_OOB_FILL_NONE);
  if (r != CUDA_SUCCESS) fprintf(stderr, "tensor map encode failed: %d\n", (int)r);
}

extern "C" void kernel_launch(void* const* d_in, const int* in_sizes, int n_in, void* d_out, int out_size) {
  void* fn = nullptr;
  cudaDriverEntryPointQueryResult qr;
  cudaGetDriverEntryPoint("cuTensorMapEncodeTiled", &fn, cudaEnableDefault, &qr);
  EncFn enc = (EncFn)fn;
  Scr* G;
  cudaGetSymbolAddress((void**)&G, g_scr);
  Params P;
  { cuuint64_t d[] = {128, 16, 640}, st[] = {256, 4096}; cuuint32_t bx[] = {144, 16, 1}; mkmap(enc, &P.mS, d_in[4], 3, d, st, bx, CU_TENSOR_MAP_SWIZZLE_NONE); }
  { cuuint64_t d[] = {3840, 64, 10}, st[] = {7680, 64 * 7680}; cuuint32_t bx[] = {16, 64, 5}; mkmap(enc, &P.mWm, d_in[11], 3, d, st, bx, CU_TENSOR_MAP_SWIZZLE_32B); }
  { cuuint64_t d[] = {32, 20, 256, 8}, st[] = {64, 10240, 1280}; cuuint32_t bx[] = {40, 1, 9, 8}, bx2[] = {40, 1, 8, 8};
    mkmap(enc, &P.mK, d_in[1], 4, d, st, bx, CU_TENSOR_MAP_SWIZZLE_NONE); mkmap(enc, &P.mV, d_in[2], 4, d, st, bx2, CU_TENSOR_MAP_SWIZZLE_NONE); }
  { cuuint64_t d[] = {1536, 640}, st[] = {3072}; cuuint32_t bx[] = {64, 32};
    mkmap(enc, &P.mG, d_in[7], 2, d, st, bx, CU_TENSOR_MAP_SWIZZLE_128B); mkmap(enc, &P.mU, d_in[8], 2, d, st, bx, CU_TENSOR_MAP_SWIZZLE_128B); }
  { cuuint64_t d[] = {640, 1536}, st[] = {1280}; cuuint32_t bx[] = {64, 192}; mkmap(enc, &P.mD, d_in[9], 2, d, st, bx, CU_TENSOR_MAP_SWIZZLE_128B); }
  { cuuint64_t d[] = {64, 2, 8, 10, 128}, st[] = {1280, 256 * 1280, 128, 2560}; cuuint32_t bx[] = {64, 2, 8, 5, 1}; mkmap(enc, &P.mX, d_in[0], 5, d, st, bx, CU_TENSOR_MAP_SWIZZLE_128B); }
  cudaFuncSetAttribute(fused_kernel, cudaFuncAttributeMaxDynamicSharedMemorySize, SM_TOTAL + DEVSM);
  cudaLaunchConfig_t cfg = {};
  cfg.gridDim = dim3(128); cfg.blockDim = dim3(512); cfg.dynamicSmemBytes = SM_TOTAL + DEVSM; cfg.stream = cudaStreamPerThread;
  cudaLaunchAttribute at[1];
  at[0].id = cudaLaunchAttributeClusterDimension; at[0].val.clusterDim.x = 2; at[0].val.clusterDim.y = 1; at[0].val.clusterDim.z = 1;
  cfg.attrs = at; cfg.numAttrs = 1;
  cudaLaunchKernelEx(&cfg, fused_kernel, (const bf16*)d_in[1], (const bf16*)d_in[2], (const bf16*)d_in[3], (const bf16*)d_in[5], (const bf16*)d_in[10], G,
                     (const bf16*)d_in[7], (const bf16*)d_in[8], (const bf16*)d_in[9], (bf16*)d_out, (const bf16*)d_in[4], P);
}
```

```cpp
#include <cuda_runtime.h>
#include <cuda.h>
#include <cuda_bf16.h>
#include <stdio.h>
#include <stdint.h>
typedef __nv_bfloat16 bf16;
__device__ __forceinline__ uint32_t smem_u32(const void* p) { return (uint32_t)__cvta_generic_to_shared(p); }
__device__ __forceinline__ void mbar_init(uint32_t bar, int cnt) { asm volatile("mbarrier.init.shared::cta.b64 [%0], %1;" ::"r"(bar), "r"(cnt) : "memory"); }
__device__ __forceinline__ void mbar_expect(uint32_t bar, int bytes) { asm volatile("mbarrier.arrive.expect_tx.shared::cta.b64 _, [%0], %1;" ::"r"(bar), "r"(bytes) : "memory"); }
__device__ __forceinline__ void mbar_arrive(uint32_t bar) { asm volatile("mbarrier.arrive.shared::cta.b64 _, [%0];" ::"r"(bar) : "memory"); }
__device__ __forceinline__ void mbar_arrive_remote(uint32_t bar) { asm volatile("mbarrier.arrive.relaxed.cluster.shared::cluster.b64 _, [%0];" ::"r"(bar) : "memory"); }
__device__ __forceinline__ uint32_t mapa(uint32_t a, uint32_t cta) { uint32_t r; asm("mapa.shared::cluster.u32 %0, %1, %2;" : "=r"(r) : "r"(a), "r"(cta)); return r; }
__device__ __forceinline__ bool mbar_try(uint32_t bar, int parity) {
  uint32_t ok;
  asm volatile("{\n.reg .pred p;\nmbarrier.try_wait.parity.shared::cta.b64 p, [%1], %2;\nselp.u32 %0, 1, 0, p;\n}" : "=r"(ok) : "r"(bar), "r"(parity) : "memory");
  return ok;
}
__device__ __forceinline__ void mbar_wait(uint32_t bar, int parity) {
#pragma unroll 1
  for (int i = 0; i < (1 << 20); i++) { if (mbar_try(bar, parity)) return; }
  __trap();
}
__device__ __forceinline__ bool elect() {
  uint32_t p;
  asm volatile("{\n.reg .pred P;\nelect.sync _|P, 0xffffffff;\nselp.u32 %0, 1, 0, P;\n}" : "=r"(p));
  return p;
}
__device__ __forceinline__ void tma2d(uint32_t dst, const CUtensorMap* m, int c0, int c1, uint32_t bar) {
  asm volatile("cp.async.bulk.tensor.2d.shared::cluster.global.mbarrier::complete_tx::bytes [%0], [%1, {%3, %4}], [%2];" ::"r"(dst), "l"(m), "r"(bar), "r"(c0), "r"(c1) : "memory");
}
__device__ __forceinline__ void tma3d(uint32_t dst, const CUtensorMap* m, int c0, int c1, int c2, uint32_t bar) {
  asm volatile("cp.async.bulk.tensor.3d.shared::cluster.global.mbarrier::complete_tx::bytes [%0], [%1, {%3, %4, %5}], [%2];" ::"r"(dst), "l"(m), "r"(bar), "r"(c0), "r"(c1), "r"(c2) : "memory");
}
__device__ __forceinline__ void tma4d(uint32_t dst, const CUtensorMap* m, int c0, int c1, int c2, int c3, uint32_t bar) {
  asm volatile("cp.async.bulk.tensor.4d.shared::cluster.global.mbarrier::complete_tx::bytes [%0], [%1, {%3, %4, %5, %6}], [%2];" ::"r"(dst), "l"(m), "r"(bar), "r"(c0), "r"(c1), "r"(c2), "r"(c3) : "memory");
}
__device__ __forceinline__ void tma5d(uint32_t dst, const CUtensorMap* m, int c0, int c1, int c2, int c3, int c4, uint32_t bar) {
  asm volatile("cp.async.bulk.tensor.5d.shared::cluster.global.mbarrier::complete_tx::bytes [%0], [%1, {%3, %4, %5, %6, %7}], [%2];" ::"r"(dst), "l"(m), "r"(bar), "r"(c0), "r"(c1), "r"(c2), "r"(c3), "r"(c4) : "memory");
}
__device__ __forceinline__ void tma_store2d(const CUtensorMap* m, uint32_t src, int c0, int c1) {
  asm volatile("cp.async.bulk.tensor.2d.global.shared::cta.bulk_group [%0, {%2, %3}], [%1];" ::"l"(m), "r"(src), "r"(c0), "r"(c1) : "memory");
}
__device__ __forceinline__ void tma_store4d(const CUtensorMap* m, uint32_t src, int c0, int c1, int c2, int c3) {
  asm volatile("cp.async.bulk.tensor.4d.global.shared::cta.bulk_group [%0, {%2, %3, %4, %5}], [%1];" ::"l"(m), "r"(src), "r"(c0), "r"(c1), "r"(c2), "r"(c3) : "memory");
}
__device__ __forceinline__ void tma_prefetch2d(const CUtensorMap* m, int c0, int c1) {
  asm volatile("cp.async.bulk.prefetch.tensor.2d.L2.global [%0, {%1, %2}];" ::"l"(m), "r"(c0), "r"(c1) : "memory");
}
__device__ __forceinline__ void bulk_g2s(uint32_t dst, const void* src, int bytes, uint32_t bar) {
  asm volatile("cp.async.bulk.shared::cluster.global.mbarrier::complete_tx::bytes [%0], [%1], %2, [%3];" ::"r"(dst), "l"(src), "r"(bytes), "r"(bar) : "memory");
}
__device__ __forceinline__ void bulk_s2g(void* dst, uint32_t src, int bytes) {
  asm volatile("cp.async.bulk.global.shared::cta.bulk_group [%0], [%1], %2;" ::"l"(dst), "r"(src), "r"(bytes) : "memory");
}
__device__ __forceinline__ void cp16(uint32_t dst, const void* src) { asm volatile("cp.async.cg.shared.global [%0], [%1], 16;" ::"r"(dst), "l"(src) : "memory"); }
__device__ __forceinline__ void cp16z(uint32_t dst, const void* src, int n) { asm volatile("cp.async.cg.shared.global [%0], [%1], 16, %2;" ::"r"(dst), "l"(src), "r"(n) : "memory"); }
__device__ __forceinline__ void cp_arrive(uint32_t bar) { asm volatile("cp.async.mbarrier.arrive.noinc.shared::cta.b64 [%0];" ::"r"(bar) : "memory"); }
__device__ __forceinline__ void st_async4(uint32_t dst, const uint32_t* v, uint32_t bar) {
  asm volatile("st.async.weak.shared::cluster.mbarrier::complete_tx::bytes.v4.b32 [%0], {%1, %2, %3, %4}, [%5];" ::"r"(dst), "r"(v[0]), "r"(v[1]), "r"(v[2]), "r"(v[3]), "r"(bar) : "memory");
}
__device__ __forceinline__ void wg_fence() { asm volatile("wgmma.fence.sync.aligned;" ::: "memory"); }
__device__ __forceinline__ void wg_commit() { asm volatile("wgmma.commit_group.sync.aligned;" ::: "memory"); }
template <int N> __device__ __forceinline__ void wg_wait() { asm volatile("wgmma.wait_group.sync.aligned %0;" ::"n"(N) : "memory"); }
__device__ __forceinline__ uint64_t mkdesc(uint32_t addr, uint32_t lbo, uint32_t sbo, uint32_t swz) {
  return (uint64_t)((addr & 0x3FFFF) >> 4) | ((uint64_t)(lbo >> 4) << 16) | ((uint64_t)(sbo >> 4) << 32) | ((uint64_t)swz << 62);
}
__device__ __forceinline__ void ldsm4t(uint32_t* r, uint32_t a) {
  asm volatile("ldmatrix.sync.aligned.m8n8.x4.trans.shared.b16 {%0,%1,%2,%3}, [%4];" : "=r"(r[0]), "=r"(r[1]), "=r"(r[2]), "=r"(r[3]) : "r"(a) : "memory");
}
__device__ __forceinline__ void stsm4(uint32_t a, const uint32_t* r) {
  asm volatile("stmatrix.sync.aligned.m8n8.x4.shared.b16 [%0], {%1,%2,%3,%4};" ::"r"(a), "r"(r[0]), "r"(r[1]), "r"(r[2]), "r"(r[3]) : "memory");
}
__device__ __forceinline__ void stsm4t(uint32_t a, const uint32_t* r) {
  asm volatile("stmatrix.sync.aligned.m8n8.x4.trans.shared.b16 [%0], {%1,%2,%3,%4};" ::"r"(a), "r"(r[0]), "r"(r[1]), "r"(r[2]), "r"(r[3]) : "memory");
}
__device__ __forceinline__ void bar_sync(int id, int n) { asm volatile("bar.sync %0, %1;" ::"r"(id), "r"(n) : "memory"); }
__device__ __forceinline__ void bar_arrive(int id, int n) { asm volatile("bar.arrive %0, %1;" ::"r"(id), "r"(n) : "memory"); }
__device__ __forceinline__ uint32_t lds32(uint32_t a) { uint32_t v; asm volatile("ld.shared.b32 %0, [%1];" : "=r"(v) : "r"(a) : "memory"); return v; }
__device__ __forceinline__ uint2 lds64(uint32_t a) { uint2 v; asm volatile("ld.shared.v2.b32 {%0,%1}, [%2];" : "=r"(v.x), "=r"(v.y) : "r"(a) : "memory"); return v; }
__device__ __forceinline__ uint4 lds128(uint32_t a) { uint4 v; asm volatile("ld.shared.v4.b32 {%0,%1,%2,%3}, [%4];" : "=r"(v.x), "=r"(v.y), "=r"(v.z), "=r"(v.w) : "r"(a) : "memory"); return v; }
__device__ __forceinline__ void sts16(uint32_t a, uint32_t v) { asm volatile("st.shared.b16 [%0], %1;" ::"r"(a), "h"((uint16_t)v) : "memory"); }
__device__ __forceinline__ void sts32(uint32_t a, uint32_t v) { asm volatile("st.shared.b32 [%0], %1;" ::"r"(a), "r"(v) : "memory"); }
__device__ __forceinline__ void sts64(uint32_t a, uint32_t x, uint32_t y) { asm volatile("st.shared.v2.b32 [%0], {%1,%2};" ::"r"(a), "r"(x), "r"(y) : "memory"); }
__device__ __forceinline__ void sts128(uint32_t a, uint4 v) { asm volatile("st.shared.v4.b32 [%0], {%1,%2,%3,%4};" ::"r"(a), "r"(v.x), "r"(v.y), "r"(v.z), "r"(v.w) : "memory"); }
template<int TB> __device__ __forceinline__ void wgmma_rs_n128(float* d, const uint32_t* a, uint64_t db, int sd) {
  asm volatile("{\n.reg .pred p;\nsetp.ne.b32 p, %69, 0;\n"
    "wgmma.mma_async.sync.aligned.m64n128k16.f32.bf16.bf16 {%0, %1, %2, %3, %4, %5, %6, %7, %8, %9, %10, %11, %12, %13, %14, %15, %16, %17, %18, %19, %20, %21, %22, %23, %24, %25, %26, %27, %28, %29, %30, %31, %32, %33, %34, %35, %36, %37, %38, %39, %40, %41, %42, %43, %44, %45, %46, %47, %48, %49, %50, %51, %52, %53, %54, %55, %56, %57, %58, %59, %60, %61, %62, %63}, {%64, %65, %66, %67}, %68, p, 1, 1, %70;\n}"
    : "+f"(d[0]), "+f"(d[1]), "+f"(d[2]), "+f"(d[3]), "+f"(d[4]), "+f"(d[5]), "+f"(d[6]), "+f"(d[7]), "+f"(d[8]), "+f"(d[9]), "+f"(d[10]), "+f"(d[11]), "+f"(d[12]), "+f"(d[13]), "+f"(d[14]), "+f"(d[15]), "+f"(d[16]), "+f"(d[17]), "+f"(d[18]), "+f"(d[19]), "+f"(d[20]), "+f"(d[21]), "+f"(d[22]), "+f"(d[23]), "+f"(d[24]), "+f"(d[25]), "+f"(d[26]), "+f"(d[27]), "+f"(d[28]), "+f"(d[29]), "+f"(d[30]), "+f"(d[31]), "+f"(d[32]), "+f"(d[33]), "+f"(d[34]), "+f"(d[35]), "+f"(d[36]), "+f"(d[37]), "+f"(d[38]), "+f"(d[39]), "+f"(d[40]), "+f"(d[41]), "+f"(d[42]), "+f"(d[43]), "+f"(d[44]), "+f"(d[45]), "+f"(d[46]), "+f"(d[47]), "+f"(d[48]), "+f"(d[49]), "+f"(d[50]), "+f"(d[51]), "+f"(d[52]), "+f"(d[53]), "+f"(d[54]), "+f"(d[55]), "+f"(d[56]), "+f"(d[57]), "+f"(d[58]), "+f"(d[59]), "+f"(d[60]), "+f"(d[61]), "+f"(d[62]), "+f"(d[63])
    : "r"(a[0]), "r"(a[1]), "r"(a[2]), "r"(a[3]), "l"(db), "r"(sd), "n"(TB));
}

template<int TB> __device__ __forceinline__ void wgmma_rs_n160(float* d, const uint32_t* a, uint64_t db, int sd) {
  asm volatile("{\n.reg .pred p;\nsetp.ne.b32 p, %85, 0;\n"
    "wgmma.mma_async.sync.aligned.m64n160k16.f32.bf16.bf16 {%0, %1, %2, %3, %4, %5, %6, %7, %8, %9, %10, %11, %12, %13, %14, %15, %16, %17, %18, %19, %20, %21, %22, %23, %24, %25, %26, %27, %28, %29, %30, %31, %32, %33, %34, %35, %36, %37, %38, %39, %40, %41, %42, %43, %44, %45, %46, %47, %48, %49, %50, %51, %52, %53, %54, %55, %56, %57, %58, %59, %60, %61, %62, %63, %64, %65, %66, %67, %68, %69, %70, %71, %72, %73, %74, %75, %76, %77, %78, %79}, {%80, %81, %82, %83}, %84, p, 1, 1, %86;\n}"
    : "+f"(d[0]), "+f"(d[1]), "+f"(d[2]), "+f"(d[3]), "+f"(d[4]), "+f"(d[5]), "+f"(d[6]), "+f"(d[7]), "+f"(d[8]), "+f"(d[9]), "+f"(d[10]), "+f"(d[11]), "+f"(d[12]), "+f"(d[13]), "+f"(d[14]), "+f"(d[15]), "+f"(d[16]), "+f"(d[17]), "+f"(d[18]), "+f"(d[19]), "+f"(d[20]), "+f"(d[21]), "+f"(d[22]), "+f"(d[23]), "+f"(d[24]), "+f"(d[25]), "+f"(d[26]), "+f"(d[27]), "+f"(d[28]), "+f"(d[29]), "+f"(d[30]), "+f"(d[31]), "+f"(d[32]), "+f"(d[33]), "+f"(d[34]), "+f"(d[35]), "+f"(d[36]), "+f"(d[37]), "+f"(d[38]), "+f"(d[39]), "+f"(d[40]), "+f"(d[41]), "+f"(d[42]), "+f"(d[43]), "+f"(d[44]), "+f"(d[45]), "+f"(d[46]), "+f"(d[47]), "+f"(d[48]), "+f"(d[49]), "+f"(d[50]), "+f"(d[51]), "+f"(d[52]), "+f"(d[53]), "+f"(d[54]), "+f"(d[55]), "+f"(d[56]), "+f"(d[57]), "+f"(d[58]), "+f"(d[59]), "+f"(d[60]), "+f"(d[61]), "+f"(d[62]), "+f"(d[63]), "+f"(d[64]), "+f"(d[65]), "+f"(d[66]), "+f"(d[67]), "+f"(d[68]), "+f"(d[69]), "+f"(d[70]), "+f"(d[71]), "+f"(d[72]), "+f"(d[73]), "+f"(d[74]), "+f"(d[75]), "+f"(d[76]), "+f"(d[77]), "+f"(d[78]), "+f"(d[79])
    : "r"(a[0]), "r"(a[1]), "r"(a[2]), "r"(a[3]), "l"(db), "r"(sd), "n"(TB));
}

template<int TB> __device__ __forceinline__ void wgmma_rs_n192(float* d, const uint32_t* a, uint64_t db, int sd) {
  asm volatile("{\n.reg .pred p;\nsetp.ne.b32 p, %101, 0;\n"
    "wgmma.mma_async.sync.aligned.m64n192k16.f32.bf16.bf16 {%0, %1, %2, %3, %4, %5, %6, %7, %8, %9, %10, %11, %12, %13, %14, %15, %16, %17, %18, %19, %20, %21, %22, %23, %24, %25, %26, %27, %28, %29, %30, %31, %32, %33, %34, %35, %36, %37, %38, %39, %40, %41, %42, %43, %44, %45, %46, %47, %48, %49, %50, %51, %52, %53, %54, %55, %56, %57, %58, %59, %60, %61, %62, %63, %64, %65, %66, %67, %68, %69, %70, %71, %72, %73, %74, %75, %76, %77, %78, %79, %80, %81, %82, %83, %84, %85, %86, %87, %88, %89, %90, %91, %92, %93, %94, %95}, {%96, %97, %98, %99}, %100, p, 1, 1, %102;\n}"
    : "+f"(d[0]), "+f"(d[1]), "+f"(d[2]), "+f"(d[3]), "+f"(d[4]), "+f"(d[5]), "+f"(d[6]), "+f"(d[7]), "+f"(d[8]), "+f"(d[9]), "+f"(d[10]), "+f"(d[11]), "+f"(d[12]), "+f"(d[13]), "+f"(d[14]), "+f"(d[15]), "+f"(d[16]), "+f"(d[17]), "+f"(d[18]), "+f"(d[19]), "+f"(d[20]), "+f"(d[21]), "+f"(d[22]), "+f"(d[23]), "+f"(d[24]), "+f"(d[25]), "+f"(d[26]), "+f"(d[27]), "+f"(d[28]), "+f"(d[29]), "+f"(d[30]), "+f"(d[31]), "+f"(d[32]), "+f"(d[33]), "+f"(d[34]), "+f"(d[35]), "+f"(d[36]), "+f"(d[37]), "+f"(d[38]), "+f"(d[39]), "+f"(d[40]), "+f"(d[41]), "+f"(d[42]), "+f"(d[43]), "+f"(d[44]), "+f"(d[45]), "+f"(d[46]), "+f"(d[47]), "+f"(d[48]), "+f"(d[49]), "+f"(d[50]), "+f"(d[51]), "+f"(d[52]), "+f"(d[53]), "+f"(d[54]), "+f"(d[55]), "+f"(d[56]), "+f"(d[57]), "+f"(d[58]), "+f"(d[59]), "+f"(d[60]), "+f"(d[61]), "+f"(d[62]), "+f"(d[63]), "+f"(d[64]), "+f"(d[65]), "+f"(d[66]), "+f"(d[67]), "+f"(d[68]), "+f"(d[69]), "+f"(d[70]), "+f"(d[71]), "+f"(d[72]), "+f"(d[73]), "+f"(d[74]), "+f"(d[75]), "+f"(d[76]), "+f"(d[77]), "+f"(d[78]), "+f"(d[79]), "+f"(d[80]), "+f"(d[81]), "+f"(d[82]), "+f"(d[83]), "+f"(d[84]), "+f"(d[85]), "+f"(d[86]), "+f"(d[87]), "+f"(d[88]), "+f"(d[89]), "+f"(d[90]), "+f"(d[91]), "+f"(d[92]), "+f"(d[93]), "+f"(d[94]), "+f"(d[95])
    : "r"(a[0]), "r"(a[1]), "r"(a[2]), "r"(a[3]), "l"(db), "r"(sd), "n"(TB));
}

template<int TB> __device__ __forceinline__ void wgmma_rs_n32(float* d, const uint32_t* a, uint64_t db, int sd) {
  asm volatile("{\n.reg .pred p;\nsetp.ne.b32 p, %21, 0;\n"
    "wgmma.mma_async.sync.aligned.m64n32k16.f32.bf16.bf16 {%0, %1, %2, %3, %4, %5, %6, %7, %8, %9, %10, %11, %12, %13, %14, %15}, {%16, %17, %18, %19}, %20, p, 1, 1, %22;\n}"
    : "+f"(d[0]), "+f"(d[1]), "+f"(d[2]), "+f"(d[3]), "+f"(d[4]), "+f"(d[5]), "+f"(d[6]), "+f"(d[7]), "+f"(d[8]), "+f"(d[9]), "+f"(d[10]), "+f"(d[11]), "+f"(d[12]), "+f"(d[13]), "+f"(d[14]), "+f"(d[15])
    : "r"(a[0]), "r"(a[1]), "r"(a[2]), "r"(a[3]), "l"(db), "r"(sd), "n"(TB));
}

template<int TB> __device__ __forceinline__ void wgmma_rs_n64(float* d, const uint32_t* a, uint64_t db, int sd) {
  asm volatile("{\n.reg .pred p;\nsetp.ne.b32 p, %37, 0;\n"
    "wgmma.mma_async.sync.aligned.m64n64k16.f32.bf16.bf16 {%0, %1, %2, %3, %4, %5, %6, %7, %8, %9, %10, %11, %12, %13, %14, %15, %16, %17, %18, %19, %20, %21, %22, %23, %24, %25, %26, %27, %28, %29, %30, %31}, {%32, %33, %34, %35}, %36, p, 1, 1, %38;\n}"
    : "+f"(d[0]), "+f"(d[1]), "+f"(d[2]), "+f"(d[3]), "+f"(d[4]), "+f"(d[5]), "+f"(d[6]), "+f"(d[7]), "+f"(d[8]), "+f"(d[9]), "+f"(d[10]), "+f"(d[11]), "+f"(d[12]), "+f"(d[13]), "+f"(d[14]), "+f"(d[15]), "+f"(d[16]), "+f"(d[17]), "+f"(d[18]), "+f"(d[19]), "+f"(d[20]), "+f"(d[21]), "+f"(d[22]), "+f"(d[23]), "+f"(d[24]), "+f"(d[25]), "+f"(d[26]), "+f"(d[27]), "+f"(d[28]), "+f"(d[29]), "+f"(d[30]), "+f"(d[31])
    : "r"(a[0]), "r"(a[1]), "r"(a[2]), "r"(a[3]), "l"(db), "r"(sd), "n"(TB));
}

template<int TB> __device__ __forceinline__ void wgmma_rs_n96(float* d, const uint32_t* a, uint64_t db, int sd) {
  asm volatile("{\n.reg .pred p;\nsetp.ne.b32 p, %53, 0;\n"
    "wgmma.mma_async.sync.aligned.m64n96k16.f32.bf16.bf16 {%0, %1, %2, %3, %4, %5, %6, %7, %8, %9, %10, %11, %12, %13, %14, %15, %16, %17, %18, %19, %20, %21, %22, %23, %24, %25, %26, %27, %28, %29, %30, %31, %32, %33, %34, %35, %36, %37, %38, %39, %40, %41, %42, %43, %44, %45, %46, %47}, {%48, %49, %50, %51}, %52, p, 1, 1, %54;\n}"
    : "+f"(d[0]), "+f"(d[1]), "+f"(d[2]), "+f"(d[3]), "+f"(d[4]), "+f"(d[5]), "+f"(d[6]), "+f"(d[7]), "+f"(d[8]), "+f"(d[9]), "+f"(d[10]), "+f"(d[11]), "+f"(d[12]), "+f"(d[13]), "+f"(d[14]), "+f"(d[15]), "+f"(d[16]), "+f"(d[17]), "+f"(d[18]), "+f"(d[19]), "+f"(d[20]), "+f"(d[21]), "+f"(d[22]), "+f"(d[23]), "+f"(d[24]), "+f"(d[25]), "+f"(d[26]), "+f"(d[27]), "+f"(d[28]), "+f"(d[29]), "+f"(d[30]), "+f"(d[31]), "+f"(d[32]), "+f"(d[33]), "+f"(d[34]), "+f"(d[35]), "+f"(d[36]), "+f"(d[37]), "+f"(d[38]), "+f"(d[39]), "+f"(d[40]), "+f"(d[41]), "+f"(d[42]), "+f"(d[43]), "+f"(d[44]), "+f"(d[45]), "+f"(d[46]), "+f"(d[47])
    : "r"(a[0]), "r"(a[1]), "r"(a[2]), "r"(a[3]), "l"(db), "r"(sd), "n"(TB));
}

template<int TA, int TB> __device__ __forceinline__ void wgmma_ss_n192(float* d, uint64_t da, uint64_t db, int sd) {
  asm volatile("{\n.reg .pred p;\nsetp.ne.b32 p, %98, 0;\n"
    "wgmma.mma_async.sync.aligned.m64n192k16.f32.bf16.bf16 {%0, %1, %2, %3, %4, %5, %6, %7, %8, %9, %10, %11, %12, %13, %14, %15, %16, %17, %18, %19, %20, %21, %22, %23, %24, %25, %26, %27, %28, %29, %30, %31, %32, %33, %34, %35, %36, %37, %38, %39, %40, %41, %42, %43, %44, %45, %46, %47, %48, %49, %50, %51, %52, %53, %54, %55, %56, %57, %58, %59, %60, %61, %62, %63, %64, %65, %66, %67, %68, %69, %70, %71, %72, %73, %74, %75, %76, %77, %78, %79, %80, %81, %82, %83, %84, %85, %86, %87, %88, %89, %90, %91, %92, %93, %94, %95}, %96, %97, p, 1, 1, %99, %100;\n}"
    : "+f"(d[0]), "+f"(d[1]), "+f"(d[2]), "+f"(d[3]), "+f"(d[4]), "+f"(d[5]), "+f"(d[6]), "+f"(d[7]), "+f"(d[8]), "+f"(d[9]), "+f"(d[10]), "+f"(d[11]), "+f"(d[12]), "+f"(d[13]), "+f"(d[14]), "+f"(d[15]), "+f"(d[16]), "+f"(d[17]), "+f"(d[18]), "+f"(d[19]), "+f"(d[20]), "+f"(d[21]), "+f"(d[22]), "+f"(d[23]), "+f"(d[24]), "+f"(d[25]), "+f"(d[26]), "+f"(d[27]), "+f"(d[28]), "+f"(d[29]), "+f"(d[30]), "+f"(d[31]), "+f"(d[32]), "+f"(d[33]), "+f"(d[34]), "+f"(d[35]), "+f"(d[36]), "+f"(d[37]), "+f"(d[38]), "+f"(d[39]), "+f"(d[40]), "+f"(d[41]), "+f"(d[42]), "+f"(d[43]), "+f"(d[44]), "+f"(d[45]), "+f"(d[46]), "+f"(d[47]), "+f"(d[48]), "+f"(d[49]), "+f"(d[50]), "+f"(d[51]), "+f"(d[52]), "+f"(d[53]), "+f"(d[54]), "+f"(d[55]), "+f"(d[56]), "+f"(d[57]), "+f"(d[58]), "+f"(d[59]), "+f"(d[60]), "+f"(d[61]), "+f"(d[62]), "+f"(d[63]), "+f"(d[64]), "+f"(d[65]), "+f"(d[66]), "+f"(d[67]), "+f"(d[68]), "+f"(d[69]), "+f"(d[70]), "+f"(d[71]), "+f"(d[72]), "+f"(d[73]), "+f"(d[74]), "+f"(d[75]), "+f"(d[76]), "+f"(d[77]), "+f"(d[78]), "+f"(d[79]), "+f"(d[80]), "+f"(d[81]), "+f"(d[82]), "+f"(d[83]), "+f"(d[84]), "+f"(d[85]), "+f"(d[86]), "+f"(d[87]), "+f"(d[88]), "+f"(d[89]), "+f"(d[90]), "+f"(d[91]), "+f"(d[92]), "+f"(d[93]), "+f"(d[94]), "+f"(d[95])
    : "l"(da), "l"(db), "r"(sd), "n"(TA), "n"(TB));
}

template<int TA, int TB> __device__ __forceinline__ void wgmma_ss_n8(float* d, uint64_t da, uint64_t db, int sd) {
  asm volatile("{\n.reg .pred p;\nsetp.ne.b32 p, %6, 0;\n"
    "wgmma.mma_async.sync.aligned.m64n8k16.f32.bf16.bf16 {%0, %1, %2, %3}, %4, %5, p, 1, 1, %7, %8;\n}"
    : "+f"(d[0]), "+f"(d[1]), "+f"(d[2]), "+f"(d[3])
    : "l"(da), "l"(db), "r"(sd), "n"(TA), "n"(TB));
}

constexpr int S_ = 2048, D_ = 640, F_ = 1536;

struct Scr {
  uint32_t flag[32 * 8];
  uint32_t mv[2 * 2048];
  bf16 cimg[8 * 6 * 512];
  uint2 st2[S_];
  bf16 kvT[D_ * S_];
  bf16 zT[D_ * S_];
  bf16 AT[D_ * S_];
};
__device__ __align__(1024) Scr g_scr;
__device__ __forceinline__ uint32_t clk() { uint32_t c; asm volatile("mov.u32 %0, %%clock;" : "=r"(c) :: "memory"); return c; }
#define DEVSM 0
#define STAMP(id)
#define STAMPIF(c, id)
constexpr int FL_X = 5, FL_C = 128;
#define CD 600
#define SD 1000

constexpr int SM_X = 1024, SM_EXT = 21504, SM_SMALL = 29696, SM_STAT = 30720, SM_CB = 32768, SM_RING = 34816, SM_TOTAL = SM_RING + 6 * 32768;
constexpr int SMALL_LN = 224, SMALL_RED = 320, SMALL_DUMMY = 1008, SMALL_E = 1012, SMALL_TS = 160;
constexpr int JOB_SZ = 10880, JOB_V = 5760, R_X = 5 * 32768, R_BOX = R_X + 12288;
constexpr int K1OFF = 4672, KSZ = 9472, CSZ = KSZ + 4224;
enum { B_KJ = 0, B_X = 5, B_EXT = 7, B_X1 = 8, B_P0 = 9, B_FB = 10, B_PEER = 20, B_RECV = 24, B_A = 30, B_E0 = 35, B_BOX = 38, B_F = 44, B_ST0 = 45, B_GB = 46,
       B_F1 = 48, B_E1 = 54, B_EB = 60,
       B_Z = 80, B_K = 85, B_EW = 88, B_ST2 = 94, B_XF = 95, B_LN = 96, B_KVS = 98, B_BD = 99,
       B_B = 106, B_S = 112 };
__device__ __forceinline__ uint32_t chan_base(uint32_t sb, int ch) { return sb + SM_RING + (2 + (ch >> 1)) * 32768 + (ch & 1) * CSZ; }

struct Params { CUtensorMap mS, mX, mWm, mK, mV, mG, mU, mD; };

__device__ __forceinline__ void flag_add(Scr* G, int id) { asm volatile("red.relaxed.gpu.global.add.u32 [%0], 1;" ::"l"(G->flag + id) : "memory"); }
__device__ __forceinline__ uint32_t rdback(const void* p) { uint32_t v; asm volatile("ld.relaxed.gpu.global.u32 %0, [%1];" : "=r"(v) : "l"(p) : "memory"); return v; }
__device__ __forceinline__ void st_tag(uint2* p, uint32_t v, uint32_t t) { asm volatile("st.relaxed.gpu.global.v2.u32 [%0], {%1, %2};" ::"l"(p), "r"(v), "r"(t) : "memory"); }
__device__ __forceinline__ void spin(uint32_t t, uint32_t d) { if (d) while (clk() - t < d); }
__device__ __forceinline__ uint2 ld_tag(const uint2* p) { uint2 v; asm volatile("ld.relaxed.gpu.global.v2.u32 {%0, %1}, [%2];" : "=r"(v.x), "=r"(v.y) : "l"(p) : "memory"); return v; }
__device__ __forceinline__ uint4 ld_tag2(const uint2* p) {
  uint4 v;
  asm volatile("ld.relaxed.gpu.global.v4.u32 {%0, %1, %2, %3}, [%4];" : "=r"(v.x), "=r"(v.y), "=r"(v.z), "=r"(v.w) : "l"(p) : "memory");
  return v;
}
__device__ __forceinline__ void stg128(void* p, uint4 v) { asm volatile("st.global.v4.b32 [%0], {%1, %2, %3, %4};" ::"l"(p), "r"(v.x), "r"(v.y), "r"(v.z), "r"(v.w) : "memory"); }
__device__ __forceinline__ uint32_t epoch(uint32_t sb) { return lds32(sb + SM_SMALL + SMALL_E); }
__device__ __forceinline__ void rdwait(uint32_t sb, uint32_t v) { sts32(sb + SM_SMALL + SMALL_DUMMY, v); }
__device__ __forceinline__ void fence_async_s() { asm volatile("fence.proxy.async.shared::cta;" ::: "memory"); }
__device__ __forceinline__ void fence_async_g() { asm volatile("fence.proxy.async.global;" ::: "memory"); }
__device__ __forceinline__ void bulk_done() { asm volatile("cp.async.bulk.commit_group;\n\tcp.async.bulk.wait_group 0;" ::: "memory"); }
__device__ __forceinline__ void flag_wait(Scr* G, int id, uint32_t target) {
  const uint32_t* p = G->flag + id;
#pragma unroll 1
  for (int i = 0; i < (1 << 20); i++) {
    uint32_t v;
    asm volatile("ld.relaxed.gpu.global.u32 %0, [%1];" : "=r"(v) : "l"(p) : "memory");
    if ((int)(v - target) >= 0) return;
  }
  __trap();
}
__device__ __forceinline__ int tbase(int pb) { return 127 - (32 * (pb >> 6) + 8 * (pb & 8) + 4 * ((2 * (pb & 3) - ((pb >> 2) & 1)) & 7) + ((pb >> 4) & 3)); }
__device__ __forceinline__ uint32_t hmul(uint32_t a, uint32_t b) { uint32_t d; asm("mul.rn.bf16x2 %0, %1, %2;" : "=r"(d) : "r"(a), "r"(b)); return d; }
__device__ __forceinline__ uint32_t hadd(uint32_t a, uint32_t b) { uint32_t d; asm("add.rn.bf16x2 %0, %1, %2;" : "=r"(d) : "r"(a), "r"(b)); return d; }
__device__ __forceinline__ uint32_t hsub(uint32_t a, uint32_t b) { uint32_t d; asm("sub.rn.bf16x2 %0, %1, %2;" : "=r"(d) : "r"(a), "r"(b)); return d; }
__device__ __forceinline__ uint32_t hfma(uint32_t a, uint32_t b, uint32_t c) { uint32_t d; asm("fma.rn.bf16x2 %0, %1, %2, %3;" : "=r"(d) : "r"(a), "r"(b), "r"(c)); return d; }
__device__ __forceinline__ uint32_t pack2(float lo, float hi) { uint32_t d; asm("cvt.rn.bf16x2.f32 %0, %1, %2;" : "=r"(d) : "f"(hi), "f"(lo)); return d; }
__device__ __forceinline__ float blo(uint32_t v) { return __uint_as_float(v << 16); }
__device__ __forceinline__ float bhi(uint32_t v) { return __uint_as_float(v & 0xffff0000u); }
__device__ __forceinline__ uint32_t tagged(uint32_t v, uint32_t e1) { return (v & ~1u) | (e1 & 1); }
__device__ __forceinline__ float rbf(float v) { return blo(pack2(v, 0.f)); }
template <int N> __device__ __forceinline__ void bfly(float* v, int mask, bool up) {
#pragma unroll
  for (int i = 0; i < N / 2; i++) {
    float send = up ? v[i] : v[i + N / 2], keep = up ? v[i + N / 2] : v[i];
    v[i] = keep + __shfl_xor_sync(0xffffffffu, send, mask);
  }
}
__device__ __forceinline__ bool mod_first(int b) { return !(b & 1) || !(b & 6); }
__device__ __forceinline__ int mod_grp(int b, int j) {
  const int m = b >> 3, s = b & 7, t = 16 * s + m, v = j ? (t * 43) >> 10 : s >> 1;
  if (j == 2) return b + 112;
  if (j == 0 && s == 1) return m + (m < 8 ? 152 : 192);
  return v < 4 ? (v == 3 ? 160 : 40 * v) + (j ? 16 + t - 24 * v : m) : t + 24;
}

__device__ __forceinline__ void kv_load(const bf16* gk, const bf16* gv, const bf16* gs, uint32_t sb, int b, int r, int tid) {
  const int row = tid >> 2, col = 128 * r + 32 * (b & 3);
  const uint32_t a = sb + SM_RING + r * JOB_SZ + (row >> 3) * 80 + (tid & 3) * 16, ak = a + (row & 7) * 720, av = a + (row & 7) * 640 + JOB_V;
  const int o = (64 * (b >> 2) + row) * D_ + col + 8 * (tid & 3);
  cp16(ak + 80, gk + o);
  cp16(ak + 400, gk + o + 32 * D_);
  cp16(av, gv + o);
  cp16(av + 320, gv + o + 32 * D_);
  if (tid < 12) cp16z(ak + 3600, gk + (b < 4 ? o : o - 3 * D_), b < 4 ? 0 : 16);
  else if (tid >= 112) cp16(sb + SM_CB + 256 * r + 16 * (tid - 112), gs + 4 * col + 8 * (tid - 112));
}
__device__ __forceinline__ void load_kv(const Params& P, const bf16* gs, uint32_t sb, int b, int r) {
  const uint32_t a = sb + SM_RING + r * JOB_SZ, bar = sb + 8 * (B_B + r);
  const int cg = 4 * r + (b & 3);
  mbar_expect(bar, JOB_SZ + 256);
  tma4d(a, &P.mK, 0, cg, 8 * (b >> 2) - 1, 0, bar);
  tma4d(a + JOB_V, &P.mV, 0, cg, 8 * (b >> 2), 0, bar);
  bulk_g2s(sb + SM_CB + 256 * r, gs + 128 * cg, 256, bar);
}
__device__ __forceinline__ uint4* kv_dst(Scr* G, int b, int r, int tid) {
  return (uint4*)(G->kvT + (128 * r + 32 * (b & 3) + 8 * (tid >> 5) + 2 * (tid & 3)) * S_ + 2040 - 64 * (b >> 2)) - ((tid >> 2) & 7);
}
__device__ __forceinline__ void kv_job(Scr* G, uint32_t sb, int b, int r, int tid) {
  const int cp = 4 * (tid >> 5) + (tid & 3);
  const uint32_t ka = sb + SM_RING + r * JOB_SZ + ((tid >> 2) & 7) * 80 + cp * 4;
  mbar_wait(sb + 8 * (B_B + r), 0);
  STAMPIF(tid == 0, 56 + r);
  const uint4 sk = lds128(sb + SM_CB + 256 * r + 16 * cp);
  const uint32_t s0 = __byte_perm(sk.x, sk.z, 0x5410), s1 = __byte_perm(sk.x, sk.z, 0x7632), s2 = __byte_perm(sk.y, sk.w, 0x5410), s3 = __byte_perm(sk.y, sk.w, 0x7632);
  uint32_t kk[11], o[8];
#pragma unroll
  for (int i = 0; i < 11; i++) kk[i] = lds32(ka + 720 * ((i + 5) & 7) + 80 * ((i + 5) >> 3));
#pragma unroll
  for (int i = 0; i < 8; i++) {
    uint32_t v = lds32(ka + JOB_V + 640 * i);
    o[i] = hmul(hfma(kk[i + 3], s0, hfma(kk[i + 2], s1, hfma(kk[i + 1], s2, hmul(kk[i], s3)))), v);
  }
  uint4* dst = kv_dst(G, b, r, tid);
  dst[0] = make_uint4(__byte_perm(o[7], o[6], 0x5410), __byte_perm(o[5], o[4], 0x5410), __byte_perm(o[3], o[2], 0x5410), __byte_perm(o[1], o[0], 0x5410) | 1);
  dst[256] = make_uint4(__byte_perm(o[7], o[6], 0x7632), __byte_perm(o[5], o[4], 0x7632), __byte_perm(o[3], o[2], 0x7632), __byte_perm(o[1], o[0], 0x7632) | 1);
  if (tid == 0) { sts32(sb + SM_SMALL + SMALL_TS + 4 * r, clk()); mbar_arrive(sb + 8 * (B_KJ + r)); }
}
__device__ __forceinline__ void u_wait(uint4& a, uint4& c, const void* p) {
  asm volatile("{\n.reg .pred p;\n.reg .b32 t, n;\nmov.b32 n, 0;\n"
               "L0:\nlop3.b32 t, %3, %7, 1, 0x80;\nsetp.eq.b32 p, t, 0;\nvote.sync.any.pred p, p, 0xffffffff;\n@!p bra.uni L1;\n"
               "ld.relaxed.gpu.global.v4.u32 {%0, %1, %2, %3}, [%8];\nld.relaxed.gpu.global.v4.u32 {%4, %5, %6, %7}, [%8+2048];\n"
               "add.u32 n, n, 1;\nsetp.lt.u32 p, n, 1000000;\n@p bra.uni L0;\ntrap;\nL1:\n}"
               : "+r"(a.x), "+r"(a.y), "+r"(a.z), "+r"(a.w), "+r"(c.x), "+r"(c.y), "+r"(c.z), "+r"(c.w) : "l"(p) : "memory");
}
__device__ __forceinline__ uint64_t box_a(uint32_t sb) { return mkdesc(sb + SM_RING + R_BOX, 256, 1024, 3); }
__device__ __forceinline__ uint64_t box_b(uint32_t sb) { return mkdesc(sb + SM_STAT, 64, 128, 0); }
__device__ __forceinline__ void mod_put(Scr* G, uint32_t sb, const float* a, int b, int j, uint32_t e1, int tid) {
  const uint32_t red = sb + SM_STAT + 1536;
  if ((tid & 3) == tid >> 6) sts64(red + 32 * ((tid >> 2) & 7) + 8 * (tid >> 5), __float_as_uint((tid & 32) ? a[1] : a[0]), __float_as_uint((tid & 32) ? a[3] : a[2]));
  bar_sync(j ? 4 : 5, 128);
  if (tid < 16) {
    const uint4 u = lds128(red + 32 * (tid & 7)), v = lds128(red + 32 * (tid & 7) + 16);
    asm volatile("" : "+r"(b));
    const int grp = mod_grp(b, j);
    const uint32_t one = (grp >= 40 && grp < 80) || (grp >= 160 && grp < 200) ? 0x3f803f80u : 0u;
    const float lo = __uint_as_float(u.x) + __uint_as_float(u.z) + __uint_as_float(v.x) + __uint_as_float(v.z);
    const float hi = __uint_as_float(u.y) + __uint_as_float(u.w) + __uint_as_float(v.y) + __uint_as_float(v.w);
    asm volatile("st.relaxed.gpu.global.u32 [%0], %1;" ::"l"(G->mv + 8 * grp + 256 * (tid & 8) + (tid & 7)),
                 "r"(((tid >> 3) ^ e1) & 1 ? 0 : ~hadd(pack2(lo, hi), one)) : "memory");
  }
}
__device__ __forceinline__ void mod_box(Scr* G, uint32_t sb, int b, int j, uint32_t e1, int tid) {
  float a[4];
  uint64_t da = box_a(sb), db = box_b(sb);
#pragma unroll
  for (int h = 0; h < 2; h++) {
    mbar_wait(sb + 8 * (B_BOX + 2 * j + h), 0);
    STAMPIF(tid == 0 && j == 0, 71 + h);
    wg_fence();
#pragma unroll
    for (int n = 5 * h; n < 5 * h + 5; n++) wgmma_ss_n8<1, 0>(a, da + 128 * n, db + 8 * n, n != 0);
    wg_commit();
  }
  wg_wait<0>();
#pragma unroll
  for (int i = 0; i < 4; i++) asm volatile("" : "+f"(a[i])::"memory");
  mod_put(G, sb, a, b, j, e1, tid);
}
__device__ __forceinline__ void a_check(uint32_t sa, const void* ga, uint32_t tag) {
  asm volatile("{\n.reg .pred p;\n.reg .b32 t, n, x, y, z;\n.reg .b64 g;\n"
               "ld.shared.b32 t, [%0];\nlop3.b32 t, t, %2, 1, 0x28;\nsetp.ne.b32 p, t, 0;\nvote.sync.any.pred p, p, 0xffffffff;\n@!p bra.uni L1;\nmov.b32 n, 0;\n"
               "L0:\nld.relaxed.gpu.global.b32 t, [%1];\nlop3.b32 t, t, %2, 1, 0x28;\nsetp.ne.b32 p, t, 0;\nvote.sync.any.pred p, p, 0xffffffff;\n@!p bra.uni L2;\n"
               "add.u32 n, n, 1;\nsetp.lt.u32 p, n, 1000000;\n@p bra.uni L0;\ntrap;\nL2:\n"
               "and.b64 g, %1, -32;\nand.b32 n, %0, -32;\n"
               "ld.relaxed.gpu.global.v4.b32 {t, x, y, z}, [g];\nst.shared.v4.b32 [n], {t, x, y, z};\n"
               "ld.relaxed.gpu.global.v4.b32 {t, x, y, z}, [g+16];\nst.shared.v4.b32 [n+16], {t, x, y, z};\n"
               "fence.proxy.async.shared::cta;\nbar.warp.sync 0xffffffff;\nL1:\n}" ::"r"(sa), "l"(ga), "r"(tag) : "memory");
}
__device__ __forceinline__ void z_wait(uint4& a, uint4& c, uint32_t* v, const void* p, const void* q, uint32_t e1) {
  asm volatile("{\n.reg .pred p;\n.reg .b32 t, n;\nmov.b32 n, 0;\n"
               "L0:\nlop3.b32 t, %3, %7, %14, 0x81;\nand.b32 t, t, 1;\nmin.u32 t, t, %8;\nmin.u32 t, t, %9;\nmin.u32 t, t, %10;\nmin.u32 t, t, %11;\n"
               "setp.eq.b32 p, t, 0;\nvote.sync.any.pred p, p, 0xffffffff;\n@!p bra.uni L1;\n"
               "ld.relaxed.gpu.global.v4.u32 {%0, %1, %2, %3}, [%12];\nld.relaxed.gpu.global.v4.u32 {%4, %5, %6, %7}, [%12+32768];\n"
               "ld.relaxed.gpu.global.u32 %8, [%13];\nld.relaxed.gpu.global.u32 %9, [%13+1280];\nld.relaxed.gpu.global.u32 %10, [%13+2560];\nld.relaxed.gpu.global.u32 %11, [%13+5120];\n"
               "add.u32 n, n, 1;\nsetp.lt.u32 p, n, 1000000;\n@p bra.uni L0;\ntrap;\nL1:\n}"
               : "+r"(a.x), "+r"(a.y), "+r"(a.z), "+r"(a.w), "+r"(c.x), "+r"(c.y), "+r"(c.z), "+r"(c.w), "+r"(v[0]), "+r"(v[1]), "+r"(v[2]), "+r"(v[3])
               : "l"(p), "l"(q), "r"(e1) : "memory");
}
__device__ __forceinline__ void load_x(const Params& P, uint32_t sb, int b, int h) {
  const uint32_t bar = sb + 8 * (B_X + h);
  mbar_expect(bar, 10240);
  tma5d(sb + SM_X + h * 10240, &P.mX, 0, 0, 0, 5 * h, tbase(b), bar);
}
__device__ __forceinline__ uint32_t x_addr(uint32_t sb, int w, int lane) {
  const int rho = 15 - (4 * (lane >> 3) + 2 * (lane & 1) + ((lane >> 1) & 1));
  return sb + SM_X + (w >> 1) * 2048 + rho * 128 + (((2 * (w & 1) + (lane & 4)) ^ (rho & 7)) << 4);
}
__device__ __forceinline__ void ln1_job(uint32_t sb, int tid) {
  const uint32_t xr = sb + SM_X + 16 * tid;
  float pv, s1 = 0.f, s2 = 0.f, s3 = 0.f;
#pragma unroll 1
  for (int h = 0; h < 2; h++) {
    mbar_wait(sb + 8 * (B_X + h), 0);
    STAMPIF(tid == 0, 25);
    pv = blo(lds32(xr & ~127u));
#pragma unroll
    for (int n = 0; n < 5; n++) {
      const uint4 v = lds128(xr + 10240 * h + 2048 * n);
      const uint32_t u[4] = {v.x, v.y, v.z, v.w};
#pragma unroll
      for (int j = 0; j < 4; j++) {
        const float a = blo(u[j]) - pv, c = bhi(u[j]) - pv;
        s1 += a + c; s2 += a * a; s3 += c * c;
      }
    }
  }
  s2 += s3;
#pragma unroll
  for (int o = 1; o < 8; o <<= 1) { s1 += __shfl_xor_sync(0xffffffffu, s1, o); s2 += __shfl_xor_sync(0xffffffffu, s2, o); }
  const float mu = s1 * (1.f / D_), var = fmaxf(s2 * (1.f / D_) - mu * mu, 0.f);
  const float rs = __frcp_rn(rbf(__fsqrt_rn(rbf(rbf(var) + 1e-5f))));
  const int i = 15 - (tid >> 3), j = tid & 7;
  if (j < 2) sts16(sb + SM_SMALL + SMALL_LN + 32 * j + 16 * (i & 1) + (i & 14), pack2(j ? rs : pv + mu, 0.f));
  bar_sync(5, 128);
  STAMPIF(tid == 0, 75);
}
__device__ __forceinline__ void load_box(const Params& P, uint32_t sb, int b, int cls) {
  const uint32_t bar = sb + 8 * (B_BOX + cls);
  mbar_expect(bar, 10240);
  tma3d(sb + SM_RING + R_BOX + 10240 * (cls & 1), &P.mWm, 16 * mod_grp(b, cls >> 1), 0, 5 * (cls & 1), bar);
}
__device__ __forceinline__ void load_ssm(const Params& P, uint32_t sb, int b, int r) {
  const uint32_t bar = sb + 8 * (B_S + r);
  mbar_expect(bar, 16 * 288);
  tma3d(chan_base(sb, r) + 128, &P.mS, 0, 0, 128 * r + b, bar);
}
__device__ __forceinline__ void k1_job(uint32_t sb, int r, int tid, uint32_t dv) {
  const uint32_t a0 = chan_base(sb, r) + 128 + 16 * tid + 32 * (tid >> 4);
  mbar_wait(sb + 8 * (B_S + r), 0);
#pragma unroll
  for (int n = 0; n < 2; n++) {
    const uint32_t a = a0 + 2304 * n;
    uint4 v = lds128(a);
    if (n == 0 && tid == 0) { v.x = hadd(v.x, dv); sts32(a, v.x); }
    const uint32_t pv = lds32(a - ((tid & 15) ? 4 : 36));
    sts128(a + K1OFF, make_uint4(__byte_perm(pv, v.x, 0x5432), __byte_perm(v.x, v.y, 0x5432), __byte_perm(v.y, v.z, 0x5432), __byte_perm(v.z, v.w, 0x5432)));
  }
}

__device__ __forceinline__ int out_blk(int s, int p) { const int t = p + (s >> 1); return t < 5 ? t : t - 5; }
__device__ __forceinline__ void l2_prefetch(const void* p, int bytes) { asm volatile("cp.async.bulk.prefetch.L2.global [%0], %1;" ::"l"(p), "r"(bytes) : "memory"); }
__device__ __forceinline__ void pf_line(const void* p) { asm volatile("prefetch.global.L2 [%0];" ::"l"(p) : "memory"); }
__device__ __forceinline__ int role(int bx) {
  const int c = bx >> 1, d = c - 36, q = (d * 37) >> 8, k = d - 7 * q;
  const int rank = c < 4 ? 12 + c : c < 36 ? ((c - 4) & 7) * 8 + ((c - 4) >> 3) : (k ? k + 1 : 0) * 8 + 4 + q;
  return 8 * (rank & 15) + 2 * (rank >> 4) + (bx & 1);
}
enum { K_KV, K_SSM, K_BOX, K_PW, K_PD, K_PKV, K_PSSM, K_PBOX, K_W, K_X, K_ST, K_END = 15 };
#define E(t, bar, kind, r) ((t) << 16 | (bar) << 8 | (kind) << 4 | (r))
#define SCHED E(2800, 255, K_BOX, 0), E(0, 255, K_BOX, 1), E(3700, 255, K_KV, 2), E(4400, 255, K_SSM, 2), E(4800, 255, K_KV, 3), E(5500, 255, K_X, 0), \
              E(6400, 255, K_KV, 4), E(7100, 255, K_X, 1), E(7900, 255, K_SSM, 3), E(8300, 255, K_SSM, 4), E(8600, 255, K_BOX, 2), E(9500, 255, K_PW, 0), \
              E(10100, 255, K_BOX, 3)
#define XPF 2
#define XBOTH 0
#define AUXP 0xfedcb0217ull
constexpr int aux_last(int mask) { int r = 0; for (uint64_t p = AUXP; p; p >>= 4) if ((mask >> (p & 15)) & 1) r = p & 15; return r; }
constexpr int kLastKv = aux_last(0x0e);
#define XI 8
#define XW 0
#define PWM 0x3c
#define STM 0x7c0
#define PDM 0x3800
#define KV4C 3
#define CVT 1
#define UPOS 4
#define UD 1000
#define UD1 6400
#define NP 6
#define NQ 6
#define SPOS(i) (2 * ((i) - NQ) + 13)
#define LH0 4
#define LH1 5
#define LM 0
#define PT 1
#define ZP 0
#define ITW 0
constexpr uint32_t kSched[] = {SCHED, E(0, 255, K_END, 0)};
struct In { const bf16 *k, *v, *sk, *Wg, *Wu, *Wd, *ss; };
__device__ __forceinline__ void load_w(const Params& P, uint32_t sb, int s, int it) {
  const int st = it % 5;
  mbar_wait(sb + 8 * (B_E1 + st), (it / 5) & 1);
  const uint32_t a = sb + SM_RING + st * 32768 + 8192, fb = sb + 8 * (B_F1 + st);
  mbar_expect(fb, 24576);
#pragma unroll
  for (int j = 0; j < 3; j++) {
    tma2d(a + 8192 * j, &P.mG, 192 * s + 64 * j, 32 * it, fb);
    tma2d(a + 8192 * j + 4096, &P.mU, 192 * s + 64 * j, 32 * it, fb);
  }
}

template <int I> __device__ __forceinline__ int sched_run(const Params& P, const In& in, uint32_t sb, int b, int lane, uint32_t t_0) {
  constexpr uint32_t e = kSched[I];
  constexpr int kind = (e >> 4) & 15, r = e & 15, bar = (e >> 8) & 255;
  if constexpr (kind == K_END) return 0;
  else {
    if constexpr ((e >> 16) != 0) while (clk() - t_0 < (e >> 16));
    if (bar != 255) mbar_wait(sb + 8 * bar, 0);
    if (kind == K_BOX && r == 2) mbar_wait(sb + 8 * B_BD, 0);
    if (kind == K_PKV) {
      const bf16* kvp = (lane < 16 ? in.k : in.v) + (16 * b + (lane & 15)) * D_ + 128 * r;
      pf_line(kvp); pf_line(kvp + 64);
    } else {
      if (elect()) {
        if (kind == K_KV) load_kv(P, in.sk, sb, b, r);
        if (kind == K_X) load_x(P, sb, b, r);
        if (kind == K_SSM) load_ssm(P, sb, b, r);
        if (kind == K_BOX && (r > 1 || mod_first(b))) load_box(P, sb, b, r);
        if (kind == K_PW) { l2_prefetch(in.Wg + (128 * r + b) * F_, 2 * F_); l2_prefetch(in.Wu + (128 * r + b) * F_, 2 * F_); }
        if (kind == K_PSSM) l2_prefetch(in.ss + (128 * r + b) * S_, 4096);
      }
      __syncwarp();
    }
    return sched_run<I + 1>(P, in, sb, b, lane, t_0) + (kind == K_PW);
  }
}

__global__ void __launch_bounds__(512, 1) fused_kernel(const bf16* __restrict__ gk, const bf16* __restrict__ gv, const bf16* __restrict__ gsk,
                                                       const bf16* __restrict__ gD, const bf16* __restrict__ gc, Scr* G, const bf16* gWg, const bf16* gWu,
                                                       const bf16* gWd, bf16* gout, const bf16* gss, const __grid_constant__ Params P) {
  extern __shared__ __align__(1024) char smem_raw[];
  const uint32_t sb = smem_u32(smem_raw), ring = sb + SM_RING;
  const int b = role(blockIdx.x), m = b >> 3, s = b & 7;
  const uint32_t t_0 = clk();
  const int wg = __shfl_sync(0xffffffffu, threadIdx.x >> 7, 0);
  const int tid = threadIdx.x & 127, lane = tid & 31;
  const int w = __shfl_sync(0xffffffffu, tid >> 5, 0);
  if (wg < 2) {
    kv_load(gk, gv, gsk, sb, b, wg, tid);
  } else {
    if (wg == 2) {
      if (tid < 40) {
        int c = tid & 7;
        sts128(chan_base(sb, tid >> 3) + (c < 2 ? 80 + c * K1OFF : KSZ + 4096 + (c - 2) * 16), make_uint4(0, 0, 0, 0));
      }
    }
    if (elect()) {
      const int j = 4 * (3 - wg) + w - 1;
      if (j < 4) asm volatile("prefetch.tensormap [%0];" ::"l"(&P.mX + j) : "memory");
      if (j < 0) {
#pragma unroll
        for (int i = 0; i < 5; i++) mbar_init(sb + 8 * (B_S + i), 1);
        fence_async_s();
        if (XPF > 0) load_ssm(P, sb, b, 0);
        if (XPF > 1) load_ssm(P, sb, b, 1);
      } else {
        const int c = j < 3 ? 1 : j < 5 ? 2 : 4;
#pragma unroll
        for (int i = 0; i < 16; i++) mbar_init(sb + 128 * j + 8 * i, i < 10 || j < 6 ? c : i < 12 ? 128 : 1);
      }
    }
    fence_async_s();
  }
  __syncthreads();
  STAMPIF(threadIdx.x == 0, 55);

  if (wg < 2) {
    cp_arrive(sb + 8 * (B_B + wg));
    asm volatile("setmaxnreg.inc.sync.aligned.u32 224;");
    STAMPIF(threadIdx.x == 0, 82);
    const int g = lane >> 2, q = lane & 3;
    if (wg == 1) bar_arrive(1, 256);
    const uint32_t dv = *(const uint16_t*)(gD + 128 * wg + b);
    {
      const int b0 = (g >> 1) & 1, b1 = g >> 2, u = q + 4 * b0 - w;
      const uint32_t fo = 128 + (g & 1) * K1OFF + 288 * b1 + 4 * u, fo0 = fo - (u < 0 ? 32 : 0);
      const bool wrap = b0 && q == 0;
      const int src1 = b0 ? ((lane & 20) | ((q - 1) & 3)) : (lane | 8);
      const uint2* pu = (const uint2*)(G->kvT + (128 * wg + b) * S_ + 8 * tid);
      uint4 u0 = make_uint4(0, 0, 0, 0), u1 = u0;
      if (UPOS & 1) { u0 = ld_tag2(pu); u1 = ld_tag2(pu + 256); }
#pragma unroll 1
      for (int ch = wg; ch < 5; ch += 2) {
        const uint32_t base = chan_base(sb, ch);
        if (ch < 2 || ch == KV4C) {
          kv_job(G, sb, b, ch < 2 ? ch : 4, tid);
          STAMPIF(tid == 0, ch < 2 ? 1 + ch : 24);
        }
        if (ch < 2) {
          k1_job(sb, wg, tid, dv);
          bar_sync(3 + wg, 128);
        } else {
          mbar_wait(sb + 8 * (B_K + ch - 2), 0);
          if (UPOS & 4) { u0 = ld_tag2(pu); u1 = ld_tag2(pu + 256); }
          mbar_wait(sb + 8 * (B_S + ch), 0);
        }
        const uint32_t fa = base + fo, fa0 = base + fo0;
        uint32_t af[16][4];
#pragma unroll
        for (int j = 0; j < 16; j++) {
          const int o = 64 * (j & 1) + 576 * (j >> 1);
          af[j][0] = lds32(((j & 1) ? fa : fa0) + o); af[j][1] = lds32(fa + o + 128); af[j][2] = lds32(fa + o + 32); af[j][3] = lds32(fa + o + 160);
        }
        STAMPIF(tid == 0, 40 + ch);
        mbar_wait(sb + 8 * B_E0, 0);
        const uint32_t e1 = epoch(sb);
        if (ch == 1) spin(t_0, UD1);
        u_wait(u0, u1, pu);
        sts128(base + KSZ + 16 * tid, u0);
        sts128(base + KSZ + 2048 + 16 * tid, u1);
        fence_async_s();
        float acc[128];
        const uint64_t db = mkdesc(base + KSZ, 32, 128, 0);
        bar_sync(1 + wg, 256);
        wg_fence();
        wgmma_rs_n64<0>(acc + 96, af[0], db + 192, 0);
        wgmma_rs_n192<0>(acc, af[0], db, 0);
        wgmma_rs_n64<0>(acc + 96, af[1], db + 196, 1);
        wgmma_rs_n192<0>(acc, af[1], db + 4, 1);
        wgmma_rs_n32<0>(acc + 96, af[2], db + 224, 1);
        wgmma_rs_n192<0>(acc, af[2], db + 32, 1);
        wgmma_rs_n32<0>(acc + 96, af[3], db + 228, 1);
        wgmma_rs_n192<0>(acc, af[3], db + 36, 1);
        wgmma_rs_n192<0>(acc, af[4], db + 64, 1);
        wgmma_rs_n192<0>(acc, af[5], db + 68, 1);
        wgmma_rs_n160<0>(acc, af[6], db + 96, 1);
        wgmma_rs_n160<0>(acc, af[7], db + 100, 1);
        if (CVT == 2) wg_commit();
        wgmma_rs_n128<0>(acc, af[8], db + 128, 1);
        wgmma_rs_n128<0>(acc, af[9], db + 132, 1);
        if (CVT == 1) wg_commit();
        wgmma_rs_n96<0>(acc, af[10], db + 160, 1);
        wgmma_rs_n96<0>(acc, af[11], db + 164, 1);
        if (CVT == 0) bar_arrive(2 - wg, 256);
        wgmma_rs_n64<0>(acc, af[12], db + 192, 1);
        wgmma_rs_n64<0>(acc, af[13], db + 196, 1);
        wgmma_rs_n32<0>(acc, af[14], db + 224, 1);
        wgmma_rs_n32<0>(acc, af[15], db + 228, 1);
        wg_commit();
        if (ZP == 0) {
          stg128((void*)pu, make_uint4(0, 0, 0, 0));
          stg128((void*)(pu + 256), make_uint4(0, 0, 0, 0));
        }
        if (tid < 2 && ch == (wg == (KV4C & 1) && KV4C < 5 ? KV4C : wg)) mbar_arrive(sb + 8 * (B_E1 + tid));
        if (CVT) { wg_wait<1>(); if (ch < 4) bar_arrive(2 - wg, 256); }
        STAMPIF(tid == 0, 3 + ch);
        if (ZP == 1) {
          stg128((void*)pu, make_uint4(0, 0, 0, 0));
          stg128((void*)(pu + 256), make_uint4(0, 0, 0, 0));
        }
        wg_wait<0>();
#pragma unroll
        for (int i = 0; i < 128; i++) asm volatile("" : "+f"(acc[i])::"memory");
        bar_sync(3 + wg, 128);
        if (tid <= (ch >> 2)) mbar_arrive(sb + 8 * (B_E1 + 2 + (ch >> 1)));
        float S0[33], T[34];
#pragma unroll
        for (int i = 0; i < 31; i++) S0[i] = acc[4 * i] + acc[4 * i + 6];
        S0[31] = acc[124]; S0[32] = 0.f;
#pragma unroll
        for (int i = 0; i < 32; i++) {
          float s1 = i < 31 ? acc[4 * i + 1] + acc[4 * i + 7] : acc[125];
          T[i] = (wrap ? S0[i + 1] : S0[i]) + __shfl_sync(0xffffffffu, s1, src1);
        }
        T[32] = 0.f; T[33] = 0.f;
        uint4* pz = (uint4*)(G->zT + (128 * ch + b) * S_) + ((tid & 120) | (2 * q) | (g & 1));
#pragma unroll
        for (int h = 0; h < 2; h++) {
          float y[8];
#pragma unroll
          for (int mu = 0; mu < 8; mu++) y[mu] = (b1 ? T[4 * mu + 4 + h] : T[4 * mu + h]) + __shfl_xor_sync(0xffffffffu, T[4 * mu + 2 + h], 16);
          pz[128 * h] = make_uint4(pack2(y[0], y[1]), pack2(y[2], y[3]), pack2(y[4], y[5]), tagged(pack2(y[6], y[7]), e1));
        }
        __syncwarp();
        if (lane == 0) mbar_arrive(sb + 8 * (B_Z + ch));
        if (ZP == 2) {
          stg128((void*)pu, make_uint4(0, 0, 0, 0));
          stg128((void*)(pu + 256), make_uint4(0, 0, 0, 0));
        }
        pu += 128 * S_ / 2;
        STAMPIF(tid == 0, 8 + ch);
      }
    }
    uint32_t hh[96];
    {
      float ga[192];
      float* ua = ga + 96;
      const uint64_t da0 = mkdesc(ring + wg * 2048, 512, 256, 3), db0 = mkdesc(ring + 8192, 4096, 1024, 1);
      int st = 0, ph = 0;
      mbar_wait(sb + 8 * B_BD, 0);
      const uint32_t e1 = epoch(sb);
      if (wg) {
        mod_box(G, sb, b, 1, e1, tid);
        __syncwarp();
        if (lane == 0) mbar_arrive(sb + 8 * (B_BD + 1));
        STAMPIF(tid == 0, 73);
      }
      const bool cs = b < 96;
      const int x0 = wg ? XI : 99,
                x1 = x0 + (cs ? 4 : 2), xs = cs ? 4 : 8;
      uint64_t xa = cs ? mkdesc(sb + SM_EXT, 4096, 1024, 1) : box_a(sb), xb = cs ? mkdesc(sb + SM_CB, 32, 128, 0) : box_b(sb);
      uint64_t ya = xa + (cs ? (SM_RING + R_X - SM_EXT) / 16 : 256), yb = xb + 16;
      float bx[4];
#pragma unroll 1
      for (int it = 0; it < 19; it++) {
        if (it == x0) {
          mbar_wait(sb + 8 * (cs ? B_F : B_BOX + 4), 0);
          mbar_wait(sb + 8 * (cs ? B_ST0 : B_BOX + 5), 0);
          STAMPIF(tid == 0, 76);
        }
        if (it == x1 + XW) {
          wg_wait<XW>();
#pragma unroll
          for (int i = 0; i < 4; i++) asm volatile("" : "+f"(bx[i])::"memory");
          if (!cs) mod_put(G, sb, bx, b, 2, e1, tid);
          else {
            const int row = (m < 6 ? 0 : 4) + q;
            uint16_t* dst = (uint16_t*)G->cimg + s * 3072 + (m % 6) * 512 + row * 64 + g;
#pragma unroll
            for (int j = 0; j < 2; j++) {
              const float c1 = __shfl_sync(0xffffffffu, bx[2 * j], lane & 28), c2 = __shfl_sync(0xffffffffu, bx[2 * j + 1], lane & 28);
              const float t = (lane & 2) ? c2 : c1, hi = rbf(t);
              dst[((2 * w + j) ^ row) << 3] = (uint16_t)pack2((lane & 1) ? t - hi : hi, 0.f);
            }
          }
          __syncwarp();
          if (lane == 0) mbar_arrive(sb + 8 * (B_BD + 2));
          STAMPIF(tid == 0, 77);
        }
        mbar_wait(sb + 8 * (B_F1 + st), ph);
        STAMPIF(tid == 0 && it == 0, 13 + wg);
        if (ITW == 1) STAMPIF(tid == 0 && it >= 10, 90 + it + 10 * wg);
        else if (ITW == 2) STAMPIF(tid == 0 && it < 10, 100 + it + 10 * wg);
        else if (ITW < 3) STAMPIF(threadIdx.x == ITW, 100 + it);
        const uint64_t da = da0 + st * 2048, db = db0 + st * 2048;
        if (it >= x0 && it < x1) {
          wg_fence();
          wgmma_ss_n8<1, 0>(bx, xa, xb, it != x0);
          wgmma_ss_n192<1, 1>(ga, da, db, 1);
          wgmma_ss_n8<1, 0>(bx, ya, yb, 1);
          wgmma_ss_n192<1, 1>(ua, da, db + 768, 1);
          wgmma_ss_n8<1, 0>(bx, ya + 128, yb + xs, 1);
          wgmma_ss_n192<1, 1>(ga, da + 256, db + 128, 1);
          wgmma_ss_n8<1, 0>(bx, ya + 256, yb + 2 * xs, 1);
          wgmma_ss_n192<1, 1>(ua, da + 256, db + 128 + 768, 1);
          wgmma_ss_n8<1, 0>(bx, ya + 384, yb + 3 * xs, 1);
          wg_commit();
          xa += 128; xb += xs; ya += 512; yb += 4 * xs;
        } else {
          wg_fence();
          wgmma_ss_n192<1, 1>(ga, da, db, it != 0);
          wgmma_ss_n192<1, 1>(ua, da, db + 768, it != 0);
          wgmma_ss_n192<1, 1>(ga, da + 256, db + 128, 1);
          wgmma_ss_n192<1, 1>(ua, da + 256, db + 128 + 768, 1);
          wg_commit();
        }
        wg_wait<1>();
        if (it > 0 && tid == 0) mbar_arrive(sb + 8 * (B_E1 + (st == 0 ? 4 : st - 1)));
        if (++st == 5) { st = 0; ph ^= 1; }
      }
      const uint32_t la = ring + wg * 2048 + tid * 16, ra = mapa(la, (b & 1) ^ 1), rp = mapa(sb + 8 * (B_PEER + 2 * wg), (b & 1) ^ 1), rb = rp + 8 * (B_RECV - B_PEER);
      uint32_t sa[24];
      auto addr = [&](int j) {
        sa[2 * j] = ra + (j < 2 ? 5 : (j >> 1) - 1) * 32768 + (j & 1) * 4096;
        sa[2 * j + 1] = (sa[2 * j] >> 31) + (rb + 8 * (j / 6));
        asm volatile("" : "+r"(sa[2 * j]), "+r"(sa[2 * j + 1]));
      };
      auto send = [&](int j) { st_async4(sa[2 * j], hh + 4 * j, sa[2 * j + 1]); };
      auto pack = [&](int c) {
#pragma unroll
        for (int i = 0; i < 64; i++) asm volatile("" : "+f"(ga[64 * c + i])::"memory");
#pragma unroll
        for (int i = 0; i < 4; i++) addr(4 * c + i);
#pragma unroll
        for (int i = 0; i < 16; i++) {
          const int j = 64 * c + 2 * i;
          hh[16 * c + i] = pack2(ga[j] * ga[j + 32], ga[j + 1] * ga[j + 33]);
          asm volatile("" : "+r"(hh[16 * c + i])::"memory");
          if ((i & 3) == 3 && 4 * c + i / 4 < NP) send(4 * c + i / 4);
          if (c == 2 && NQ > NP && i == 0) mbar_wait(sb + 8 * (B_PEER + 2 * wg), 0);
          if (c == 2 && (i & 3) == 3 && NP + i / 4 < NQ) send(NP + i / 4);
        }
      };
      STAMPIF(threadIdx.x == 0, 61);
      mbar_wait(sb + 8 * (B_F1 + 4), 1);
      mbar_wait(sb + 8 * B_EXT, 0);
      mbar_wait(sb + 8 * B_ST2, 0);
      const uint64_t de = mkdesc(sb + SM_EXT, 1024, 0, 1), ds = mkdesc(sb + SM_STAT + wg * 1024, 0, 128, 0);
#pragma unroll
      for (int c = 0; c < 2; c++) {
        wg_fence();
        wgmma_ss_n192<1, 1>(ga + 96 * c, da0 + 8192, db0 + 8192 + 768 * c, 1);
        wgmma_ss_n192<1, 1>(ga + 96 * c, da0 + 8192 + 256, db0 + 8192 + 128 + 768 * c, 1);
        wgmma_ss_n192<0, 1>(ga + 96 * c, ds, de + 192 * c, 1);
        wg_commit();
        if (c == 0) { mbar_wait(sb + 8 * B_P0, 0); mbar_wait(sb + 8 * B_FB, 0); }
        wg_wait<1>();
        if (c == 0 && tid == 0) {
          mbar_arrive(sb + 8 * (B_E1 + 3));
          mbar_arrive_remote(rp);
        }
      }
      STAMPIF(tid == 0, 15 + wg);
      float acc[64], rs[2] = {};
      uint4 pf[4], gb = {};
      uint32_t ln, os, ol, og;
      const char *po, *pq;
      const uint64_t dd0 = mkdesc(ring + 8192, 0, 1024, 1);
      bool ok = false;
#pragma unroll
      for (int c = 0; c < 3; c++) {
        pack(c);
        if (c == 1) ok = mbar_try(sb + 8 * (B_FB + 1), 0);
        STAMPIF(tid == 0 && c == 0, wg ? 89 : 121);
        if (ITW == 3) STAMPIF(tid == 0 && c > 0, 99 + c + 10 * wg);
        wg_fence();
#pragma unroll
        for (int k = 4 * c; k < 4 * c + 4; k++) wgmma_rs_n64<1>(acc, hh + 4 * k, dd0 + 5 * 2048 + 128 * k, k);
        wg_commit();
        if (c == 0) {
          wg_wait<1>();
          if (tid == 0) {
            mbar_arrive(sb + 8 * (B_E1 + 4));
            mbar_arrive_remote(rp + 8);
          }
        }
        if (c == 1 && !ok) mbar_wait(sb + 8 * (B_FB + 1), 0);
      }
      auto recv = [&](int j) {
        const uint4 v = lds128(la + (j < 2 ? 5 : (j >> 1) - 1) * 32768 + (j & 1) * 4096);
        hh[48 + 4 * j] = v.x; hh[49 + 4 * j] = v.y; hh[50 + 4 * j] = v.z; hh[51 + 4 * j] = v.w;
      };
      auto stage = [&](const float* a, int i) {
        const uint32_t v[4] = {pack2(a[8 * i] * rs[0], a[8 * i + 1] * rs[0]), pack2(a[8 * i + 2] * rs[1], a[8 * i + 3] * rs[1]),
                               pack2(a[8 * i + 4] * rs[0], a[8 * i + 5] * rs[0]), pack2(a[8 * i + 6] * rs[1], a[8 * i + 7] * rs[1])};
        stsm4(os + 32 * i, v);
      };
      auto fetch = [&](int p) {
        __syncwarp();
#pragma unroll
        for (int i = 0; i < 4; i++) pf[i] = lds128(ol + 576 * i);
      };
      auto next = [&](int p) {
        gb = lds128(og + 256 * out_blk(s, p));
        pq = po + 128 * out_blk(s, p);
        asm volatile("" : "+l"(pq));
      };
      auto add = [&](int p, int i) {
        asm volatile("red.relaxed.gpu.global.add.noftz.v4.bf16x2 [%0], {%1, %2, %3, %4};" ::"l"(pq - (i & 1) * 2048 * D_ - (i >> 1) * 2 * D_),
                     "r"(hmul(pf[i].x, gb.x)), "r"(hmul(pf[i].y, gb.y)), "r"(hmul(pf[i].z, gb.z)), "r"(hmul(pf[i].w, gb.w)) : "memory");
      };
#pragma unroll
      for (int h = 2; h < 20; h++) {
        const int gr = h >> 1, pe = gr < 4 ? gr >> 1 : gr & 1, ac = (gr < 4 ? gr : gr >> 1) & 1;
        const int ep = h == 7 || h == 8 ? 0 : h > 8 && (h & 3) == 1 || h > 8 && (h & 3) == 2 ? (h >> 2) - 1 : -1;
        if (!(h & 1) && h > 2 && !(PT && ok)) mbar_wait(sb + 8 * (B_FB + gr), 0);
        if (h == LH0 || h == LH1) mbar_wait(sb + 8 * (B_RECV + 2 * wg + (h == LH1)), 0);
        if (h == LH0 && (h == 4 || !LM) || h == LH1 && (h == 5 || !LM)) {
#pragma unroll
          for (int j = 0; j < 6; j++) recv(6 * (h == LH1) + j);
        }
        if (h == SPOS(6) / 6 && NQ <= 6) mbar_wait(sb + 8 * (B_PEER + 2 * wg), 0);
        if (h == SPOS(10) / 6) mbar_wait(sb + 8 * (B_PEER + 2 * wg + 1), 0);
        if (h == 6) {
          mbar_wait(sb + 8 * B_X1, 0);
          mbar_wait(sb + 8 * B_GB, 0);
          asm volatile("mov.u32 %0, %%laneid;" : "=r"(ln));
#pragma unroll
          for (int i = 0; i < 2; i++) rs[i] = blo(lds32(sb + SM_STAT + (4 * wg + w) * 256 + (ln & 28) * 4 + 128 * i + 4));
        }
        STAMPIF(tid == 0 && h % 4 == 0 && h < 16, (wg ? 89 : 121) + h / 4);
        STAMPIF(tid == 0 && h == 16, wg ? 97 : 96);
        if (ITW == 3) STAMPIF(tid == 0 && h < 10, 100 + h + 10 * wg);
        if (ITW == 4) STAMPIF(tid == 0 && h >= 10, 90 + h + 10 * wg);
        const uint64_t db = dd0 + (((gr + 5) % 6) * 2048 + (gr << 16));
        if (PT && (h & 1) && h < 19) ok = mbar_try(sb + 8 * (B_FB + gr + 1), 0);
        wg_fence();
#pragma unroll
        for (int j = 0; j < 6; j++) {
          const int k = 6 * (h & 1) + j;
          wgmma_rs_n64<1>(acc + 32 * ac, hh + 48 * pe + 4 * k, db + 128 * k, pe || k);
#pragma unroll
          for (int i = NQ; i < 12; i++) if (SPOS(i) == 6 * h + j) send(i);
          if (LM && h == LH0 && h < 4) { recv(j); wg_fence(); }
          if (LM && h == LH1 && h < 5) { recv(6 + j); wg_fence(); }
          if (ep >= 0 && (h & 1)) {
            if (j < 4) stage(acc + 32 * (1 - ac), j);
            if (j == 4) fetch(ep);
          }
          if (ep >= 0 && !(h & 1) && j > 0 && j < 5) add(ep, j - 1);
          if (ep >= 0 && !(h & 1) && j == 5) next(ep + 1);
        }
        wg_commit();
        STAMPIF(tid == 0 && h == 3, 81);
        if (h == 6) {
#pragma unroll
          for (int i = 0; i < 2; i++) rs[i] = __fdividef(0.25f, rs[i] * rs[i]);
          const uint32_t ob = sb + SM_X + (4 * wg + w) * 2304;
          os = ob + (ln & 15) * 144 + (ln & 16); ol = ob + (ln >> 3) * 16 + ln * 16;
          po = (const char*)(gout + (1793 + 2 * tbase(8 * m + 4 * wg + w)) * D_) + (int)(640 * (s & 1) + 16 * ln - (ln >> 3) * (512 * D_ + 128));
          og = sb + SM_CB + 32 * (ln & 7);
          asm volatile("" : "+r"(os), "+r"(ol), "+r"(og), "+l"(po));
          next(0);
        }
        if (h == 2 || h == 4 || h == 6 || h == 8 || h == 12 || h == 16) {
          wg_wait<1>();
          if (h < 12 && tid == 0) mbar_arrive(sb + 8 * (B_EB + gr - 1));
          if (h >= 6) {
#pragma unroll
            for (int j = 0; j < 32; j++) asm volatile("" : "+f"(acc[32 * (1 - ac) + j])::"memory");
          }
        }
      }
      STAMPIF(tid == 0, wg ? 95 : 93);
      wg_wait<0>();
#pragma unroll
      for (int i = 0; i < 32; i++) asm volatile("" : "+f"(acc[i])::"memory");
      STAMPIF(tid == 0, wg ? 50 : 18);
#pragma unroll
      for (int i = 0; i < 4; i++) stage(acc, i);
      fetch(4);
#pragma unroll
      for (int i = 0; i < 4; i++) add(4, i);
    }
  } else if (wg == 2) {
    asm volatile("setmaxnreg.dec.sync.aligned.u32 40;");
    const uint32_t e1 = (rdback(G->flag + 8 * m + 4) >> 5) + 1;
    if (tid < 80) {
      uint4 c = ((const uint4*)gc)[tid];
#pragma unroll 1
      for (int i = 0; i < 4; i++) {
        const float lo = blo(c.x), hi = bhi(c.x);
        sts32(sb + SM_STAT + 16 * tid + 4 * i, pack2(__fdividef(lo, 1.f + __expf(-lo)), __fdividef(hi, 1.f + __expf(-hi))));
        c.x = c.y; c.y = c.z; c.z = c.w;
      }
    }
    if (tid == 0) { sts32(sb + SM_SMALL + SMALL_E, e1); mbar_arrive(sb + 8 * B_E0); }
    fence_async_s();
    bar_sync(5, 128);
    int tl = tid;
#pragma unroll 1
    for (uint64_t pr = AUXP; pr; pr >>= 4) {
      asm volatile("" : "+r"(tl));
      const int op = pr & 15, tid = tl, lane = tid & 31;
      if (op == 0) {
        ln1_job(sb, tid);
      } else if (op < 4) {
        kv_job(G, sb, b, op + 1, tid);
        STAMPIF(tid == 0, 21 + op);
      } else if (op < 11) {
        if (mod_first(b)) mod_box(G, sb, b, 0, e1, tid);
        __syncwarp();
        if (lane == 0) mbar_arrive(sb + 8 * B_BD);
        STAMPIF(tid == 0, 27);
      } else {
        const int r = op - 11, cg = 8 * r + 4 * (w >> 1) + (lane & 2) + (w & 1), g = lane >> 2;
        const uint2* pz = (const uint2*)(G->zT + (16 * cg + g) * S_ + 16 * b + 8 * (lane & 1));
        const uint32_t* pc = G->mv + 2048 * (e1 & 1) + 8 * cg + g;
        const uint32_t la = sb + SM_SMALL + SMALL_LN + 16 * (lane & 1);
        uint32_t xa = x_addr(sb, w, lane) + 4096 * r, ao = ((40 * m + cg) * 8 + s) * 32 + 2 * g + ((lane ^ (lane >> 4)) & 1), xn[8], xv[8];
        const uint4 m4 = lds128(la), s4 = lds128(la + 32);
        const uint32_t m_[4] = {m4.x, m4.y, m4.z, m4.w}, s_[4] = {s4.x, s4.y, s4.z, s4.w};
        ldsm4t(xv, xa);
        ldsm4t(xv + 4, xa ^ 16);
#pragma unroll
        for (int j = 0; j < 8; j++) {
          xn[j] = hmul(hsub(xv[j], m_[j & 3]), s_[j & 3]);
          asm volatile("" : "+r"(xn[j]));
        }
        asm volatile("" : "+r"(ao));
        mbar_wait(sb + 8 * (B_BD + (r > 1)), 0);
        mbar_wait(sb + 8 * (B_Z + r), 0);
        STAMPIF(tid == 0 && r == 0, 28);
        uint4 z[2] = {ld_tag2(pz), ld_tag2(pz + 4096)};
        uint32_t c[4] = {rdback(pc), rdback(pc + 320), rdback(pc + 640), rdback(pc + 1280)};
        z_wait(z[0], z[1], c, pz, pc, e1);
        asm volatile("" : "+r"(xa));
        STAMPIF(tid == 0 && r == 0, 83);
        uint4* pa = (uint4*)G->AT + ao;
#pragma unroll
        for (int j = 0; j < 4; j++) c[j] = ~c[j];
#pragma unroll
        for (int n = 0; n < 2; n++) {
          const uint32_t z_[4] = {z[n].x, z[n].y, z[n].z, z[n].w}, sel = n ? 0x3232 : 0x1010;
          const uint32_t sa = __byte_perm(c[0], 0, sel), ca1 = __byte_perm(c[1], 0, sel), ga = __byte_perm(c[2], 0, sel), cb1 = __byte_perm(c[3], 0, sel);
          uint32_t o[4], a[4];
#pragma unroll
          for (int j = 0; j < 4; j++) {
            o[j] = hfma(ga, hmul(hfma(xn[4 * n + j], ca1, sa), z_[j]), xv[4 * n + j]);
            a[j] = hmul(o[j], cb1);
          }
          a[2 * n + 1] = tagged(a[2 * n + 1], e1);
          pa[16 * n] = make_uint4(a[0], a[1], a[2], a[3]);
          if (n) { __syncwarp(); if (elect()) flag_add(G, 8 * m + r); }
          stsm4t(xa ^ (16 * n), o);
        }
        __syncwarp();
        {
          int lane;
          asm volatile("mov.u32 %0, %%laneid;" : "=r"(lane));
          const int c = 2 * (w & 1) + (lane & 1) + 2 * (lane & 2), g = lane >> 2;
          const uint32_t a = sb + SM_X + 4096 * r + (w >> 1) * 2048 + g * 128 + ((c ^ g) << 4);
          const uint4 v0 = lds128(a), v1 = lds128(a + 1024);
          char* po = (char*)gout + (2 * tbase(b) + 128 * (g & 6) + (g & 1)) * 2 * D_ + 256 * r + 64 * (w & 2) + 16 * c;
          stg128(po, v0);
          stg128(po + 2048 * D_, v1);
        }
        __syncwarp();
        if (elect()) mbar_arrive(sb + 8 * (B_EW + r));
        STAMPIF(tid == 0, 29 + r);
      }
      if (op == kLastKv) { __syncwarp(); if (elect()) mbar_arrive(sb + 8 * B_KVS); }
    }
    {
      const uint4 m4 = lds128(sb + SM_SMALL + SMALL_LN + 16 * (lane & 1));
      const uint32_t m_[4] = {m4.x, m4.y, m4.z, m4.w}, xa = x_addr(sb, w, lane);
      float a[16];
#pragma unroll
      for (int i = 0; i < 16; i++) a[i] = 0.f;
#pragma unroll 2
      for (int n = 0; n < 10; n++) {
        uint32_t x_[4];
        ldsm4t(x_, (xa ^ (16 * (n & 1))) + 2048 * (n & 14));
#pragma unroll
        for (int i = 0; i < 4; i++) {
          const float d0 = blo(x_[i]) - blo(m_[i]), d1 = bhi(x_[i]) - bhi(m_[i]);
          a[4 * i] += d0; a[4 * i + 1] += d0 * d0; a[4 * i + 2] += d1; a[4 * i + 3] += d1 * d1;
        }
      }
      STAMPIF(lane == 0, 67 + (w & 1) + 11 * (w >> 1));
      bfly<16>(a, 16, lane & 16); bfly<8>(a, 8, lane & 8); bfly<4>(a, 4, lane & 4); bfly<2>(a, 2, lane & 2);
      if (lane == 0) mbar_arrive(sb + 8 * B_XF);
      STAMPIF(tid == 0, 88);
      sts32(sb + SM_SMALL + SMALL_RED + 16 * lane + 4 * w, __float_as_uint(a[0]));
      bar_sync(5, 128);
      if (w == 0) {
        const uint4 v = lds128(sb + SM_SMALL + SMALL_RED + 16 * lane);
        const float s1 = __uint_as_float(v.x) + __uint_as_float(v.y) + __uint_as_float(v.z) + __uint_as_float(v.w), s2 = __shfl_xor_sync(0xffffffffu, s1, 2);
        const int p = 8 * (lane & 1) + (lane >> 2);
        const float pv = blo(lds32(sb + SM_SMALL + SMALL_LN + 4 * (p >> 1)) >> (16 * (p & 1)));
        const float mu = s1 * (1.f / D_), var = fmaxf(s2 * (1.f / D_) - mu * mu, 0.f);
        const float sd = rbf(__fsqrt_rn(rbf(rbf(var) + 1e-5f)));
        if (!(lane & 2)) st_tag(G->st2 + 16 * b + p, pack2(-0.5f * (pv + mu), 0.5f * sd), e1);
      }
      STAMPIF(tid == 0, 87);
    }
    {
      uint2 v;
      spin(clk(), SD);
      mbar_wait(sb + 8 * (B_BD + 2), 0);
#pragma unroll 1
      for (int i = 0;; i++) {
        v = ld_tag(G->st2 + 128 * m + tid);
        if (__all_sync(0xffffffffu, v.y == e1)) break;
        if (i > (1 << 20)) __trap();
      }
      const uint32_t hm = __byte_perm(v.x, 0, 0x1010), hs = __byte_perm(v.x, 0, 0x3232);
      sts128(sb + SM_STAT + 16 * tid, make_uint4(hm, hs, hm, hs));
      fence_async_s();
      __syncwarp();
      if (lane == 0) mbar_arrive(sb + 8 * B_ST2);
      STAMPIF(tid == 0, 21);
    }
  } else {
    asm volatile("setmaxnreg.dec.sync.aligned.u32 24;");
    if (w != 0) {
    if (w == 2 && lane < 3) asm volatile("prefetch.tensormap [%0];" ::"l"(&P.mG + lane) : "memory");
    if (w & 1) {
#pragma unroll 1
      for (int j = 4; j < 10; j++) {
        k1_job(sb, j >> 1, 64 * (j & 1) + 16 * (w & 2) + lane, *(const uint16_t*)(gD + 64 * (j & 14) + b));
        if (UD && w == 1 && (j & 1)) {
          mbar_wait(sb + 8 * (B_KJ + (j >> 1)), 0);
          const uint32_t t = lds32(sb + SM_SMALL + SMALL_TS + 4 * (j >> 1));
          while (clk() - t < UD);
        }
        __syncwarp();
        if (lane == 0) mbar_arrive(sb + 8 * (B_K + (j >> 1) - 2));
      }
      STAMPIF(tid == 32, 74);
    }
    if (w == 1) {
     {
      mbar_wait(sb + 8 * B_KVS, 0);
      const uint32_t e1 = epoch(sb);
      if (elect()) {
        mbar_wait(sb + 8 * B_EW, 0);
#pragma unroll 1
        for (int it = 0; it < 20; it++) {
          int st = it % 5;
          if ((it & 3) == 0) { flag_wait(G, 8 * m + (it >> 2), e1 * 32); STAMP(45 + (it >> 2)); }
          mbar_wait(sb + 8 * (B_E1 + st), (it / 5) & 1);
          uint32_t fb = sb + 8 * (B_A + st);
          mbar_expect(fb, 8192);
          bulk_g2s(ring + st * 32768, G->AT + (20 * m + it) * 4096, 8192, fb);
        }
        mbar_wait(sb + 8 * B_XF, 0);
        flag_wait(G, 8 * m + FL_X, e1 * 8);
        mbar_arrive(sb + 8 * B_X1);
        STAMP(86);
      }
     }
    } else if (w == 2) {
      if (lane < 4) mbar_expect(sb + 8 * (B_RECV + lane), 12288);
      mbar_wait(sb + 8 * B_BD, 0);
      const uint32_t e1 = epoch(sb), ao = 256 * (lane & 16) + 32 * (lane & 15) + 4 * (lane & 4) + (lane & 8) + 4;
#pragma unroll 1
      for (int it = 0; it < 20; it++) {
        const int st = it % 5;
        const uint32_t a = ring + st * 32768 + ao;
        mbar_wait(sb + 8 * (B_A + st), (it / 5) & 1);
        uint32_t t = 0;
#pragma unroll
        for (int j = 0; j < 8; j++) t |= lds32(a + 512 * j) ^ e1;
        if (__any_sync(0xffffffffu, t & 1)) {
#pragma unroll 1
          for (int j = 0; j < 8; j++) a_check(a + 512 * j, (const char*)G->AT + (20 * m + it) * 8192 + ao + 512 * j, e1);
        }
        if (lane == 0) mbar_arrive(sb + 8 * (B_F1 + st));
      }
    } else {
      mbar_wait(sb + 8 * B_KVS, 0);
      mbar_wait(sb + 8 * (B_BD + 1), 0);
      if (b >= 96 && elect()) { load_box(P, sb, b, 4); load_box(P, sb, b, 5); }
      spin(clk(), CD);
      __syncwarp();
      const uint32_t e1 = epoch(sb);
#pragma unroll 1
      for (int n = 0; n < 5; n++) {
        int lane;
        asm volatile("mov.u32 %0, %%laneid;" : "=r"(lane));
        if (n == 3) {
          fence_async_s();
          __syncwarp();
          if (lane == 0) mbar_arrive(sb + 8 * B_F);
          STAMPIF(lane == 0, 34);
          {
            mbar_wait(sb + 8 * (B_EW + 4), 0);
            const char* po = (char*)gout + (2 * tbase(b) + 64 * (lane & 28) + ((lane >> 1) & 1)) * 2 * D_ + (lane & 1) * 640;
            uint32_t v = 0;
#pragma unroll
            for (int r = 0; r < 5; r++) v ^= rdback(po + 128 * r);
            rdwait(sb, v);
            __syncwarp();
            if (lane == 0) flag_add(G, 8 * m + FL_X);
            STAMPIF(lane == 0, 94);
          }
          mbar_wait(sb + 8 * (B_BD + 2), 0);
          if (lane < 2) mbar_arrive(sb + 8 * (B_E1 + 5));
          if (m < 12) {
            rdwait(sb, rdback(G->cimg + s * 3072 + (m % 6) * 512 + (m < 6 ? 0 : 256) + 64 * (lane & 3)));
            __syncwarp();
            if (lane == 0) flag_add(G, FL_C + 8 * s);
            STAMPIF(lane == 0, 35);
          }
          if (elect()) {
            flag_wait(G, FL_C + 8 * s, e1 * 12);
            fence_async_g();
            STAMP(54);
            mbar_expect(sb + 8 * B_EXT, 6144);
            bulk_g2s(sb + SM_EXT, G->cimg + s * 3072, 6144, sb + 8 * B_EXT);
          }
          __syncwarp();
          mbar_wait(sb + 8 * B_ST2, 0);
        }
        const int j = n < 3 ? min(16 * n + (lane >> 1), 39) : min(16 * n - 8 + (lane >> 1), 59), k = j < 20 ? j : j < 40 ? j - 20 : j - 40;
        const uint2* pj = (const uint2*)(G->mv + 2048 * (e1 & 1) + 4 * (lane & 1) + 8 * (k + (j < 40 ? (j < 20 ? 160 : 120) + (m < 6 ? 0 : 20) : 200 + 20 * (s & 1))));
        uint4 a;
#pragma unroll 1
        for (int i = 0;; i++) {
          a = ld_tag2(pj);
          if (__all_sync(0xffffffffu, a.x != 0)) break;
          if (i > (1 << 20)) __trap();
        }
        const uint32_t d = sb + SM_CB + 64 * k + 8 * (lane & 1) + (j >= 20 && j < 40 ? 16 : 0);
        sts64(d, ~__byte_perm(a.x, a.y, 0x5410), ~__byte_perm(a.z, a.w, 0x5410));
        sts64(d + 32, ~__byte_perm(a.x, a.y, 0x7632), ~__byte_perm(a.z, a.w, 0x7632));
      }
      __syncwarp();
      if (lane == 0) mbar_arrive(sb + 8 * B_GB);
      STAMPIF(lane == 0, 39);
    }
    } else {
      STAMPIF(lane == 0, 62);
      int rw = sched_run<0>(P, In{gk, gv, gsk, gWg, gWu, gWd, gss}, sb, b, lane, __shfl_sync(0xffffffffu, t_0, 0));
      if (elect()) {
        STAMP(69);
        mbar_wait(sb + 8 * B_KVS, 0);
        STAMP(70);
        int rd = 0, c = 0;
#pragma unroll 1
        for (int it = 0; it < 20; it++) {
          load_w(P, sb, s, it);
          if ((PWM >> it) & 1) { l2_prefetch(gWg + (128 * rw + b) * F_, 2 * F_); l2_prefetch(gWu + (128 * rw + b) * F_, 2 * F_); rw++; }
          if ((PDM >> it) & 1) { l2_prefetch(gWd + (512 * rd + 4 * b) * D_, 8 * D_); rd++; }
          if (((STM >> it) & 1) && b < 96) {
            const int grp = m % 6;
            if (c == 4) mbar_wait(sb + 8 * (B_BD + 1), 0);
            if (c == 0) mbar_expect(sb + 8 * B_ST0, 40960);
#pragma unroll
            for (int j = 0; j < 2; j++, c++)
              tma2d(sb + (c < 2 ? SM_EXT : SM_RING + R_X - 8192) + 4096 * c, &P.mG + (grp & 1), 192 * s + 64 * (grp >> 1), (m < 6 ? 0 : 320) + 32 * c, sb + 8 * B_ST0);
          }
        }
#pragma unroll
        for (int k = 0; k < 10; k++) {
          const int st = (k + 5) % 6, pe = k < 4 ? k >> 1 : k & 1, ps = k < 4 ? k & 1 : k >> 1;
          mbar_wait(sb + 8 * (k < 6 ? B_E1 + st : B_EB + k - 6), 0);
          if (k == 2) mbar_arrive_remote(mapa(sb + 8 * B_P0, (b & 1) ^ 1));
          mbar_expect(sb + 8 * (B_FB + k), 24576);
          tma2d(ring + st * 32768 + 8192, &P.mD, 320 * (s & 1) + 64 * out_blk(s, ps), 192 * (s ^ pe), sb + 8 * (B_FB + k));
        }
      }
    }
  }
}

typedef CUresult (*EncFn)(CUtensorMap*, CUtensorMapDataType, cuuint32_t, void*, const cuuint64_t*, const cuuint64_t*, const cuuint32_t*, const cuuint32_t*,
                          CUtensorMapInterleave, CUtensorMapSwizzle, CUtensorMapL2promotion, CUtensorMapFloatOOBfill);
static void mkmap(EncFn enc, CUtensorMap* m, const void* p, int rank, const cuuint64_t* dims, const cuuint64_t* strides, const cuuint32_t* box, CUtensorMapSwizzle sw) {
  cuuint32_t es[5] = {1, 1, 1, 1, 1};
  CUresult r = enc(m, CU_TENSOR_MAP_DATA_TYPE_BFLOAT16, rank, (void*)p, dims, strides, box, es, CU_TENSOR_MAP_INTERLEAVE_NONE, sw,
                   CU_TENSOR_MAP_L2_PROMOTION_L2_128B, CU_TENSOR_MAP_FLOAT_OOB_FILL_NONE);
  if (r != CUDA_SUCCESS) fprintf(stderr, "tensor map encode failed: %d\n", (int)r);
}

extern "C" void kernel_launch(void* const* d_in, const int* in_sizes, int n_in, void* d_out, int out_size) {
  void* fn = nullptr;
  cudaDriverEntryPointQueryResult qr;
  cudaGetDriverEntryPoint("cuTensorMapEncodeTiled", &fn, cudaEnableDefault, &qr);
  EncFn enc = (EncFn)fn;
  Scr* G;
  cudaGetSymbolAddress((void**)&G, g_scr);
  Params P;
  { cuuint64_t d[] = {128, 16, 640}, st[] = {256, 4096}; cuuint32_t bx[] = {144, 16, 1}; mkmap(enc, &P.mS, d_in[4], 3, d, st, bx, CU_TENSOR_MAP_SWIZZLE_NONE); }
  { cuuint64_t d[] = {3840, 64, 10}, st[] = {7680, 64 * 7680}; cuuint32_t bx[] = {16, 64, 5}; mkmap(enc, &P.mWm, d_in[11], 3, d, st, bx, CU_TENSOR_MAP_SWIZZLE_32B); }
  { cuuint64_t d[] = {32, 20, 256, 8}, st[] = {64, 10240, 1280}; cuuint32_t bx[] = {40, 1, 9, 8}, bx2[] = {40, 1, 8, 8};
    mkmap(enc, &P.mK, d_in[1], 4, d, st, bx, CU_TENSOR_MAP_SWIZZLE_NONE); mkmap(enc, &P.mV, d_in[2], 4, d, st, bx2, CU_TENSOR_MAP_SWIZZLE_NONE); }
  { cuuint64_t d[] = {1536, 640}, st[] = {3072}; cuuint32_t bx[] = {64, 32};
    mkmap(enc, &P.mG, d_in[7], 2, d, st, bx, CU_TENSOR_MAP_SWIZZLE_128B); mkmap(enc, &P.mU, d_in[8], 2, d, st, bx, CU_TENSOR_MAP_SWIZZLE_128B); }
  { cuuint64_t d[] = {640, 1536}, st[] = {1280}; cuuint32_t bx[] = {64, 192}; mkmap(enc, &P.mD, d_in[9], 2, d, st, bx, CU_TENSOR_MAP_SWIZZLE_128B); }
  { cuuint64_t d[] = {64, 2, 8, 10, 128}, st[] = {1280, 256 * 1280, 128, 2560}; cuuint32_t bx[] = {64, 2, 8, 5, 1}; mkmap(enc, &P.mX, d_in[0], 5, d, st, bx, CU_TENSOR_MAP_SWIZZLE_128B); }
  cudaFuncSetAttribute(fused_kernel, cudaFuncAttributeMaxDynamicSharedMemorySize, SM_TOTAL + DEVSM);
  cudaLaunchConfig_t cfg = {};
  cfg.gridDim = dim3(128); cfg.blockDim = dim3(512); cfg.dynamicSmemBytes = SM_TOTAL + DEVSM; cfg.stream = cudaStreamPerThread;
  cudaLaunchAttribute at[1];
  at[0].id = cudaLaunchAttributeClusterDimension; at[0].val.clusterDim.x = 2; at[0].val.clusterDim.y = 1; at[0].val.clusterDim.z = 1;
  cfg.attrs = at; cfg.numAttrs = 1;
  cudaLaunchKernelEx(&cfg, fused_kernel, (const bf16*)d_in[1], (const bf16*)d_in[2], (const bf16*)d_in[3], (const bf16*)d_in[5], (const bf16*)d_in[10], G,
                     (const bf16*)d_in[7], (const bf16*)d_in[8], (const bf16*)d_in[9], (bf16*)d_out, (const bf16*)d_in[4], P);
}
```

```cpp
#include <cuda_runtime.h>
#include <cuda.h>
#include <cuda_bf16.h>
#include <stdio.h>
#include <stdint.h>
typedef __nv_bfloat16 bf16;
__device__ __forceinline__ uint32_t smem_u32(const void* p) { return (uint32_t)__cvta_generic_to_shared(p); }
__device__ __forceinline__ void mbar_init(uint32_t bar, int cnt) { asm volatile("mbarrier.init.shared::cta.b64 [%0], %1;" ::"r"(bar), "r"(cnt) : "memory"); }
__device__ __forceinline__ void mbar_expect(uint32_t bar, int bytes) { asm volatile("mbarrier.arrive.expect_tx.shared::cta.b64 _, [%0], %1;" ::"r"(bar), "r"(bytes) : "memory"); }
__device__ __forceinline__ void mbar_arrive(uint32_t bar) { asm volatile("mbarrier.arrive.shared::cta.b64 _, [%0];" ::"r"(bar) : "memory"); }
__device__ __forceinline__ void mbar_arrive_remote(uint32_t bar) { asm volatile("mbarrier.arrive.relaxed.cluster.shared::cluster.b64 _, [%0];" ::"r"(bar) : "memory"); }
__device__ __forceinline__ uint32_t mapa(uint32_t a, uint32_t cta) { uint32_t r; asm("mapa.shared::cluster.u32 %0, %1, %2;" : "=r"(r) : "r"(a), "r"(cta)); return r; }
__device__ __forceinline__ bool mbar_try(uint32_t bar, int parity) {
  uint32_t ok;
  asm volatile("{\n.reg .pred p;\nmbarrier.try_wait.parity.shared::cta.b64 p, [%1], %2;\nselp.u32 %0, 1, 0, p;\n}" : "=r"(ok) : "r"(bar), "r"(parity) : "memory");
  return ok;
}
__device__ __forceinline__ void mbar_wait(uint32_t bar, int parity) {
#pragma unroll 1
  for (int i = 0; i < (1 << 20); i++) { if (mbar_try(bar, parity)) return; }
  __trap();
}
__device__ __forceinline__ bool elect() {
  uint32_t p;
  asm volatile("{\n.reg .pred P;\nelect.sync _|P, 0xffffffff;\nselp.u32 %0, 1, 0, P;\n}" : "=r"(p));
  return p;
}
__device__ __forceinline__ void tma2d(uint32_t dst, const CUtensorMap* m, int c0, int c1, uint32_t bar) {
  asm volatile("cp.async.bulk.tensor.2d.shared::cluster.global.mbarrier::complete_tx::bytes [%0], [%1, {%3, %4}], [%2];" ::"r"(dst), "l"(m), "r"(bar), "r"(c0), "r"(c1) : "memory");
}
__device__ __forceinline__ void tma3d(uint32_t dst, const CUtensorMap* m, int c0, int c1, int c2, uint32_t bar) {
  asm volatile("cp.async.bulk.tensor.3d.shared::cluster.global.mbarrier::complete_tx::bytes [%0], [%1, {%3, %4, %5}], [%2];" ::"r"(dst), "l"(m), "r"(bar), "r"(c0), "r"(c1), "r"(c2) : "memory");
}
__device__ __forceinline__ void tma4d(uint32_t dst, const CUtensorMap* m, int c0, int c1, int c2, int c3, uint32_t bar) {
  asm volatile("cp.async.bulk.tensor.4d.shared::cluster.global.mbarrier::complete_tx::bytes [%0], [%1, {%3, %4, %5, %6}], [%2];" ::"r"(dst), "l"(m), "r"(bar), "r"(c0), "r"(c1), "r"(c2), "r"(c3) : "memory");
}
__device__ __forceinline__ void tma5d(uint32_t dst, const CUtensorMap* m, int c0, int c1, int c2, int c3, int c4, uint32_t bar) {
  asm volatile("cp.async.bulk.tensor.5d.shared::cluster.global.mbarrier::complete_tx::bytes [%0], [%1, {%3, %4, %5, %6, %7}], [%2];" ::"r"(dst), "l"(m), "r"(bar), "r"(c0), "r"(c1), "r"(c2), "r"(c3), "r"(c4) : "memory");
}
__device__ __forceinline__ void tma_store2d(const CUtensorMap* m, uint32_t src, int c0, int c1) {
  asm volatile("cp.async.bulk.tensor.2d.global.shared::cta.bulk_group [%0, {%2, %3}], [%1];" ::"l"(m), "r"(src), "r"(c0), "r"(c1) : "memory");
}
__device__ __forceinline__ void tma_store4d(const CUtensorMap* m, uint32_t src, int c0, int c1, int c2, int c3) {
  asm volatile("cp.async.bulk.tensor.4d.global.shared::cta.bulk_group [%0, {%2, %3, %4, %5}], [%1];" ::"l"(m), "r"(src), "r"(c0), "r"(c1), "r"(c2), "r"(c3) : "memory");
}
__device__ __forceinline__ void tma_prefetch2d(const CUtensorMap* m, int c0, int c1) {
  asm volatile("cp.async.bulk.prefetch.tensor.2d.L2.global [%0, {%1, %2}];" ::"l"(m), "r"(c0), "r"(c1) : "memory");
}
__device__ __forceinline__ void bulk_g2s(uint32_t dst, const void* src, int bytes, uint32_t bar) {
  asm volatile("cp.async.bulk.shared::cluster.global.mbarrier::complete_tx::bytes [%0], [%1], %2, [%3];" ::"r"(dst), "l"(src), "r"(bytes), "r"(bar) : "memory");
}
__device__ __forceinline__ void bulk_s2g(void* dst, uint32_t src, int bytes) {
  asm volatile("cp.async.bulk.global.shared::cta.bulk_group [%0], [%1], %2;" ::"l"(dst), "r"(src), "r"(bytes) : "memory");
}
__device__ __forceinline__ void cp16(uint32_t dst, const void* src) { asm volatile("cp.async.cg.shared.global [%0], [%1], 16;" ::"r"(dst), "l"(src) : "memory"); }
__device__ __forceinline__ void cp16z(uint32_t dst, const void* src, int n) { asm volatile("cp.async.cg.shared.global [%0], [%1], 16, %2;" ::"r"(dst), "l"(src), "r"(n) : "memory"); }
__device__ __forceinline__ void cp_arrive(uint32_t bar) { asm volatile("cp.async.mbarrier.arrive.noinc.shared::cta.b64 [%0];" ::"r"(bar) : "memory"); }
__device__ __forceinline__ void st_async4(uint32_t dst, const uint32_t* v, uint32_t bar) {
  asm volatile("st.async.weak.shared::cluster.mbarrier::complete_tx::bytes.v4.b32 [%0], {%1, %2, %3, %4}, [%5];" ::"r"(dst), "r"(v[0]), "r"(v[1]), "r"(v[2]), "r"(v[3]), "r"(bar) : "memory");
}
__device__ __forceinline__ void wg_fence() { asm volatile("wgmma.fence.sync.aligned;" ::: "memory"); }
__device__ __forceinline__ void wg_commit() { asm volatile("wgmma.commit_group.sync.aligned;" ::: "memory"); }
template <int N> __device__ __forceinline__ void wg_wait() { asm volatile("wgmma.wait_group.sync.aligned %0;" ::"n"(N) : "memory"); }
__device__ __forceinline__ uint64_t mkdesc(uint32_t addr, uint32_t lbo, uint32_t sbo, uint32_t swz) {
  return (uint64_t)((addr & 0x3FFFF) >> 4) | ((uint64_t)(lbo >> 4) << 16) | ((uint64_t)(sbo >> 4) << 32) | ((uint64_t)swz << 62);
}
__device__ __forceinline__ void ldsm4t(uint32_t* r, uint32_t a) {
  asm volatile("ldmatrix.sync.aligned.m8n8.x4.trans.shared.b16 {%0,%1,%2,%3}, [%4];" : "=r"(r[0]), "=r"(r[1]), "=r"(r[2]), "=r"(r[3]) : "r"(a) : "memory");
}
__device__ __forceinline__ void stsm4(uint32_t a, const uint32_t* r) {
  asm volatile("stmatrix.sync.aligned.m8n8.x4.shared.b16 [%0], {%1,%2,%3,%4};" ::"r"(a), "r"(r[0]), "r"(r[1]), "r"(r[2]), "r"(r[3]) : "memory");
}
__device__ __forceinline__ void stsm4t(uint32_t a, const uint32_t* r) {
  asm volatile("stmatrix.sync.aligned.m8n8.x4.trans.shared.b16 [%0], {%1,%2,%3,%4};" ::"r"(a), "r"(r[0]), "r"(r[1]), "r"(r[2]), "r"(r[3]) : "memory");
}
__device__ __forceinline__ void bar_sync(int id, int n) { asm volatile("bar.sync %0, %1;" ::"r"(id), "r"(n) : "memory"); }
__device__ __forceinline__ void bar_arrive(int id, int n) { asm volatile("bar.arrive %0, %1;" ::"r"(id), "r"(n) : "memory"); }
__device__ __forceinline__ uint32_t lds32(uint32_t a) { uint32_t v; asm volatile("ld.shared.b32 %0, [%1];" : "=r"(v) : "r"(a) : "memory"); return v; }
__device__ __forceinline__ uint2 lds64(uint32_t a) { uint2 v; asm volatile("ld.shared.v2.b32 {%0,%1}, [%2];" : "=r"(v.x), "=r"(v.y) : "r"(a) : "memory"); return v; }
__device__ __forceinline__ uint4 lds128(uint32_t a) { uint4 v; asm volatile("ld.shared.v4.b32 {%0,%1,%2,%3}, [%4];" : "=r"(v.x), "=r"(v.y), "=r"(v.z), "=r"(v.w) : "r"(a) : "memory"); return v; }
__device__ __forceinline__ void sts16(uint32_t a, uint32_t v) { asm volatile("st.shared.b16 [%0], %1;" ::"r"(a), "h"((uint16_t)v) : "memory"); }
__device__ __forceinline__ void sts32(uint32_t a, uint32_t v) { asm volatile("st.shared.b32 [%0], %1;" ::"r"(a), "r"(v) : "memory"); }
__device__ __forceinline__ void sts64(uint32_t a, uint32_t x, uint32_t y) { asm volatile("st.shared.v2.b32 [%0], {%1,%2};" ::"r"(a), "r"(x), "r"(y) : "memory"); }
__device__ __forceinline__ void sts128(uint32_t a, uint4 v) { asm volatile("st.shared.v4.b32 [%0], {%1,%2,%3,%4};" ::"r"(a), "r"(v.x), "r"(v.y), "r"(v.z), "r"(v.w) : "memory"); }
template<int TB> __device__ __forceinline__ void wgmma_rs_n128(float* d, const uint32_t* a, uint64_t db, int sd) {
  asm volatile("{\n.reg .pred p;\nsetp.ne.b32 p, %69, 0;\n"
    "wgmma.mma_async.sync.aligned.m64n128k16.f32.bf16.bf16 {%0, %1, %2, %3, %4, %5, %6, %7, %8, %9, %10, %11, %12, %13, %14, %15, %16, %17, %18, %19, %20, %21, %22, %23, %24, %25, %26, %27, %28, %29, %30, %31, %32, %33, %34, %35, %36, %37, %38, %39, %40, %41, %42, %43, %44, %45, %46, %47, %48, %49, %50, %51, %52, %53, %54, %55, %56, %57, %58, %59, %60, %61, %62, %63}, {%64, %65, %66, %67}, %68, p, 1, 1, %70;\n}"
    : "+f"(d[0]), "+f"(d[1]), "+f"(d[2]), "+f"(d[3]), "+f"(d[4]), "+f"(d[5]), "+f"(d[6]), "+f"(d[7]), "+f"(d[8]), "+f"(d[9]), "+f"(d[10]), "+f"(d[11]), "+f"(d[12]), "+f"(d[13]), "+f"(d[14]), "+f"(d[15]), "+f"(d[16]), "+f"(d[17]), "+f"(d[18]), "+f"(d[19]), "+f"(d[20]), "+f"(d[21]), "+f"(d[22]), "+f"(d[23]), "+f"(d[24]), "+f"(d[25]), "+f"(d[26]), "+f"(d[27]), "+f"(d[28]), "+f"(d[29]), "+f"(d[30]), "+f"(d[31]), "+f"(d[32]), "+f"(d[33]), "+f"(d[34]), "+f"(d[35]), "+f"(d[36]), "+f"(d[37]), "+f"(d[38]), "+f"(d[39]), "+f"(d[40]), "+f"(d[41]), "+f"(d[42]), "+f"(d[43]), "+f"(d[44]), "+f"(d[45]), "+f"(d[46]), "+f"(d[47]), "+f"(d[48]), "+f"(d[49]), "+f"(d[50]), "+f"(d[51]), "+f"(d[52]), "+f"(d[53]), "+f"(d[54]), "+f"(d[55]), "+f"(d[56]), "+f"(d[57]), "+f"(d[58]), "+f"(d[59]), "+f"(d[60]), "+f"(d[61]), "+f"(d[62]), "+f"(d[63])
    : "r"(a[0]), "r"(a[1]), "r"(a[2]), "r"(a[3]), "l"(db), "r"(sd), "n"(TB));
}

template<int TB> __device__ __forceinline__ void wgmma_rs_n160(float* d, const uint32_t* a, uint64_t db, int sd) {
  asm volatile("{\n.reg .pred p;\nsetp.ne.b32 p, %85, 0;\n"
    "wgmma.mma_async.sync.aligned.m64n160k16.f32.bf16.bf16 {%0, %1, %2, %3, %4, %5, %6, %7, %8, %9, %10, %11, %12, %13, %14, %15, %16, %17, %18, %19, %20, %21, %22, %23, %24, %25, %26, %27, %28, %29, %30, %31, %32, %33, %34, %35, %36, %37, %38, %39, %40, %41, %42, %43, %44, %45, %46, %47, %48, %49, %50, %51, %52, %53, %54, %55, %56, %57, %58, %59, %60, %61, %62, %63, %64, %65, %66, %67, %68, %69, %70, %71, %72, %73, %74, %75, %76, %77, %78, %79}, {%80, %81, %82, %83}, %84, p, 1, 1, %86;\n}"
    : "+f"(d[0]), "+f"(d[1]), "+f"(d[2]), "+f"(d[3]), "+f"(d[4]), "+f"(d[5]), "+f"(d[6]), "+f"(d[7]), "+f"(d[8]), "+f"(d[9]), "+f"(d[10]), "+f"(d[11]), "+f"(d[12]), "+f"(d[13]), "+f"(d[14]), "+f"(d[15]), "+f"(d[16]), "+f"(d[17]), "+f"(d[18]), "+f"(d[19]), "+f"(d[20]), "+f"(d[21]), "+f"(d[22]), "+f"(d[23]), "+f"(d[24]), "+f"(d[25]), "+f"(d[26]), "+f"(d[27]), "+f"(d[28]), "+f"(d[29]), "+f"(d[30]), "+f"(d[31]), "+f"(d[32]), "+f"(d[33]), "+f"(d[34]), "+f"(d[35]), "+f"(d[36]), "+f"(d[37]), "+f"(d[38]), "+f"(d[39]), "+f"(d[40]), "+f"(d[41]), "+f"(d[42]), "+f"(d[43]), "+f"(d[44]), "+f"(d[45]), "+f"(d[46]), "+f"(d[47]), "+f"(d[48]), "+f"(d[49]), "+f"(d[50]), "+f"(d[51]), "+f"(d[52]), "+f"(d[53]), "+f"(d[54]), "+f"(d[55]), "+f"(d[56]), "+f"(d[57]), "+f"(d[58]), "+f"(d[59]), "+f"(d[60]), "+f"(d[61]), "+f"(d[62]), "+f"(d[63]), "+f"(d[64]), "+f"(d[65]), "+f"(d[66]), "+f"(d[67]), "+f"(d[68]), "+f"(d[69]), "+f"(d[70]), "+f"(d[71]), "+f"(d[72]), "+f"(d[73]), "+f"(d[74]), "+f"(d[75]), "+f"(d[76]), "+f"(d[77]), "+f"(d[78]), "+f"(d[79])
    : "r"(a[0]), "r"(a[1]), "r"(a[2]), "r"(a[3]), "l"(db), "r"(sd), "n"(TB));
}

template<int TB> __device__ __forceinline__ void wgmma_rs_n192(float* d, const uint32_t* a, uint64_t db, int sd) {
  asm volatile("{\n.reg .pred p;\nsetp.ne.b32 p, %101, 0;\n"
    "wgmma.mma_async.sync.aligned.m64n192k16.f32.bf16.bf16 {%0, %1, %2, %3, %4, %5, %6, %7, %8, %9, %10, %11, %12, %13, %14, %15, %16, %17, %18, %19, %20, %21, %22, %23, %24, %25, %26, %27, %28, %29, %30, %31, %32, %33, %34, %35, %36, %37, %38, %39, %40, %41, %42, %43, %44, %45, %46, %47, %48, %49, %50, %51, %52, %53, %54, %55, %56, %57, %58, %59, %60, %61, %62, %63, %64, %65, %66, %67, %68, %69, %70, %71, %72, %73, %74, %75, %76, %77, %78, %79, %80, %81, %82, %83, %84, %85, %86, %87, %88, %89, %90, %91, %92, %93, %94, %95}, {%96, %97, %98, %99}, %100, p, 1, 1, %102;\n}"
    : "+f"(d[0]), "+f"(d[1]), "+f"(d[2]), "+f"(d[3]), "+f"(d[4]), "+f"(d[5]), "+f"(d[6]), "+f"(d[7]), "+f"(d[8]), "+f"(d[9]), "+f"(d[10]), "+f"(d[11]), "+f"(d[12]), "+f"(d[13]), "+f"(d[14]), "+f"(d[15]), "+f"(d[16]), "+f"(d[17]), "+f"(d[18]), "+f"(d[19]), "+f"(d[20]), "+f"(d[21]), "+f"(d[22]), "+f"(d[23]), "+f"(d[24]), "+f"(d[25]), "+f"(d[26]), "+f"(d[27]), "+f"(d[28]), "+f"(d[29]), "+f"(d[30]), "+f"(d[31]), "+f"(d[32]), "+f"(d[33]), "+f"(d[34]), "+f"(d[35]), "+f"(d[36]), "+f"(d[37]), "+f"(d[38]), "+f"(d[39]), "+f"(d[40]), "+f"(d[41]), "+f"(d[42]), "+f"(d[43]), "+f"(d[44]), "+f"(d[45]), "+f"(d[46]), "+f"(d[47]), "+f"(d[48]), "+f"(d[49]), "+f"(d[50]), "+f"(d[51]), "+f"(d[52]), "+f"(d[53]), "+f"(d[54]), "+f"(d[55]), "+f"(d[56]), "+f"(d[57]), "+f"(d[58]), "+f"(d[59]), "+f"(d[60]), "+f"(d[61]), "+f"(d[62]), "+f"(d[63]), "+f"(d[64]), "+f"(d[65]), "+f"(d[66]), "+f"(d[67]), "+f"(d[68]), "+f"(d[69]), "+f"(d[70]), "+f"(d[71]), "+f"(d[72]), "+f"(d[73]), "+f"(d[74]), "+f"(d[75]), "+f"(d[76]), "+f"(d[77]), "+f"(d[78]), "+f"(d[79]), "+f"(d[80]), "+f"(d[81]), "+f"(d[82]), "+f"(d[83]), "+f"(d[84]), "+f"(d[85]), "+f"(d[86]), "+f"(d[87]), "+f"(d[88]), "+f"(d[89]), "+f"(d[90]), "+f"(d[91]), "+f"(d[92]), "+f"(d[93]), "+f"(d[94]), "+f"(d[95])
    : "r"(a[0]), "r"(a[1]), "r"(a[2]), "r"(a[3]), "l"(db), "r"(sd), "n"(TB));
}

template<int TB> __device__ __forceinline__ void wgmma_rs_n32(float* d, const uint32_t* a, uint64_t db, int sd) {
  asm volatile("{\n.reg .pred p;\nsetp.ne.b32 p, %21, 0;\n"
    "wgmma.mma_async.sync.aligned.m64n32k16.f32.bf16.bf16 {%0, %1, %2, %3, %4, %5, %6, %7, %8, %9, %10, %11, %12, %13, %14, %15}, {%16, %17, %18, %19}, %20, p, 1, 1, %22;\n}"
    : "+f"(d[0]), "+f"(d[1]), "+f"(d[2]), "+f"(d[3]), "+f"(d[4]), "+f"(d[5]), "+f"(d[6]), "+f"(d[7]), "+f"(d[8]), "+f"(d[9]), "+f"(d[10]), "+f"(d[11]), "+f"(d[12]), "+f"(d[13]), "+f"(d[14]), "+f"(d[15])
    : "r"(a[0]), "r"(a[1]), "r"(a[2]), "r"(a[3]), "l"(db), "r"(sd), "n"(TB));
}

template<int TB> __device__ __forceinline__ void wgmma_rs_n64(float* d, const uint32_t* a, uint64_t db, int sd) {
  asm volatile("{\n.reg .pred p;\nsetp.ne.b32 p, %37, 0;\n"
    "wgmma.mma_async.sync.aligned.m64n64k16.f32.bf16.bf16 {%0, %1, %2, %3, %4, %5, %6, %7, %8, %9, %10, %11, %12, %13, %14, %15, %16, %17, %18, %19, %20, %21, %22, %23, %24, %25, %26, %27, %28, %29, %30, %31}, {%32, %33, %34, %35}, %36, p, 1, 1, %38;\n}"
    : "+f"(d[0]), "+f"(d[1]), "+f"(d[2]), "+f"(d[3]), "+f"(d[4]), "+f"(d[5]), "+f"(d[6]), "+f"(d[7]), "+f"(d[8]), "+f"(d[9]), "+f"(d[10]), "+f"(d[11]), "+f"(d[12]), "+f"(d[13]), "+f"(d[14]), "+f"(d[15]), "+f"(d[16]), "+f"(d[17]), "+f"(d[18]), "+f"(d[19]), "+f"(d[20]), "+f"(d[21]), "+f"(d[22]), "+f"(d[23]), "+f"(d[24]), "+f"(d[25]), "+f"(d[26]), "+f"(d[27]), "+f"(d[28]), "+f"(d[29]), "+f"(d[30]), "+f"(d[31])
    : "r"(a[0]), "r"(a[1]), "r"(a[2]), "r"(a[3]), "l"(db), "r"(sd), "n"(TB));
}

template<int TB> __device__ __forceinline__ void wgmma_rs_n96(float* d, const uint32_t* a, uint64_t db, int sd) {
  asm volatile("{\n.reg .pred p;\nsetp.ne.b32 p, %53, 0;\n"
    "wgmma.mma_async.sync.aligned.m64n96k16.f32.bf16.bf16 {%0, %1, %2, %3, %4, %5, %6, %7, %8, %9, %10, %11, %12, %13, %14, %15, %16, %17, %18, %19, %20, %21, %22, %23, %24, %25, %26, %27, %28, %29, %30, %31, %32, %33, %34, %35, %36, %37, %38, %39, %40, %41, %42, %43, %44, %45, %46, %47}, {%48, %49, %50, %51}, %52, p, 1, 1, %54;\n}"
    : "+f"(d[0]), "+f"(d[1]), "+f"(d[2]), "+f"(d[3]), "+f"(d[4]), "+f"(d[5]), "+f"(d[6]), "+f"(d[7]), "+f"(d[8]), "+f"(d[9]), "+f"(d[10]), "+f"(d[11]), "+f"(d[12]), "+f"(d[13]), "+f"(d[14]), "+f"(d[15]), "+f"(d[16]), "+f"(d[17]), "+f"(d[18]), "+f"(d[19]), "+f"(d[20]), "+f"(d[21]), "+f"(d[22]), "+f"(d[23]), "+f"(d[24]), "+f"(d[25]), "+f"(d[26]), "+f"(d[27]), "+f"(d[28]), "+f"(d[29]), "+f"(d[30]), "+f"(d[31]), "+f"(d[32]), "+f"(d[33]), "+f"(d[34]), "+f"(d[35]), "+f"(d[36]), "+f"(d[37]), "+f"(d[38]), "+f"(d[39]), "+f"(d[40]), "+f"(d[41]), "+f"(d[42]), "+f"(d[43]), "+f"(d[44]), "+f"(d[45]), "+f"(d[46]), "+f"(d[47])
    : "r"(a[0]), "r"(a[1]), "r"(a[2]), "r"(a[3]), "l"(db), "r"(sd), "n"(TB));
}

template<int TA, int TB> __device__ __forceinline__ void wgmma_ss_n192(float* d, uint64_t da, uint64_t db, int sd) {
  asm volatile("{\n.reg .pred p;\nsetp.ne.b32 p, %98, 0;\n"
    "wgmma.mma_async.sync.aligned.m64n192k16.f32.bf16.bf16 {%0, %1, %2, %3, %4, %5, %6, %7, %8, %9, %10, %11, %12, %13, %14, %15, %16, %17, %18, %19, %20, %21, %22, %23, %24, %25, %26, %27, %28, %29, %30, %31, %32, %33, %34, %35, %36, %37, %38, %39, %40, %41, %42, %43, %44, %45, %46, %47, %48, %49, %50, %51, %52, %53, %54, %55, %56, %57, %58, %59, %60, %61, %62, %63, %64, %65, %66, %67, %68, %69, %70, %71, %72, %73, %74, %75, %76, %77, %78, %79, %80, %81, %82, %83, %84, %85, %86, %87, %88, %89, %90, %91, %92, %93, %94, %95}, %96, %97, p, 1, 1, %99, %100;\n}"
    : "+f"(d[0]), "+f"(d[1]), "+f"(d[2]), "+f"(d[3]), "+f"(d[4]), "+f"(d[5]), "+f"(d[6]), "+f"(d[7]), "+f"(d[8]), "+f"(d[9]), "+f"(d[10]), "+f"(d[11]), "+f"(d[12]), "+f"(d[13]), "+f"(d[14]), "+f"(d[15]), "+f"(d[16]), "+f"(d[17]), "+f"(d[18]), "+f"(d[19]), "+f"(d[20]), "+f"(d[21]), "+f"(d[22]), "+f"(d[23]), "+f"(d[24]), "+f"(d[25]), "+f"(d[26]), "+f"(d[27]), "+f"(d[28]), "+f"(d[29]), "+f"(d[30]), "+f"(d[31]), "+f"(d[32]), "+f"(d[33]), "+f"(d[34]), "+f"(d[35]), "+f"(d[36]), "+f"(d[37]), "+f"(d[38]), "+f"(d[39]), "+f"(d[40]), "+f"(d[41]), "+f"(d[42]), "+f"(d[43]), "+f"(d[44]), "+f"(d[45]), "+f"(d[46]), "+f"(d[47]), "+f"(d[48]), "+f"(d[49]), "+f"(d[50]), "+f"(d[51]), "+f"(d[52]), "+f"(d[53]), "+f"(d[54]), "+f"(d[55]), "+f"(d[56]), "+f"(d[57]), "+f"(d[58]), "+f"(d[59]), "+f"(d[60]), "+f"(d[61]), "+f"(d[62]), "+f"(d[63]), "+f"(d[64]), "+f"(d[65]), "+f"(d[66]), "+f"(d[67]), "+f"(d[68]), "+f"(d[69]), "+f"(d[70]), "+f"(d[71]), "+f"(d[72]), "+f"(d[73]), "+f"(d[74]), "+f"(d[75]), "+f"(d[76]), "+f"(d[77]), "+f"(d[78]), "+f"(d[79]), "+f"(d[80]), "+f"(d[81]), "+f"(d[82]), "+f"(d[83]), "+f"(d[84]), "+f"(d[85]), "+f"(d[86]), "+f"(d[87]), "+f"(d[88]), "+f"(d[89]), "+f"(d[90]), "+f"(d[91]), "+f"(d[92]), "+f"(d[93]), "+f"(d[94]), "+f"(d[95])
    : "l"(da), "l"(db), "r"(sd), "n"(TA), "n"(TB));
}

template<int TA, int TB> __device__ __forceinline__ void wgmma_ss_n8(float* d, uint64_t da, uint64_t db, int sd) {
  asm volatile("{\n.reg .pred p;\nsetp.ne.b32 p, %6, 0;\n"
    "wgmma.mma_async.sync.aligned.m64n8k16.f32.bf16.bf16 {%0, %1, %2, %3}, %4, %5, p, 1, 1, %7, %8;\n}"
    : "+f"(d[0]), "+f"(d[1]), "+f"(d[2]), "+f"(d[3])
    : "l"(da), "l"(db), "r"(sd), "n"(TA), "n"(TB));
}

constexpr int S_ = 2048, D_ = 640, F_ = 1536;

struct Scr {
  uint32_t flag[32 * 8];
  uint32_t mv[2 * 2048];
  bf16 cimg[8 * 6 * 512];
  uint2 st2[S_];
  bf16 kvT[D_ * S_];
  bf16 zT[D_ * S_];
  bf16 AT[D_ * S_];
};
__device__ __align__(1024) Scr g_scr;
__device__ __forceinline__ uint32_t clk() { uint32_t c; asm volatile("mov.u32 %0, %%clock;" : "=r"(c) :: "memory"); return c; }
#define DEVSM 0
#define STAMP(id)
#define STAMPIF(c, id)
constexpr int FL_X = 5, FL_C = 128;
#define CD 600
#define SD 1000

constexpr int SM_X = 1024, SM_EXT = 21504, SM_SMALL = 29696, SM_STAT = 30720, SM_CB = 32768, SM_RING = 34816, SM_TOTAL = SM_RING + 6 * 32768;
constexpr int SMALL_LN = 224, SMALL_RED = 320, SMALL_DUMMY = 1008, SMALL_E = 1012, SMALL_TS = 160;
constexpr int JOB_SZ = 10880, JOB_V = 5760, R_X = 5 * 32768, R_BOX = R_X + 12288;
constexpr int K1OFF = 4672, KSZ = 9472, CSZ = KSZ + 4224;
enum { B_KJ = 0, B_X = 5, B_EXT = 7, B_X1 = 8, B_P0 = 9, B_FB = 10, B_PEER = 20, B_RECV = 24, B_A = 30, B_E0 = 35, B_BOX = 38, B_F = 44, B_ST0 = 45, B_GB = 46,
       B_F1 = 48, B_E1 = 54, B_EB = 60,
       B_Z = 80, B_K = 85, B_EW = 88, B_ST2 = 94, B_XF = 95, B_KV4 = 96, B_KVS = 98, B_BD = 99,
       B_B = 106, B_S = 112 };
__device__ __forceinline__ uint32_t chan_base(uint32_t sb, int ch) { return sb + SM_RING + (2 + (ch >> 1)) * 32768 + (ch & 1) * CSZ; }

struct Params { CUtensorMap mS, mX, mWm, mK, mV, mG, mU, mD; };

__device__ __forceinline__ void flag_add(Scr* G, int id) { asm volatile("red.relaxed.gpu.global.add.u32 [%0], 1;" ::"l"(G->flag + id) : "memory"); }
__device__ __forceinline__ uint32_t rdback(const void* p) { uint32_t v; asm volatile("ld.relaxed.gpu.global.u32 %0, [%1];" : "=r"(v) : "l"(p) : "memory"); return v; }
__device__ __forceinline__ void st_tag(uint2* p, uint32_t v, uint32_t t) { asm volatile("st.relaxed.gpu.global.v2.u32 [%0], {%1, %2};" ::"l"(p), "r"(v), "r"(t) : "memory"); }
__device__ __forceinline__ void spin(uint32_t t, uint32_t d) { if (d) while (clk() - t < d); }
__device__ __forceinline__ uint2 ld_tag(const uint2* p) { uint2 v; asm volatile("ld.relaxed.gpu.global.v2.u32 {%0, %1}, [%2];" : "=r"(v.x), "=r"(v.y) : "l"(p) : "memory"); return v; }
__device__ __forceinline__ uint4 ld_tag2(const uint2* p) {
  uint4 v;
  asm volatile("ld.relaxed.gpu.global.v4.u32 {%0, %1, %2, %3}, [%4];" : "=r"(v.x), "=r"(v.y), "=r"(v.z), "=r"(v.w) : "l"(p) : "memory");
  return v;
}
__device__ __forceinline__ void stg128(void* p, uint4 v) { asm volatile("st.global.v4.b32 [%0], {%1, %2, %3, %4};" ::"l"(p), "r"(v.x), "r"(v.y), "r"(v.z), "r"(v.w) : "memory"); }
__device__ __forceinline__ uint32_t epoch(uint32_t sb) { return lds32(sb + SM_SMALL + SMALL_E); }
__device__ __forceinline__ void rdwait(uint32_t sb, uint32_t v) { sts32(sb + SM_SMALL + SMALL_DUMMY, v); }
__device__ __forceinline__ void fence_async_s() { asm volatile("fence.proxy.async.shared::cta;" ::: "memory"); }
__device__ __forceinline__ void fence_async_g() { asm volatile("fence.proxy.async.global;" ::: "memory"); }
__device__ __forceinline__ void bulk_done() { asm volatile("cp.async.bulk.commit_group;\n\tcp.async.bulk.wait_group 0;" ::: "memory"); }
__device__ __forceinline__ void flag_wait(Scr* G, int id, uint32_t target) {
  const uint32_t* p = G->flag + id;
#pragma unroll 1
  for (int i = 0; i < (1 << 20); i++) {
    uint32_t v;
    asm volatile("ld.relaxed.gpu.global.u32 %0, [%1];" : "=r"(v) : "l"(p) : "memory");
    if ((int)(v - target) >= 0) return;
  }
  __trap();
}
__device__ __forceinline__ int tbase(int pb) { return 127 - (32 * (pb >> 6) + 8 * (pb & 8) + 4 * ((2 * (pb & 3) - ((pb >> 2) & 1)) & 7) + ((pb >> 4) & 3)); }
__device__ __forceinline__ uint32_t hmul(uint32_t a, uint32_t b) { uint32_t d; asm("mul.rn.bf16x2 %0, %1, %2;" : "=r"(d) : "r"(a), "r"(b)); return d; }
__device__ __forceinline__ uint32_t hadd(uint32_t a, uint32_t b) { uint32_t d; asm("add.rn.bf16x2 %0, %1, %2;" : "=r"(d) : "r"(a), "r"(b)); return d; }
__device__ __forceinline__ uint32_t hsub(uint32_t a, uint32_t b) { uint32_t d; asm("sub.rn.bf16x2 %0, %1, %2;" : "=r"(d) : "r"(a), "r"(b)); return d; }
__device__ __forceinline__ uint32_t hfma(uint32_t a, uint32_t b, uint32_t c) { uint32_t d; asm("fma.rn.bf16x2 %0, %1, %2, %3;" : "=r"(d) : "r"(a), "r"(b), "r"(c)); return d; }
__device__ __forceinline__ uint32_t pack2(float lo, float hi) { uint32_t d; asm("cvt.rn.bf16x2.f32 %0, %1, %2;" : "=r"(d) : "f"(hi), "f"(lo)); return d; }
__device__ __forceinline__ float blo(uint32_t v) { return __uint_as_float(v << 16); }
__device__ __forceinline__ float bhi(uint32_t v) { return __uint_as_float(v & 0xffff0000u); }
__device__ __forceinline__ uint32_t tagged(uint32_t v, uint32_t e1) { return (v & ~1u) | (e1 & 1); }
__device__ __forceinline__ float rbf(float v) { return blo(pack2(v, 0.f)); }
template <int N> __device__ __forceinline__ void bfly(float* v, int mask, bool up) {
#pragma unroll
  for (int i = 0; i < N / 2; i++) {
    float send = up ? v[i] : v[i + N / 2], keep = up ? v[i + N / 2] : v[i];
    v[i] = keep + __shfl_xor_sync(0xffffffffu, send, mask);
  }
}
#define MG 0
__device__ __forceinline__ bool mod_first(int b) { return MG ? (b & 3) != 3 : !(b & 1) || !(b & 6); }
__device__ __forceinline__ int mod_grp(int b, int j) {
  if (MG) {
  const int m = b >> 3, s = b & 7, t = 16 * (j ? min(s, 6) : s - (s >> 2)) + m, v = j ? s : (t * 43) >> 10;
  if (j == 2) return b + 112;
  return v < 4 ? (v == 3 ? 160 : 40 * v) + (j ? 24 + m : t - 24 * v) : t + (t < 104 ? 56 : 96);
  }
  const int m = b >> 3, s = b & 7, t = 16 * s + m, v = j ? (t * 43) >> 10 : s >> 1;
  if (j == 2) return b + 112;
  if (j == 0 && s == 1) return m + (m < 8 ? 152 : 192);
  return v < 4 ? (v == 3 ? 160 : 40 * v) + (j ? 16 + t - 24 * v : m) : t + 24;
}

__device__ __forceinline__ void kv_load(const bf16* gk, const bf16* gv, const bf16* gs, uint32_t sb, int b, int r, int tid) {
  const int row = tid >> 2, col = 128 * r + 32 * (b & 3);
  const uint32_t a = sb + SM_RING + r * JOB_SZ + (row >> 3) * 80 + (tid & 3) * 16, ak = a + (row & 7) * 720, av = a + (row & 7) * 640 + JOB_V;
  const int o = (64 * (b >> 2) + row) * D_ + col + 8 * (tid & 3);
  cp16(ak + 80, gk + o);
  cp16(ak + 400, gk + o + 32 * D_);
  cp16(av, gv + o);
  cp16(av + 320, gv + o + 32 * D_);
  if (tid < 12) cp16z(ak + 3600, gk + (b < 4 ? o : o - 3 * D_), b < 4 ? 0 : 16);
  else if (tid >= 112) cp16(sb + SM_CB + 256 * r + 16 * (tid - 112), gs + 4 * col + 8 * (tid - 112));
}
__device__ __forceinline__ void load_kv(const Params& P, const bf16* gs, uint32_t sb, int b, int r) {
  const uint32_t a = sb + SM_RING + r * JOB_SZ, bar = sb + 8 * (B_B + r);
  const int cg = 4 * r + (b & 3);
  mbar_expect(bar, JOB_SZ + 256);
  tma4d(a, &P.mK, 0, cg, 8 * (b >> 2) - 1, 0, bar);
  tma4d(a + JOB_V, &P.mV, 0, cg, 8 * (b >> 2), 0, bar);
  bulk_g2s(sb + SM_CB + 256 * r, gs + 128 * cg, 256, bar);
}
__device__ __forceinline__ uint4* kv_dst(Scr* G, int b, int r, int tid) {
  return (uint4*)(G->kvT + (128 * r + 32 * (b & 3) + 8 * (tid >> 5) + 2 * (tid & 3)) * S_ + 2040 - 64 * (b >> 2)) - ((tid >> 2) & 7);
}
__device__ __forceinline__ void kv_job(Scr* G, uint32_t sb, int b, int r, int tid) {
  const int cp = 4 * (tid >> 5) + (tid & 3);
  const uint32_t ka = sb + SM_RING + r * JOB_SZ + ((tid >> 2) & 7) * 80 + cp * 4;
  mbar_wait(sb + 8 * (B_B + r), 0);
  STAMPIF(tid == 0, 56 + r);
  const uint4 sk = lds128(sb + SM_CB + 256 * r + 16 * cp);
  const uint32_t s0 = __byte_perm(sk.x, sk.z, 0x5410), s1 = __byte_perm(sk.x, sk.z, 0x7632), s2 = __byte_perm(sk.y, sk.w, 0x5410), s3 = __byte_perm(sk.y, sk.w, 0x7632);
  uint32_t kk[11], o[8];
#pragma unroll
  for (int i = 0; i < 11; i++) kk[i] = lds32(ka + 720 * ((i + 5) & 7) + 80 * ((i + 5) >> 3));
#pragma unroll
  for (int i = 0; i < 8; i++) {
    uint32_t v = lds32(ka + JOB_V + 640 * i);
    o[i] = hmul(hfma(kk[i + 3], s0, hfma(kk[i + 2], s1, hfma(kk[i + 1], s2, hmul(kk[i], s3)))), v);
  }
  uint4* dst = kv_dst(G, b, r, tid);
  dst[0] = make_uint4(__byte_perm(o[7], o[6], 0x5410), __byte_perm(o[5], o[4], 0x5410), __byte_perm(o[3], o[2], 0x5410), __byte_perm(o[1], o[0], 0x5410) | 1);
  dst[256] = make_uint4(__byte_perm(o[7], o[6], 0x7632), __byte_perm(o[5], o[4], 0x7632), __byte_perm(o[3], o[2], 0x7632), __byte_perm(o[1], o[0], 0x7632) | 1);
  if (tid == 0) { sts32(sb + SM_SMALL + SMALL_TS + 4 * r, clk()); mbar_arrive(sb + 8 * (B_KJ + r)); }
}
__device__ __forceinline__ void u_wait(uint4& a, uint4& c, const void* p) {
  asm volatile("{\n.reg .pred p;\n.reg .b32 t, n;\nmov.b32 n, 0;\n"
               "L0:\nlop3.b32 t, %3, %7, 1, 0x80;\nsetp.eq.b32 p, t, 0;\nvote.sync.any.pred p, p, 0xffffffff;\n@!p bra.uni L1;\n"
               "ld.relaxed.gpu.global.v4.u32 {%0, %1, %2, %3}, [%8];\nld.relaxed.gpu.global.v4.u32 {%4, %5, %6, %7}, [%8+2048];\n"
               "add.u32 n, n, 1;\nsetp.lt.u32 p, n, 1000000;\n@p bra.uni L0;\ntrap;\nL1:\n}"
               : "+r"(a.x), "+r"(a.y), "+r"(a.z), "+r"(a.w), "+r"(c.x), "+r"(c.y), "+r"(c.z), "+r"(c.w) : "l"(p) : "memory");
}
__device__ __forceinline__ uint64_t box_a(uint32_t sb) { return mkdesc(sb + SM_RING + R_BOX, 256, 1024, 3); }
__device__ __forceinline__ uint64_t box_b(uint32_t sb) { return mkdesc(sb + SM_STAT, 64, 128, 0); }
__device__ __forceinline__ void mod_put(Scr* G, uint32_t sb, const float* a, int b, int j, uint32_t e1, int tid) {
  const uint32_t red = sb + SM_STAT + 1536;
  if ((tid & 3) == tid >> 6) sts64(red + 32 * ((tid >> 2) & 7) + 8 * (tid >> 5), __float_as_uint((tid & 32) ? a[1] : a[0]), __float_as_uint((tid & 32) ? a[3] : a[2]));
  bar_sync(j ? 4 : 5, 128);
  if (tid < 16) {
    const uint4 u = lds128(red + 32 * (tid & 7)), v = lds128(red + 32 * (tid & 7) + 16);
    asm volatile("" : "+r"(b));
    const int grp = mod_grp(b, j);
    const uint32_t one = (grp >= 40 && grp < 80) || (grp >= 160 && grp < 200) ? 0x3f803f80u : 0u;
    const float lo = __uint_as_float(u.x) + __uint_as_float(u.z) + __uint_as_float(v.x) + __uint_as_float(v.z);
    const float hi = __uint_as_float(u.y) + __uint_as_float(u.w) + __uint_as_float(v.y) + __uint_as_float(v.w);
    asm volatile("st.relaxed.gpu.global.u32 [%0], %1;" ::"l"(G->mv + 8 * grp + 256 * (tid & 8) + (tid & 7)),
                 "r"(((tid >> 3) ^ e1) & 1 ? 0 : ~hadd(pack2(lo, hi), one)) : "memory");
  }
}
__device__ __forceinline__ void mod_box(Scr* G, uint32_t sb, int b, int j, uint32_t e1, int tid) {
  float a[4];
  uint64_t da = box_a(sb), db = box_b(sb);
#pragma unroll
  for (int h = 0; h < 2; h++) {
    mbar_wait(sb + 8 * (B_BOX + 2 * j + h), 0);
    STAMPIF(tid == 0 && j == 0, 71 + h);
    wg_fence();
#pragma unroll
    for (int n = 5 * h; n < 5 * h + 5; n++) wgmma_ss_n8<1, 0>(a, da + 128 * n, db + 8 * n, n != 0);
    wg_commit();
  }
  wg_wait<0>();
#pragma unroll
  for (int i = 0; i < 4; i++) asm volatile("" : "+f"(a[i])::"memory");
  mod_put(G, sb, a, b, j, e1, tid);
}
__device__ __forceinline__ void a_check(uint32_t sa, const void* ga, uint32_t tag) {
  asm volatile("{\n.reg .pred p;\n.reg .b32 t, n, x, y, z;\n.reg .b64 g;\n"
               "ld.shared.b32 t, [%0];\nlop3.b32 t, t, %2, 1, 0x28;\nsetp.ne.b32 p, t, 0;\nvote.sync.any.pred p, p, 0xffffffff;\n@!p bra.uni L1;\nmov.b32 n, 0;\n"
               "L0:\nld.relaxed.gpu.global.b32 t, [%1];\nlop3.b32 t, t, %2, 1, 0x28;\nsetp.ne.b32 p, t, 0;\nvote.sync.any.pred p, p, 0xffffffff;\n@!p bra.uni L2;\n"
               "add.u32 n, n, 1;\nsetp.lt.u32 p, n, 1000000;\n@p bra.uni L0;\ntrap;\nL2:\n"
               "and.b64 g, %1, -32;\nand.b32 n, %0, -32;\n"
               "ld.relaxed.gpu.global.v4.b32 {t, x, y, z}, [g];\nst.shared.v4.b32 [n], {t, x, y, z};\n"
               "ld.relaxed.gpu.global.v4.b32 {t, x, y, z}, [g+16];\nst.shared.v4.b32 [n+16], {t, x, y, z};\n"
               "fence.proxy.async.shared::cta;\nbar.warp.sync 0xffffffff;\nL1:\n}" ::"r"(sa), "l"(ga), "r"(tag) : "memory");
}
__device__ __forceinline__ void z_wait(uint4& a, uint4& c, uint32_t* v, const void* G, uint32_t zo, uint32_t co, uint32_t e1) {
  asm volatile("{\n.reg .pred p;\n.reg .b32 t, n;\n.reg .b64 x, y;\nmov.b32 n, 0;\n"
               "L0:\nlop3.b32 t, %3, %7, %14, 0x81;\nand.b32 t, t, 1;\nmin.u32 t, t, %8;\nmin.u32 t, t, %9;\nmin.u32 t, t, %10;\nmin.u32 t, t, %11;\n"
               "setp.eq.b32 p, t, 0;\nvote.sync.any.pred p, p, 0xffffffff;\n@!p bra.uni L1;\n"
               "shr.u32 t, n, 31;\nadd.u32 t, t, %12;\ncvt.u64.u32 x, t;\nadd.s64 x, x, %15;\nshr.u32 t, n, 30;\nadd.u32 t, t, %13;\ncvt.u64.u32 y, t;\nadd.s64 y, y, %15;\n"
               "ld.relaxed.gpu.global.v4.u32 {%0, %1, %2, %3}, [x];\nld.relaxed.gpu.global.v4.u32 {%4, %5, %6, %7}, [x+32768];\n"
               "ld.relaxed.gpu.global.u32 %8, [y];\nld.relaxed.gpu.global.u32 %9, [y+1280];\nld.relaxed.gpu.global.u32 %10, [y+2560];\nld.relaxed.gpu.global.u32 %11, [y+5120];\n"
               "add.u32 n, n, 1;\nsetp.lt.u32 p, n, 1000000;\n@p bra.uni L0;\ntrap;\nL1:\n}"
               : "+r"(a.x), "+r"(a.y), "+r"(a.z), "+r"(a.w), "+r"(c.x), "+r"(c.y), "+r"(c.z), "+r"(c.w), "+r"(v[0]), "+r"(v[1]), "+r"(v[2]), "+r"(v[3])
               : "r"(zo), "r"(co), "r"(e1), "l"(G) : "memory");
}
__device__ __forceinline__ void load_x(const Params& P, uint32_t sb, int b, int h) {
  const uint32_t bar = sb + 8 * (B_X + h);
  mbar_expect(bar, 10240);
  tma5d(sb + SM_X + h * 10240, &P.mX, 0, 0, 0, 5 * h, tbase(b), bar);
}
__device__ __forceinline__ uint32_t x_addr(uint32_t sb, int w, int lane) {
  const int rho = 15 - (4 * (lane >> 3) + 2 * (lane & 1) + ((lane >> 1) & 1));
  return sb + SM_X + (w >> 1) * 2048 + rho * 128 + (((2 * (w & 1) + (lane & 4)) ^ (rho & 7)) << 4);
}
__device__ __forceinline__ void ln1_half(uint32_t sb, int tid, int h, float& s1, float& s2, float& pv) {
  const uint32_t xr = sb + SM_X + 16 * tid;
  float s3 = 0.f;
  mbar_wait(sb + 8 * (B_X + h), 0);
  STAMPIF(tid == 0, 25);
  pv = blo(lds32(xr & ~127u));
#pragma unroll
  for (int n = 0; n < 5; n++) {
    const uint4 v = lds128(xr + 10240 * h + 2048 * n);
    const uint32_t u[4] = {v.x, v.y, v.z, v.w};
#pragma unroll
    for (int j = 0; j < 4; j++) {
      const float a = blo(u[j]) - pv, c = bhi(u[j]) - pv;
      s1 += a + c; s2 += a * a; s3 += c * c;
    }
  }
  s2 += s3;
}
__device__ __forceinline__ void ln1_end(uint32_t sb, int tid, float s1, float s2, float pv) {
#pragma unroll
  for (int o = 1; o < 8; o <<= 1) { s1 += __shfl_xor_sync(0xffffffffu, s1, o); s2 += __shfl_xor_sync(0xffffffffu, s2, o); }
  const float mu = s1 * (1.f / D_), var = fmaxf(s2 * (1.f / D_) - mu * mu, 0.f);
  const float rs = __frcp_rn(rbf(__fsqrt_rn(rbf(rbf(var) + 1e-5f))));
  const int i = 15 - (tid >> 3), j = tid & 7;
  if (j < 2) sts16(sb + SM_SMALL + SMALL_LN + 32 * j + 16 * (i & 1) + (i & 14), pack2(j ? rs : pv + mu, 0.f));
  bar_sync(5, 128);
  STAMPIF(tid == 0, 75);
}
__device__ __forceinline__ void load_box(const Params& P, uint32_t sb, int b, int cls) {
  const uint32_t bar = sb + 8 * (B_BOX + cls);
  mbar_expect(bar, 10240);
  tma3d(sb + SM_RING + R_BOX + 10240 * (cls & 1), &P.mWm, 16 * mod_grp(b, cls >> 1), 0, 5 * (cls & 1), bar);
}
__device__ __forceinline__ void load_ssm(const Params& P, uint32_t sb, int b, int r) {
  const uint32_t bar = sb + 8 * (B_S + r);
  mbar_expect(bar, 16 * 288);
  tma3d(chan_base(sb, r) + 128, &P.mS, 0, 0, 128 * r + b, bar);
}
__device__ __forceinline__ void k1_job(uint32_t sb, int r, int tid, uint32_t dv) {
  const uint32_t a0 = chan_base(sb, r) + 128 + 16 * tid + 32 * (tid >> 4);
  mbar_wait(sb + 8 * (B_S + r), 0);
  uint4 v[2];
  uint32_t pv[2];
#pragma unroll
  for (int n = 0; n < 2; n++) { v[n] = lds128(a0 + 2304 * n); pv[n] = lds32(a0 + 2304 * n - ((tid & 15) ? 4 : 36)); }
  if (tid == 0) { v[0].x = hadd(v[0].x, dv); sts32(a0, v[0].x); }
#pragma unroll
  for (int n = 0; n < 2; n++)
    sts128(a0 + 2304 * n + K1OFF, make_uint4(__byte_perm(pv[n], v[n].x, 0x5432), __byte_perm(v[n].x, v[n].y, 0x5432), __byte_perm(v[n].y, v[n].z, 0x5432), __byte_perm(v[n].z, v[n].w, 0x5432)));
}

__device__ __forceinline__ int out_blk(int s, int p) { const int t = p + (s >> 1); return t < 5 ? t : t - 5; }
__device__ __forceinline__ void l2_prefetch(const void* p, int bytes) { asm volatile("cp.async.bulk.prefetch.L2.global [%0], %1;" ::"l"(p), "r"(bytes) : "memory"); }
__device__ __forceinline__ void pf_line(const void* p) { asm volatile("prefetch.global.L2 [%0];" ::"l"(p) : "memory"); }
__device__ __forceinline__ int role(int bx) {
  const int c = bx >> 1, d = c - 36, q = (d * 37) >> 8, k = d - 7 * q;
  const int rank = c < 4 ? 12 + c : c < 36 ? ((c - 4) & 7) * 8 + ((c - 4) >> 3) : (k ? k + 1 : 0) * 8 + 4 + q;
  return 8 * (rank & 15) + 2 * (rank >> 4) + (bx & 1);
}
enum { K_KV, K_SSM, K_BOX, K_PW, K_PD, K_PKV, K_PSSM, K_PBOX, K_W, K_X, K_ST, K_END = 15 };
#define E(t, bar, kind, r) ((t) << 16 | (bar) << 8 | (kind) << 4 | (r))
#define SCHED E(2800, 255, K_BOX, 0), E(0, 255, K_BOX, 1), E(3700, 255, K_KV, 2), E(4400, 255, K_SSM, 2), E(4800, 255, K_KV, 3), E(5500, 255, K_X, 0), \
              E(6400, 255, K_KV, 4), E(7100, 255, K_X, 1), E(7900, 255, K_SSM, 3), E(8300, 255, K_SSM, 4), E(8600, 255, K_BOX, 2), E(9500, 255, K_PW, 0), \
              E(10100, 255, K_BOX, 3)
#define XPF 2
#define XBOTH 0
#define XI 8
#define XW 0
#define PWM 0x3c
#define STM 0x7c0
#define PDM 0x3800
#define KV4C 3
#define CVT 1
#define UPOS 4
#define UD 1000
#define UD1 6400
#define NP 6
#define NQ 6
#define SPOS(i) (2 * ((i) - NQ) + 13)
#define LH0 4
#define LH1 5
#define LM 0
#define PT 1
#define ZP 0
#define BD 1200
#define BX3 2
#define ER 0
#define PL 1
#define K1N 1
#define ZD 0
#define PK 0
#define ZF 1
#define ITW 0
constexpr uint32_t kSched[] = {SCHED, E(0, 255, K_END, 0)};
struct In { const bf16 *k, *v, *sk, *Wg, *Wu, *Wd, *ss; };
__device__ __forceinline__ void load_w(const Params& P, uint32_t sb, int s, int it) {
  const int st = it % 5;
  mbar_wait(sb + 8 * (B_E1 + st), (it / 5) & 1);
  const uint32_t a = sb + SM_RING + st * 32768 + 8192, fb = sb + 8 * (B_F1 + st);
  mbar_expect(fb, 24576);
#pragma unroll
  for (int j = 0; j < 3; j++) {
    tma2d(a + 8192 * j, &P.mG, 192 * s + 64 * j, 32 * it, fb);
    tma2d(a + 8192 * j + 4096, &P.mU, 192 * s + 64 * j, 32 * it, fb);
  }
}

template <int I> __device__ __forceinline__ int sched_run(const Params& P, const In& in, uint32_t sb, int b, int lane, uint32_t t_0) {
  constexpr uint32_t e = kSched[I];
  constexpr int kind = (e >> 4) & 15, r = e & 15, bar = (e >> 8) & 255;
  if constexpr (kind == K_END) return 0;
  else {
    if constexpr ((e >> 16) != 0) while (clk() - t_0 < (e >> 16));
    if (bar != 255) mbar_wait(sb + 8 * bar, 0);
    if (kind == K_BOX && r == 2) mbar_wait(sb + 8 * B_BD, 0);
    if (kind == K_PKV) {
      const bf16* kvp = (lane < 16 ? in.k : in.v) + (16 * b + (lane & 15)) * D_ + 128 * r;
      pf_line(kvp); pf_line(kvp + 64);
    } else {
      if (elect()) {
        if (kind == K_KV) load_kv(P, in.sk, sb, b, r);
        if (kind == K_X) load_x(P, sb, b, r);
        if (kind == K_SSM) load_ssm(P, sb, b, r);
        if (kind == K_BOX && (r > 1 || mod_first(b))) load_box(P, sb, b, r);
        if (kind == K_PW) { l2_prefetch(in.Wg + (128 * r + b) * F_, 2 * F_); l2_prefetch(in.Wu + (128 * r + b) * F_, 2 * F_); }
        if (kind == K_PSSM) l2_prefetch(in.ss + (128 * r + b) * S_, 4096);
      }
      __syncwarp();
    }
    return sched_run<I + 1>(P, in, sb, b, lane, t_0) + (kind == K_PW);
  }
}

__global__ void __launch_bounds__(512, 1) fused_kernel(const bf16* __restrict__ gk, const bf16* __restrict__ gv, const bf16* __restrict__ gsk,
                                                       const bf16* __restrict__ gD, const bf16* __restrict__ gc, Scr* G, const bf16* gWg, const bf16* gWu,
                                                       const bf16* gWd, bf16* gout, const bf16* gss, const __grid_constant__ Params P) {
  extern __shared__ __align__(1024) char smem_raw[];
  const uint32_t sb = smem_u32(smem_raw), ring = sb + SM_RING;
  const int b = role(blockIdx.x), m = b >> 3, s = b & 7;
  const uint32_t t_0 = clk();
  const int wg = __shfl_sync(0xffffffffu, threadIdx.x >> 7, 0);
  const int tid = threadIdx.x & 127, lane = tid & 31;
  const int w = __shfl_sync(0xffffffffu, tid >> 5, 0);
  if (wg < 2) {
    kv_load(gk, gv, gsk, sb, b, wg, tid);
  } else {
    if (wg == 2) {
      if (tid < 40) {
        int c = tid & 7;
        sts128(chan_base(sb, tid >> 3) + (c < 2 ? 80 + c * K1OFF : KSZ + 4096 + (c - 2) * 16), make_uint4(0, 0, 0, 0));
      }
    }
    if (elect()) {
      const int j = 4 * (3 - wg) + w - 1;
      if (j < 4) asm volatile("prefetch.tensormap [%0];" ::"l"(&P.mX + j) : "memory");
      if (j < 0) {
#pragma unroll
        for (int i = 0; i < 5; i++) mbar_init(sb + 8 * (B_S + i), 1);
        fence_async_s();
        if (XPF > 0) load_ssm(P, sb, b, 0);
        if (XPF > 1) load_ssm(P, sb, b, 1);
      } else {
        const int c = j < 3 ? 1 : j < 5 ? 2 : 4;
#pragma unroll
        for (int i = 0; i < 16; i++) mbar_init(sb + 128 * j + 8 * i, i < 10 || j < 6 ? c : i < 12 ? 128 : 1);
      }
    }
    fence_async_s();
  }
  __syncthreads();
  STAMPIF(threadIdx.x == 0, 55);

  if (wg < 2) {
    cp_arrive(sb + 8 * (B_B + wg));
    asm volatile("setmaxnreg.inc.sync.aligned.u32 224;");
    STAMPIF(threadIdx.x == 0, 82);
    const int g = lane >> 2, q = lane & 3;
    if (wg == 1) bar_arrive(1, 256);
    const uint32_t dv = *(const uint16_t*)(gD + 128 * wg + b);
    {
      const int b0 = (g >> 1) & 1, b1 = g >> 2, u = q + 4 * b0 - w;
      const uint32_t fo = 128 + (g & 1) * K1OFF + 288 * b1 + 4 * u, fo0 = fo - (u < 0 ? 32 : 0);
      const bool wrap = b0 && q == 0;
      const int src1 = b0 ? ((lane & 20) | ((q - 1) & 3)) : (lane | 8);
      const uint2* pu = (const uint2*)(G->kvT + (128 * wg + b) * S_ + 8 * tid);
      uint4 u0 = make_uint4(0, 0, 0, 0), u1 = u0;
      if (UPOS & 1) { u0 = ld_tag2(pu); u1 = ld_tag2(pu + 256); }
#pragma unroll 1
      for (int ch = wg; ch < 5; ch += 2) {
        const uint32_t base = chan_base(sb, ch);
        if (ch < 2 || ch == KV4C) {
          kv_job(G, sb, b, ch < 2 ? ch : 4, tid);
          if (ER && ch > 1) { __syncwarp(); if (lane == 0) mbar_arrive(sb + 8 * B_KV4); }
          STAMPIF(tid == 0, ch < 2 ? 1 + ch : 24);
        }
        if (ch < 2) {
          k1_job(sb, wg, tid, dv);
          bar_sync(3 + wg, 128);
        } else {
          mbar_wait(sb + 8 * (B_K + ch - 2), 0);
          if (UPOS & 4) { u0 = ld_tag2(pu); u1 = ld_tag2(pu + 256); }
          mbar_wait(sb + 8 * (B_S + ch), 0);
        }
        const uint32_t fa = base + fo, fa0 = base + fo0;
        uint32_t af[16][4];
#pragma unroll
        for (int j = 0; j < 16; j++) {
          const int o = 64 * (j & 1) + 576 * (j >> 1);
          af[j][0] = lds32(((j & 1) ? fa : fa0) + o); af[j][1] = lds32(fa + o + 128); af[j][2] = lds32(fa + o + 32); af[j][3] = lds32(fa + o + 160);
        }
        STAMPIF(tid == 0, 40 + ch);
        mbar_wait(sb + 8 * B_E0, 0);
        const uint32_t e1 = epoch(sb);
        if (ch == 1) spin(t_0, UD1);
        u_wait(u0, u1, pu);
        if (ITW == 5) STAMPIF(tid == 0 && ch, 105 + ch);
        sts128(base + KSZ + 16 * tid, u0);
        sts128(base + KSZ + 2048 + 16 * tid, u1);
        fence_async_s();
        float acc[128];
        const uint64_t db = mkdesc(base + KSZ, 32, 128, 0);
        bar_sync(1 + wg, 256);
        if (ITW == 5) STAMPIF(tid == 0 && ch, 115 + ch);
        wg_fence();
        wgmma_rs_n64<0>(acc + 96, af[0], db + 192, 0);
        wgmma_rs_n192<0>(acc, af[0], db, 0);
        wgmma_rs_n64<0>(acc + 96, af[1], db + 196, 1);
        wgmma_rs_n192<0>(acc, af[1], db + 4, 1);
        wgmma_rs_n32<0>(acc + 96, af[2], db + 224, 1);
        wgmma_rs_n192<0>(acc, af[2], db + 32, 1);
        wgmma_rs_n32<0>(acc + 96, af[3], db + 228, 1);
        wgmma_rs_n192<0>(acc, af[3], db + 36, 1);
        wgmma_rs_n192<0>(acc, af[4], db + 64, 1);
        wgmma_rs_n192<0>(acc, af[5], db + 68, 1);
        wgmma_rs_n160<0>(acc, af[6], db + 96, 1);
        wgmma_rs_n160<0>(acc, af[7], db + 100, 1);
        if (CVT == 2) wg_commit();
        wgmma_rs_n128<0>(acc, af[8], db + 128, 1);
        wgmma_rs_n128<0>(acc, af[9], db + 132, 1);
        if (CVT == 1) wg_commit();
        wgmma_rs_n96<0>(acc, af[10], db + 160, 1);
        wgmma_rs_n96<0>(acc, af[11], db + 164, 1);
        if (CVT == 0) bar_arrive(2 - wg, 256);
        wgmma_rs_n64<0>(acc, af[12], db + 192, 1);
        wgmma_rs_n64<0>(acc, af[13], db + 196, 1);
        wgmma_rs_n32<0>(acc, af[14], db + 224, 1);
        wgmma_rs_n32<0>(acc, af[15], db + 228, 1);
        wg_commit();
        if (ZP == 0) {
          stg128((void*)pu, make_uint4(0, 0, 0, 0));
          stg128((void*)(pu + 256), make_uint4(0, 0, 0, 0));
        }
        if (tid < 2 && ch == (!ER && wg == (KV4C & 1) && KV4C < 5 ? KV4C : wg)) mbar_arrive(sb + 8 * (B_E1 + tid));
        if (CVT) { wg_wait<1>(); if (ch < 4) bar_arrive(2 - wg, 256); }
        STAMPIF(tid == 0, 3 + ch);
        if (BX3 == 2 && ch == 3) {
          mod_box(G, sb, b, 1, e1, tid);
          __syncwarp();
          if (lane == 0) mbar_arrive(sb + 8 * (B_BD + 1));
          STAMPIF(tid == 0, 73);
        }
        if (ZP == 1) {
          stg128((void*)pu, make_uint4(0, 0, 0, 0));
          stg128((void*)(pu + 256), make_uint4(0, 0, 0, 0));
        }
        wg_wait<0>();
#pragma unroll
        for (int i = 0; i < 128; i++) asm volatile("" : "+f"(acc[i])::"memory");
        bar_sync(3 + wg, 128);
        if (tid <= (ch >> 2)) mbar_arrive(sb + 8 * (B_E1 + 2 + (ch >> 1)));
        float S0[33], T[34];
#pragma unroll
        for (int i = 0; i < 31; i++) S0[i] = acc[4 * i] + acc[4 * i + 6];
        S0[31] = acc[124]; S0[32] = 0.f;
        if (PK & 1) {
#pragma unroll
          for (int i = 0; i < 32; i += 2) {
            const uint32_t v = __shfl_sync(0xffffffffu, pack2(acc[4 * i + 1] + acc[4 * i + 7], i < 30 ? acc[4 * i + 5] + acc[4 * i + 11] : acc[125]), src1);
            T[i] = (wrap ? S0[i + 1] : S0[i]) + blo(v);
            T[i + 1] = (wrap ? S0[i + 2] : S0[i + 1]) + bhi(v);
          }
        } else {
#pragma unroll
          for (int i = 0; i < 32; i++) {
            float s1 = i < 31 ? acc[4 * i + 1] + acc[4 * i + 7] : acc[125];
            T[i] = (wrap ? S0[i + 1] : S0[i]) + __shfl_sync(0xffffffffu, s1, src1);
          }
        }
        T[32] = 0.f; T[33] = 0.f;
        uint4* pz = (uint4*)(G->zT + (128 * ch + b) * S_) + ((tid & 120) | (2 * q) | (g & 1));
#pragma unroll
        for (int h = 0; h < 2; h++) {
          float y[8];
          if (PK & 2) {
#pragma unroll
            for (int mu = 0; mu < 8; mu += 2) {
              const uint32_t v = __shfl_xor_sync(0xffffffffu, pack2(T[4 * mu + 2 + h], T[4 * mu + 6 + h]), 16);
              y[mu] = (b1 ? T[4 * mu + 4 + h] : T[4 * mu + h]) + blo(v);
              y[mu + 1] = (b1 ? T[4 * mu + 8 + h] : T[4 * mu + 4 + h]) + bhi(v);
            }
          } else {
#pragma unroll
            for (int mu = 0; mu < 8; mu++) y[mu] = (b1 ? T[4 * mu + 4 + h] : T[4 * mu + h]) + __shfl_xor_sync(0xffffffffu, T[4 * mu + 2 + h], 16);
          }
          pz[128 * h] = make_uint4(pack2(y[0], y[1]), pack2(y[2], y[3]), pack2(y[4], y[5]), tagged(pack2(y[6], y[7]), e1));
        }
        __syncwarp();
        if (lane == 0) mbar_arrive(sb + 8 * (B_Z + ch));
        if (ZP == 2) {
          stg128((void*)pu, make_uint4(0, 0, 0, 0));
          stg128((void*)(pu + 256), make_uint4(0, 0, 0, 0));
        }
        pu += 128 * S_ / 2;
        STAMPIF(tid == 0, 8 + ch);
      }
    }
    uint32_t hh[96];
    {
      float ga[192];
      float* ua = ga + 96;
      const uint64_t da0 = mkdesc(ring + wg * 2048, 512, 256, 3), db0 = mkdesc(ring + 8192, 4096, 1024, 1);
      int st = PL, ph = 0;
      if (ITW == 7) STAMPIF(tid == 0, 110 + wg);
      float bx[4];
      if (wg && BX3 < 2) {
        mbar_wait(sb + 8 * (B_BOX + 2), 0);
        mbar_wait(sb + 8 * (B_BOX + 3), 0);
        wg_fence();
#pragma unroll
        for (int n = 0; n < 10; n++) wgmma_ss_n8<1, 0>(bx, box_a(sb) + 128 * n, box_b(sb) + 8 * n, n != 0);
        wg_commit();
        if (ITW == 7) STAMPIF(tid == 0, 120);
      }
      const uint32_t e1 = epoch(sb);
      auto put = [&]() {
#pragma unroll
        for (int i = 0; i < 4; i++) asm volatile("" : "+f"(bx[i])::"memory");
        mod_put(G, sb, bx, b, 1, e1, tid);
        __syncwarp();
        if (lane == 0) mbar_arrive(sb + 8 * (B_BD + 1));
        STAMPIF(tid == 0, 73);
      };
      if (wg && BX3 == 0) { wg_wait<0>(); put(); }
      mbar_wait(sb + 8 * B_F1, 0);
      STAMPIF(tid == 0, 13 + wg);
      wg_fence();
      wgmma_ss_n192<1, 1>(ga, da0, db0, 0);
      wgmma_ss_n192<1, 1>(ua, da0, db0 + 768, 0);
      wgmma_ss_n192<1, 1>(ga, da0 + 256, db0 + 128, 1);
      wgmma_ss_n192<1, 1>(ua, da0 + 256, db0 + 128 + 768, 1);
      wg_commit();
      if (wg && BX3 == 1) { wg_wait<1>(); put(); }
      mbar_wait(sb + 8 * B_BD, 0);
      if (ITW == 7) STAMPIF(tid == 0, 112 + wg);
      const bool cs = b < 96;
      const int x0 = wg ? XI : 99,
                x1 = x0 + (cs ? 4 : 2), xs = cs ? 4 : 8;
      uint64_t xa = cs ? mkdesc(sb + SM_EXT, 4096, 1024, 1) : box_a(sb), xb = cs ? mkdesc(sb + SM_CB, 32, 128, 0) : box_b(sb);
      uint64_t ya = xa + (cs ? (SM_RING + R_X - SM_EXT) / 16 : 256), yb = xb + 16;
      if (ITW == 7) STAMPIF(tid == 0, 114 + wg);
#pragma unroll 1
      for (int it = PL; it < 19; it++) {
        if (it == x0) {
          mbar_wait(sb + 8 * (cs ? B_F : B_BOX + 4), 0);
          mbar_wait(sb + 8 * (cs ? B_ST0 : B_BOX + 5), 0);
          STAMPIF(tid == 0, 76);
        }
        if (it == x1 + XW) {
          wg_wait<XW>();
#pragma unroll
          for (int i = 0; i < 4; i++) asm volatile("" : "+f"(bx[i])::"memory");
          if (!cs) mod_put(G, sb, bx, b, 2, e1, tid);
          else {
            const int row = (m < 6 ? 0 : 4) + q;
            uint16_t* dst = (uint16_t*)G->cimg + s * 3072 + (m % 6) * 512 + row * 64 + g;
#pragma unroll
            for (int j = 0; j < 2; j++) {
              const float c1 = __shfl_sync(0xffffffffu, bx[2 * j], lane & 28), c2 = __shfl_sync(0xffffffffu, bx[2 * j + 1], lane & 28);
              const float t = (lane & 2) ? c2 : c1, hi = rbf(t);
              dst[((2 * w + j) ^ row) << 3] = (uint16_t)pack2((lane & 1) ? t - hi : hi, 0.f);
            }
          }
          __syncwarp();
          if (lane == 0) mbar_arrive(sb + 8 * (B_BD + 2));
          STAMPIF(tid == 0, 77);
        }
        if (ITW == 7) STAMPIF(tid == 0 && it == 0, 116 + wg);
        mbar_wait(sb + 8 * (B_F1 + st), ph);
        STAMPIF(tid == 0 && it == 0, 13 + wg);
        if (ITW == 1) STAMPIF(tid == 0 && it >= 10, 90 + it + 10 * wg);
        else if (ITW == 2) STAMPIF(tid == 0 && it < 10, 100 + it + 10 * wg);
        else if (ITW < 3) STAMPIF(threadIdx.x == ITW, 100 + it);
        const uint64_t da = da0 + st * 2048, db = db0 + st * 2048;
        if (it >= x0 && it < x1) {
          wg_fence();
          wgmma_ss_n8<1, 0>(bx, xa, xb, it != x0);
          wgmma_ss_n192<1, 1>(ga, da, db, 1);
          wgmma_ss_n8<1, 0>(bx, ya, yb, 1);
          wgmma_ss_n192<1, 1>(ua, da, db + 768, 1);
          wgmma_ss_n8<1, 0>(bx, ya + 128, yb + xs, 1);
          wgmma_ss_n192<1, 1>(ga, da + 256, db + 128, 1);
          wgmma_ss_n8<1, 0>(bx, ya + 256, yb + 2 * xs, 1);
          wgmma_ss_n192<1, 1>(ua, da + 256, db + 128 + 768, 1);
          wgmma_ss_n8<1, 0>(bx, ya + 384, yb + 3 * xs, 1);
          wg_commit();
          xa += 128; xb += xs; ya += 512; yb += 4 * xs;
        } else {
          wg_fence();
          wgmma_ss_n192<1, 1>(ga, da, db, PL || it != 0);
          wgmma_ss_n192<1, 1>(ua, da, db + 768, PL || it != 0);
          wgmma_ss_n192<1, 1>(ga, da + 256, db + 128, 1);
          wgmma_ss_n192<1, 1>(ua, da + 256, db + 128 + 768, 1);
          wg_commit();
        }
        wg_wait<1>();
        if ((PL || it > 0) && tid == 0) mbar_arrive(sb + 8 * (B_E1 + (st == 0 ? 4 : st - 1)));
        if (++st == 5) { st = 0; ph ^= 1; }
      }
      const uint32_t la = ring + wg * 2048 + tid * 16, ra = mapa(la, (b & 1) ^ 1), rp = mapa(sb + 8 * (B_PEER + 2 * wg), (b & 1) ^ 1), rb = rp + 8 * (B_RECV - B_PEER);
      uint32_t sa[24];
      auto addr = [&](int j) {
        sa[2 * j] = ra + (j < 2 ? 5 : (j >> 1) - 1) * 32768 + (j & 1) * 4096;
        sa[2 * j + 1] = (sa[2 * j] >> 31) + (rb + 8 * (j / 6));
        asm volatile("" : "+r"(sa[2 * j]), "+r"(sa[2 * j + 1]));
      };
      auto send = [&](int j) { st_async4(sa[2 * j], hh + 4 * j, sa[2 * j + 1]); };
      auto pack = [&](int c) {
#pragma unroll
        for (int i = 0; i < 64; i++) asm volatile("" : "+f"(ga[64 * c + i])::"memory");
#pragma unroll
        for (int i = 0; i < 4; i++) addr(4 * c + i);
#pragma unroll
        for (int i = 0; i < 16; i++) {
          const int j = 64 * c + 2 * i;
          hh[16 * c + i] = pack2(ga[j] * ga[j + 32], ga[j + 1] * ga[j + 33]);
          asm volatile("" : "+r"(hh[16 * c + i])::"memory");
          if ((i & 3) == 3 && 4 * c + i / 4 < NP) send(4 * c + i / 4);
          if (c == 2 && NQ > NP && i == 0) mbar_wait(sb + 8 * (B_PEER + 2 * wg), 0);
          if (c == 2 && (i & 3) == 3 && NP + i / 4 < NQ) send(NP + i / 4);
        }
      };
      STAMPIF(threadIdx.x == 0, 61);
      mbar_wait(sb + 8 * (B_F1 + 4), 1);
      mbar_wait(sb + 8 * B_EXT, 0);
      mbar_wait(sb + 8 * B_ST2, 0);
      const uint64_t de = mkdesc(sb + SM_EXT, 1024, 0, 1), ds = mkdesc(sb + SM_STAT + wg * 1024, 0, 128, 0);
#pragma unroll
      for (int c = 0; c < 2; c++) {
        wg_fence();
        wgmma_ss_n192<1, 1>(ga + 96 * c, da0 + 8192, db0 + 8192 + 768 * c, 1);
        wgmma_ss_n192<1, 1>(ga + 96 * c, da0 + 8192 + 256, db0 + 8192 + 128 + 768 * c, 1);
        wgmma_ss_n192<0, 1>(ga + 96 * c, ds, de + 192 * c, 1);
        wg_commit();
        if (c == 0) { mbar_wait(sb + 8 * B_P0, 0); mbar_wait(sb + 8 * B_FB, 0); }
        wg_wait<1>();
        if (c == 0 && tid == 0) {
          mbar_arrive(sb + 8 * (B_E1 + 3));
          mbar_arrive_remote(rp);
        }
      }
      STAMPIF(tid == 0, 15 + wg);
      float acc[64], rs[2] = {};
      uint4 pf[4], gb = {};
      uint32_t ln, os, ol, og;
      const char *po, *pq;
      const uint64_t dd0 = mkdesc(ring + 8192, 0, 1024, 1);
      bool ok = false;
#pragma unroll
      for (int c = 0; c < 3; c++) {
        pack(c);
        if (c == 1) ok = mbar_try(sb + 8 * (B_FB + 1), 0);
        STAMPIF(tid == 0 && c == 0, wg ? 89 : 121);
        if (ITW == 3) STAMPIF(tid == 0 && c > 0, 99 + c + 10 * wg);
        wg_fence();
#pragma unroll
        for (int k = 4 * c; k < 4 * c + 4; k++) wgmma_rs_n64<1>(acc, hh + 4 * k, dd0 + 5 * 2048 + 128 * k, k);
        wg_commit();
        if (c == 0) {
          wg_wait<1>();
          if (tid == 0) {
            mbar_arrive(sb + 8 * (B_E1 + 4));
            mbar_arrive_remote(rp + 8);
          }
        }
        if (c == 1 && !ok) mbar_wait(sb + 8 * (B_FB + 1), 0);
      }
      auto recv = [&](int j) {
        const uint4 v = lds128(la + (j < 2 ? 5 : (j >> 1) - 1) * 32768 + (j & 1) * 4096);
        hh[48 + 4 * j] = v.x; hh[49 + 4 * j] = v.y; hh[50 + 4 * j] = v.z; hh[51 + 4 * j] = v.w;
      };
      auto stage = [&](const float* a, int i) {
        const uint32_t v[4] = {pack2(a[8 * i] * rs[0], a[8 * i + 1] * rs[0]), pack2(a[8 * i + 2] * rs[1], a[8 * i + 3] * rs[1]),
                               pack2(a[8 * i + 4] * rs[0], a[8 * i + 5] * rs[0]), pack2(a[8 * i + 6] * rs[1], a[8 * i + 7] * rs[1])};
        stsm4(os + 32 * i, v);
      };
      auto fetch = [&](int p) {
        __syncwarp();
#pragma unroll
        for (int i = 0; i < 4; i++) pf[i] = lds128(ol + 576 * i);
      };
      auto next = [&](int p) {
        gb = lds128(og + 256 * out_blk(s, p));
        pq = po + 128 * out_blk(s, p);
        asm volatile("" : "+l"(pq));
      };
      auto add = [&](int p, int i) {
        asm volatile("red.relaxed.gpu.global.add.noftz.v4.bf16x2 [%0], {%1, %2, %3, %4};" ::"l"(pq - (i & 1) * 2048 * D_ - (i >> 1) * 2 * D_),
                     "r"(hmul(pf[i].x, gb.x)), "r"(hmul(pf[i].y, gb.y)), "r"(hmul(pf[i].z, gb.z)), "r"(hmul(pf[i].w, gb.w)) : "memory");
      };
#pragma unroll
      for (int h = 2; h < 20; h++) {
        const int gr = h >> 1, pe = gr < 4 ? gr >> 1 : gr & 1, ac = (gr < 4 ? gr : gr >> 1) & 1;
        const int ep = h == 7 || h == 8 ? 0 : h > 8 && (h & 3) == 1 || h > 8 && (h & 3) == 2 ? (h >> 2) - 1 : -1;
        if (!(h & 1) && h > 2 && !(PT && ok)) mbar_wait(sb + 8 * (B_FB + gr), 0);
        if (h == LH0 || h == LH1) mbar_wait(sb + 8 * (B_RECV + 2 * wg + (h == LH1)), 0);
        if (h == LH0 && (h == 4 || !LM) || h == LH1 && (h == 5 || !LM)) {
#pragma unroll
          for (int j = 0; j < 6; j++) recv(6 * (h == LH1) + j);
        }
        if (h == SPOS(6) / 6 && NQ <= 6) mbar_wait(sb + 8 * (B_PEER + 2 * wg), 0);
        if (h == SPOS(10) / 6) mbar_wait(sb + 8 * (B_PEER + 2 * wg + 1), 0);
        if (h == 6) {
          mbar_wait(sb + 8 * B_X1, 0);
          mbar_wait(sb + 8 * B_GB, 0);
          asm volatile("mov.u32 %0, %%laneid;" : "=r"(ln));
#pragma unroll
          for (int i = 0; i < 2; i++) rs[i] = blo(lds32(sb + SM_STAT + (4 * wg + w) * 256 + (ln & 28) * 4 + 128 * i + 4));
        }
        STAMPIF(tid == 0 && h % 4 == 0 && h < 16, (wg ? 89 : 121) + h / 4);
        STAMPIF(tid == 0 && h == 16, wg ? 97 : 96);
        if (ITW == 3) STAMPIF(tid == 0 && h < 10, 100 + h + 10 * wg);
        if (ITW == 4) STAMPIF(tid == 0 && h >= 10, 90 + h + 10 * wg);
        const uint64_t db = dd0 + (((gr + 5) % 6) * 2048 + (gr << 16));
        if (PT && (h & 1) && h < 19) ok = mbar_try(sb + 8 * (B_FB + gr + 1), 0);
        wg_fence();
#pragma unroll
        for (int j = 0; j < 6; j++) {
          const int k = 6 * (h & 1) + j;
          wgmma_rs_n64<1>(acc + 32 * ac, hh + 48 * pe + 4 * k, db + 128 * k, pe || k);
#pragma unroll
          for (int i = NQ; i < 12; i++) if (SPOS(i) == 6 * h + j) send(i);
          if (LM && h == LH0 && h < 4) { recv(j); wg_fence(); }
          if (LM && h == LH1 && h < 5) { recv(6 + j); wg_fence(); }
          if (ep >= 0 && (h & 1)) {
            if (j < 4) stage(acc + 32 * (1 - ac), j);
            if (j == 4) fetch(ep);
          }
          if (ep >= 0 && !(h & 1) && j > 0 && j < 5) add(ep, j - 1);
          if (ep >= 0 && !(h & 1) && j == 5) next(ep + 1);
        }
        wg_commit();
        STAMPIF(tid == 0 && h == 3, 81);
        if (h == 6) {
#pragma unroll
          for (int i = 0; i < 2; i++) rs[i] = __fdividef(0.25f, rs[i] * rs[i]);
          const uint32_t ob = sb + SM_X + (4 * wg + w) * 2304;
          os = ob + (ln & 15) * 144 + (ln & 16); ol = ob + (ln >> 3) * 16 + ln * 16;
          po = (const char*)(gout + (1793 + 2 * tbase(8 * m + 4 * wg + w)) * D_) + (int)(640 * (s & 1) + 16 * ln - (ln >> 3) * (512 * D_ + 128));
          og = sb + SM_CB + 32 * (ln & 7);
          asm volatile("" : "+r"(os), "+r"(ol), "+r"(og), "+l"(po));
          next(0);
        }
        if (h == 2 || h == 4 || h == 6 || h == 8 || h == 12 || h == 16) {
          wg_wait<1>();
          if (h < 12 && tid == 0) mbar_arrive(sb + 8 * (B_EB + gr - 1));
          if (h >= 6) {
#pragma unroll
            for (int j = 0; j < 32; j++) asm volatile("" : "+f"(acc[32 * (1 - ac) + j])::"memory");
          }
        }
      }
      STAMPIF(tid == 0, wg ? 95 : 93);
      wg_wait<0>();
#pragma unroll
      for (int i = 0; i < 32; i++) asm volatile("" : "+f"(acc[i])::"memory");
      STAMPIF(tid == 0, wg ? 50 : 18);
#pragma unroll
      for (int i = 0; i < 4; i++) stage(acc, i);
      fetch(4);
#pragma unroll
      for (int i = 0; i < 4; i++) add(4, i);
    }
  } else if (wg == 2) {
    asm volatile("setmaxnreg.dec.sync.aligned.u32 40;");
    const uint32_t e1 = (rdback(G->flag + 8 * m + 4) >> 5) + 1;
    if (tid < 80) {
      uint4 c = ((const uint4*)gc)[tid];
#pragma unroll 1
      for (int i = 0; i < 4; i++) {
        const float lo = blo(c.x), hi = bhi(c.x);
        sts32(sb + SM_STAT + 16 * tid + 4 * i, pack2(__fdividef(lo, 1.f + __expf(-lo)), __fdividef(hi, 1.f + __expf(-hi))));
        c.x = c.y; c.y = c.z; c.z = c.w;
      }
    }
    if (tid == 0) { sts32(sb + SM_SMALL + SMALL_E, e1); mbar_arrive(sb + 8 * B_E0); }
    fence_async_s();
    bar_sync(5, 128);
    if (mod_first(b)) mod_box(G, sb, b, 0, e1, tid);
    __syncwarp();
    if (lane == 0) mbar_arrive(sb + 8 * B_BD);
    STAMPIF(tid == 0, 27);
    float s1 = 0.f, s2 = 0.f, pv;
#pragma unroll 1
    for (int r = 2; r < 5; r++) {
      if (KV4C > 4 || r < 4) {
        kv_job(G, sb, b, r, tid);
        STAMPIF(tid == 0, 20 + r);
      }
      if (r == (KV4C > 4 ? 4 : 3)) { __syncwarp(); if (elect()) mbar_arrive(sb + 8 * B_KVS); }
      if (r > 2) ln1_half(sb, tid, r - 3, s1, s2, pv);
    }
    {
      const int cg = 4 * (w >> 1) + (lane & 2) + (w & 1), g = lane >> 2;
      uint32_t zo = offsetof(Scr, zT) + 2 * ((16 * cg + g) * S_ + 16 * b + 8 * (lane & 1)), co = offsetof(Scr, mv) + 4 * (2048 * (e1 & 1) + 8 * cg + g);
      uint4 z[2];
      uint32_t c[4];
      auto zld = [&]() {
        asm volatile("" : "+r"(zo), "+r"(co));
        const uint2* pz = (const uint2*)((const char*)G + zo);
        const uint32_t* pc = (const uint32_t*)((const char*)G + co);
        z[0] = ld_tag2(pz); z[1] = ld_tag2(pz + 4096);
        c[0] = rdback(pc); c[1] = rdback(pc + 320); c[2] = rdback(pc + 640); c[3] = rdback(pc + 1280);
      };
      STAMPIF(tid == 0, 28);
      if (ZF < 2) zld();
      ln1_end(sb, tid, s1, s2, pv);
      int tl = tid;
#pragma unroll 1
      for (int r = 0; r < 5; r++) {
        asm volatile("" : "+r"(tl));
        const int lane = tl & 31;
        if (ITW == 6) STAMPIF(tid == 0 && r < 2, 100 + 10 * r);
        if (ZF == 3) { if (r == 2 + MG) { mbar_wait(sb + 8 * (B_BD + 1), 0); spin(clk(), BD); } if (r == 0) spin(t_0, ZD); zld(); }
        const uint32_t la = sb + SM_SMALL + SMALL_LN + 16 * (lane & 1);
        uint32_t xa = x_addr(sb, w, lane) + 4096 * r, xv[8];
        const uint4 m4 = lds128(la), s4 = lds128(la + 32);
        const uint32_t m_[4] = {m4.x, m4.y, m4.z, m4.w}, s_[4] = {s4.x, s4.y, s4.z, s4.w};
        ldsm4t(xv, xa);
        ldsm4t(xv + 4, xa ^ 16);
        if (ZF == 2) { if (r == 2 + MG) { mbar_wait(sb + 8 * (B_BD + 1), 0); spin(clk(), BD); } if (r == 0) spin(t_0, ZD); zld(); }
        if (ITW == 6) STAMPIF(tid == 0 && r < 2, 104 + 10 * r);
        z_wait(z[0], z[1], c, G, zo, co, e1);
        asm volatile("" : "+r"(xa));
        const uint32_t zc = (zo - (uint32_t)offsetof(Scr, zT)) >> 11, ao = (320 * m + s) * 32 + ((zc & ~31u) << 3) + (zc & 14) + (((zo >> 4) ^ (zc >> 3)) & 1);
        STAMPIF(tid == 0 && r == 0, 83);
        if (ITW == 6) STAMPIF(tid == 0 && r < 2, 105 + 10 * r);
        uint32_t h[8];
        {
          const uint32_t sa = ~c[0], ca1 = ~c[1];
#pragma unroll
          for (int j = 0; j < 8; j++) {
            const uint32_t z_[8] = {z[0].x, z[0].y, z[0].z, z[0].w, z[1].x, z[1].y, z[1].z, z[1].w}, sel = j > 3 ? 0x3232 : 0x1010;
            h[j] = hmul(hfma(hmul(hsub(xv[j], m_[j & 3]), s_[j & 3]), __byte_perm(ca1, 0, sel), __byte_perm(sa, 0, sel)), z_[j]);
            asm volatile("" : "+r"(h[j]));
          }
        }
        uint4* pa = (uint4*)G->AT + ao;
#pragma unroll
        for (int n = 0; n < 2; n++) {
          const uint32_t sel = n ? 0x3232 : 0x1010, ga = __byte_perm(~c[2], 0, sel), cb1 = __byte_perm(~c[3], 0, sel);
          uint32_t o[4], a[4];
#pragma unroll
          for (int j = 0; j < 4; j++) {
            o[j] = hfma(ga, h[4 * n + j], xv[4 * n + j]);
            a[j] = hmul(o[j], cb1);
          }
          a[2 * n + 1] = tagged(a[2 * n + 1], e1);
          pa[16 * n] = make_uint4(a[0], a[1], a[2], a[3]);
          if (n) { __syncwarp(); if (elect()) flag_add(G, 8 * m + r); }
          if (ITW == 6) STAMPIF(tid == 0 && r < 2, 106 + n + 10 * r);
          stsm4t(xa ^ (16 * n), o);
        }
        if (r < 4) { zo += 256 * S_; co += 256; }
        if (ZF == 1) { if (r == 1 + MG) { mbar_wait(sb + 8 * (B_BD + 1), 0); spin(clk(), BD); } zld(); }
        __syncwarp();
        {
          int lane;
          asm volatile("mov.u32 %0, %%laneid;" : "=r"(lane));
          const int c = 2 * (w & 1) + (lane & 1) + 2 * (lane & 2), g = lane >> 2;
          const uint32_t a = sb + SM_X + 4096 * r + (w >> 1) * 2048 + g * 128 + ((c ^ g) << 4);
          const uint4 v0 = lds128(a), v1 = lds128(a + 1024);
          char* po = (char*)gout + (2 * tbase(b) + 128 * (g & 6) + (g & 1)) * 2 * D_ + 256 * r + 64 * (w & 2) + 16 * c;
          if (ITW == 6) STAMPIF(tid == 0 && r < 2, 108 + 10 * r);
          stg128(po, v0);
          stg128(po + 2048 * D_, v1);
        }
        __syncwarp();
        if (elect()) mbar_arrive(sb + 8 * (B_EW + r));
        STAMPIF(tid == 0, 29 + r);
        if (ZF == 0) { if (r == 1 + MG) { mbar_wait(sb + 8 * (B_BD + 1), 0); spin(clk(), BD); } zld(); }
      }
    }
    {
      const uint4 m4 = lds128(sb + SM_SMALL + SMALL_LN + 16 * (lane & 1));
      const uint32_t m_[4] = {m4.x, m4.y, m4.z, m4.w}, xa = x_addr(sb, w, lane);
      float a[16];
#pragma unroll
      for (int i = 0; i < 16; i++) a[i] = 0.f;
#pragma unroll 2
      for (int n = 0; n < 10; n++) {
        uint32_t x_[4];
        ldsm4t(x_, (xa ^ (16 * (n & 1))) + 2048 * (n & 14));
#pragma unroll
        for (int i = 0; i < 4; i++) {
          const float d0 = blo(x_[i]) - blo(m_[i]), d1 = bhi(x_[i]) - bhi(m_[i]);
          a[4 * i] += d0; a[4 * i + 1] += d0 * d0; a[4 * i + 2] += d1; a[4 * i + 3] += d1 * d1;
        }
      }
      STAMPIF(lane == 0, 67 + (w & 1) + 11 * (w >> 1));
      bfly<16>(a, 16, lane & 16); bfly<8>(a, 8, lane & 8); bfly<4>(a, 4, lane & 4); bfly<2>(a, 2, lane & 2);
      if (lane == 0) mbar_arrive(sb + 8 * B_XF);
      STAMPIF(tid == 0, 88);
      sts32(sb + SM_SMALL + SMALL_RED + 16 * lane + 4 * w, __float_as_uint(a[0]));
      bar_sync(5, 128);
      if (w == 0) {
        const uint4 v = lds128(sb + SM_SMALL + SMALL_RED + 16 * lane);
        const float s1 = __uint_as_float(v.x) + __uint_as_float(v.y) + __uint_as_float(v.z) + __uint_as_float(v.w), s2 = __shfl_xor_sync(0xffffffffu, s1, 2);
        const int p = 8 * (lane & 1) + (lane >> 2);
        const float pv = blo(lds32(sb + SM_SMALL + SMALL_LN + 4 * (p >> 1)) >> (16 * (p & 1)));
        const float mu = s1 * (1.f / D_), var = fmaxf(s2 * (1.f / D_) - mu * mu, 0.f);
        const float sd = rbf(__fsqrt_rn(rbf(rbf(var) + 1e-5f)));
        if (!(lane & 2)) st_tag(G->st2 + 16 * b + p, pack2(-0.5f * (pv + mu), 0.5f * sd), e1);
      }
      STAMPIF(tid == 0, 87);
    }
    {
      uint2 v;
      spin(clk(), SD);
      mbar_wait(sb + 8 * (B_BD + 2), 0);
#pragma unroll 1
      for (int i = 0;; i++) {
        v = ld_tag(G->st2 + 128 * m + tid);
        if (__all_sync(0xffffffffu, v.y == e1)) break;
        if (i > (1 << 20)) __trap();
      }
      const uint32_t hm = __byte_perm(v.x, 0, 0x1010), hs = __byte_perm(v.x, 0, 0x3232);
      sts128(sb + SM_STAT + 16 * tid, make_uint4(hm, hs, hm, hs));
      fence_async_s();
      __syncwarp();
      if (lane == 0) mbar_arrive(sb + 8 * B_ST2);
      STAMPIF(tid == 0, 21);
    }
  } else {
    asm volatile("setmaxnreg.dec.sync.aligned.u32 24;");
    if (w != 0) {
    if (w == 2 && lane < 3) asm volatile("prefetch.tensormap [%0];" ::"l"(&P.mG + lane) : "memory");
    if (w & 1) {
      const uint32_t dv = *(const uint16_t*)(gD + 128 * min(lane, 4) + b);
#pragma unroll 1
      for (int j = 4; j < 10; j++) {
        k1_job(sb, j >> 1, 64 * (j & 1) + 16 * (w & 2) + lane, K1N ? __shfl_sync(0xffffffffu, dv, j >> 1) : *(const uint16_t*)(gD + 64 * (j & 14) + b));
        if (ITW == 5) STAMPIF(lane == 0, 96 + j + 5 * (w & 2));
        if (UD && w == 1 && (j & 1)) {
          mbar_wait(sb + 8 * (B_KJ + (j >> 1)), 0);
          const uint32_t t = lds32(sb + SM_SMALL + SMALL_TS + 4 * (j >> 1));
          while (clk() - t < UD);
        }
        __syncwarp();
        if (lane == 0) mbar_arrive(sb + 8 * (B_K + (j >> 1) - 2));
      }
      STAMPIF(tid == 32, 74);
    }
    if (w == 1) {
     {
      mbar_wait(sb + 8 * B_KVS, 0);
      const uint32_t e1 = epoch(sb);
      if (elect()) {
        if (ER) mbar_wait(sb + 8 * B_KV4, 0);
        mbar_wait(sb + 8 * B_EW, 0);
#pragma unroll 1
        for (int it = 0; it < 20; it++) {
          int st = it % 5;
          if ((it & 3) == 0) { flag_wait(G, 8 * m + (it >> 2), e1 * 32); STAMP(45 + (it >> 2)); }
          mbar_wait(sb + 8 * (B_E1 + st), (it / 5) & 1);
          uint32_t fb = sb + 8 * (B_A + st);
          mbar_expect(fb, 8192);
          bulk_g2s(ring + st * 32768, G->AT + (20 * m + it) * 4096, 8192, fb);
        }
        mbar_wait(sb + 8 * B_XF, 0);
        flag_wait(G, 8 * m + FL_X, e1 * 8);
        mbar_arrive(sb + 8 * B_X1);
        STAMP(86);
      }
     }
    } else if (w == 2) {
      if (lane < 4) mbar_expect(sb + 8 * (B_RECV + lane), 12288);
      mbar_wait(sb + 8 * B_BD, 0);
      const uint32_t e1 = epoch(sb), ao = 256 * (lane & 16) + 32 * (lane & 15) + 4 * (lane & 4) + (lane & 8) + 4;
#pragma unroll 1
      for (int it = 0; it < 20; it++) {
        const int st = it % 5;
        const uint32_t a = ring + st * 32768 + ao;
        mbar_wait(sb + 8 * (B_A + st), (it / 5) & 1);
        if (ITW == 7) STAMPIF(lane == 0 && it < 4, 100 + it);
        uint32_t t = 0;
#pragma unroll
        for (int j = 0; j < 8; j++) t |= lds32(a + 512 * j) ^ e1;
        if (__any_sync(0xffffffffu, t & 1)) {
#pragma unroll 1
          for (int j = 0; j < 8; j++) a_check(a + 512 * j, (const char*)G->AT + (20 * m + it) * 8192 + ao + 512 * j, e1);
        }
        if (lane == 0) mbar_arrive(sb + 8 * (B_F1 + st));
        if (ITW == 7) STAMPIF(lane == 0 && it < 4, 104 + it);
      }
    } else {
      mbar_wait(sb + 8 * B_KVS, 0);
      mbar_wait(sb + 8 * (B_BD + 1), 0);
      if (b >= 96 && elect()) { load_box(P, sb, b, 4); load_box(P, sb, b, 5); }
      spin(clk(), CD);
      __syncwarp();
      const uint32_t e1 = epoch(sb);
#pragma unroll 1
      for (int n = 0; n < 5; n++) {
        int lane;
        asm volatile("mov.u32 %0, %%laneid;" : "=r"(lane));
        if (n == 3) {
          fence_async_s();
          __syncwarp();
          if (lane == 0) mbar_arrive(sb + 8 * B_F);
          STAMPIF(lane == 0, 34);
          {
            mbar_wait(sb + 8 * (B_EW + 4), 0);
            const char* po = (char*)gout + (2 * tbase(b) + 64 * (lane & 28) + ((lane >> 1) & 1)) * 2 * D_ + (lane & 1) * 640;
            uint32_t v = 0;
#pragma unroll
            for (int r = 0; r < 5; r++) v ^= rdback(po + 128 * r);
            rdwait(sb, v);
            __syncwarp();
            if (lane == 0) flag_add(G, 8 * m + FL_X);
            STAMPIF(lane == 0, 94);
          }
          mbar_wait(sb + 8 * (B_BD + 2), 0);
          if (lane < 2) mbar_arrive(sb + 8 * (B_E1 + 5));
          if (m < 12) {
            rdwait(sb, rdback(G->cimg + s * 3072 + (m % 6) * 512 + (m < 6 ? 0 : 256) + 64 * (lane & 3)));
            __syncwarp();
            if (lane == 0) flag_add(G, FL_C + 8 * s);
            STAMPIF(lane == 0, 35);
          }
          if (elect()) {
            flag_wait(G, FL_C + 8 * s, e1 * 12);
            fence_async_g();
            STAMP(54);
            mbar_expect(sb + 8 * B_EXT, 6144);
            bulk_g2s(sb + SM_EXT, G->cimg + s * 3072, 6144, sb + 8 * B_EXT);
          }
          __syncwarp();
          mbar_wait(sb + 8 * B_ST2, 0);
        }
        const int j = n < 3 ? min(16 * n + (lane >> 1), 39) : min(16 * n - 8 + (lane >> 1), 59), k = j < 20 ? j : j < 40 ? j - 20 : j - 40;
        const uint2* pj = (const uint2*)(G->mv + 2048 * (e1 & 1) + 4 * (lane & 1) + 8 * (k + (j < 40 ? (j < 20 ? 160 : 120) + (m < 6 ? 0 : 20) : 200 + 20 * (s & 1))));
        uint4 a;
#pragma unroll 1
        for (int i = 0;; i++) {
          a = ld_tag2(pj);
          if (__all_sync(0xffffffffu, a.x != 0)) break;
          if (i > (1 << 20)) __trap();
        }
        const uint32_t d = sb + SM_CB + 64 * k + 8 * (lane & 1) + (j >= 20 && j < 40 ? 16 : 0);
        sts64(d, ~__byte_perm(a.x, a.y, 0x5410), ~__byte_perm(a.z, a.w, 0x5410));
        sts64(d + 32, ~__byte_perm(a.x, a.y, 0x7632), ~__byte_perm(a.z, a.w, 0x7632));
      }
      __syncwarp();
      if (lane == 0) mbar_arrive(sb + 8 * B_GB);
      STAMPIF(lane == 0, 39);
    }
    } else {
      STAMPIF(lane == 0, 62);
      int rw = sched_run<0>(P, In{gk, gv, gsk, gWg, gWu, gWd, gss}, sb, b, lane, __shfl_sync(0xffffffffu, t_0, 0));
      if (elect()) {
        STAMP(69);
        mbar_wait(sb + 8 * B_KVS, 0);
        if (ER) mbar_wait(sb + 8 * B_KV4, 0);
        STAMP(70);
        int rd = 0, c = 0;
#pragma unroll 1
        for (int it = 0; it < 20; it++) {
          load_w(P, sb, s, it);
          if ((PWM >> it) & 1) { l2_prefetch(gWg + (128 * rw + b) * F_, 2 * F_); l2_prefetch(gWu + (128 * rw + b) * F_, 2 * F_); rw++; }
          if ((PDM >> it) & 1) { l2_prefetch(gWd + (512 * rd + 4 * b) * D_, 8 * D_); rd++; }
          if (((STM >> it) & 1) && b < 96) {
            const int grp = m % 6;
            if (c == 4) mbar_wait(sb + 8 * (B_BD + 1), 0);
            if (c == 0) mbar_expect(sb + 8 * B_ST0, 40960);
#pragma unroll
            for (int j = 0; j < 2; j++, c++)
              tma2d(sb + (c < 2 ? SM_EXT : SM_RING + R_X - 8192) + 4096 * c, &P.mG + (grp & 1), 192 * s + 64 * (grp >> 1), (m < 6 ? 0 : 320) + 32 * c, sb + 8 * B_ST0);
          }
        }
#pragma unroll
        for (int k = 0; k < 10; k++) {
          const int st = (k + 5) % 6, pe = k < 4 ? k >> 1 : k & 1, ps = k < 4 ? k & 1 : k >> 1;
          mbar_wait(sb + 8 * (k < 6 ? B_E1 + st : B_EB + k - 6), 0);
          if (k == 2) mbar_arrive_remote(mapa(sb + 8 * B_P0, (b & 1) ^ 1));
          mbar_expect(sb + 8 * (B_FB + k), 24576);
          tma2d(ring + st * 32768 + 8192, &P.mD, 320 * (s & 1) + 64 * out_blk(s, ps), 192 * (s ^ pe), sb + 8 * (B_FB + k));
        }
      }
    }
  }
}

typedef CUresult (*EncFn)(CUtensorMap*, CUtensorMapDataType, cuuint32_t, void*, const cuuint64_t*, const cuuint64_t*, const cuuint32_t*, const cuuint32_t*,
                          CUtensorMapInterleave, CUtensorMapSwizzle, CUtensorMapL2promotion, CUtensorMapFloatOOBfill);
static void mkmap(EncFn enc, CUtensorMap* m, const void* p, int rank, const cuuint64_t* dims, const cuuint64_t* strides, const cuuint32_t* box, CUtensorMapSwizzle sw) {
  cuuint32_t es[5] = {1, 1, 1, 1, 1};
  CUresult r = enc(m, CU_TENSOR_MAP_DATA_TYPE_BFLOAT16, rank, (void*)p, dims, strides, box, es, CU_TENSOR_MAP_INTERLEAVE_NONE, sw,
                   CU_TENSOR_MAP_L2_PROMOTION_L2_128B, CU_TENSOR_MAP_FLOAT_OOB_FILL_NONE);
  if (r != CUDA_SUCCESS) fprintf(stderr, "tensor map encode failed: %d\n", (int)r);
}

extern "C" void kernel_launch(void* const* d_in, const int* in_sizes, int n_in, void* d_out, int out_size) {
  void* fn = nullptr;
  cudaDriverEntryPointQueryResult qr;
  cudaGetDriverEntryPoint("cuTensorMapEncodeTiled", &fn, cudaEnableDefault, &qr);
  EncFn enc = (EncFn)fn;
  Scr* G;
  cudaGetSymbolAddress((void**)&G, g_scr);
  Params P;
  { cuuint64_t d[] = {128, 16, 640}, st[] = {256, 4096}; cuuint32_t bx[] = {144, 16, 1}; mkmap(enc, &P.mS, d_in[4], 3, d, st, bx, CU_TENSOR_MAP_SWIZZLE_NONE); }
  { cuuint64_t d[] = {3840, 64, 10}, st[] = {7680, 64 * 7680}; cuuint32_t bx[] = {16, 64, 5}; mkmap(enc, &P.mWm, d_in[11], 3, d, st, bx, CU_TENSOR_MAP_SWIZZLE_32B); }
  { cuuint64_t d[] = {32, 20, 256, 8}, st[] = {64, 10240, 1280}; cuuint32_t bx[] = {40, 1, 9, 8}, bx2[] = {40, 1, 8, 8};
    mkmap(enc, &P.mK, d_in[1], 4, d, st, bx, CU_TENSOR_MAP_SWIZZLE_NONE); mkmap(enc, &P.mV, d_in[2], 4, d, st, bx2, CU_TENSOR_MAP_SWIZZLE_NONE); }
  { cuuint64_t d[] = {1536, 640}, st[] = {3072}; cuuint32_t bx[] = {64, 32};
    mkmap(enc, &P.mG, d_in[7], 2, d, st, bx, CU_TENSOR_MAP_SWIZZLE_128B); mkmap(enc, &P.mU, d_in[8], 2, d, st, bx, CU_TENSOR_MAP_SWIZZLE_128B); }
  { cuuint64_t d[] = {640, 1536}, st[] = {1280}; cuuint32_t bx[] = {64, 192}; mkmap(enc, &P.mD, d_in[9], 2, d, st, bx, CU_TENSOR_MAP_SWIZZLE_128B); }
  { cuuint64_t d[] = {64, 2, 8, 10, 128}, st[] = {1280, 256 * 1280, 128, 2560}; cuuint32_t bx[] = {64, 2, 8, 5, 1}; mkmap(enc, &P.mX, d_in[0], 5, d, st, bx, CU_TENSOR_MAP_SWIZZLE_128B); }
  cudaFuncSetAttribute(fused_kernel, cudaFuncAttributeMaxDynamicSharedMemorySize, SM_TOTAL + DEVSM);
  cudaLaunchConfig_t cfg = {};
  cfg.gridDim = dim3(128); cfg.blockDim = dim3(512); cfg.dynamicSmemBytes = SM_TOTAL + DEVSM; cfg.stream = cudaStreamPerThread;
  cudaLaunchAttribute at[1];
  at[0].id = cudaLaunchAttributeClusterDimension; at[0].val.clusterDim.x = 2; at[0].val.clusterDim.y = 1; at[0].val.clusterDim.z = 1;
  cfg.attrs = at; cfg.numAttrs = 1;
  cudaLaunchKernelEx(&cfg, fused_kernel, (const bf16*)d_in[1], (const bf16*)d_in[2], (const bf16*)d_in[3], (const bf16*)d_in[5], (const bf16*)d_in[10], G,
                     (const bf16*)d_in[7], (const bf16*)d_in[8], (const bf16*)d_in[9], (bf16*)d_out, (const bf16*)d_in[4], P);
}
```

```cpp
#include <cuda_runtime.h>
#include <cuda.h>
#include <cuda_bf16.h>
#include <stdio.h>
#include <stdint.h>
typedef __nv_bfloat16 bf16;
__device__ __forceinline__ uint32_t smem_u32(const void* p) { return (uint32_t)__cvta_generic_to_shared(p); }
__device__ __forceinline__ void mbar_init(uint32_t bar, int cnt) { asm volatile("mbarrier.init.shared::cta.b64 [%0], %1;" ::"r"(bar), "r"(cnt) : "memory"); }
__device__ __forceinline__ void mbar_expect(uint32_t bar, int bytes) { asm volatile("mbarrier.arrive.expect_tx.shared::cta.b64 _, [%0], %1;" ::"r"(bar), "r"(bytes) : "memory"); }
__device__ __forceinline__ void mbar_arrive(uint32_t bar) { asm volatile("mbarrier.arrive.shared::cta.b64 _, [%0];" ::"r"(bar) : "memory"); }
__device__ __forceinline__ void mbar_arrive_remote(uint32_t bar) { asm volatile("mbarrier.arrive.relaxed.cluster.shared::cluster.b64 _, [%0];" ::"r"(bar) : "memory"); }
__device__ __forceinline__ uint32_t mapa(uint32_t a, uint32_t cta) { uint32_t r; asm("mapa.shared::cluster.u32 %0, %1, %2;" : "=r"(r) : "r"(a), "r"(cta)); return r; }
__device__ __forceinline__ bool mbar_try(uint32_t bar, int parity) {
  uint32_t ok;
  asm volatile("{\n.reg .pred p;\nmbarrier.try_wait.parity.shared::cta.b64 p, [%1], %2;\nselp.u32 %0, 1, 0, p;\n}" : "=r"(ok) : "r"(bar), "r"(parity) : "memory");
  return ok;
}
__device__ __forceinline__ void mbar_wait(uint32_t bar, int parity) {
#pragma unroll 1
  for (int i = 0; i < (1 << 20); i++) { if (mbar_try(bar, parity)) return; }
  __trap();
}
__device__ __forceinline__ bool elect() {
  uint32_t p;
  asm volatile("{\n.reg .pred P;\nelect.sync _|P, 0xffffffff;\nselp.u32 %0, 1, 0, P;\n}" : "=r"(p));
  return p;
}
__device__ __forceinline__ void tma2d(uint32_t dst, const CUtensorMap* m, int c0, int c1, uint32_t bar) {
  asm volatile("cp.async.bulk.tensor.2d.shared::cluster.global.mbarrier::complete_tx::bytes [%0], [%1, {%3, %4}], [%2];" ::"r"(dst), "l"(m), "r"(bar), "r"(c0), "r"(c1) : "memory");
}
__device__ __forceinline__ void tma3d(uint32_t dst, const CUtensorMap* m, int c0, int c1, int c2, uint32_t bar) {
  asm volatile("cp.async.bulk.tensor.3d.shared::cluster.global.mbarrier::complete_tx::bytes [%0], [%1, {%3, %4, %5}], [%2];" ::"r"(dst), "l"(m), "r"(bar), "r"(c0), "r"(c1), "r"(c2) : "memory");
}
__device__ __forceinline__ void tma4d(uint32_t dst, const CUtensorMap* m, int c0, int c1, int c2, int c3, uint32_t bar) {
  asm volatile("cp.async.bulk.tensor.4d.shared::cluster.global.mbarrier::complete_tx::bytes [%0], [%1, {%3, %4, %5, %6}], [%2];" ::"r"(dst), "l"(m), "r"(bar), "r"(c0), "r"(c1), "r"(c2), "r"(c3) : "memory");
}
__device__ __forceinline__ void tma5d(uint32_t dst, const CUtensorMap* m, int c0, int c1, int c2, int c3, int c4, uint32_t bar) {
  asm volatile("cp.async.bulk.tensor.5d.shared::cluster.global.mbarrier::complete_tx::bytes [%0], [%1, {%3, %4, %5, %6, %7}], [%2];" ::"r"(dst), "l"(m), "r"(bar), "r"(c0), "r"(c1), "r"(c2), "r"(c3), "r"(c4) : "memory");
}
__device__ __forceinline__ void tma_store2d(const CUtensorMap* m, uint32_t src, int c0, int c1) {
  asm volatile("cp.async.bulk.tensor.2d.global.shared::cta.bulk_group [%0, {%2, %3}], [%1];" ::"l"(m), "r"(src), "r"(c0), "r"(c1) : "memory");
}
__device__ __forceinline__ void tma_store4d(const CUtensorMap* m, uint32_t src, int c0, int c1, int c2, int c3) {
  asm volatile("cp.async.bulk.tensor.4d.global.shared::cta.bulk_group [%0, {%2, %3, %4, %5}], [%1];" ::"l"(m), "r"(src), "r"(c0), "r"(c1), "r"(c2), "r"(c3) : "memory");
}
__device__ __forceinline__ void tma_prefetch2d(const CUtensorMap* m, int c0, int c1) {
  asm volatile("cp.async.bulk.prefetch.tensor.2d.L2.global [%0, {%1, %2}];" ::"l"(m), "r"(c0), "r"(c1) : "memory");
}
__device__ __forceinline__ void bulk_g2s(uint32_t dst, const void* src, int bytes, uint32_t bar) {
  asm volatile("cp.async.bulk.shared::cluster.global.mbarrier::complete_tx::bytes [%0], [%1], %2, [%3];" ::"r"(dst), "l"(src), "r"(bytes), "r"(bar) : "memory");
}
__device__ __forceinline__ void bulk_s2g(void* dst, uint32_t src, int bytes) {
  asm volatile("cp.async.bulk.global.shared::cta.bulk_group [%0], [%1], %2;" ::"l"(dst), "r"(src), "r"(bytes) : "memory");
}
__device__ __forceinline__ void cp16(uint32_t dst, const void* src) { asm volatile("cp.async.cg.shared.global [%0], [%1], 16;" ::"r"(dst), "l"(src) : "memory"); }
__device__ __forceinline__ void cp16z(uint32_t dst, const void* src, int n) { asm volatile("cp.async.cg.shared.global [%0], [%1], 16, %2;" ::"r"(dst), "l"(src), "r"(n) : "memory"); }
__device__ __forceinline__ void cp_arrive(uint32_t bar) { asm volatile("cp.async.mbarrier.arrive.noinc.shared::cta.b64 [%0];" ::"r"(bar) : "memory"); }
__device__ __forceinline__ void st_async4(uint32_t dst, const uint32_t* v, uint32_t bar) {
  asm volatile("st.async.weak.shared::cluster.mbarrier::complete_tx::bytes.v4.b32 [%0], {%1, %2, %3, %4}, [%5];" ::"r"(dst), "r"(v[0]), "r"(v[1]), "r"(v[2]), "r"(v[3]), "r"(bar) : "memory");
}
__device__ __forceinline__ void wg_fence() { asm volatile("wgmma.fence.sync.aligned;" ::: "memory"); }
__device__ __forceinline__ void wg_commit() { asm volatile("wgmma.commit_group.sync.aligned;" ::: "memory"); }
template <int N> __device__ __forceinline__ void wg_wait() { asm volatile("wgmma.wait_group.sync.aligned %0;" ::"n"(N) : "memory"); }
__device__ __forceinline__ uint64_t mkdesc(uint32_t addr, uint32_t lbo, uint32_t sbo, uint32_t swz) {
  return (uint64_t)((addr & 0x3FFFF) >> 4) | ((uint64_t)(lbo >> 4) << 16) | ((uint64_t)(sbo >> 4) << 32) | ((uint64_t)swz << 62);
}
__device__ __forceinline__ void ldsm4t(uint32_t* r, uint32_t a) {
  asm volatile("ldmatrix.sync.aligned.m8n8.x4.trans.shared.b16 {%0,%1,%2,%3}, [%4];" : "=r"(r[0]), "=r"(r[1]), "=r"(r[2]), "=r"(r[3]) : "r"(a) : "memory");
}
__device__ __forceinline__ void stsm4(uint32_t a, const uint32_t* r) {
  asm volatile("stmatrix.sync.aligned.m8n8.x4.shared.b16 [%0], {%1,%2,%3,%4};" ::"r"(a), "r"(r[0]), "r"(r[1]), "r"(r[2]), "r"(r[3]) : "memory");
}
__device__ __forceinline__ void stsm4t(uint32_t a, const uint32_t* r) {
  asm volatile("stmatrix.sync.aligned.m8n8.x4.trans.shared.b16 [%0], {%1,%2,%3,%4};" ::"r"(a), "r"(r[0]), "r"(r[1]), "r"(r[2]), "r"(r[3]) : "memory");
}
__device__ __forceinline__ void bar_sync(int id, int n) { asm volatile("bar.sync %0, %1;" ::"r"(id), "r"(n) : "memory"); }
__device__ __forceinline__ void bar_arrive(int id, int n) { asm volatile("bar.arrive %0, %1;" ::"r"(id), "r"(n) : "memory"); }
__device__ __forceinline__ uint32_t lds32(uint32_t a) { uint32_t v; asm volatile("ld.shared.b32 %0, [%1];" : "=r"(v) : "r"(a) : "memory"); return v; }
__device__ __forceinline__ uint2 lds64(uint32_t a) { uint2 v; asm volatile("ld.shared.v2.b32 {%0,%1}, [%2];" : "=r"(v.x), "=r"(v.y) : "r"(a) : "memory"); return v; }
__device__ __forceinline__ uint4 lds128(uint32_t a) { uint4 v; asm volatile("ld.shared.v4.b32 {%0,%1,%2,%3}, [%4];" : "=r"(v.x), "=r"(v.y), "=r"(v.z), "=r"(v.w) : "r"(a) : "memory"); return v; }
__device__ __forceinline__ void sts16(uint32_t a, uint32_t v) { asm volatile("st.shared.b16 [%0], %1;" ::"r"(a), "h"((uint16_t)v) : "memory"); }
__device__ __forceinline__ void sts32(uint32_t a, uint32_t v) { asm volatile("st.shared.b32 [%0], %1;" ::"r"(a), "r"(v) : "memory"); }
__device__ __forceinline__ void sts64(uint32_t a, uint32_t x, uint32_t y) { asm volatile("st.shared.v2.b32 [%0], {%1,%2};" ::"r"(a), "r"(x), "r"(y) : "memory"); }
__device__ __forceinline__ void sts128(uint32_t a, uint4 v) { asm volatile("st.shared.v4.b32 [%0], {%1,%2,%3,%4};" ::"r"(a), "r"(v.x), "r"(v.y), "r"(v.z), "r"(v.w) : "memory"); }
template<int TB> __device__ __forceinline__ void wgmma_rs_n128(float* d, const uint32_t* a, uint64_t db, int sd) {
  asm volatile("{\n.reg .pred p;\nsetp.ne.b32 p, %69, 0;\n"
    "wgmma.mma_async.sync.aligned.m64n128k16.f32.bf16.bf16 {%0, %1, %2, %3, %4, %5, %6, %7, %8, %9, %10, %11, %12, %13, %14, %15, %16, %17, %18, %19, %20, %21, %22, %23, %24, %25, %26, %27, %28, %29, %30, %31, %32, %33, %34, %35, %36, %37, %38, %39, %40, %41, %42, %43, %44, %45, %46, %47, %48, %49, %50, %51, %52, %53, %54, %55, %56, %57, %58, %59, %60, %61, %62, %63}, {%64, %65, %66, %67}, %68, p, 1, 1, %70;\n}"
    : "+f"(d[0]), "+f"(d[1]), "+f"(d[2]), "+f"(d[3]), "+f"(d[4]), "+f"(d[5]), "+f"(d[6]), "+f"(d[7]), "+f"(d[8]), "+f"(d[9]), "+f"(d[10]), "+f"(d[11]), "+f"(d[12]), "+f"(d[13]), "+f"(d[14]), "+f"(d[15]), "+f"(d[16]), "+f"(d[17]), "+f"(d[18]), "+f"(d[19]), "+f"(d[20]), "+f"(d[21]), "+f"(d[22]), "+f"(d[23]), "+f"(d[24]), "+f"(d[25]), "+f"(d[26]), "+f"(d[27]), "+f"(d[28]), "+f"(d[29]), "+f"(d[30]), "+f"(d[31]), "+f"(d[32]), "+f"(d[33]), "+f"(d[34]), "+f"(d[35]), "+f"(d[36]), "+f"(d[37]), "+f"(d[38]), "+f"(d[39]), "+f"(d[40]), "+f"(d[41]), "+f"(d[42]), "+f"(d[43]), "+f"(d[44]), "+f"(d[45]), "+f"(d[46]), "+f"(d[47]), "+f"(d[48]), "+f"(d[49]), "+f"(d[50]), "+f"(d[51]), "+f"(d[52]), "+f"(d[53]), "+f"(d[54]), "+f"(d[55]), "+f"(d[56]), "+f"(d[57]), "+f"(d[58]), "+f"(d[59]), "+f"(d[60]), "+f"(d[61]), "+f"(d[62]), "+f"(d[63])
    : "r"(a[0]), "r"(a[1]), "r"(a[2]), "r"(a[3]), "l"(db), "r"(sd), "n"(TB));
}

template<int TB> __device__ __forceinline__ void wgmma_rs_n160(float* d, const uint32_t* a, uint64_t db, int sd) {
  asm volatile("{\n.reg .pred p;\nsetp.ne.b32 p, %85, 0;\n"
    "wgmma.mma_async.sync.aligned.m64n160k16.f32.bf16.bf16 {%0, %1, %2, %3, %4, %5, %6, %7, %8, %9, %10, %11, %12, %13, %14, %15, %16, %17, %18, %19, %20, %21, %22, %23, %24, %25, %26, %27, %28, %29, %30, %31, %32, %33, %34, %35, %36, %37, %38, %39, %40, %41, %42, %43, %44, %45, %46, %47, %48, %49, %50, %51, %52, %53, %54, %55, %56, %57, %58, %59, %60, %61, %62, %63, %64, %65, %66, %67, %68, %69, %70, %71, %72, %73, %74, %75, %76, %77, %78, %79}, {%80, %81, %82, %83}, %84, p, 1, 1, %86;\n}"
    : "+f"(d[0]), "+f"(d[1]), "+f"(d[2]), "+f"(d[3]), "+f"(d[4]), "+f"(d[5]), "+f"(d[6]), "+f"(d[7]), "+f"(d[8]), "+f"(d[9]), "+f"(d[10]), "+f"(d[11]), "+f"(d[12]), "+f"(d[13]), "+f"(d[14]), "+f"(d[15]), "+f"(d[16]), "+f"(d[17]), "+f"(d[18]), "+f"(d[19]), "+f"(d[20]), "+f"(d[21]), "+f"(d[22]), "+f"(d[23]), "+f"(d[24]), "+f"(d[25]), "+f"(d[26]), "+f"(d[27]), "+f"(d[28]), "+f"(d[29]), "+f"(d[30]), "+f"(d[31]), "+f"(d[32]), "+f"(d[33]), "+f"(d[34]), "+f"(d[35]), "+f"(d[36]), "+f"(d[37]), "+f"(d[38]), "+f"(d[39]), "+f"(d[40]), "+f"(d[41]), "+f"(d[42]), "+f"(d[43]), "+f"(d[44]), "+f"(d[45]), "+f"(d[46]), "+f"(d[47]), "+f"(d[48]), "+f"(d[49]), "+f"(d[50]), "+f"(d[51]), "+f"(d[52]), "+f"(d[53]), "+f"(d[54]), "+f"(d[55]), "+f"(d[56]), "+f"(d[57]), "+f"(d[58]), "+f"(d[59]), "+f"(d[60]), "+f"(d[61]), "+f"(d[62]), "+f"(d[63]), "+f"(d[64]), "+f"(d[65]), "+f"(d[66]), "+f"(d[67]), "+f"(d[68]), "+f"(d[69]), "+f"(d[70]), "+f"(d[71]), "+f"(d[72]), "+f"(d[73]), "+f"(d[74]), "+f"(d[75]), "+f"(d[76]), "+f"(d[77]), "+f"(d[78]), "+f"(d[79])
    : "r"(a[0]), "r"(a[1]), "r"(a[2]), "r"(a[3]), "l"(db), "r"(sd), "n"(TB));
}

template<int TB> __device__ __forceinline__ void wgmma_rs_n192(float* d, const uint32_t* a, uint64_t db, int sd) {
  asm volatile("{\n.reg .pred p;\nsetp.ne.b32 p, %101, 0;\n"
    "wgmma.mma_async.sync.aligned.m64n192k16.f32.bf16.bf16 {%0, %1, %2, %3, %4, %5, %6, %7, %8, %9, %10, %11, %12, %13, %14, %15, %16, %17, %18, %19, %20, %21, %22, %23, %24, %25, %26, %27, %28, %29, %30, %31, %32, %33, %34, %35, %36, %37, %38, %39, %40, %41, %42, %43, %44, %45, %46, %47, %48, %49, %50, %51, %52, %53, %54, %55, %56, %57, %58, %59, %60, %61, %62, %63, %64, %65, %66, %67, %68, %69, %70, %71, %72, %73, %74, %75, %76, %77, %78, %79, %80, %81, %82, %83, %84, %85, %86, %87, %88, %89, %90, %91, %92, %93, %94, %95}, {%96, %97, %98, %99}, %100, p, 1, 1, %102;\n}"
    : "+f"(d[0]), "+f"(d[1]), "+f"(d[2]), "+f"(d[3]), "+f"(d[4]), "+f"(d[5]), "+f"(d[6]), "+f"(d[7]), "+f"(d[8]), "+f"(d[9]), "+f"(d[10]), "+f"(d[11]), "+f"(d[12]), "+f"(d[13]), "+f"(d[14]), "+f"(d[15]), "+f"(d[16]), "+f"(d[17]), "+f"(d[18]), "+f"(d[19]), "+f"(d[20]), "+f"(d[21]), "+f"(d[22]), "+f"(d[23]), "+f"(d[24]), "+f"(d[25]), "+f"(d[26]), "+f"(d[27]), "+f"(d[28]), "+f"(d[29]), "+f"(d[30]), "+f"(d[31]), "+f"(d[32]), "+f"(d[33]), "+f"(d[34]), "+f"(d[35]), "+f"(d[36]), "+f"(d[37]), "+f"(d[38]), "+f"(d[39]), "+f"(d[40]), "+f"(d[41]), "+f"(d[42]), "+f"(d[43]), "+f"(d[44]), "+f"(d[45]), "+f"(d[46]), "+f"(d[47]), "+f"(d[48]), "+f"(d[49]), "+f"(d[50]), "+f"(d[51]), "+f"(d[52]), "+f"(d[53]), "+f"(d[54]), "+f"(d[55]), "+f"(d[56]), "+f"(d[57]), "+f"(d[58]), "+f"(d[59]), "+f"(d[60]), "+f"(d[61]), "+f"(d[62]), "+f"(d[63]), "+f"(d[64]), "+f"(d[65]), "+f"(d[66]), "+f"(d[67]), "+f"(d[68]), "+f"(d[69]), "+f"(d[70]), "+f"(d[71]), "+f"(d[72]), "+f"(d[73]), "+f"(d[74]), "+f"(d[75]), "+f"(d[76]), "+f"(d[77]), "+f"(d[78]), "+f"(d[79]), "+f"(d[80]), "+f"(d[81]), "+f"(d[82]), "+f"(d[83]), "+f"(d[84]), "+f"(d[85]), "+f"(d[86]), "+f"(d[87]), "+f"(d[88]), "+f"(d[89]), "+f"(d[90]), "+f"(d[91]), "+f"(d[92]), "+f"(d[93]), "+f"(d[94]), "+f"(d[95])
    : "r"(a[0]), "r"(a[1]), "r"(a[2]), "r"(a[3]), "l"(db), "r"(sd), "n"(TB));
}

template<int TB> __device__ __forceinline__ void wgmma_rs_n32(float* d, const uint32_t* a, uint64_t db, int sd) {
  asm volatile("{\n.reg .pred p;\nsetp.ne.b32 p, %21, 0;\n"
    "wgmma.mma_async.sync.aligned.m64n32k16.f32.bf16.bf16 {%0, %1, %2, %3, %4, %5, %6, %7, %8, %9, %10, %11, %12, %13, %14, %15}, {%16, %17, %18, %19}, %20, p, 1, 1, %22;\n}"
    : "+f"(d[0]), "+f"(d[1]), "+f"(d[2]), "+f"(d[3]), "+f"(d[4]), "+f"(d[5]), "+f"(d[6]), "+f"(d[7]), "+f"(d[8]), "+f"(d[9]), "+f"(d[10]), "+f"(d[11]), "+f"(d[12]), "+f"(d[13]), "+f"(d[14]), "+f"(d[15])
    : "r"(a[0]), "r"(a[1]), "r"(a[2]), "r"(a[3]), "l"(db), "r"(sd), "n"(TB));
}

template<int TB> __device__ __forceinline__ void wgmma_rs_n64(float* d, const uint32_t* a, uint64_t db, int sd) {
  asm volatile("{\n.reg .pred p;\nsetp.ne.b32 p, %37, 0;\n"
    "wgmma.mma_async.sync.aligned.m64n64k16.f32.bf16.bf16 {%0, %1, %2, %3, %4, %5, %6, %7, %8, %9, %10, %11, %12, %13, %14, %15, %16, %17, %18, %19, %20, %21, %22, %23, %24, %25, %26, %27, %28, %29, %30, %31}, {%32, %33, %34, %35}, %36, p, 1, 1, %38;\n}"
    : "+f"(d[0]), "+f"(d[1]), "+f"(d[2]), "+f"(d[3]), "+f"(d[4]), "+f"(d[5]), "+f"(d[6]), "+f"(d[7]), "+f"(d[8]), "+f"(d[9]), "+f"(d[10]), "+f"(d[11]), "+f"(d[12]), "+f"(d[13]), "+f"(d[14]), "+f"(d[15]), "+f"(d[16]), "+f"(d[17]), "+f"(d[18]), "+f"(d[19]), "+f"(d[20]), "+f"(d[21]), "+f"(d[22]), "+f"(d[23]), "+f"(d[24]), "+f"(d[25]), "+f"(d[26]), "+f"(d[27]), "+f"(d[28]), "+f"(d[29]), "+f"(d[30]), "+f"(d[31])
    : "r"(a[0]), "r"(a[1]), "r"(a[2]), "r"(a[3]), "l"(db), "r"(sd), "n"(TB));
}

template<int TB> __device__ __forceinline__ void wgmma_rs_n96(float* d, const uint32_t* a, uint64_t db, int sd) {
  asm volatile("{\n.reg .pred p;\nsetp.ne.b32 p, %53, 0;\n"
    "wgmma.mma_async.sync.aligned.m64n96k16.f32.bf16.bf16 {%0, %1, %2, %3, %4, %5, %6, %7, %8, %9, %10, %11, %12, %13, %14, %15, %16, %17, %18, %19, %20, %21, %22, %23, %24, %25, %26, %27, %28, %29, %30, %31, %32, %33, %34, %35, %36, %37, %38, %39, %40, %41, %42, %43, %44, %45, %46, %47}, {%48, %49, %50, %51}, %52, p, 1, 1, %54;\n}"
    : "+f"(d[0]), "+f"(d[1]), "+f"(d[2]), "+f"(d[3]), "+f"(d[4]), "+f"(d[5]), "+f"(d[6]), "+f"(d[7]), "+f"(d[8]), "+f"(d[9]), "+f"(d[10]), "+f"(d[11]), "+f"(d[12]), "+f"(d[13]), "+f"(d[14]), "+f"(d[15]), "+f"(d[16]), "+f"(d[17]), "+f"(d[18]), "+f"(d[19]), "+f"(d[20]), "+f"(d[21]), "+f"(d[22]), "+f"(d[23]), "+f"(d[24]), "+f"(d[25]), "+f"(d[26]), "+f"(d[27]), "+f"(d[28]), "+f"(d[29]), "+f"(d[30]), "+f"(d[31]), "+f"(d[32]), "+f"(d[33]), "+f"(d[34]), "+f"(d[35]), "+f"(d[36]), "+f"(d[37]), "+f"(d[38]), "+f"(d[39]), "+f"(d[40]), "+f"(d[41]), "+f"(d[42]), "+f"(d[43]), "+f"(d[44]), "+f"(d[45]), "+f"(d[46]), "+f"(d[47])
    : "r"(a[0]), "r"(a[1]), "r"(a[2]), "r"(a[3]), "l"(db), "r"(sd), "n"(TB));
}

template<int TA, int TB> __device__ __forceinline__ void wgmma_ss_n192(float* d, uint64_t da, uint64_t db, int sd) {
  asm volatile("{\n.reg .pred p;\nsetp.ne.b32 p, %98, 0;\n"
    "wgmma.mma_async.sync.aligned.m64n192k16.f32.bf16.bf16 {%0, %1, %2, %3, %4, %5, %6, %7, %8, %9, %10, %11, %12, %13, %14, %15, %16, %17, %18, %19, %20, %21, %22, %23, %24, %25, %26, %27, %28, %29, %30, %31, %32, %33, %34, %35, %36, %37, %38, %39, %40, %41, %42, %43, %44, %45, %46, %47, %48, %49, %50, %51, %52, %53, %54, %55, %56, %57, %58, %59, %60, %61, %62, %63, %64, %65, %66, %67, %68, %69, %70, %71, %72, %73, %74, %75, %76, %77, %78, %79, %80, %81, %82, %83, %84, %85, %86, %87, %88, %89, %90, %91, %92, %93, %94, %95}, %96, %97, p, 1, 1, %99, %100;\n}"
    : "+f"(d[0]), "+f"(d[1]), "+f"(d[2]), "+f"(d[3]), "+f"(d[4]), "+f"(d[5]), "+f"(d[6]), "+f"(d[7]), "+f"(d[8]), "+f"(d[9]), "+f"(d[10]), "+f"(d[11]), "+f"(d[12]), "+f"(d[13]), "+f"(d[14]), "+f"(d[15]), "+f"(d[16]), "+f"(d[17]), "+f"(d[18]), "+f"(d[19]), "+f"(d[20]), "+f"(d[21]), "+f"(d[22]), "+f"(d[23]), "+f"(d[24]), "+f"(d[25]), "+f"(d[26]), "+f"(d[27]), "+f"(d[28]), "+f"(d[29]), "+f"(d[30]), "+f"(d[31]), "+f"(d[32]), "+f"(d[33]), "+f"(d[34]), "+f"(d[35]), "+f"(d[36]), "+f"(d[37]), "+f"(d[38]), "+f"(d[39]), "+f"(d[40]), "+f"(d[41]), "+f"(d[42]), "+f"(d[43]), "+f"(d[44]), "+f"(d[45]), "+f"(d[46]), "+f"(d[47]), "+f"(d[48]), "+f"(d[49]), "+f"(d[50]), "+f"(d[51]), "+f"(d[52]), "+f"(d[53]), "+f"(d[54]), "+f"(d[55]), "+f"(d[56]), "+f"(d[57]), "+f"(d[58]), "+f"(d[59]), "+f"(d[60]), "+f"(d[61]), "+f"(d[62]), "+f"(d[63]), "+f"(d[64]), "+f"(d[65]), "+f"(d[66]), "+f"(d[67]), "+f"(d[68]), "+f"(d[69]), "+f"(d[70]), "+f"(d[71]), "+f"(d[72]), "+f"(d[73]), "+f"(d[74]), "+f"(d[75]), "+f"(d[76]), "+f"(d[77]), "+f"(d[78]), "+f"(d[79]), "+f"(d[80]), "+f"(d[81]), "+f"(d[82]), "+f"(d[83]), "+f"(d[84]), "+f"(d[85]), "+f"(d[86]), "+f"(d[87]), "+f"(d[88]), "+f"(d[89]), "+f"(d[90]), "+f"(d[91]), "+f"(d[92]), "+f"(d[93]), "+f"(d[94]), "+f"(d[95])
    : "l"(da), "l"(db), "r"(sd), "n"(TA), "n"(TB));
}

template<int TA, int TB> __device__ __forceinline__ void wgmma_ss_n8(float* d, uint64_t da, uint64_t db, int sd) {
  asm volatile("{\n.reg .pred p;\nsetp.ne.b32 p, %6, 0;\n"
    "wgmma.mma_async.sync.aligned.m64n8k16.f32.bf16.bf16 {%0, %1, %2, %3}, %4, %5, p, 1, 1, %7, %8;\n}"
    : "+f"(d[0]), "+f"(d[1]), "+f"(d[2]), "+f"(d[3])
    : "l"(da), "l"(db), "r"(sd), "n"(TA), "n"(TB));
}

constexpr int S_ = 2048, D_ = 640, F_ = 1536;

struct Scr {
  uint32_t flag[32 * 8];
  uint32_t mv[2 * 2048];
  bf16 cimg[8 * 6 * 512];
  uint2 st2[S_];
  bf16 kvT[D_ * S_];
  bf16 zT[D_ * S_];
  bf16 AT[D_ * S_];
};
__device__ __align__(1024) Scr g_scr;
__device__ __forceinline__ uint32_t clk() { uint32_t c; asm volatile("mov.u32 %0, %%clock;" : "=r"(c) :: "memory"); return c; }
#define DEVSM 0
#define STAMP(id)
#define STAMPIF(c, id)
#define ITW 0
#define P3 0
constexpr int FL_X = 5, FL_C = 128;
#define CD 600
#define SD 1000

constexpr int SM_X = 1024, SM_EXT = 21504, SM_SMALL = 29696, SM_STAT = 30720, SM_CB = 32768, SM_RING = 34816, SM_TOTAL = SM_RING + 6 * 32768;
constexpr int SMALL_LN = 224, SMALL_RED = 320, SMALL_DUMMY = 1008, SMALL_E = 1012, SMALL_TS = 160, SMALL_H = 864;
constexpr int JOB_SZ = 10880, JOB_V = 5760, R_X = 5 * 32768, R_BOX = R_X + 12288;
constexpr int K1OFF = 4672, KSZ = 9472, CSZ = KSZ + 4224;
enum { B_KJ = 0, B_X = 5, B_EXT = 7, B_X1 = 8, B_P0 = 9, B_FB = 10, B_PEER = 20, B_RECV = 24, B_U = 28, B_A = 30, B_E0 = 35, B_BOX = 38, B_F = 44, B_ST0 = 45, B_GB = 46,
       B_F1 = 48, B_E1 = 54, B_EB = 60,
       B_Z = 80, B_K = 85, B_EW = 88, B_ST2 = 94, B_XF = 95, B_KV4 = 96, B_KVS = 98, B_BD = 99,
       B_B = 106, B_S = 112 };
__device__ __forceinline__ uint32_t chan_base(uint32_t sb, int ch) { return sb + SM_RING + (2 + (ch >> 1)) * 32768 + (ch & 1) * CSZ; }

struct Params { CUtensorMap mS, mX, mWm, mK, mV, mG, mU, mD; };

__device__ __forceinline__ void flag_add(Scr* G, int id) { asm volatile("red.relaxed.gpu.global.add.u32 [%0], 1;" ::"l"(G->flag + id) : "memory"); }
__device__ __forceinline__ uint32_t rdback(const void* p) { uint32_t v; asm volatile("ld.relaxed.gpu.global.u32 %0, [%1];" : "=r"(v) : "l"(p) : "memory"); return v; }
__device__ __forceinline__ void st_tag(uint2* p, uint32_t v, uint32_t t) { asm volatile("st.relaxed.gpu.global.v2.u32 [%0], {%1, %2};" ::"l"(p), "r"(v), "r"(t) : "memory"); }
__device__ __forceinline__ void spin(uint32_t t, uint32_t d) { if (d) while (clk() - t < d); }
__device__ __forceinline__ uint2 ld_tag(const uint2* p) { uint2 v; asm volatile("ld.relaxed.gpu.global.v2.u32 {%0, %1}, [%2];" : "=r"(v.x), "=r"(v.y) : "l"(p) : "memory"); return v; }
__device__ __forceinline__ uint4 ld_tag2(const uint2* p) {
  uint4 v;
  asm volatile("ld.relaxed.gpu.global.v4.u32 {%0, %1, %2, %3}, [%4];" : "=r"(v.x), "=r"(v.y), "=r"(v.z), "=r"(v.w) : "l"(p) : "memory");
  return v;
}
__device__ __forceinline__ void stg128(void* p, uint4 v) { asm volatile("st.global.v4.b32 [%0], {%1, %2, %3, %4};" ::"l"(p), "r"(v.x), "r"(v.y), "r"(v.z), "r"(v.w) : "memory"); }
__device__ __forceinline__ uint32_t ldv32(uint32_t a) { uint32_t v; asm volatile("ld.volatile.shared.b32 %0, [%1];" : "=r"(v) : "r"(a) : "memory"); return v; }
__device__ __forceinline__ uint4 ldv128(uint32_t a) { uint4 v; asm volatile("ld.volatile.shared.v4.b32 {%0,%1,%2,%3}, [%4];" : "=r"(v.x), "=r"(v.y), "=r"(v.z), "=r"(v.w) : "r"(a) : "memory"); return v; }
__device__ __forceinline__ uint32_t epoch(uint32_t sb) { return lds32(sb + SM_SMALL + SMALL_E); }
__device__ __forceinline__ void rdwait(uint32_t sb, uint32_t v) { sts32(sb + SM_SMALL + SMALL_DUMMY, v); }
__device__ __forceinline__ void fence_async_s() { asm volatile("fence.proxy.async.shared::cta;" ::: "memory"); }
__device__ __forceinline__ void fence_async_g() { asm volatile("fence.proxy.async.global;" ::: "memory"); }
__device__ __forceinline__ void bulk_done() { asm volatile("cp.async.bulk.commit_group;\n\tcp.async.bulk.wait_group 0;" ::: "memory"); }
__device__ __forceinline__ void flag_wait(Scr* G, int id, uint32_t target) {
  const uint32_t* p = G->flag + id;
#pragma unroll 1
  for (int i = 0; i < (1 << 20); i++) {
    uint32_t v;
    asm volatile("ld.relaxed.gpu.global.u32 %0, [%1];" : "=r"(v) : "l"(p) : "memory");
    if ((int)(v - target) >= 0) return;
  }
  __trap();
}
__device__ __forceinline__ void hint_wait(Scr* G, uint32_t sa, int id, uint32_t target) {
#pragma unroll 1
  for (int i = 0; i < (1 << 20); i++) {
    const uint32_t t = clk();
    cp16(sa + 4 * (id & 4), G->flag + (id & ~3));
    spin(t, P3);
    if ((int)(lds32(sa + 4 * (id & 7)) - target) >= 0) return;
  }
  __trap();
}
__device__ __forceinline__ int tbase(int pb) { return 127 - (32 * (pb >> 6) + 8 * (pb & 8) + 4 * ((2 * (pb & 3) - ((pb >> 2) & 1)) & 7) + ((pb >> 4) & 3)); }
__device__ __forceinline__ uint32_t hmul(uint32_t a, uint32_t b) { uint32_t d; asm("mul.rn.bf16x2 %0, %1, %2;" : "=r"(d) : "r"(a), "r"(b)); return d; }
__device__ __forceinline__ uint32_t hadd(uint32_t a, uint32_t b) { uint32_t d; asm("add.rn.bf16x2 %0, %1, %2;" : "=r"(d) : "r"(a), "r"(b)); return d; }
__device__ __forceinline__ uint32_t hsub(uint32_t a, uint32_t b) { uint32_t d; asm("sub.rn.bf16x2 %0, %1, %2;" : "=r"(d) : "r"(a), "r"(b)); return d; }
__device__ __forceinline__ uint32_t hfma(uint32_t a, uint32_t b, uint32_t c) { uint32_t d; asm("fma.rn.bf16x2 %0, %1, %2, %3;" : "=r"(d) : "r"(a), "r"(b), "r"(c)); return d; }
__device__ __forceinline__ uint32_t pack2(float lo, float hi) { uint32_t d; asm("cvt.rn.bf16x2.f32 %0, %1, %2;" : "=r"(d) : "f"(hi), "f"(lo)); return d; }
__device__ __forceinline__ float blo(uint32_t v) { return __uint_as_float(v << 16); }
__device__ __forceinline__ float bhi(uint32_t v) { return __uint_as_float(v & 0xffff0000u); }
__device__ __forceinline__ uint32_t tagged(uint32_t v, uint32_t e1) { return (v & ~1u) | (e1 & 1); }
__device__ __forceinline__ float rbf(float v) { return blo(pack2(v, 0.f)); }
__device__ __forceinline__ float sdev(float var) { float d; asm("sqrt.approx.ftz.f32 %0, %1;" : "=f"(d) : "f"(rbf(rbf(var) + 1e-5f))); return rbf(d); }
template <int N> __device__ __forceinline__ void bfly(float* v, int mask, bool up) {
#pragma unroll
  for (int i = 0; i < N / 2; i++) {
    float send = up ? v[i] : v[i + N / 2], keep = up ? v[i + N / 2] : v[i];
    v[i] = keep + __shfl_xor_sync(0xffffffffu, send, mask);
  }
}
#define BX3 2
#define XO 0
#define ZA 0
#define XE 0
#define EA 1
#define AD 300
#define XP 0
#define DR 0
#define KVV 0
#define OPQ 4
#define SL 1
#define UT 5
#define UD0 1000
#define EH 1
#define NA 16
#define BS 0
#define UF 1
#define ZS 1
#define LV 5
#define TG 2
#define RL 2
#define MG 0
__device__ __forceinline__ bool mod_first(int b) { return MG ? (b & 3) != 3 : !(b & 1) || !(b & 6); }
__device__ __forceinline__ int mod_grp(int b, int j) {
  if (MG) {
  const int m = b >> 3, s = b & 7, t = 16 * (j ? min(s, 6) : s - (s >> 2)) + m, v = j ? s : (t * 43) >> 10;
  if (j == 2) return b + 112;
  return v < 4 ? (v == 3 ? 160 : 40 * v) + (j ? 24 + m : t - 24 * v) : t + (t < 104 ? 56 : 96);
  }
  const int m = b >> 3, s = b & 7, t = 16 * s + m, v = j ? (t * 43) >> 10 : s >> 1;
  if (j == 2) return b + 112;
  if (j == 0 && s == 1) return m + (m < 8 ? 152 : 192);
  return v < 4 ? (v == 3 ? 160 : 40 * v) + (j ? 16 + t - 24 * v : m) : t + 24;
}

__device__ __forceinline__ void kv_load(const bf16* gk, const bf16* gv, const bf16* gs, uint32_t sb, int b, int r, int tid) {
  const int row = tid >> 2, col = 128 * r + 32 * (b & 3);
  const uint32_t a = sb + SM_RING + r * JOB_SZ + (row >> 3) * 80 + (tid & 3) * 16, ak = a + (row & 7) * 720, av = a + (row & 7) * 640 + JOB_V;
  const int o = (64 * (b >> 2) + row) * D_ + col + 8 * (tid & 3);
  cp16(ak + 80, gk + o);
  cp16(ak + 400, gk + o + 32 * D_);
  cp16(av, gv + o);
  cp16(av + 320, gv + o + 32 * D_);
  if (tid < 12) cp16z(ak + 3600, gk + (b < 4 ? o : o - 3 * D_), b < 4 ? 0 : 16);
  else if (tid >= 112) cp16(sb + SM_CB + 256 * r + 16 * (tid - 112), gs + 4 * col + 8 * (tid - 112));
}
__device__ __forceinline__ void load_kv(const Params& P, const bf16* gs, uint32_t sb, int b, int r) {
  const uint32_t a = sb + SM_RING + r * JOB_SZ, bar = sb + 8 * (B_B + r);
  const int cg = 4 * r + (b & 3);
  mbar_expect(bar, JOB_SZ + 256);
  tma4d(a, &P.mK, 0, cg, 8 * (b >> 2) - 1, 0, bar);
  tma4d(a + JOB_V, &P.mV, 0, cg, 8 * (b >> 2), 0, bar);
  bulk_g2s(sb + SM_CB + 256 * r, gs + 128 * cg, 256, bar);
}
__device__ __forceinline__ uint4* kv_dst(Scr* G, int b, int r, int tid) {
  return (uint4*)(G->kvT + (128 * r + 32 * (b & 3) + 8 * (tid >> 5) + 2 * (tid & 3)) * S_ + 2040 - 64 * (b >> 2)) - ((tid >> 2) & 7);
}
__device__ __forceinline__ void kv_job(Scr* G, uint32_t sb, int b, int r, int tid, uint32_t e1) {
  const int cp = 4 * (tid >> 5) + (tid & 3);
  const uint32_t ka = sb + SM_RING + r * JOB_SZ + ((tid >> 2) & 7) * 80 + cp * 4;
  mbar_wait(sb + 8 * (B_B + r), 0);
  STAMPIF(tid == 0, 56 + r);
  uint32_t kk[11], vv[8], o[8];
  if (KVV) {
#pragma unroll
    for (int i = 0; i < 11; i++) kk[i] = ldv32(ka + 720 * ((i + 5) & 7) + 80 * ((i + 5) >> 3));
#pragma unroll
    for (int i = 0; i < 8; i++) vv[i] = ldv32(ka + JOB_V + 640 * i);
  }
  const uint4 sk = ldv128(sb + SM_CB + 256 * r + 16 * cp);
  const uint32_t s0 = __byte_perm(sk.x, sk.z, 0x5410), s1 = __byte_perm(sk.x, sk.z, 0x7632), s2 = __byte_perm(sk.y, sk.w, 0x5410), s3 = __byte_perm(sk.y, sk.w, 0x7632);
#pragma unroll
  for (int i = 0; i < 11; i++) if (!KVV) kk[i] = lds32(ka + 720 * ((i + 5) & 7) + 80 * ((i + 5) >> 3));
#pragma unroll
  for (int i = 0; i < 8; i++) {
    uint32_t v = KVV ? vv[i] : lds32(ka + JOB_V + 640 * i);
    o[i] = hmul(hfma(kk[i + 3], s0, hfma(kk[i + 2], s1, hfma(kk[i + 1], s2, hmul(kk[i], s3)))), v);
  }
  uint4* dst = kv_dst(G, b, r, tid);
  dst[0] = make_uint4(__byte_perm(o[7], o[6], 0x5410), __byte_perm(o[5], o[4], 0x5410), __byte_perm(o[3], o[2], 0x5410), tagged(__byte_perm(o[1], o[0], 0x5410), e1));
  dst[256] = make_uint4(__byte_perm(o[7], o[6], 0x7632), __byte_perm(o[5], o[4], 0x7632), __byte_perm(o[3], o[2], 0x7632), tagged(__byte_perm(o[1], o[0], 0x7632), e1));
  if (tid == 0) { sts32(sb + SM_SMALL + SMALL_TS + 4 * r, clk()); mbar_arrive(sb + 8 * (B_KJ + r)); }
}
__device__ __forceinline__ void u_wait(uint4& a, uint4& c, const void* p) {
  asm volatile("{\n.reg .pred p;\n.reg .b32 t, n;\nmov.b32 n, 0;\n"
               "L0:\nlop3.b32 t, %3, %7, 1, 0x80;\nsetp.eq.b32 p, t, 0;\nvote.sync.any.pred p, p, 0xffffffff;\n@!p bra.uni L1;\n"
               "ld.relaxed.gpu.global.v4.u32 {%0, %1, %2, %3}, [%8];\nld.relaxed.gpu.global.v4.u32 {%4, %5, %6, %7}, [%8+2048];\n"
               "add.u32 n, n, 1;\nsetp.lt.u32 p, n, 1000000;\n@p bra.uni L0;\ntrap;\nL1:\n}"
               : "+r"(a.x), "+r"(a.y), "+r"(a.z), "+r"(a.w), "+r"(c.x), "+r"(c.y), "+r"(c.z), "+r"(c.w) : "l"(p) : "memory");
}
__device__ __forceinline__ void u_fix(uint4 a, uint4 c, const void* p, uint32_t sa, uint32_t e1) {
  asm volatile("{\n.reg .pred p;\n.reg .b32 t, n;\nmov.b32 n, 0;\n"
               "lop3.b32 t, %3, %7, %10, 0x81;\nand.b32 t, t, 1;\nsetp.eq.b32 p, t, 0;\nvote.sync.any.pred p, p, 0xffffffff;\n@!p bra.uni L2;\n"
               "L0:\nld.relaxed.gpu.global.v4.u32 {%0, %1, %2, %3}, [%8];\nld.relaxed.gpu.global.v4.u32 {%4, %5, %6, %7}, [%8+2048];\n"
               "lop3.b32 t, %3, %7, %10, 0x81;\nand.b32 t, t, 1;\nsetp.eq.b32 p, t, 0;\nvote.sync.any.pred p, p, 0xffffffff;\n@!p bra.uni L1;\n"
               "add.u32 n, n, 1;\nsetp.lt.u32 p, n, 1000000;\n@p bra.uni L0;\ntrap;\n"
               "L1:\nst.shared.v4.b32 [%9], {%0, %1, %2, %3};\nst.shared.v4.b32 [%9+2048], {%4, %5, %6, %7};\nL2:\n}"
               : "+r"(a.x), "+r"(a.y), "+r"(a.z), "+r"(a.w), "+r"(c.x), "+r"(c.y), "+r"(c.z), "+r"(c.w) : "l"(p), "r"(sa), "r"(e1) : "memory");
}
__device__ __forceinline__ void stv128(uint32_t a, uint4 v) { asm volatile("st.volatile.shared.v4.b32 [%0], {%1,%2,%3,%4};" ::"r"(a), "r"(v.x), "r"(v.y), "r"(v.z), "r"(v.w) : "memory"); }
__device__ __forceinline__ uint64_t box_a(uint32_t sb) { return mkdesc(sb + SM_RING + R_BOX, 256, 1024, 3); }
__device__ __forceinline__ uint64_t box_b(uint32_t sb) { return mkdesc(sb + SM_STAT, 64, 128, 0); }
__device__ __forceinline__ void mod_put(Scr* G, uint32_t sb, const float* a, int b, int j, uint32_t e1, int tid) {
  const uint32_t red = sb + SM_STAT + 1536;
  if ((tid & 3) == tid >> 6) sts64(red + 32 * ((tid >> 2) & 7) + 8 * (tid >> 5), __float_as_uint((tid & 32) ? a[1] : a[0]), __float_as_uint((tid & 32) ? a[3] : a[2]));
  bar_sync(j > (BX3 >= 3) ? 4 : 5, 128);
  if (tid < 16) {
    const uint4 u = lds128(red + 32 * (tid & 7)), v = lds128(red + 32 * (tid & 7) + 16);
    asm volatile("" : "+r"(b));
    const int grp = mod_grp(b, j);
    const uint32_t one = (grp >= 40 && grp < 80) || (grp >= 160 && grp < 200) ? 0x3f803f80u : 0u;
    const float lo = __uint_as_float(u.x) + __uint_as_float(u.z) + __uint_as_float(v.x) + __uint_as_float(v.z);
    const float hi = __uint_as_float(u.y) + __uint_as_float(u.w) + __uint_as_float(v.y) + __uint_as_float(v.w);
    asm volatile("st.relaxed.gpu.global.u32 [%0], %1;" ::"l"(G->mv + 8 * grp + 256 * (tid & 8) + (tid & 7)),
                 "r"(((tid >> 3) ^ e1) & 1 ? 0 : ~hadd(pack2(lo, hi), one)) : "memory");
  }
}
__device__ __forceinline__ void mod_box(Scr* G, uint32_t sb, int b, int j, uint32_t e1, int tid) {
  float a[4];
  uint64_t da = box_a(sb), db = box_b(sb);
#pragma unroll
  for (int h = 0; h < 2; h++) {
    mbar_wait(sb + 8 * (B_BOX + 2 * j + h), 0);
    STAMPIF(tid == 0 && j == 0, 71 + h);
    wg_fence();
#pragma unroll
    for (int n = 5 * h; n < 5 * h + 5; n++) wgmma_ss_n8<1, 0>(a, da + 128 * n, db + 8 * n, n != 0);
    wg_commit();
  }
  wg_wait<0>();
#pragma unroll
  for (int i = 0; i < 4; i++) asm volatile("" : "+f"(a[i])::"memory");
  mod_put(G, sb, a, b, j, e1, tid);
}
__device__ __forceinline__ void a_check(uint32_t sa, const void* ga, uint32_t tag) {
  asm volatile("{\n.reg .pred p;\n.reg .b32 t, n, x, y, z;\n.reg .b64 g;\n"
               "ld.shared.b32 t, [%0];\nlop3.b32 t, t, %2, 1, 0x28;\nsetp.ne.b32 p, t, 0;\nvote.sync.any.pred p, p, 0xffffffff;\n@!p bra.uni L1;\nmov.b32 n, 0;\n"
               "L0:\nld.relaxed.gpu.global.b32 t, [%1];\nlop3.b32 t, t, %2, 1, 0x28;\nsetp.ne.b32 p, t, 0;\nvote.sync.any.pred p, p, 0xffffffff;\n@!p bra.uni L2;\n"
               "add.u32 n, n, 1;\nsetp.lt.u32 p, n, 1000000;\n@p bra.uni L0;\ntrap;\nL2:\n"
               "and.b64 g, %1, -32;\nand.b32 n, %0, -32;\n"
               "ld.relaxed.gpu.global.v4.b32 {t, x, y, z}, [g];\nst.shared.v4.b32 [n], {t, x, y, z};\n"
               "ld.relaxed.gpu.global.v4.b32 {t, x, y, z}, [g+16];\nst.shared.v4.b32 [n+16], {t, x, y, z};\n"
               "fence.proxy.async.shared::cta;\nbar.warp.sync 0xffffffff;\nL1:\n}" ::"r"(sa), "l"(ga), "r"(tag) : "memory");
}
__device__ __forceinline__ void z_wait(uint4& a, uint4& c, uint32_t* v, const void* G, uint32_t zo, uint32_t co, uint32_t e1) {
  asm volatile("{\n.reg .pred p;\n.reg .b32 t, n;\n.reg .b64 x, y;\nmov.b32 n, 0;\n"
               "L0:\nlop3.b32 t, %3, %7, %14, 0x81;\nand.b32 t, t, 1;\nmin.u32 t, t, %8;\nmin.u32 t, t, %9;\nmin.u32 t, t, %10;\nmin.u32 t, t, %11;\n"
               "setp.eq.b32 p, t, 0;\nvote.sync.any.pred p, p, 0xffffffff;\n@!p bra.uni L1;\n"
               "shr.u32 t, n, 31;\nadd.u32 t, t, %12;\ncvt.u64.u32 x, t;\nadd.s64 x, x, %15;\nshr.u32 t, n, 30;\nadd.u32 t, t, %13;\ncvt.u64.u32 y, t;\nadd.s64 y, y, %15;\n"
               "ld.relaxed.gpu.global.v4.u32 {%0, %1, %2, %3}, [x];\nld.relaxed.gpu.global.v4.u32 {%4, %5, %6, %7}, [x+32768];\n"
               "ld.relaxed.gpu.global.u32 %8, [y];\nld.relaxed.gpu.global.u32 %9, [y+1280];\nld.relaxed.gpu.global.u32 %10, [y+2560];\nld.relaxed.gpu.global.u32 %11, [y+5120];\n"
               "add.u32 n, n, 1;\nsetp.lt.u32 p, n, 1000000;\n@p bra.uni L0;\ntrap;\nL1:\n}"
               : "+r"(a.x), "+r"(a.y), "+r"(a.z), "+r"(a.w), "+r"(c.x), "+r"(c.y), "+r"(c.z), "+r"(c.w), "+r"(v[0]), "+r"(v[1]), "+r"(v[2]), "+r"(v[3])
               : "r"(zo), "r"(co), "r"(e1), "l"(G) : "memory");
}
__device__ __forceinline__ void load_x(const Params& P, uint32_t sb, int b, int h) {
  const uint32_t bar = sb + 8 * (B_X + h);
  mbar_expect(bar, 10240);
  tma5d(sb + SM_X + h * 10240, &P.mX, 0, 0, 0, 5 * h, tbase(b), bar);
}
__device__ __forceinline__ uint32_t x_addr(uint32_t sb, int w, int lane) {
  const int rho = 15 - (4 * (lane >> 3) + 2 * (lane & 1) + ((lane >> 1) & 1));
  return sb + SM_X + (w >> 1) * 2048 + rho * 128 + (((2 * (w & 1) + (lane & 4)) ^ (rho & 7)) << 4);
}
__device__ __forceinline__ void ln1_half(uint32_t sb, int tid, int h, int dry, float& s1, float& s2, float& pv) {
  const uint32_t xr = sb + SM_X + 16 * tid;
  float s3 = 0.f;
  if (ITW == 8) STAMPIF(tid == 0, 102 + 2 * h);
  if (!dry) mbar_wait(sb + 8 * (B_X + h), 0);
  STAMPIF(tid == 0, 25);
  if (ITW == 8) STAMPIF(tid == 0, 103 + 2 * h);
  uint4 v[5];
#pragma unroll
  for (int n = 0; n < 5; n++) v[n] = n < LV ? ldv128(xr + 10240 * h + 2048 * n) : lds128(xr + 10240 * h + 2048 * n);
  pv = blo(ldv32(xr & ~127u));
#pragma unroll
  for (int n = 0; n < 5; n++) {
    const uint32_t u[4] = {v[n].x, v[n].y, v[n].z, v[n].w};
#pragma unroll
    for (int j = 0; j < 4; j++) {
      const float a = blo(u[j]) - pv, c = bhi(u[j]) - pv;
      s1 += a + c; s2 += a * a; s3 += c * c;
    }
  }
  s2 += s3;
}
__device__ __forceinline__ void ln1_end(uint32_t sb, int tid, float s1, float s2, float pv) {
#pragma unroll
  for (int o = 1; o < 8; o <<= 1) { s1 += __shfl_xor_sync(0xffffffffu, s1, o); s2 += __shfl_xor_sync(0xffffffffu, s2, o); }
  if (ITW == 8) { asm volatile("" : "+f"(s1), "+f"(s2)); STAMPIF(tid == 0, 107); }
  const float mu = s1 * (1.f / D_), var = fmaxf(s2 * (1.f / D_) - mu * mu, 0.f);
  float rs;
  asm("rcp.approx.ftz.f32 %0, %1;" : "=f"(rs) : "f"(sdev(var)));
  const int i = 15 - (tid >> 3), j = tid & 7;
  if (j < 2) sts16(sb + SM_SMALL + SMALL_LN + 32 * j + 16 * (i & 1) + (i & 14), pack2(j ? rs : pv + mu, 0.f));
  if (ITW == 8) STAMPIF(tid == 0, 108);
  bar_sync(5, 128);
  STAMPIF(tid == 0, 75);
}
__device__ __forceinline__ void load_box(const Params& P, uint32_t sb, int b, int cls) {
  const uint32_t bar = sb + 8 * (B_BOX + cls);
  mbar_expect(bar, 10240);
  tma3d(sb + SM_RING + R_BOX + 10240 * (cls & 1), &P.mWm, 16 * mod_grp(b, cls >> 1), 0, 5 * (cls & 1), bar);
}
__device__ __forceinline__ void load_ssm(const Params& P, uint32_t sb, int b, int r) {
  const uint32_t bar = sb + 8 * (B_S + r);
  mbar_expect(bar, 16 * 288);
  tma3d(chan_base(sb, r) + 128, &P.mS, 0, 0, 128 * r + b, bar);
}
__device__ __forceinline__ void k1_job(uint32_t sb, int r, int tid, uint32_t dv) {
  const uint32_t a0 = chan_base(sb, r) + 128 + 16 * tid + 32 * (tid >> 4);
  mbar_wait(sb + 8 * (B_S + r), 0);
  uint4 v[2];
  uint32_t pv[2];
#pragma unroll
  for (int n = 0; n < 2; n++) { v[n] = lds128(a0 + 2304 * n); pv[n] = lds32(a0 + 2304 * n - ((tid & 15) ? 4 : 36)); }
  if (tid == 0) { v[0].x = hadd(v[0].x, dv); sts32(a0, v[0].x); }
#pragma unroll
  for (int n = 0; n < 2; n++)
    sts128(a0 + 2304 * n + K1OFF, make_uint4(__byte_perm(pv[n], v[n].x, 0x5432), __byte_perm(v[n].x, v[n].y, 0x5432), __byte_perm(v[n].y, v[n].z, 0x5432), __byte_perm(v[n].z, v[n].w, 0x5432)));
}

__device__ __forceinline__ int out_blk(int s, int p) { const int t = p + (s >> 1); return t < 5 ? t : t - 5; }
__device__ __forceinline__ void l2_prefetch(const void* p, int bytes) { asm volatile("cp.async.bulk.prefetch.L2.global [%0], %1;" ::"l"(p), "r"(bytes) : "memory"); }
__device__ __forceinline__ void pf_line(const void* p) { asm volatile("prefetch.global.L2 [%0];" ::"l"(p) : "memory"); }
__device__ __forceinline__ int role(int bx) {
  const int c = bx >> 1, d = c - 36, q = (d * 37) >> 8, k = d - 7 * q;
  const int rank = c < 4 ? 12 + c : c < 36 ? ((c - 4) & 7) * 8 + ((c - 4) >> 3) : (k ? k + 1 : 0) * 8 + 4 + q;
  return 8 * (rank & 15) + 2 * (rank >> 4) + (bx & 1);
}
enum { K_KV, K_SSM, K_BOX, K_PW, K_PD, K_PKV, K_PSSM, K_PBOX, K_W, K_X, K_ST, K_END = 15 };
#define E(t, bar, kind, r) ((t) << 16 | (bar) << 8 | (kind) << 4 | (r))
#define SCHED E(2800, 255, K_BOX, 0), E(0, 255, K_BOX, 1), E(3700, 255, K_KV, 2), E(4400, 255, K_SSM, 2), E(4800, 255, XO ? K_X : K_KV, XO ? 0 : 3), E(5500, 255, XO ? K_KV : K_X, XO ? 3 : 0), \
              E(6400, 255, XP ? K_X : K_KV, XP ? 1 : 4), E(7100, 255, XP ? K_KV : K_X, XP ? 4 : 1), E(7900, 255, K_SSM, 3), E(8300, 255, K_SSM, 4), E(8600, 255, K_BOX, 2), E(9500, 255, K_PW, 0), \
              E(10100, 255, K_BOX, 3)
#define XPF 2
#define XBOTH 0
#define XI 8
#define XW 0
#define PWM 0x3c
#define STM 0x7c0
#define PDM 0x3800
#define KV4C 3
#define CVT 1
#define UPOS 4
#define UD 1000
#define UD1 6400
#define NP 6
#define NQ 6
#define SPOS(i) (2 * ((i) - NQ) + 13)
#define LH0 4
#define LH1 5
#define LM 0
#define PT 1
#define ZP 0
#define BD 1200
#define ER 0
#define PL 1
#define K1N 1
#define ZD 10100
#define PK 0
#define ZF 1
constexpr uint32_t kSched[] = {SCHED, E(0, 255, K_END, 0)};
struct In { const bf16 *k, *v, *sk, *Wg, *Wu, *Wd, *ss; };
__device__ __forceinline__ void load_w(const Params& P, uint32_t sb, int s, int it) {
  const int st = it % 5;
  mbar_wait(sb + 8 * (B_E1 + st), (it / 5) & 1);
  const uint32_t a = sb + SM_RING + st * 32768 + 8192, fb = sb + 8 * (B_F1 + st);
  mbar_expect(fb, 24576);
#pragma unroll
  for (int j = 0; j < 3; j++) {
    tma2d(a + 8192 * j, &P.mG, 192 * s + 64 * j, 32 * it, fb);
    tma2d(a + 8192 * j + 4096, &P.mU, 192 * s + 64 * j, 32 * it, fb);
  }
}

template <int I> __device__ __forceinline__ int sched_run(const Params& P, const In& in, uint32_t sb, int b, int lane, uint32_t t_0) {
  constexpr uint32_t e = kSched[I];
  constexpr int kind = (e >> 4) & 15, r = e & 15, bar = (e >> 8) & 255;
  if constexpr (kind == K_END) return 0;
  else {
    if constexpr ((e >> 16) != 0) while (clk() - t_0 < (e >> 16));
    if (bar != 255) mbar_wait(sb + 8 * bar, 0);
    if (kind == K_BOX && r == 2) mbar_wait(sb + 8 * B_BD, 0);
    if (kind == K_PKV) {
      const bf16* kvp = (lane < 16 ? in.k : in.v) + (16 * b + (lane & 15)) * D_ + 128 * r;
      pf_line(kvp); pf_line(kvp + 64);
    } else {
      if (elect()) {
        if (kind == K_KV) load_kv(P, in.sk, sb, b, r);
        if (kind == K_X) load_x(P, sb, b, r);
        if (kind == K_SSM) load_ssm(P, sb, b, r);
        if (kind == K_BOX && (r > 1 || mod_first(b))) load_box(P, sb, b, r);
        if (kind == K_PW) { l2_prefetch(in.Wg + (128 * r + b) * F_, 2 * F_); l2_prefetch(in.Wu + (128 * r + b) * F_, 2 * F_); }
        if (kind == K_PSSM) l2_prefetch(in.ss + (128 * r + b) * S_, 4096);
      }
      __syncwarp();
    }
    return sched_run<I + 1>(P, in, sb, b, lane, t_0) + (kind == K_PW);
  }
}

__global__ void __launch_bounds__(512, 1) fused_kernel(const bf16* __restrict__ gk, const bf16* __restrict__ gv, const bf16* __restrict__ gsk,
                                                       const bf16* __restrict__ gD, const bf16* __restrict__ gc, Scr* G, const bf16* gWg, const bf16* gWu,
                                                       const bf16* gWd, bf16* gout, const bf16* gss, const __grid_constant__ Params P) {
  extern __shared__ __align__(1024) char smem_raw[];
  const uint32_t sb = smem_u32(smem_raw), ring = sb + SM_RING;
  const int b = role(blockIdx.x), m = b >> 3, s = b & 7;
  const uint32_t t_0 = clk();
  const int wg = __shfl_sync(0xffffffffu, threadIdx.x >> 7, 0);
  const int tid = threadIdx.x & 127, lane = tid & 31;
  const int w = __shfl_sync(0xffffffffu, tid >> 5, 0);
  uint32_t e1 = 0;
  if (wg < 2) {
    kv_load(gk, gv, gsk, sb, b, wg, tid);
    if (TG == 1) e1 = rdback(G->flag + 8 * m + 4);
  } else {
    if (wg == 2) {
      if (tid < 40) {
        int c = tid & 7;
        sts128(chan_base(sb, tid >> 3) + (c < 2 ? 80 + c * K1OFF : KSZ + 4096 + (c - 2) * 16), make_uint4(0, 0, 0, 0));
      }
    }
    if (elect()) {
      const int j = 4 * (3 - wg) + w - 1;
      if (j < 4) asm volatile("prefetch.tensormap [%0];" ::"l"(&P.mX + j) : "memory");
      if (j < 0) {
#pragma unroll
        for (int i = 0; i < 5; i++) mbar_init(sb + 8 * (B_S + i), 1);
        fence_async_s();
        if (XPF > 0) load_ssm(P, sb, b, 0);
        if (XPF > 1) load_ssm(P, sb, b, 1);
      } else {
        const int c = j < 3 ? 1 : j < 5 ? 2 : 4;
#pragma unroll
        for (int i = 0; i < 16; i++) mbar_init(sb + 128 * j + 8 * i, i < 10 || j < 6 ? c : i < 12 ? 128 : 1);
      }
    }
    fence_async_s();
  }
  __syncthreads();
  STAMPIF(threadIdx.x == 0, 55);

  if (wg < 2) {
    cp_arrive(sb + 8 * (B_B + wg));
    asm volatile("setmaxnreg.inc.sync.aligned.u32 224;");
    STAMPIF(threadIdx.x == 0, 82);
    const int g = lane >> 2, q = lane & 3;
    constexpr int NB = UT < 5 ? 288 : 256;
    if (wg == 1) bar_arrive(1, NB);
    const uint32_t dv = *(const uint16_t*)(gD + 128 * wg + b);
    if (TG == 3) e1 = rdback(G->flag + 8 * m + 4 + (__shfl_sync(0xffffffffu, tid, tid) >> 8));
    e1 = (e1 >> 5) + 1;
    {
      const int tid = (OPQ & 4) ? __shfl_sync(0xffffffffu, threadIdx.x & 127, threadIdx.x) : threadIdx.x & 127, lane = tid & 31, g = lane >> 2, q = lane & 3;
      const int b0 = (g >> 1) & 1, b1 = g >> 2, u = q + 4 * b0 - w;
      const uint32_t fo = 128 + (g & 1) * K1OFF + 288 * b1 + 4 * u, fo0 = fo - (u < 0 ? 32 : 0);
      const bool wrap = b0 && q == 0;
      const int src1 = b0 ? ((lane & 20) | ((q - 1) & 3)) : (lane | 8);
      const uint2* pu = (const uint2*)(G->kvT + (128 * wg + b) * S_ + 8 * tid);
      uint4 u0 = make_uint4(0, 0, 0, 0), u1 = make_uint4(0, 0, 0, 1);
#pragma unroll 1
      for (int ch = wg; ch < 5; ch += 2) {
        const uint32_t base = chan_base(sb, ch);
        if (ch < 2 || ch == KV4C) {
          kv_job(G, sb, b, ch < 2 ? ch : 4, tid, TG ? e1 : 1);
          if (ER && ch > 1) { __syncwarp(); if (lane == 0) mbar_arrive(sb + 8 * B_KV4); }
          STAMPIF(tid == 0, ch < 2 ? 1 + ch : 24);
        }
        if (ch < 2) {
          k1_job(sb, wg, tid, dv);
          bar_sync(3 + wg, 128);
        } else {
          mbar_wait(sb + 8 * (B_K + ch - 2), 0);
          if (UT == 5) {
            u0 = ld_tag2(pu); u1 = ld_tag2(pu + 256);
            if (BS) mbar_wait(sb + 8 * (B_S + ch), 0);
          }
        }
        const uint32_t fa = base + fo, fa0 = base + fo0;
        uint32_t af[16][4];
        auto afl = [&](int j) {
          const int o = 64 * (j & 1) + 576 * (j >> 1);
          if (UF) { af[j][0] = ldv32(((j & 1) ? fa : fa0) + o); af[j][1] = ldv32(fa + o + 128); af[j][2] = ldv32(fa + o + 32); af[j][3] = ldv32(fa + o + 160); }
          else { af[j][0] = lds32(((j & 1) ? fa : fa0) + o); af[j][1] = lds32(fa + o + 128); af[j][2] = lds32(fa + o + 32); af[j][3] = lds32(fa + o + 160); }
        };
#pragma unroll
        for (int j = 0; j < NA; j++) afl(j);
        if (UF) {
          stv128(base + KSZ + 16 * tid, u0);
          stv128(base + KSZ + 2048 + 16 * tid, u1);
#pragma unroll
          for (int j = NA; j < 16; j++) afl(j);
        }
        STAMPIF(tid == 0, 40 + ch);
        const uint32_t tg = e1;
        if (!(TG & 1) && (!EH || ch < 2)) { mbar_wait(sb + 8 * B_E0, 0); e1 = epoch(sb); }
        if (ch < UT) {
          if (ch == 1) spin(t_0, UD1);
          if (UT == 2) u0.w = 0;
          if (UF) u_fix(u0, u1, pu, base + KSZ + 16 * tid, TG ? tg : 1);
          else u_wait(u0, u1, pu);
          if (ITW == 5) STAMPIF(tid == 0, 105 + ch);
          if (!UF) {
            sts128(base + KSZ + 16 * tid, u0);
            sts128(base + KSZ + 2048 + 16 * tid, u1);
#pragma unroll
            for (int j = NA; j < 16; j++) afl(j);
          }
          fence_async_s();
        }
        float acc[128];
        const uint64_t db = mkdesc(base + KSZ, 32, 128, 0);
        bar_sync(1 + wg, NB);
        if (ITW == 5) STAMPIF(tid == 0, 115 + ch);
        wg_fence();
        wgmma_rs_n64<0>(acc + 96, af[0], db + 192, 0);
        wgmma_rs_n192<0>(acc, af[0], db, 0);
        wgmma_rs_n64<0>(acc + 96, af[1], db + 196, 1);
        wgmma_rs_n192<0>(acc, af[1], db + 4, 1);
        wgmma_rs_n32<0>(acc + 96, af[2], db + 224, 1);
        wgmma_rs_n192<0>(acc, af[2], db + 32, 1);
        wgmma_rs_n32<0>(acc + 96, af[3], db + 228, 1);
        wgmma_rs_n192<0>(acc, af[3], db + 36, 1);
        wgmma_rs_n192<0>(acc, af[4], db + 64, 1);
        wgmma_rs_n192<0>(acc, af[5], db + 68, 1);
        wgmma_rs_n160<0>(acc, af[6], db + 96, 1);
        wgmma_rs_n160<0>(acc, af[7], db + 100, 1);
        if (CVT == 2) wg_commit();
        wgmma_rs_n128<0>(acc, af[8], db + 128, 1);
        wgmma_rs_n128<0>(acc, af[9], db + 132, 1);
        if (CVT == 1) wg_commit();
        wgmma_rs_n96<0>(acc, af[10], db + 160, 1);
        wgmma_rs_n96<0>(acc, af[11], db + 164, 1);
        if (CVT == 0) bar_arrive(2 - wg, NB);
        wgmma_rs_n64<0>(acc, af[12], db + 192, 1);
        wgmma_rs_n64<0>(acc, af[13], db + 196, 1);
        wgmma_rs_n32<0>(acc, af[14], db + 224, 1);
        wgmma_rs_n32<0>(acc, af[15], db + 228, 1);
        wg_commit();
        if ((!TG || TG == 2 && ch < 2) && ZP == 0 && ch < UT) {
          stg128((void*)pu, make_uint4(0, 0, 0, 0));
          stg128((void*)(pu + 256), make_uint4(0, 0, 0, 0));
        }
        if (tid < 2 && ch == (!ER && wg == (KV4C & 1) && KV4C < 5 ? KV4C : wg)) mbar_arrive(sb + 8 * (B_E1 + tid));
        if (CVT) { wg_wait<1>(); if (ch < 4) bar_arrive(2 - wg, NB); }
        STAMPIF(tid == 0, 3 + ch);
        if (BX3 == 2 && ch == 3) {
          mod_box(G, sb, b, 1, e1, tid);
          __syncwarp();
          if (lane == 0) mbar_arrive(sb + 8 * (B_BD + 1));
          STAMPIF(tid == 0, 73);
        }
        if (ZP == 1) {
          stg128((void*)pu, make_uint4(0, 0, 0, 0));
          stg128((void*)(pu + 256), make_uint4(0, 0, 0, 0));
        }
        wg_wait<0>();
#pragma unroll
        for (int i = 0; i < 128; i++) asm volatile("" : "+f"(acc[i])::"memory");
        if (!RL) {
          bar_sync(3 + wg, 128);
          if (tid <= (ch >> 2)) mbar_arrive(sb + 8 * (B_E1 + 2 + (ch >> 1)));
        }
        if (RL == 2 && lane == 0) mbar_arrive(sb + 8 * (B_Z + ch));
        float S0[33], T[34];
#pragma unroll
        for (int i = 0; i < 31; i++) S0[i] = acc[4 * i] + acc[4 * i + 6];
        S0[31] = acc[124]; S0[32] = 0.f;
        if (PK & 1) {
#pragma unroll
          for (int i = 0; i < 32; i += 2) {
            const uint32_t v = __shfl_sync(0xffffffffu, pack2(acc[4 * i + 1] + acc[4 * i + 7], i < 30 ? acc[4 * i + 5] + acc[4 * i + 11] : acc[125]), src1);
            T[i] = (wrap ? S0[i + 1] : S0[i]) + blo(v);
            T[i + 1] = (wrap ? S0[i + 2] : S0[i + 1]) + bhi(v);
          }
        } else {
#pragma unroll
          for (int i = 0; i < 32; i++) {
            float s1 = i < 31 ? acc[4 * i + 1] + acc[4 * i + 7] : acc[125];
            T[i] = (wrap ? S0[i + 1] : S0[i]) + __shfl_sync(0xffffffffu, s1, src1);
          }
        }
        T[32] = 0.f; T[33] = 0.f;
        uint4* pz = (uint4*)(G->zT + (128 * ch + b) * S_) + ((tid & 120) | (2 * q) | (g & 1));
#pragma unroll
        for (int h = 0; h < 2; h++) {
          float y[8];
          if (PK & 2) {
#pragma unroll
            for (int mu = 0; mu < 8; mu += 2) {
              const uint32_t v = __shfl_xor_sync(0xffffffffu, pack2(T[4 * mu + 2 + h], T[4 * mu + 6 + h]), 16);
              y[mu] = (b1 ? T[4 * mu + 4 + h] : T[4 * mu + h]) + blo(v);
              y[mu + 1] = (b1 ? T[4 * mu + 8 + h] : T[4 * mu + 4 + h]) + bhi(v);
            }
          } else {
#pragma unroll
            for (int mu = 0; mu < 8; mu++) y[mu] = (b1 ? T[4 * mu + 4 + h] : T[4 * mu + h]) + __shfl_xor_sync(0xffffffffu, T[4 * mu + 2 + h], 16);
          }
          pz[128 * h] = make_uint4(pack2(y[0], y[1]), pack2(y[2], y[3]), pack2(y[4], y[5]), tagged(pack2(y[6], y[7]), e1));
        }
        if (RL == 1 && lane == 0) mbar_arrive(sb + 8 * (B_Z + ch));
        if (ZP == 2) {
          stg128((void*)pu, make_uint4(0, 0, 0, 0));
          stg128((void*)(pu + 256), make_uint4(0, 0, 0, 0));
        }
        pu += 128 * S_ / 2;
        STAMPIF(tid == 0, 8 + ch);
      }
    }
    uint32_t hh[96];
    {
      float ga[192];
      float* ua = ga + 96;
      const uint64_t da0 = mkdesc(ring + wg * 2048, 512, 256, 3), db0 = mkdesc(ring + 8192, 4096, 1024, 1);
      int st = PL, ph = 0;
      if (ITW == 7) STAMPIF(tid == 0, 110 + wg);
      float bx[4];
      if (wg && BX3 < 2) {
        mbar_wait(sb + 8 * (B_BOX + 2), 0);
        mbar_wait(sb + 8 * (B_BOX + 3), 0);
        wg_fence();
#pragma unroll
        for (int n = 0; n < 10; n++) wgmma_ss_n8<1, 0>(bx, box_a(sb) + 128 * n, box_b(sb) + 8 * n, n != 0);
        wg_commit();
        if (ITW == 7) STAMPIF(tid == 0, 120);
      }
      auto put = [&]() {
#pragma unroll
        for (int i = 0; i < 4; i++) asm volatile("" : "+f"(bx[i])::"memory");
        mod_put(G, sb, bx, b, 1, e1, tid);
        __syncwarp();
        if (lane == 0) mbar_arrive(sb + 8 * (B_BD + 1));
        STAMPIF(tid == 0, 73);
      };
      if (wg && BX3 == 0) { wg_wait<0>(); put(); }
      mbar_wait(sb + 8 * B_F1, 0);
      STAMPIF(tid == 0, 13 + wg);
      wg_fence();
      wgmma_ss_n192<1, 1>(ga, da0, db0, 0);
      wgmma_ss_n192<1, 1>(ua, da0, db0 + 768, 0);
      wgmma_ss_n192<1, 1>(ga, da0 + 256, db0 + 128, 1);
      wgmma_ss_n192<1, 1>(ua, da0 + 256, db0 + 128 + 768, 1);
      wg_commit();
      if (wg && BX3 == 1) { wg_wait<1>(); put(); }
      mbar_wait(sb + 8 * B_BD, 0);
      if (ITW == 7) STAMPIF(tid == 0, 112 + wg);
      const bool cs = b < 96;
      const int x0 = wg ? XI : 99,
                x1 = x0 + (cs ? 4 : 2), xs = cs ? 4 : 8;
      uint64_t xa = cs ? mkdesc(sb + SM_EXT, 4096, 1024, 1) : box_a(sb), xb = cs ? mkdesc(sb + SM_CB, 32, 128, 0) : box_b(sb);
      uint64_t ya = xa + (cs ? (SM_RING + R_X - SM_EXT) / 16 : 256), yb = xb + 16;
      if (ITW == 7) STAMPIF(tid == 0, 114 + wg);
#pragma unroll 1
      for (int it = PL; it < 19; it++) {
        if (it == x0) {
          mbar_wait(sb + 8 * (cs ? B_F : B_BOX + 4), 0);
          mbar_wait(sb + 8 * (cs ? B_ST0 : B_BOX + 5), 0);
          STAMPIF(tid == 0, 76);
        }
        if (it == x1 + XW) {
          wg_wait<XW>();
#pragma unroll
          for (int i = 0; i < 4; i++) asm volatile("" : "+f"(bx[i])::"memory");
          if (!cs) mod_put(G, sb, bx, b, 2, e1, tid);
          else {
            const int row = (m < 6 ? 0 : 4) + q;
            uint16_t* dst = (uint16_t*)G->cimg + s * 3072 + (m % 6) * 512 + row * 64 + g;
#pragma unroll
            for (int j = 0; j < 2; j++) {
              const float c1 = __shfl_sync(0xffffffffu, bx[2 * j], lane & 28), c2 = __shfl_sync(0xffffffffu, bx[2 * j + 1], lane & 28);
              const float t = (lane & 2) ? c2 : c1, hi = rbf(t);
              dst[((2 * w + j) ^ row) << 3] = (uint16_t)pack2((lane & 1) ? t - hi : hi, 0.f);
            }
          }
          __syncwarp();
          if (lane == 0) mbar_arrive(sb + 8 * (B_BD + 2));
          STAMPIF(tid == 0, 77);
        }
        if (ITW == 7) STAMPIF(tid == 0 && it == 0, 116 + wg);
        mbar_wait(sb + 8 * (B_F1 + st), ph);
        STAMPIF(tid == 0 && it == 0, 13 + wg);
        if (ITW == 1) STAMPIF(tid == 0 && it >= 10, 90 + it + 10 * wg);
        else if (ITW == 2) STAMPIF(tid == 0 && it < 10, 100 + it + 10 * wg);
        else if (ITW < 3) STAMPIF(threadIdx.x == ITW, 100 + it);
        const uint64_t da = da0 + st * 2048, db = db0 + st * 2048;
        if (it >= x0 && it < x1) {
          wg_fence();
          wgmma_ss_n8<1, 0>(bx, xa, xb, it != x0);
          wgmma_ss_n192<1, 1>(ga, da, db, 1);
          wgmma_ss_n8<1, 0>(bx, ya, yb, 1);
          wgmma_ss_n192<1, 1>(ua, da, db + 768, 1);
          wgmma_ss_n8<1, 0>(bx, ya + 128, yb + xs, 1);
          wgmma_ss_n192<1, 1>(ga, da + 256, db + 128, 1);
          wgmma_ss_n8<1, 0>(bx, ya + 256, yb + 2 * xs, 1);
          wgmma_ss_n192<1, 1>(ua, da + 256, db + 128 + 768, 1);
          wgmma_ss_n8<1, 0>(bx, ya + 384, yb + 3 * xs, 1);
          wg_commit();
          xa += 128; xb += xs; ya += 512; yb += 4 * xs;
        } else {
          wg_fence();
          wgmma_ss_n192<1, 1>(ga, da, db, PL || it != 0);
          wgmma_ss_n192<1, 1>(ua, da, db + 768, PL || it != 0);
          wgmma_ss_n192<1, 1>(ga, da + 256, db + 128, 1);
          wgmma_ss_n192<1, 1>(ua, da + 256, db + 128 + 768, 1);
          wg_commit();
        }
        wg_wait<1>();
        if ((PL || it > 0) && tid == 0) mbar_arrive(sb + 8 * (B_E1 + (st == 0 ? 4 : st - 1)));
        if (++st == 5) { st = 0; ph ^= 1; }
      }
      const uint32_t la = ring + wg * 2048 + tid * 16, ra = mapa(la, (b & 1) ^ 1), rp = mapa(sb + 8 * (B_PEER + 2 * wg), (b & 1) ^ 1), rb = rp + 8 * (B_RECV - B_PEER);
      uint32_t sa[24];
      auto addr = [&](int j) {
        sa[2 * j] = ra + (j < 2 ? 5 : (j >> 1) - 1) * 32768 + (j & 1) * 4096;
        sa[2 * j + 1] = (sa[2 * j] >> 31) + (rb + 8 * (j / 6));
        asm volatile("" : "+r"(sa[2 * j]), "+r"(sa[2 * j + 1]));
      };
      auto send = [&](int j) { st_async4(sa[2 * j], hh + 4 * j, sa[2 * j + 1]); };
      auto pack = [&](int c) {
#pragma unroll
        for (int i = 0; i < 64; i++) asm volatile("" : "+f"(ga[64 * c + i])::"memory");
#pragma unroll
        for (int i = 0; i < 4; i++) addr(4 * c + i);
#pragma unroll
        for (int i = 0; i < 16; i++) {
          const int j = 64 * c + 2 * i;
          hh[16 * c + i] = pack2(ga[j] * ga[j + 32], ga[j + 1] * ga[j + 33]);
          asm volatile("" : "+r"(hh[16 * c + i])::"memory");
          if ((i & 3) == 3 && 4 * c + i / 4 < NP) send(4 * c + i / 4);
          if (c == 2 && NQ > NP && i == 0) mbar_wait(sb + 8 * (B_PEER + 2 * wg), 0);
          if (c == 2 && (i & 3) == 3 && NP + i / 4 < NQ) send(NP + i / 4);
        }
      };
      STAMPIF(threadIdx.x == 0, 61);
      mbar_wait(sb + 8 * (B_F1 + 4), 1);
      mbar_wait(sb + 8 * B_EXT, 0);
      mbar_wait(sb + 8 * B_ST2, 0);
      const uint64_t de = mkdesc(sb + SM_EXT, 1024, 0, 1), ds = mkdesc(sb + SM_STAT + wg * 1024, 0, 128, 0);
#pragma unroll
      for (int c = 0; c < 2; c++) {
        wg_fence();
        wgmma_ss_n192<1, 1>(ga + 96 * c, da0 + 8192, db0 + 8192 + 768 * c, 1);
        wgmma_ss_n192<1, 1>(ga + 96 * c, da0 + 8192 + 256, db0 + 8192 + 128 + 768 * c, 1);
        wgmma_ss_n192<0, 1>(ga + 96 * c, ds, de + 192 * c, 1);
        wg_commit();
        if (c == 0) { mbar_wait(sb + 8 * B_P0, 0); mbar_wait(sb + 8 * B_FB, 0); }
        wg_wait<1>();
        if (c == 0 && tid == 0) {
          mbar_arrive(sb + 8 * (B_E1 + 3));
          mbar_arrive_remote(rp);
        }
      }
      STAMPIF(tid == 0, 15 + wg);
      float acc[64], rs[2] = {};
      uint4 pf[4], gb = {};
      uint32_t ln, os, ol, og;
      const char *po, *pq;
      const uint64_t dd0 = mkdesc(ring + 8192, 0, 1024, 1);
      bool ok = false;
#pragma unroll
      for (int c = 0; c < 3; c++) {
        pack(c);
        if (c == 1) ok = mbar_try(sb + 8 * (B_FB + 1), 0);
        STAMPIF(tid == 0 && c == 0, wg ? 89 : 121);
        if (ITW == 3) STAMPIF(tid == 0 && c > 0, 99 + c + 10 * wg);
        wg_fence();
#pragma unroll
        for (int k = 4 * c; k < 4 * c + 4; k++) wgmma_rs_n64<1>(acc, hh + 4 * k, dd0 + 5 * 2048 + 128 * k, k);
        wg_commit();
        if (c == 0) {
          wg_wait<1>();
          if (tid == 0) {
            mbar_arrive(sb + 8 * (B_E1 + 4));
            mbar_arrive_remote(rp + 8);
          }
        }
        if (c == 1 && !ok) mbar_wait(sb + 8 * (B_FB + 1), 0);
      }
      auto recv = [&](int j) {
        const uint4 v = lds128(la + (j < 2 ? 5 : (j >> 1) - 1) * 32768 + (j & 1) * 4096);
        hh[48 + 4 * j] = v.x; hh[49 + 4 * j] = v.y; hh[50 + 4 * j] = v.z; hh[51 + 4 * j] = v.w;
      };
      auto stage = [&](const float* a, int i) {
        const uint32_t v[4] = {pack2(a[8 * i] * rs[0], a[8 * i + 1] * rs[0]), pack2(a[8 * i + 2] * rs[1], a[8 * i + 3] * rs[1]),
                               pack2(a[8 * i + 4] * rs[0], a[8 * i + 5] * rs[0]), pack2(a[8 * i + 6] * rs[1], a[8 * i + 7] * rs[1])};
        stsm4(os + 32 * i, v);
      };
      auto fetch = [&](int p) {
        __syncwarp();
#pragma unroll
        for (int i = 0; i < 4; i++) pf[i] = lds128(ol + 576 * i);
      };
      auto next = [&](int p) {
        gb = lds128(og + 256 * out_blk(s, p));
        pq = po + 128 * out_blk(s, p);
        asm volatile("" : "+l"(pq));
      };
      auto add = [&](int p, int i) {
        asm volatile("red.relaxed.gpu.global.add.noftz.v4.bf16x2 [%0], {%1, %2, %3, %4};" ::"l"(pq - (i & 1) * 2048 * D_ - (i >> 1) * 2 * D_),
                     "r"(hmul(pf[i].x, gb.x)), "r"(hmul(pf[i].y, gb.y)), "r"(hmul(pf[i].z, gb.z)), "r"(hmul(pf[i].w, gb.w)) : "memory");
      };
#pragma unroll
      for (int h = 2; h < 20; h++) {
        const int gr = h >> 1, pe = gr < 4 ? gr >> 1 : gr & 1, ac = (gr < 4 ? gr : gr >> 1) & 1;
        const int ep = h == 7 || h == 8 ? 0 : h > 8 && (h & 3) == 1 || h > 8 && (h & 3) == 2 ? (h >> 2) - 1 : -1;
        if (!(h & 1) && h > 2 && !(PT && ok)) mbar_wait(sb + 8 * (B_FB + gr), 0);
        if (h == LH0 || h == LH1) mbar_wait(sb + 8 * (B_RECV + 2 * wg + (h == LH1)), 0);
        if (h == LH0 && (h == 4 || !LM) || h == LH1 && (h == 5 || !LM)) {
#pragma unroll
          for (int j = 0; j < 6; j++) recv(6 * (h == LH1) + j);
        }
        if (h == SPOS(6) / 6 && NQ <= 6) mbar_wait(sb + 8 * (B_PEER + 2 * wg), 0);
        if (h == SPOS(10) / 6) mbar_wait(sb + 8 * (B_PEER + 2 * wg + 1), 0);
        if (h == 6) {
          mbar_wait(sb + 8 * B_X1, 0);
          mbar_wait(sb + 8 * B_GB, 0);
          asm volatile("mov.u32 %0, %%laneid;" : "=r"(ln));
#pragma unroll
          for (int i = 0; i < 2; i++) rs[i] = blo(lds32(sb + SM_STAT + (4 * wg + w) * 256 + (ln & 28) * 4 + 128 * i + 4));
        }
        STAMPIF(tid == 0 && h % 4 == 0 && h < 16, (wg ? 89 : 121) + h / 4);
        STAMPIF(tid == 0 && h == 16, wg ? 97 : 96);
        if (ITW == 3) STAMPIF(tid == 0 && h < 10, 100 + h + 10 * wg);
        if (ITW == 4) STAMPIF(tid == 0 && h >= 10, 90 + h + 10 * wg);
        const uint64_t db = dd0 + (((gr + 5) % 6) * 2048 + (gr << 16));
        if (PT && (h & 1) && h < 19) ok = mbar_try(sb + 8 * (B_FB + gr + 1), 0);
        wg_fence();
#pragma unroll
        for (int j = 0; j < 6; j++) {
          const int k = 6 * (h & 1) + j;
          wgmma_rs_n64<1>(acc + 32 * ac, hh + 48 * pe + 4 * k, db + 128 * k, pe || k);
#pragma unroll
          for (int i = NQ; i < 12; i++) if (SPOS(i) == 6 * h + j) send(i);
          if (LM && h == LH0 && h < 4) { recv(j); wg_fence(); }
          if (LM && h == LH1 && h < 5) { recv(6 + j); wg_fence(); }
          if (ep >= 0 && (h & 1)) {
            if (j < 4) stage(acc + 32 * (1 - ac), j);
            if (j == 4) fetch(ep);
          }
          if (ep >= 0 && !(h & 1) && j > 0 && j < 5) add(ep, j - 1);
          if (ep >= 0 && !(h & 1) && j == 5) next(ep + 1);
        }
        wg_commit();
        STAMPIF(tid == 0 && h == 3, 81);
        if (h == 6) {
#pragma unroll
          for (int i = 0; i < 2; i++) rs[i] = __fdividef(0.25f, rs[i] * rs[i]);
          const uint32_t ob = sb + SM_X + (4 * wg + w) * 2304;
          os = ob + (ln & 15) * 144 + (ln & 16); ol = ob + (ln >> 3) * 16 + ln * 16;
          po = (const char*)(gout + (1793 + 2 * tbase(8 * m + 4 * wg + w)) * D_) + (int)(640 * (s & 1) + 16 * ln - (ln >> 3) * (512 * D_ + 128));
          og = sb + SM_CB + 32 * (ln & 7);
          asm volatile("" : "+r"(os), "+r"(ol), "+r"(og), "+l"(po));
          next(0);
        }
        if (h == 2 || h == 4 || h == 6 || h == 8 || h == 12 || h == 16) {
          wg_wait<1>();
          if (h < 12 && tid == 0) mbar_arrive(sb + 8 * (B_EB + gr - 1));
          if (h >= 6) {
#pragma unroll
            for (int j = 0; j < 32; j++) asm volatile("" : "+f"(acc[32 * (1 - ac) + j])::"memory");
          }
        }
      }
      STAMPIF(tid == 0, wg ? 95 : 93);
      wg_wait<0>();
#pragma unroll
      for (int i = 0; i < 32; i++) asm volatile("" : "+f"(acc[i])::"memory");
      STAMPIF(tid == 0, wg ? 50 : 18);
#pragma unroll
      for (int i = 0; i < 4; i++) stage(acc, i);
      fetch(4);
#pragma unroll
      for (int i = 0; i < 4; i++) add(4, i);
    }
  } else if (wg == 2) {
    asm volatile("setmaxnreg.dec.sync.aligned.u32 40;");
    const uint32_t e1 = (rdback(G->flag + 8 * m + 4) >> 5) + 1;
    if (tid < 80) {
      uint4 c = ((const uint4*)gc)[tid];
#pragma unroll 1
      for (int i = 0; i < 4; i++) {
        const float lo = blo(c.x), hi = bhi(c.x);
        sts32(sb + SM_STAT + 16 * tid + 4 * i, pack2(__fdividef(lo, 1.f + __expf(-lo)), __fdividef(hi, 1.f + __expf(-hi))));
        c.x = c.y; c.y = c.z; c.z = c.w;
      }
    }
    if (tid == 0) { sts32(sb + SM_SMALL + SMALL_E, e1); mbar_arrive(sb + 8 * B_E0); }
    fence_async_s();
    bar_sync(5, 128);
    if (mod_first(b)) mod_box(G, sb, b, 0, e1, tid);
    __syncwarp();
    if (lane == 0) mbar_arrive(sb + 8 * B_BD);
    STAMPIF(tid == 0, 27);
    float s1 = 0.f, s2 = 0.f, pv;
    int tl = (OPQ & 1) ? __shfl_sync(0xffffffffu, tid, tid) : tid;
#pragma unroll 1
    for (int r = 2 - DR; r < 5 - XO; r++) {
      asm volatile("" : "+r"(tl));
      if (DR && r == 2) s1 = s2 = 0.f;
      if ((XO || r < 4) && r > 1) {
        kv_job(G, sb, b, r, tl, TG ? e1 : 1);
        STAMPIF(tid == 0, 20 + r);
      }
      if (r == 3) { __syncwarp(); if (elect()) mbar_arrive(sb + 8 * B_KVS); }
      if (XO || r != 2) ln1_half(sb, tl, (r - 3 + XO) & 1, r < 2, s1, s2, pv);
    }
    {
      const int lane = tl & 31, cg = 4 * (w >> 1) + (lane & 2) + (w & 1), g = lane >> 2;
      uint32_t zo = offsetof(Scr, zT) + 2 * ((16 * cg + g) * S_ + 16 * b + 8 * (lane & 1)), co = offsetof(Scr, mv) + 4 * (2048 * (e1 & 1) + 8 * cg + g);
      uint4 z[2];
      uint32_t c[4];
      auto zld = [&]() {
        asm volatile("" : "+r"(zo), "+r"(co));
        const uint2* pz = (const uint2*)((const char*)G + zo);
        const uint32_t* pc = (const uint32_t*)((const char*)G + co);
        z[0] = ld_tag2(pz); z[1] = ld_tag2(pz + 4096);
        c[0] = rdback(pc); c[1] = rdback(pc + 320); c[2] = rdback(pc + 640); c[3] = rdback(pc + 1280);
      };
      STAMPIF(tid == 0, 28);
      if (ZF < 2 && !ZA) { spin(t_0, ZD); zld(); spin(t_0, ZS); }
      if (ITW == 8) STAMPIF(tid == 0, 106);
      ln1_end(sb, tl, s1, s2, pv);
      if (ZF < 2 && ZA) { spin(t_0, ZD); zld(); }
#pragma unroll 1
      for (int r = 0; r < 5; r++) {
        asm volatile("" : "+r"(tl));
        const int lane = tl & 31;
        if (ITW == 6) STAMPIF(tid == 0 && r < 2, 100 + 10 * r);
        if (ZF == 3) { if (r == 2 + MG) { mbar_wait(sb + 8 * (B_BD + 1), 0); spin(clk(), BD); } if (r == 0) spin(t_0, ZD); zld(); }
        const uint32_t la = sb + SM_SMALL + SMALL_LN + 16 * (lane & 1);
        uint32_t xa = x_addr(sb, w, lane) + 4096 * r, xv[8];
        const uint4 m4 = lds128(la), s4 = lds128(la + 32);
        const uint32_t m_[4] = {m4.x, m4.y, m4.z, m4.w}, s_[4] = {s4.x, s4.y, s4.z, s4.w};
        ldsm4t(xv, xa);
        ldsm4t(xv + 4, xa ^ 16);
        if (ZF == 2) { if (r == 2 + MG) { mbar_wait(sb + 8 * (B_BD + 1), 0); spin(clk(), BD); } if (r == 0) spin(t_0, ZD); zld(); }
        if (ITW == 6) STAMPIF(tid == 0 && r < 2, 104 + 10 * r);
        if (ITW == 8) STAMPIF(tid == 0 && r == 0, 109);
        z_wait(z[0], z[1], c, G, zo, co, e1);
        asm volatile("" : "+r"(xa));
        const uint32_t zc = (zo - (uint32_t)offsetof(Scr, zT)) >> 11, ao = (320 * m + s) * 32 + ((zc & ~31u) << 3) + (zc & 14) + (((zo >> 4) ^ (zc >> 3)) & 1);
        STAMPIF(tid == 0 && r == 0, 83);
        if (ITW == 6) STAMPIF(tid == 0 && r < 2, 105 + 10 * r);
        uint32_t h[8];
        {
          const uint32_t sa = ~c[0], ca1 = ~c[1];
#pragma unroll
          for (int j = 0; j < 8; j++) {
            const uint32_t z_[8] = {z[0].x, z[0].y, z[0].z, z[0].w, z[1].x, z[1].y, z[1].z, z[1].w}, sel = j > 3 ? 0x3232 : 0x1010;
            h[j] = hmul(hfma(hmul(hsub(xv[j], m_[j & 3]), s_[j & 3]), __byte_perm(ca1, 0, sel), __byte_perm(sa, 0, sel)), z_[j]);
            asm volatile("" : "+r"(h[j]));
          }
        }
        uint4* pa = (uint4*)G->AT + ao;
        uint32_t oo[8];
#pragma unroll
        for (int n = 0; n < 2; n++) {
          const uint32_t sel = n ? 0x3232 : 0x1010, ga = __byte_perm(~c[2], 0, sel), cb1 = __byte_perm(~c[3], 0, sel);
          uint32_t* o = oo + 4 * n, a[4];
#pragma unroll
          for (int j = 0; j < 4; j++) {
            o[j] = hfma(ga, h[4 * n + j], xv[4 * n + j]);
            a[j] = hmul(o[j], cb1);
          }
          a[2 * n + 1] = tagged(a[2 * n + 1], e1);
          pa[16 * n] = make_uint4(a[0], a[1], a[2], a[3]);
          if (n) { __syncwarp(); if (elect()) { flag_add(G, 8 * m + r); if (EA && r == 0) mbar_arrive(sb + 8 * (B_EW + 5)); } }
          if (ITW == 6) STAMPIF(tid == 0 && r < 2, 106 + n + 10 * r);
          if (ITW == 8) STAMPIF(lane == 0 && r == 0 && n, 110 + w);
          if (!SL) stsm4t(xa ^ (16 * n), o);
        }
        if (SL) { stsm4t(xa, oo); stsm4t(xa ^ 16, oo + 4); }
        if (r < 4) { zo += 256 * S_; co += 256; }
        auto x1st = [&]() {
          __syncwarp();
          int lane = tl & 31;
          if (!(OPQ & 2)) asm volatile("mov.u32 %0, %%laneid;" : "=r"(lane));
          const int c = 2 * (w & 1) + (lane & 1) + 2 * (lane & 2), g = lane >> 2;
          const uint32_t a = sb + SM_X + 4096 * r + (w >> 1) * 2048 + g * 128 + ((c ^ g) << 4);
          const uint4 v0 = lds128(a), v1 = lds128(a + 1024);
          char* po = (char*)gout + (2 * tbase(b) + 128 * (g & 6) + (g & 1)) * 2 * D_ + 256 * r + 64 * (w & 2) + 16 * c;
          if (ITW == 6) STAMPIF(tid == 0 && r < 2, 108 + 10 * r);
          stg128(po, v0);
          stg128(po + 2048 * D_, v1);
        };
        auto box1 = [&]() {
          if (BX3 >= 3) {
            mod_box(G, sb, b, 1, e1, tl);
            __syncwarp();
            if (elect()) mbar_arrive(sb + 8 * (B_BD + 1));
            STAMPIF(tid == 0, 73);
          } else mbar_wait(sb + 8 * (B_BD + 1), 0);
          if (BX3 < 4) spin(clk(), BD);
        };
        if (ZF == 1) {
          if (BX3 < 4 && r == 1 + MG) { if (XE) x1st(); box1(); }
          if (BX3 == 5 && r == 0) box1();
          zld();
        }
        if (BX3 == 6 && r == 0) box1();
        if (BX3 > 3 || ZF != 1 || !XE || r != 1 + MG) x1st();
        if (BX3 == 4 && r == 0) box1();
        __syncwarp();
        if (elect()) mbar_arrive(sb + 8 * (B_EW + r));
        STAMPIF(tid == 0, 29 + r);
        if (ZF == 0) { if (r == 1 + MG) box1(); zld(); }
      }
    }
    asm volatile("" : "+r"(tl));
    {
      const int lane = tl & 31;
      const uint4 m4 = lds128(sb + SM_SMALL + SMALL_LN + 16 * (lane & 1));
      const uint32_t m_[4] = {m4.x, m4.y, m4.z, m4.w}, xa = x_addr(sb, w, lane);
      float a[16];
#pragma unroll
      for (int i = 0; i < 16; i++) a[i] = 0.f;
#pragma unroll 2
      for (int n = 0; n < 10; n++) {
        uint32_t x_[4];
        ldsm4t(x_, (xa ^ (16 * (n & 1))) + 2048 * (n & 14));
#pragma unroll
        for (int i = 0; i < 4; i++) {
          const float d0 = blo(x_[i]) - blo(m_[i]), d1 = bhi(x_[i]) - bhi(m_[i]);
          a[4 * i] += d0; a[4 * i + 1] += d0 * d0; a[4 * i + 2] += d1; a[4 * i + 3] += d1 * d1;
        }
      }
      STAMPIF(lane == 0, 67 + (w & 1) + 11 * (w >> 1));
      bfly<16>(a, 16, lane & 16); bfly<8>(a, 8, lane & 8); bfly<4>(a, 4, lane & 4); bfly<2>(a, 2, lane & 2);
      if (lane == 0) mbar_arrive(sb + 8 * B_XF);
      STAMPIF(tid == 0, 88);
      sts32(sb + SM_SMALL + SMALL_RED + 16 * lane + 4 * w, __float_as_uint(a[0]));
      bar_sync(5, 128);
      if (w == 0) {
        const uint4 v = lds128(sb + SM_SMALL + SMALL_RED + 16 * lane);
        const float s1 = __uint_as_float(v.x) + __uint_as_float(v.y) + __uint_as_float(v.z) + __uint_as_float(v.w), s2 = __shfl_xor_sync(0xffffffffu, s1, 2);
        const int p = 8 * (lane & 1) + (lane >> 2);
        const float pv = blo(lds32(sb + SM_SMALL + SMALL_LN + 4 * (p >> 1)) >> (16 * (p & 1)));
        const float mu = s1 * (1.f / D_), var = fmaxf(s2 * (1.f / D_) - mu * mu, 0.f);
        const float sd = sdev(var);
        if (!(lane & 2)) st_tag(G->st2 + 16 * b + p, pack2(-0.5f * (pv + mu), 0.5f * sd), e1);
      }
      STAMPIF(tid == 0, 87);
    }
    {
      uint2 v;
      spin(clk(), SD);
      mbar_wait(sb + 8 * (B_BD + 2), 0);
#pragma unroll 1
      for (int i = 0;; i++) {
        v = ld_tag(G->st2 + 128 * m + tl);
        if (__all_sync(0xffffffffu, v.y == e1)) break;
        if (i > (1 << 20)) __trap();
      }
      const uint32_t hm = __byte_perm(v.x, 0, 0x1010), hs = __byte_perm(v.x, 0, 0x3232);
      sts128(sb + SM_STAT + 16 * tl, make_uint4(hm, hs, hm, hs));
      fence_async_s();
      __syncwarp();
      if (elect()) mbar_arrive(sb + 8 * B_ST2);
      STAMPIF(tid == 0, 21);
    }
  } else {
    asm volatile("setmaxnreg.dec.sync.aligned.u32 24;");
    if (w != 0) {
    if (w == 2 && lane < 3) asm volatile("prefetch.tensormap [%0];" ::"l"(&P.mG + lane) : "memory");
    if (w & 1) {
      const uint32_t dv = *(const uint16_t*)(gD + 128 * min(lane, 4) + b);
#pragma unroll 1
      for (int j = 4; j < 10; j++) {
        k1_job(sb, j >> 1, 64 * (j & 1) + 16 * (w & 2) + lane, K1N ? __shfl_sync(0xffffffffu, dv, j >> 1) : *(const uint16_t*)(gD + 64 * (j & 14) + b));
        if (ITW == 5) STAMPIF(tid == 32, 98 + (j >> 1));
        if (UT == 5 && UD && w == 1 && (j & 1)) {
          mbar_wait(sb + 8 * (B_KJ + (j >> 1)), 0);
          const uint32_t t = lds32(sb + SM_SMALL + SMALL_TS + 4 * (j >> 1));
          while (clk() - t < UD);
        }
        __syncwarp();
        if (lane == 0) mbar_arrive(sb + 8 * (B_K + (j >> 1) - 2));
      }
      STAMPIF(tid == 32, 74);
    }
    if (w == 1) {
     {
      mbar_wait(sb + 8 * B_KVS, 0);
      const uint32_t e1 = epoch(sb);
      if (elect()) {
        if (P3) { const uint32_t v = e1 * 32 - 32; sts128(sb + SM_SMALL + SMALL_H, make_uint4(v, v, v, v)); sts32(sb + SM_SMALL + SMALL_H + 16, v); }
        if (ER) mbar_wait(sb + 8 * B_KV4, 0);
        mbar_wait(sb + 8 * (B_EW + 5 * EA), 0);
        spin(clk(), AD);
#pragma unroll 1
        for (int it = 0; it < 20; it++) {
          int st = it % 5;
          if ((it & 3) == 0) { if (P3) hint_wait(G, sb + SM_SMALL + SMALL_H, 8 * m + (it >> 2), e1 * 32); else flag_wait(G, 8 * m + (it >> 2), e1 * 32); STAMP(45 + (it >> 2)); }
          mbar_wait(sb + 8 * (B_E1 + st), (it / 5) & 1);
          uint32_t fb = sb + 8 * (B_A + st);
          mbar_expect(fb, 8192);
          bulk_g2s(ring + st * 32768, G->AT + (20 * m + it) * 4096, 8192, fb);
        }
        mbar_wait(sb + 8 * B_XF, 0);
        flag_wait(G, 8 * m + FL_X, e1 * 8);
        mbar_arrive(sb + 8 * B_X1);
        STAMP(86);
      }
     }
    } else if (w == 2) {
      if (lane < 4) mbar_expect(sb + 8 * (B_RECV + lane), 12288);
      if (UT == 2) { bar_arrive(1, 288); bar_arrive(2, 288); }
      int ph = 0;
#pragma unroll 1
      for (int ch = UT; ch < 5; ch++) {
        const uint32_t ub = chan_base(sb, ch) + KSZ;
        uint4* pu = (uint4*)(G->kvT + (128 * ch + b) * S_);
        mbar_wait(sb + 8 * (B_KJ + ch), 0);
        const uint32_t t0 = lds32(sb + SM_SMALL + SMALL_TS + 4 * ch);
        while (clk() - t0 < (ch ? UD : UD0));
#pragma unroll 1
        for (int i = 0;; i++) {
          if (elect()) { mbar_expect(sb + 8 * B_U, 4096); bulk_g2s(ub, pu, 4096, sb + 8 * B_U); }
          if (ITW == 5) STAMPIF(lane == 0, 110 + ch);
          mbar_wait(sb + 8 * B_U, ph);
          ph ^= 1;
          uint32_t t = 1;
#pragma unroll
          for (int j = 0; j < 8; j++) t &= lds32(ub + 16 * lane + 512 * j + 12);
          if (__all_sync(0xffffffffu, t)) break;
          if (i > (1 << 20)) __trap();
        }
        if (ITW == 5) STAMPIF(lane == 0, 105 + ch);
        if (ch > 1) mbar_wait(sb + 8 * (B_Z + ch - 2), 0);
        bar_arrive(1 + (ch & 1), 288);
#pragma unroll
        for (int j = 0; j < 8; j++) stg128(pu + lane + 32 * j, make_uint4(0, 0, 0, 0));
      }
      if (ITW == 8) { mbar_wait(sb + 8 * B_X, 0); STAMPIF(lane == 0, 100); mbar_wait(sb + 8 * (B_X + 1), 0); STAMPIF(lane == 0, 101); }
      mbar_wait(sb + 8 * B_BD, 0);
      const uint32_t e1 = epoch(sb), ao = 256 * (lane & 16) + 32 * (lane & 15) + 4 * (lane & 4) + (lane & 8) + 4;
#pragma unroll 1
      for (int it = 0; it < 20; it++) {
        const int st = it % 5;
        const uint32_t a = ring + st * 32768 + ao;
        mbar_wait(sb + 8 * (B_A + st), (it / 5) & 1);
        if (ITW == 7) STAMPIF(lane == 0 && it < 4, 100 + it);
        if (ITW == 8) STAMPIF(lane == 0 && it < 2, 114 + it);
        uint32_t t = 0;
#pragma unroll
        for (int j = 0; j < 8; j++) t |= lds32(a + 512 * j) ^ e1;
        if (__any_sync(0xffffffffu, t & 1)) {
#pragma unroll 1
          for (int j = 0; j < 8; j++) a_check(a + 512 * j, (const char*)G->AT + (20 * m + it) * 8192 + ao + 512 * j, e1);
        }
        if (lane == 0) mbar_arrive(sb + 8 * (B_F1 + st));
        if (ITW == 7) STAMPIF(lane == 0 && it < 4, 104 + it);
        if (ITW == 8) STAMPIF(lane == 0 && it < 2, 116 + it);
      }
    } else {
      mbar_wait(sb + 8 * B_KVS, 0);
      auto rel = [&](int ch) { mbar_wait(sb + 8 * (B_Z + ch), 0); if (lane <= (ch >> 2)) mbar_arrive(sb + 8 * (B_E1 + 2 + (ch >> 1))); };
      if (RL) { rel(0); rel(1); rel(2); }
      mbar_wait(sb + 8 * (B_BD + 1), 0);
      if (b >= 96 && elect()) { load_box(P, sb, b, 4); load_box(P, sb, b, 5); }
      const uint32_t t1 = clk();
      if (RL) { rel(3); rel(4); }
      spin(t1, CD);
      __syncwarp();
      const uint32_t e1 = epoch(sb);
#pragma unroll 1
      for (int n = 0; n < 5; n++) {
        int lane;
        asm volatile("mov.u32 %0, %%laneid;" : "=r"(lane));
        if (n == 3) {
          fence_async_s();
          __syncwarp();
          if (lane == 0) mbar_arrive(sb + 8 * B_F);
          STAMPIF(lane == 0, 34);
          {
            mbar_wait(sb + 8 * (B_EW + 4), 0);
            const char* po = (char*)gout + (2 * tbase(b) + 64 * (lane & 28) + ((lane >> 1) & 1)) * 2 * D_ + (lane & 1) * 640;
            uint32_t v = 0;
#pragma unroll
            for (int r = 0; r < 5; r++) v ^= rdback(po + 128 * r);
            rdwait(sb, v);
            __syncwarp();
            if (lane == 0) flag_add(G, 8 * m + FL_X);
            STAMPIF(lane == 0, 94);
          }
          mbar_wait(sb + 8 * (B_BD + 2), 0);
          if (lane < 2) mbar_arrive(sb + 8 * (B_E1 + 5));
          if (m < 12) {
            rdwait(sb, rdback(G->cimg + s * 3072 + (m % 6) * 512 + (m < 6 ? 0 : 256) + 64 * (lane & 3)));
            __syncwarp();
            if (lane == 0) flag_add(G, FL_C + 8 * s);
            STAMPIF(lane == 0, 35);
          }
          if (elect()) {
            flag_wait(G, FL_C + 8 * s, e1 * 12);
            fence_async_g();
            STAMP(54);
            mbar_expect(sb + 8 * B_EXT, 6144);
            bulk_g2s(sb + SM_EXT, G->cimg + s * 3072, 6144, sb + 8 * B_EXT);
          }
          __syncwarp();
          mbar_wait(sb + 8 * B_ST2, 0);
        }
        const int j = n < 3 ? min(16 * n + (lane >> 1), 39) : min(16 * n - 8 + (lane >> 1), 59), k = j < 20 ? j : j < 40 ? j - 20 : j - 40;
        const uint2* pj = (const uint2*)(G->mv + 2048 * (e1 & 1) + 4 * (lane & 1) + 8 * (k + (j < 40 ? (j < 20 ? 160 : 120) + (m < 6 ? 0 : 20) : 200 + 20 * (s & 1))));
        uint4 a;
#pragma unroll 1
        for (int i = 0;; i++) {
          a = ld_tag2(pj);
          if (__all_sync(0xffffffffu, a.x != 0)) break;
          if (i > (1 << 20)) __trap();
        }
        const uint32_t d = sb + SM_CB + 64 * k + 8 * (lane & 1) + (j >= 20 && j < 40 ? 16 : 0);
        sts64(d, ~__byte_perm(a.x, a.y, 0x5410), ~__byte_perm(a.z, a.w, 0x5410));
        sts64(d + 32, ~__byte_perm(a.x, a.y, 0x7632), ~__byte_perm(a.z, a.w, 0x7632));
      }
      __syncwarp();
      if (lane == 0) mbar_arrive(sb + 8 * B_GB);
      STAMPIF(lane == 0, 39);
    }
    } else {
      STAMPIF(lane == 0, 62);
      int rw = sched_run<0>(P, In{gk, gv, gsk, gWg, gWu, gWd, gss}, sb, b, lane, __shfl_sync(0xffffffffu, t_0, 0));
      if (elect()) {
        STAMP(69);
        mbar_wait(sb + 8 * B_KVS, 0);
        if (ER) mbar_wait(sb + 8 * B_KV4, 0);
        STAMP(70);
        int rd = 0, c = 0;
#pragma unroll 1
        for (int it = 0; it < 20; it++) {
          load_w(P, sb, s, it);
          if ((PWM >> it) & 1) { l2_prefetch(gWg + (128 * rw + b) * F_, 2 * F_); l2_prefetch(gWu + (128 * rw + b) * F_, 2 * F_); rw++; }
          if ((PDM >> it) & 1) { l2_prefetch(gWd + (512 * rd + 4 * b) * D_, 8 * D_); rd++; }
          if (((STM >> it) & 1) && b < 96) {
            const int grp = m % 6;
            if (c == 4) mbar_wait(sb + 8 * (B_BD + 1), 0);
            if (c == 0) mbar_expect(sb + 8 * B_ST0, 40960);
#pragma unroll
            for (int j = 0; j < 2; j++, c++)
              tma2d(sb + (c < 2 ? SM_EXT : SM_RING + R_X - 8192) + 4096 * c, &P.mG + (grp & 1), 192 * s + 64 * (grp >> 1), (m < 6 ? 0 : 320) + 32 * c, sb + 8 * B_ST0);
          }
        }
#pragma unroll
        for (int k = 0; k < 10; k++) {
          const int st = (k + 5) % 6, pe = k < 4 ? k >> 1 : k & 1, ps = k < 4 ? k & 1 : k >> 1;
          mbar_wait(sb + 8 * (k < 6 ? B_E1 + st : B_EB + k - 6), 0);
          if (k == 2) mbar_arrive_remote(mapa(sb + 8 * B_P0, (b & 1) ^ 1));
          mbar_expect(sb + 8 * (B_FB + k), 24576);
          tma2d(ring + st * 32768 + 8192, &P.mD, 320 * (s & 1) + 64 * out_blk(s, ps), 192 * (s ^ pe), sb + 8 * (B_FB + k));
        }
      }
    }
  }
}

typedef CUresult (*EncFn)(CUtensorMap*, CUtensorMapDataType, cuuint32_t, void*, const cuuint64_t*, const cuuint64_t*, const cuuint32_t*, const cuuint32_t*,
                          CUtensorMapInterleave, CUtensorMapSwizzle, CUtensorMapL2promotion, CUtensorMapFloatOOBfill);
static void mkmap(EncFn enc, CUtensorMap* m, const void* p, int rank, const cuuint64_t* dims, const cuuint64_t* strides, const cuuint32_t* box, CUtensorMapSwizzle sw) {
  cuuint32_t es[5] = {1, 1, 1, 1, 1};
  CUresult r = enc(m, CU_TENSOR_MAP_DATA_TYPE_BFLOAT16, rank, (void*)p, dims, strides, box, es, CU_TENSOR_MAP_INTERLEAVE_NONE, sw,
                   CU_TENSOR_MAP_L2_PROMOTION_L2_128B, CU_TENSOR_MAP_FLOAT_OOB_FILL_NONE);
  if (r != CUDA_SUCCESS) fprintf(stderr, "tensor map encode failed: %d\n", (int)r);
}

extern "C" void kernel_launch(void* const* d_in, const int* in_sizes, int n_in, void* d_out, int out_size) {
  void* fn = nullptr;
  cudaDriverEntryPointQueryResult qr;
  cudaGetDriverEntryPoint("cuTensorMapEncodeTiled", &fn, cudaEnableDefault, &qr);
  EncFn enc = (EncFn)fn;
  Scr* G;
  cudaGetSymbolAddress((void**)&G, g_scr);
  Params P;
  { cuuint64_t d[] = {128, 16, 640}, st[] = {256, 4096}; cuuint32_t bx[] = {144, 16, 1}; mkmap(enc, &P.mS, d_in[4], 3, d, st, bx, CU_TENSOR_MAP_SWIZZLE_NONE); }
  { cuuint64_t d[] = {3840, 64, 10}, st[] = {7680, 64 * 7680}; cuuint32_t bx[] = {16, 64, 5}; mkmap(enc, &P.mWm, d_in[11], 3, d, st, bx, CU_TENSOR_MAP_SWIZZLE_32B); }
  { cuuint64_t d[] = {32, 20, 256, 8}, st[] = {64, 10240, 1280}; cuuint32_t bx[] = {40, 1, 9, 8}, bx2[] = {40, 1, 8, 8};
    mkmap(enc, &P.mK, d_in[1], 4, d, st, bx, CU_TENSOR_MAP_SWIZZLE_NONE); mkmap(enc, &P.mV, d_in[2], 4, d, st, bx2, CU_TENSOR_MAP_SWIZZLE_NONE); }
  { cuuint64_t d[] = {1536, 640}, st[] = {3072}; cuuint32_t bx[] = {64, 32};
    mkmap(enc, &P.mG, d_in[7], 2, d, st, bx, CU_TENSOR_MAP_SWIZZLE_128B); mkmap(enc, &P.mU, d_in[8], 2, d, st, bx, CU_TENSOR_MAP_SWIZZLE_128B); }
  { cuuint64_t d[] = {640, 1536}, st[] = {1280}; cuuint32_t bx[] = {64, 192}; mkmap(enc, &P.mD, d_in[9], 2, d, st, bx, CU_TENSOR_MAP_SWIZZLE_128B); }
  { cuuint64_t d[] = {64, 2, 8, 10, 128}, st[] = {1280, 256 * 1280, 128, 2560}; cuuint32_t bx[] = {64, 2, 8, 5, 1}; mkmap(enc, &P.mX, d_in[0], 5, d, st, bx, CU_TENSOR_MAP_SWIZZLE_128B); }
  cudaFuncSetAttribute(fused_kernel, cudaFuncAttributeMaxDynamicSharedMemorySize, SM_TOTAL + DEVSM);
  cudaLaunchConfig_t cfg = {};
  cfg.gridDim = dim3(128); cfg.blockDim = dim3(512); cfg.dynamicSmemBytes = SM_TOTAL + DEVSM; cfg.stream = cudaStreamPerThread;
  cudaLaunchAttribute at[1];
  at[0].id = cudaLaunchAttributeClusterDimension; at[0].val.clusterDim.x = 2; at[0].val.clusterDim.y = 1; at[0].val.clusterDim.z = 1;
  cfg.attrs = at; cfg.numAttrs = 1;
  cudaLaunchKernelEx(&cfg, fused_kernel, (const bf16*)d_in[1], (const bf16*)d_in[2], (const bf16*)d_in[3], (const bf16*)d_in[5], (const bf16*)d_in[10], G,
                     (const bf16*)d_in[7], (const bf16*)d_in[8], (const bf16*)d_in[9], (bf16*)d_out, (const bf16*)d_in[4], P);
}
```

```cpp
#include <cuda_runtime.h>
#include <cuda.h>
#include <cuda_bf16.h>
#include <stdio.h>
#include <stdint.h>
typedef __nv_bfloat16 bf16;
__device__ __forceinline__ uint32_t smem_u32(const void* p) { return (uint32_t)__cvta_generic_to_shared(p); }
__device__ __forceinline__ void mbar_init(uint32_t bar, int cnt) { asm volatile("mbarrier.init.shared::cta.b64 [%0], %1;" ::"r"(bar), "r"(cnt) : "memory"); }
__device__ __forceinline__ void mbar_expect(uint32_t bar, int bytes) { asm volatile("mbarrier.arrive.expect_tx.shared::cta.b64 _, [%0], %1;" ::"r"(bar), "r"(bytes) : "memory"); }
__device__ __forceinline__ void mbar_arrive(uint32_t bar) { asm volatile("mbarrier.arrive.shared::cta.b64 _, [%0];" ::"r"(bar) : "memory"); }
__device__ __forceinline__ void mbar_arrive_remote(uint32_t bar) { asm volatile("mbarrier.arrive.relaxed.cluster.shared::cluster.b64 _, [%0];" ::"r"(bar) : "memory"); }
__device__ __forceinline__ uint32_t mapa(uint32_t a, uint32_t cta) { uint32_t r; asm("mapa.shared::cluster.u32 %0, %1, %2;" : "=r"(r) : "r"(a), "r"(cta)); return r; }
__device__ __forceinline__ bool mbar_try(uint32_t bar, int parity) {
  uint32_t ok;
  asm volatile("{\n.reg .pred p;\nmbarrier.try_wait.parity.shared::cta.b64 p, [%1], %2;\nselp.u32 %0, 1, 0, p;\n}" : "=r"(ok) : "r"(bar), "r"(parity) : "memory");
  return ok;
}
__device__ __forceinline__ void mbar_wait(uint32_t bar, int parity) {
#pragma unroll 1
  for (int i = 0; i < (1 << 20); i++) { if (mbar_try(bar, parity)) return; }
  __trap();
}
__device__ __forceinline__ bool elect() {
  uint32_t p;
  asm volatile("{\n.reg .pred P;\nelect.sync _|P, 0xffffffff;\nselp.u32 %0, 1, 0, P;\n}" : "=r"(p));
  return p;
}
__device__ __forceinline__ void tma2d(uint32_t dst, const CUtensorMap* m, int c0, int c1, uint32_t bar) {
  asm volatile("cp.async.bulk.tensor.2d.shared::cluster.global.mbarrier::complete_tx::bytes [%0], [%1, {%3, %4}], [%2];" ::"r"(dst), "l"(m), "r"(bar), "r"(c0), "r"(c1) : "memory");
}
__device__ __forceinline__ void tma3d(uint32_t dst, const CUtensorMap* m, int c0, int c1, int c2, uint32_t bar) {
  asm volatile("cp.async.bulk.tensor.3d.shared::cluster.global.mbarrier::complete_tx::bytes [%0], [%1, {%3, %4, %5}], [%2];" ::"r"(dst), "l"(m), "r"(bar), "r"(c0), "r"(c1), "r"(c2) : "memory");
}
__device__ __forceinline__ void tma4d(uint32_t dst, const CUtensorMap* m, int c0, int c1, int c2, int c3, uint32_t bar) {
  asm volatile("cp.async.bulk.tensor.4d.shared::cluster.global.mbarrier::complete_tx::bytes [%0], [%1, {%3, %4, %5, %6}], [%2];" ::"r"(dst), "l"(m), "r"(bar), "r"(c0), "r"(c1), "r"(c2), "r"(c3) : "memory");
}
__device__ __forceinline__ void tma5d(uint32_t dst, const CUtensorMap* m, int c0, int c1, int c2, int c3, int c4, uint32_t bar) {
  asm volatile("cp.async.bulk.tensor.5d.shared::cluster.global.mbarrier::complete_tx::bytes [%0], [%1, {%3, %4, %5, %6, %7}], [%2];" ::"r"(dst), "l"(m), "r"(bar), "r"(c0), "r"(c1), "r"(c2), "r"(c3), "r"(c4) : "memory");
}
__device__ __forceinline__ void tma_store2d(const CUtensorMap* m, uint32_t src, int c0, int c1) {
  asm volatile("cp.async.bulk.tensor.2d.global.shared::cta.bulk_group [%0, {%2, %3}], [%1];" ::"l"(m), "r"(src), "r"(c0), "r"(c1) : "memory");
}
__device__ __forceinline__ void tma_store4d(const CUtensorMap* m, uint32_t src, int c0, int c1, int c2, int c3) {
  asm volatile("cp.async.bulk.tensor.4d.global.shared::cta.bulk_group [%0, {%2, %3, %4, %5}], [%1];" ::"l"(m), "r"(src), "r"(c0), "r"(c1), "r"(c2), "r"(c3) : "memory");
}
__device__ __forceinline__ void tma_prefetch2d(const CUtensorMap* m, int c0, int c1) {
  asm volatile("cp.async.bulk.prefetch.tensor.2d.L2.global [%0, {%1, %2}];" ::"l"(m), "r"(c0), "r"(c1) : "memory");
}
__device__ __forceinline__ void bulk_g2s(uint32_t dst, const void* src, int bytes, uint32_t bar) {
  asm volatile("cp.async.bulk.shared::cluster.global.mbarrier::complete_tx::bytes [%0], [%1], %2, [%3];" ::"r"(dst), "l"(src), "r"(bytes), "r"(bar) : "memory");
}
__device__ __forceinline__ void bulk_s2g(void* dst, uint32_t src, int bytes) {
  asm volatile("cp.async.bulk.global.shared::cta.bulk_group [%0], [%1], %2;" ::"l"(dst), "r"(src), "r"(bytes) : "memory");
}
__device__ __forceinline__ void cp16(uint32_t dst, const void* src) { asm volatile("cp.async.cg.shared.global [%0], [%1], 16;" ::"r"(dst), "l"(src) : "memory"); }
__device__ __forceinline__ void cp16z(uint32_t dst, const void* src, int n) { asm volatile("cp.async.cg.shared.global [%0], [%1], 16, %2;" ::"r"(dst), "l"(src), "r"(n) : "memory"); }
__device__ __forceinline__ void cp_arrive(uint32_t bar) { asm volatile("cp.async.mbarrier.arrive.noinc.shared::cta.b64 [%0];" ::"r"(bar) : "memory"); }
__device__ __forceinline__ void st_async4(uint32_t dst, const uint32_t* v, uint32_t bar) {
  asm volatile("st.async.weak.shared::cluster.mbarrier::complete_tx::bytes.v4.b32 [%0], {%1, %2, %3, %4}, [%5];" ::"r"(dst), "r"(v[0]), "r"(v[1]), "r"(v[2]), "r"(v[3]), "r"(bar) : "memory");
}
__device__ __forceinline__ void wg_fence() { asm volatile("wgmma.fence.sync.aligned;" ::: "memory"); }
__device__ __forceinline__ void wg_commit() { asm volatile("wgmma.commit_group.sync.aligned;" ::: "memory"); }
template <int N> __device__ __forceinline__ void wg_wait() { asm volatile("wgmma.wait_group.sync.aligned %0;" ::"n"(N) : "memory"); }
__device__ __forceinline__ uint64_t mkdesc(uint32_t addr, uint32_t lbo, uint32_t sbo, uint32_t swz) {
  return (uint64_t)((addr & 0x3FFFF) >> 4) | ((uint64_t)(lbo >> 4) << 16) | ((uint64_t)(sbo >> 4) << 32) | ((uint64_t)swz << 62);
}
__device__ __forceinline__ void ldsm4t(uint32_t* r, uint32_t a) {
  asm volatile("ldmatrix.sync.aligned.m8n8.x4.trans.shared.b16 {%0,%1,%2,%3}, [%4];" : "=r"(r[0]), "=r"(r[1]), "=r"(r[2]), "=r"(r[3]) : "r"(a) : "memory");
}
__device__ __forceinline__ void stsm4(uint32_t a, const uint32_t* r) {
  asm volatile("stmatrix.sync.aligned.m8n8.x4.shared.b16 [%0], {%1,%2,%3,%4};" ::"r"(a), "r"(r[0]), "r"(r[1]), "r"(r[2]), "r"(r[3]) : "memory");
}
__device__ __forceinline__ void stsm4t(uint32_t a, const uint32_t* r) {
  asm volatile("stmatrix.sync.aligned.m8n8.x4.trans.shared.b16 [%0], {%1,%2,%3,%4};" ::"r"(a), "r"(r[0]), "r"(r[1]), "r"(r[2]), "r"(r[3]) : "memory");
}
__device__ __forceinline__ void bar_sync(int id, int n) { asm volatile("bar.sync %0, %1;" ::"r"(id), "r"(n) : "memory"); }
__device__ __forceinline__ void bar_arrive(int id, int n) { asm volatile("bar.arrive %0, %1;" ::"r"(id), "r"(n) : "memory"); }
__device__ __forceinline__ uint32_t lds32(uint32_t a) { uint32_t v; asm volatile("ld.shared.b32 %0, [%1];" : "=r"(v) : "r"(a) : "memory"); return v; }
__device__ __forceinline__ uint2 lds64(uint32_t a) { uint2 v; asm volatile("ld.shared.v2.b32 {%0,%1}, [%2];" : "=r"(v.x), "=r"(v.y) : "r"(a) : "memory"); return v; }
__device__ __forceinline__ uint4 lds128(uint32_t a) { uint4 v; asm volatile("ld.shared.v4.b32 {%0,%1,%2,%3}, [%4];" : "=r"(v.x), "=r"(v.y), "=r"(v.z), "=r"(v.w) : "r"(a) : "memory"); return v; }
__device__ __forceinline__ void sts16(uint32_t a, uint32_t v) { asm volatile("st.shared.b16 [%0], %1;" ::"r"(a), "h"((uint16_t)v) : "memory"); }
__device__ __forceinline__ void sts32(uint32_t a, uint32_t v) { asm volatile("st.shared.b32 [%0], %1;" ::"r"(a), "r"(v) : "memory"); }
__device__ __forceinline__ void sts64(uint32_t a, uint32_t x, uint32_t y) { asm volatile("st.shared.v2.b32 [%0], {%1,%2};" ::"r"(a), "r"(x), "r"(y) : "memory"); }
__device__ __forceinline__ void sts128(uint32_t a, uint4 v) { asm volatile("st.shared.v4.b32 [%0], {%1,%2,%3,%4};" ::"r"(a), "r"(v.x), "r"(v.y), "r"(v.z), "r"(v.w) : "memory"); }
template<int TB> __device__ __forceinline__ void wgmma_rs_n128(float* d, const uint32_t* a, uint64_t db, int sd) {
  asm volatile("{\n.reg .pred p;\nsetp.ne.b32 p, %69, 0;\n"
    "wgmma.mma_async.sync.aligned.m64n128k16.f32.bf16.bf16 {%0, %1, %2, %3, %4, %5, %6, %7, %8, %9, %10, %11, %12, %13, %14, %15, %16, %17, %18, %19, %20, %21, %22, %23, %24, %25, %26, %27, %28, %29, %30, %31, %32, %33, %34, %35, %36, %37, %38, %39, %40, %41, %42, %43, %44, %45, %46, %47, %48, %49, %50, %51, %52, %53, %54, %55, %56, %57, %58, %59, %60, %61, %62, %63}, {%64, %65, %66, %67}, %68, p, 1, 1, %70;\n}"
    : "+f"(d[0]), "+f"(d[1]), "+f"(d[2]), "+f"(d[3]), "+f"(d[4]), "+f"(d[5]), "+f"(d[6]), "+f"(d[7]), "+f"(d[8]), "+f"(d[9]), "+f"(d[10]), "+f"(d[11]), "+f"(d[12]), "+f"(d[13]), "+f"(d[14]), "+f"(d[15]), "+f"(d[16]), "+f"(d[17]), "+f"(d[18]), "+f"(d[19]), "+f"(d[20]), "+f"(d[21]), "+f"(d[22]), "+f"(d[23]), "+f"(d[24]), "+f"(d[25]), "+f"(d[26]), "+f"(d[27]), "+f"(d[28]), "+f"(d[29]), "+f"(d[30]), "+f"(d[31]), "+f"(d[32]), "+f"(d[33]), "+f"(d[34]), "+f"(d[35]), "+f"(d[36]), "+f"(d[37]), "+f"(d[38]), "+f"(d[39]), "+f"(d[40]), "+f"(d[41]), "+f"(d[42]), "+f"(d[43]), "+f"(d[44]), "+f"(d[45]), "+f"(d[46]), "+f"(d[47]), "+f"(d[48]), "+f"(d[49]), "+f"(d[50]), "+f"(d[51]), "+f"(d[52]), "+f"(d[53]), "+f"(d[54]), "+f"(d[55]), "+f"(d[56]), "+f"(d[57]), "+f"(d[58]), "+f"(d[59]), "+f"(d[60]), "+f"(d[61]), "+f"(d[62]), "+f"(d[63])
    : "r"(a[0]), "r"(a[1]), "r"(a[2]), "r"(a[3]), "l"(db), "r"(sd), "n"(TB));
}

template<int TB> __device__ __forceinline__ void wgmma_rs_n160(float* d, const uint32_t* a, uint64_t db, int sd) {
  asm volatile("{\n.reg .pred p;\nsetp.ne.b32 p, %85, 0;\n"
    "wgmma.mma_async.sync.aligned.m64n160k16.f32.bf16.bf16 {%0, %1, %2, %3, %4, %5, %6, %7, %8, %9, %10, %11, %12, %13, %14, %15, %16, %17, %18, %19, %20, %21, %22, %23, %24, %25, %26, %27, %28, %29, %30, %31, %32, %33, %34, %35, %36, %37, %38, %39, %40, %41, %42, %43, %44, %45, %46, %47, %48, %49, %50, %51, %52, %53, %54, %55, %56, %57, %58, %59, %60, %61, %62, %63, %64, %65, %66, %67, %68, %69, %70, %71, %72, %73, %74, %75, %76, %77, %78, %79}, {%80, %81, %82, %83}, %84, p, 1, 1, %86;\n}"
    : "+f"(d[0]), "+f"(d[1]), "+f"(d[2]), "+f"(d[3]), "+f"(d[4]), "+f"(d[5]), "+f"(d[6]), "+f"(d[7]), "+f"(d[8]), "+f"(d[9]), "+f"(d[10]), "+f"(d[11]), "+f"(d[12]), "+f"(d[13]), "+f"(d[14]), "+f"(d[15]), "+f"(d[16]), "+f"(d[17]), "+f"(d[18]), "+f"(d[19]), "+f"(d[20]), "+f"(d[21]), "+f"(d[22]), "+f"(d[23]), "+f"(d[24]), "+f"(d[25]), "+f"(d[26]), "+f"(d[27]), "+f"(d[28]), "+f"(d[29]), "+f"(d[30]), "+f"(d[31]), "+f"(d[32]), "+f"(d[33]), "+f"(d[34]), "+f"(d[35]), "+f"(d[36]), "+f"(d[37]), "+f"(d[38]), "+f"(d[39]), "+f"(d[40]), "+f"(d[41]), "+f"(d[42]), "+f"(d[43]), "+f"(d[44]), "+f"(d[45]), "+f"(d[46]), "+f"(d[47]), "+f"(d[48]), "+f"(d[49]), "+f"(d[50]), "+f"(d[51]), "+f"(d[52]), "+f"(d[53]), "+f"(d[54]), "+f"(d[55]), "+f"(d[56]), "+f"(d[57]), "+f"(d[58]), "+f"(d[59]), "+f"(d[60]), "+f"(d[61]), "+f"(d[62]), "+f"(d[63]), "+f"(d[64]), "+f"(d[65]), "+f"(d[66]), "+f"(d[67]), "+f"(d[68]), "+f"(d[69]), "+f"(d[70]), "+f"(d[71]), "+f"(d[72]), "+f"(d[73]), "+f"(d[74]), "+f"(d[75]), "+f"(d[76]), "+f"(d[77]), "+f"(d[78]), "+f"(d[79])
    : "r"(a[0]), "r"(a[1]), "r"(a[2]), "r"(a[3]), "l"(db), "r"(sd), "n"(TB));
}

template<int TB> __device__ __forceinline__ void wgmma_rs_n192(float* d, const uint32_t* a, uint64_t db, int sd) {
  asm volatile("{\n.reg .pred p;\nsetp.ne.b32 p, %101, 0;\n"
    "wgmma.mma_async.sync.aligned.m64n192k16.f32.bf16.bf16 {%0, %1, %2, %3, %4, %5, %6, %7, %8, %9, %10, %11, %12, %13, %14, %15, %16, %17, %18, %19, %20, %21, %22, %23, %24, %25, %26, %27, %28, %29, %30, %31, %32, %33, %34, %35, %36, %37, %38, %39, %40, %41, %42, %43, %44, %45, %46, %47, %48, %49, %50, %51, %52, %53, %54, %55, %56, %57, %58, %59, %60, %61, %62, %63, %64, %65, %66, %67, %68, %69, %70, %71, %72, %73, %74, %75, %76, %77, %78, %79, %80, %81, %82, %83, %84, %85, %86, %87, %88, %89, %90, %91, %92, %93, %94, %95}, {%96, %97, %98, %99}, %100, p, 1, 1, %102;\n}"
    : "+f"(d[0]), "+f"(d[1]), "+f"(d[2]), "+f"(d[3]), "+f"(d[4]), "+f"(d[5]), "+f"(d[6]), "+f"(d[7]), "+f"(d[8]), "+f"(d[9]), "+f"(d[10]), "+f"(d[11]), "+f"(d[12]), "+f"(d[13]), "+f"(d[14]), "+f"(d[15]), "+f"(d[16]), "+f"(d[17]), "+f"(d[18]), "+f"(d[19]), "+f"(d[20]), "+f"(d[21]), "+f"(d[22]), "+f"(d[23]), "+f"(d[24]), "+f"(d[25]), "+f"(d[26]), "+f"(d[27]), "+f"(d[28]), "+f"(d[29]), "+f"(d[30]), "+f"(d[31]), "+f"(d[32]), "+f"(d[33]), "+f"(d[34]), "+f"(d[35]), "+f"(d[36]), "+f"(d[37]), "+f"(d[38]), "+f"(d[39]), "+f"(d[40]), "+f"(d[41]), "+f"(d[42]), "+f"(d[43]), "+f"(d[44]), "+f"(d[45]), "+f"(d[46]), "+f"(d[47]), "+f"(d[48]), "+f"(d[49]), "+f"(d[50]), "+f"(d[51]), "+f"(d[52]), "+f"(d[53]), "+f"(d[54]), "+f"(d[55]), "+f"(d[56]), "+f"(d[57]), "+f"(d[58]), "+f"(d[59]), "+f"(d[60]), "+f"(d[61]), "+f"(d[62]), "+f"(d[63]), "+f"(d[64]), "+f"(d[65]), "+f"(d[66]), "+f"(d[67]), "+f"(d[68]), "+f"(d[69]), "+f"(d[70]), "+f"(d[71]), "+f"(d[72]), "+f"(d[73]), "+f"(d[74]), "+f"(d[75]), "+f"(d[76]), "+f"(d[77]), "+f"(d[78]), "+f"(d[79]), "+f"(d[80]), "+f"(d[81]), "+f"(d[82]), "+f"(d[83]), "+f"(d[84]), "+f"(d[85]), "+f"(d[86]), "+f"(d[87]), "+f"(d[88]), "+f"(d[89]), "+f"(d[90]), "+f"(d[91]), "+f"(d[92]), "+f"(d[93]), "+f"(d[94]), "+f"(d[95])
    : "r"(a[0]), "r"(a[1]), "r"(a[2]), "r"(a[3]), "l"(db), "r"(sd), "n"(TB));
}

template<int TB> __device__ __forceinline__ void wgmma_rs_n32(float* d, const uint32_t* a, uint64_t db, int sd) {
  asm volatile("{\n.reg .pred p;\nsetp.ne.b32 p, %21, 0;\n"
    "wgmma.mma_async.sync.aligned.m64n32k16.f32.bf16.bf16 {%0, %1, %2, %3, %4, %5, %6, %7, %8, %9, %10, %11, %12, %13, %14, %15}, {%16, %17, %18, %19}, %20, p, 1, 1, %22;\n}"
    : "+f"(d[0]), "+f"(d[1]), "+f"(d[2]), "+f"(d[3]), "+f"(d[4]), "+f"(d[5]), "+f"(d[6]), "+f"(d[7]), "+f"(d[8]), "+f"(d[9]), "+f"(d[10]), "+f"(d[11]), "+f"(d[12]), "+f"(d[13]), "+f"(d[14]), "+f"(d[15])
    : "r"(a[0]), "r"(a[1]), "r"(a[2]), "r"(a[3]), "l"(db), "r"(sd), "n"(TB));
}

template<int TB> __device__ __forceinline__ void wgmma_rs_n64(float* d, const uint32_t* a, uint64_t db, int sd) {
  asm volatile("{\n.reg .pred p;\nsetp.ne.b32 p, %37, 0;\n"
    "wgmma.mma_async.sync.aligned.m64n64k16.f32.bf16.bf16 {%0, %1, %2, %3, %4, %5, %6, %7, %8, %9, %10, %11, %12, %13, %14, %15, %16, %17, %18, %19, %20, %21, %22, %23, %24, %25, %26, %27, %28, %29, %30, %31}, {%32, %33, %34, %35}, %36, p, 1, 1, %38;\n}"
    : "+f"(d[0]), "+f"(d[1]), "+f"(d[2]), "+f"(d[3]), "+f"(d[4]), "+f"(d[5]), "+f"(d[6]), "+f"(d[7]), "+f"(d[8]), "+f"(d[9]), "+f"(d[10]), "+f"(d[11]), "+f"(d[12]), "+f"(d[13]), "+f"(d[14]), "+f"(d[15]), "+f"(d[16]), "+f"(d[17]), "+f"(d[18]), "+f"(d[19]), "+f"(d[20]), "+f"(d[21]), "+f"(d[22]), "+f"(d[23]), "+f"(d[24]), "+f"(d[25]), "+f"(d[26]), "+f"(d[27]), "+f"(d[28]), "+f"(d[29]), "+f"(d[30]), "+f"(d[31])
    : "r"(a[0]), "r"(a[1]), "r"(a[2]), "r"(a[3]), "l"(db), "r"(sd), "n"(TB));
}

template<int TB> __device__ __forceinline__ void wgmma_rs_n96(float* d, const uint32_t* a, uint64_t db, int sd) {
  asm volatile("{\n.reg .pred p;\nsetp.ne.b32 p, %53, 0;\n"
    "wgmma.mma_async.sync.aligned.m64n96k16.f32.bf16.bf16 {%0, %1, %2, %3, %4, %5, %6, %7, %8, %9, %10, %11, %12, %13, %14, %15, %16, %17, %18, %19, %20, %21, %22, %23, %24, %25, %26, %27, %28, %29, %30, %31, %32, %33, %34, %35, %36, %37, %38, %39, %40, %41, %42, %43, %44, %45, %46, %47}, {%48, %49, %50, %51}, %52, p, 1, 1, %54;\n}"
    : "+f"(d[0]), "+f"(d[1]), "+f"(d[2]), "+f"(d[3]), "+f"(d[4]), "+f"(d[5]), "+f"(d[6]), "+f"(d[7]), "+f"(d[8]), "+f"(d[9]), "+f"(d[10]), "+f"(d[11]), "+f"(d[12]), "+f"(d[13]), "+f"(d[14]), "+f"(d[15]), "+f"(d[16]), "+f"(d[17]), "+f"(d[18]), "+f"(d[19]), "+f"(d[20]), "+f"(d[21]), "+f"(d[22]), "+f"(d[23]), "+f"(d[24]), "+f"(d[25]), "+f"(d[26]), "+f"(d[27]), "+f"(d[28]), "+f"(d[29]), "+f"(d[30]), "+f"(d[31]), "+f"(d[32]), "+f"(d[33]), "+f"(d[34]), "+f"(d[35]), "+f"(d[36]), "+f"(d[37]), "+f"(d[38]), "+f"(d[39]), "+f"(d[40]), "+f"(d[41]), "+f"(d[42]), "+f"(d[43]), "+f"(d[44]), "+f"(d[45]), "+f"(d[46]), "+f"(d[47])
    : "r"(a[0]), "r"(a[1]), "r"(a[2]), "r"(a[3]), "l"(db), "r"(sd), "n"(TB));
}

template<int TA, int TB> __device__ __forceinline__ void wgmma_ss_n192(float* d, uint64_t da, uint64_t db, int sd) {
  asm volatile("{\n.reg .pred p;\nsetp.ne.b32 p, %98, 0;\n"
    "wgmma.mma_async.sync.aligned.m64n192k16.f32.bf16.bf16 {%0, %1, %2, %3, %4, %5, %6, %7, %8, %9, %10, %11, %12, %13, %14, %15, %16, %17, %18, %19, %20, %21, %22, %23, %24, %25, %26, %27, %28, %29, %30, %31, %32, %33, %34, %35, %36, %37, %38, %39, %40, %41, %42, %43, %44, %45, %46, %47, %48, %49, %50, %51, %52, %53, %54, %55, %56, %57, %58, %59, %60, %61, %62, %63, %64, %65, %66, %67, %68, %69, %70, %71, %72, %73, %74, %75, %76, %77, %78, %79, %80, %81, %82, %83, %84, %85, %86, %87, %88, %89, %90, %91, %92, %93, %94, %95}, %96, %97, p, 1, 1, %99, %100;\n}"
    : "+f"(d[0]), "+f"(d[1]), "+f"(d[2]), "+f"(d[3]), "+f"(d[4]), "+f"(d[5]), "+f"(d[6]), "+f"(d[7]), "+f"(d[8]), "+f"(d[9]), "+f"(d[10]), "+f"(d[11]), "+f"(d[12]), "+f"(d[13]), "+f"(d[14]), "+f"(d[15]), "+f"(d[16]), "+f"(d[17]), "+f"(d[18]), "+f"(d[19]), "+f"(d[20]), "+f"(d[21]), "+f"(d[22]), "+f"(d[23]), "+f"(d[24]), "+f"(d[25]), "+f"(d[26]), "+f"(d[27]), "+f"(d[28]), "+f"(d[29]), "+f"(d[30]), "+f"(d[31]), "+f"(d[32]), "+f"(d[33]), "+f"(d[34]), "+f"(d[35]), "+f"(d[36]), "+f"(d[37]), "+f"(d[38]), "+f"(d[39]), "+f"(d[40]), "+f"(d[41]), "+f"(d[42]), "+f"(d[43]), "+f"(d[44]), "+f"(d[45]), "+f"(d[46]), "+f"(d[47]), "+f"(d[48]), "+f"(d[49]), "+f"(d[50]), "+f"(d[51]), "+f"(d[52]), "+f"(d[53]), "+f"(d[54]), "+f"(d[55]), "+f"(d[56]), "+f"(d[57]), "+f"(d[58]), "+f"(d[59]), "+f"(d[60]), "+f"(d[61]), "+f"(d[62]), "+f"(d[63]), "+f"(d[64]), "+f"(d[65]), "+f"(d[66]), "+f"(d[67]), "+f"(d[68]), "+f"(d[69]), "+f"(d[70]), "+f"(d[71]), "+f"(d[72]), "+f"(d[73]), "+f"(d[74]), "+f"(d[75]), "+f"(d[76]), "+f"(d[77]), "+f"(d[78]), "+f"(d[79]), "+f"(d[80]), "+f"(d[81]), "+f"(d[82]), "+f"(d[83]), "+f"(d[84]), "+f"(d[85]), "+f"(d[86]), "+f"(d[87]), "+f"(d[88]), "+f"(d[89]), "+f"(d[90]), "+f"(d[91]), "+f"(d[92]), "+f"(d[93]), "+f"(d[94]), "+f"(d[95])
    : "l"(da), "l"(db), "r"(sd), "n"(TA), "n"(TB));
}

template<int TA, int TB> __device__ __forceinline__ void wgmma_ss_n8(float* d, uint64_t da, uint64_t db, int sd) {
  asm volatile("{\n.reg .pred p;\nsetp.ne.b32 p, %6, 0;\n"
    "wgmma.mma_async.sync.aligned.m64n8k16.f32.bf16.bf16 {%0, %1, %2, %3}, %4, %5, p, 1, 1, %7, %8;\n}"
    : "+f"(d[0]), "+f"(d[1]), "+f"(d[2]), "+f"(d[3])
    : "l"(da), "l"(db), "r"(sd), "n"(TA), "n"(TB));
}

constexpr int S_ = 2048, D_ = 640, F_ = 1536;

struct Scr {
  uint32_t flag[32 * 8];
  uint32_t mv[2 * 2048];
  bf16 cimg[8 * 6 * 512];
  uint2 st2[S_];
  bf16 kvT[D_ * S_];
  bf16 zT[D_ * S_];
  bf16 AT[D_ * S_];
};
__device__ __align__(1024) Scr g_scr;
__device__ __forceinline__ uint32_t clk() { uint32_t c; asm volatile("mov.u32 %0, %%clock;" : "=r"(c) :: "memory"); return c; }
#define DEVSM 0
#define STAMP(id)
#define STAMPIF(c, id)
#define ITW 0
#define P3 0
constexpr int FL_X = 5, FL_C = 128;
#define CD 600
#define SD 1000

constexpr int SM_X = 1024, SM_EXT = 21504, SM_SMALL = 29696, SM_STAT = 30720, SM_CB = 32768, SM_RING = 34816, SM_TOTAL = SM_RING + 6 * 32768;
constexpr int SMALL_LN = 224, SMALL_RED = 320, SMALL_DUMMY = 1008, SMALL_E = 1012, SMALL_TS = 160, SMALL_H = 864;
constexpr int JOB_SZ = 10880, JOB_V = 5760, R_X = 5 * 32768, R_BOX = R_X + 12288;
constexpr int K1OFF = 4672, KSZ = 9472, CSZ = KSZ + 4224;
enum { B_KJ = 0, B_X = 5, B_EXT = 7, B_X1 = 8, B_P0 = 9, B_FB = 10, B_PEER = 20, B_RECV = 24, B_U = 28, B_A = 30, B_E0 = 35, B_FS = 37, B_BOX = 38, B_F = 44, B_ST0 = 45, B_GB = 46,
       B_F1 = 48, B_E1 = 54, B_EB = 60,
       B_OS = 64, B_OF = 72, B_Z = 80, B_K = 85, B_EW = 88, B_ST2 = 94, B_XF = 95, B_KV4 = 96, B_KVS = 98, B_BD = 99,
       B_B = 106, B_S = 112 };
__device__ __forceinline__ uint32_t chan_base(uint32_t sb, int ch) { return sb + SM_RING + (2 + (ch >> 1)) * 32768 + (ch & 1) * CSZ; }

struct Params { CUtensorMap mS, mX, mWm, mK, mV, mG, mU, mD; };

__device__ __forceinline__ void flag_add(Scr* G, int id) { asm volatile("red.relaxed.gpu.global.add.u32 [%0], 1;" ::"l"(G->flag + id) : "memory"); }
__device__ __forceinline__ uint32_t rdback(const void* p) { uint32_t v; asm volatile("ld.relaxed.gpu.global.u32 %0, [%1];" : "=r"(v) : "l"(p) : "memory"); return v; }
__device__ __forceinline__ void st_tag(uint2* p, uint32_t v, uint32_t t) { asm volatile("st.relaxed.gpu.global.v2.u32 [%0], {%1, %2};" ::"l"(p), "r"(v), "r"(t) : "memory"); }
__device__ __forceinline__ void spin(uint32_t t, uint32_t d) { if (d) while (clk() - t < d); }
__device__ __forceinline__ uint2 ld_tag(const uint2* p) { uint2 v; asm volatile("ld.relaxed.gpu.global.v2.u32 {%0, %1}, [%2];" : "=r"(v.x), "=r"(v.y) : "l"(p) : "memory"); return v; }
__device__ __forceinline__ uint4 ld_tag2(const uint2* p) {
  uint4 v;
  asm volatile("ld.relaxed.gpu.global.v4.u32 {%0, %1, %2, %3}, [%4];" : "=r"(v.x), "=r"(v.y), "=r"(v.z), "=r"(v.w) : "l"(p) : "memory");
  return v;
}
__device__ __forceinline__ void stg128(void* p, uint4 v) { asm volatile("st.global.v4.b32 [%0], {%1, %2, %3, %4};" ::"l"(p), "r"(v.x), "r"(v.y), "r"(v.z), "r"(v.w) : "memory"); }
__device__ __forceinline__ uint32_t ldv32(uint32_t a) { uint32_t v; asm volatile("ld.volatile.shared.b32 %0, [%1];" : "=r"(v) : "r"(a) : "memory"); return v; }
__device__ __forceinline__ uint4 ldv128(uint32_t a) { uint4 v; asm volatile("ld.volatile.shared.v4.b32 {%0,%1,%2,%3}, [%4];" : "=r"(v.x), "=r"(v.y), "=r"(v.z), "=r"(v.w) : "r"(a) : "memory"); return v; }
__device__ __forceinline__ bool mbar_test(uint32_t bar, int parity) {
  uint32_t ok;
  asm volatile("{\n.reg .pred P;\nmbarrier.test_wait.parity.shared::cta.b64 P, [%1], %2;\nselp.u32 %0, 1, 0, P;\n}" : "=r"(ok) : "r"(bar), "r"(parity) : "memory");
  return ok;
}
__device__ __forceinline__ uint32_t epoch(uint32_t sb) { return lds32(sb + SM_SMALL + SMALL_E); }
__device__ __forceinline__ void rdwait(uint32_t sb, uint32_t v) { sts32(sb + SM_SMALL + SMALL_DUMMY, v); }
__device__ __forceinline__ void fence_async_s() { asm volatile("fence.proxy.async.shared::cta;" ::: "memory"); }
__device__ __forceinline__ void fence_async_g() { asm volatile("fence.proxy.async.global;" ::: "memory"); }
__device__ __forceinline__ void bulk_done() { asm volatile("cp.async.bulk.commit_group;\n\tcp.async.bulk.wait_group 0;" ::: "memory"); }
__device__ __forceinline__ void flag_wait(Scr* G, int id, uint32_t target) {
  const uint32_t* p = G->flag + id;
#pragma unroll 1
  for (int i = 0; i < (1 << 20); i++) {
    uint32_t v;
    asm volatile("ld.relaxed.gpu.global.u32 %0, [%1];" : "=r"(v) : "l"(p) : "memory");
    if ((int)(v - target) >= 0) return;
  }
  __trap();
}
__device__ __forceinline__ void hint_wait(Scr* G, uint32_t sa, int id, uint32_t target) {
#pragma unroll 1
  for (int i = 0; i < (1 << 20); i++) {
    const uint32_t t = clk();
    cp16(sa + 4 * (id & 4), G->flag + (id & ~3));
    spin(t, P3);
    if ((int)(lds32(sa + 4 * (id & 7)) - target) >= 0) return;
  }
  __trap();
}
__device__ __forceinline__ int tbase(int pb) { return 127 - (32 * (pb >> 6) + 8 * (pb & 8) + 4 * ((2 * (pb & 3) - ((pb >> 2) & 1)) & 7) + ((pb >> 4) & 3)); }
__device__ __forceinline__ uint32_t hmul(uint32_t a, uint32_t b) { uint32_t d; asm("mul.rn.bf16x2 %0, %1, %2;" : "=r"(d) : "r"(a), "r"(b)); return d; }
__device__ __forceinline__ uint32_t hadd(uint32_t a, uint32_t b) { uint32_t d; asm("add.rn.bf16x2 %0, %1, %2;" : "=r"(d) : "r"(a), "r"(b)); return d; }
__device__ __forceinline__ uint32_t hsub(uint32_t a, uint32_t b) { uint32_t d; asm("sub.rn.bf16x2 %0, %1, %2;" : "=r"(d) : "r"(a), "r"(b)); return d; }
__device__ __forceinline__ uint32_t hfma(uint32_t a, uint32_t b, uint32_t c) { uint32_t d; asm("fma.rn.bf16x2 %0, %1, %2, %3;" : "=r"(d) : "r"(a), "r"(b), "r"(c)); return d; }
__device__ __forceinline__ uint32_t pack2(float lo, float hi) { uint32_t d; asm("cvt.rn.bf16x2.f32 %0, %1, %2;" : "=r"(d) : "f"(hi), "f"(lo)); return d; }
__device__ __forceinline__ float blo(uint32_t v) { return __uint_as_float(v << 16); }
__device__ __forceinline__ float bhi(uint32_t v) { return __uint_as_float(v & 0xffff0000u); }
__device__ __forceinline__ uint32_t tagged(uint32_t v, uint32_t e1) { return (v & ~1u) | (e1 & 1); }
__device__ __forceinline__ float rbf(float v) { return blo(pack2(v, 0.f)); }
__device__ __forceinline__ float sdev(float var) { float d; asm("sqrt.approx.ftz.f32 %0, %1;" : "=f"(d) : "f"(rbf(rbf(var) + 1e-5f))); return rbf(d); }
template <int N> __device__ __forceinline__ void bfly(float* v, int mask, bool up) {
#pragma unroll
  for (int i = 0; i < N / 2; i++) {
    float send = up ? v[i] : v[i + N / 2], keep = up ? v[i + N / 2] : v[i];
    v[i] = keep + __shfl_xor_sync(0xffffffffu, send, mask);
  }
}
#define BX3 2
#define XO 0
#define ZA 0
#define XE 0
#define EA 1
#define AD 300
#define XP 0
#define DR 0
#define KVV 0
#define OPQ 4
#define SL 1
#define UT 5
#define UD0 1000
#define EH 1
#define NA 16
#define BS 0
#define UF 1
#define ZS 1
#define LV 5
#define TG 2
#define RL 2
#define OF 1
#define OH 16
#define ES 2
#define SI 1
#define RH 5
#define NS 0
#define AT0 14200
#define AT1 0
#define BI 4
#define PC 1
#define PG 1
#define UD2 5000
#define GT 0x111
#define RX 0
#define MG 0
__device__ __forceinline__ bool mod_first(int b) { return MG ? (b & 3) != 3 : !(b & 1) || !(b & 6); }
__device__ __forceinline__ int mod_grp(int b, int j) {
  if (MG) {
  const int m = b >> 3, s = b & 7, t = 16 * (j ? min(s, 6) : s - (s >> 2)) + m, v = j ? s : (t * 43) >> 10;
  if (j == 2) return b + 112;
  return v < 4 ? (v == 3 ? 160 : 40 * v) + (j ? 24 + m : t - 24 * v) : t + (t < 104 ? 56 : 96);
  }
  const int m = b >> 3, s = b & 7, t = 16 * s + m, v = j ? (t * 43) >> 10 : s >> 1;
  if (j == 2) return b + 112;
  if (j == 0 && s == 1) return m + (m < 8 ? 152 : 192);
  return v < 4 ? (v == 3 ? 160 : 40 * v) + (j ? 16 + t - 24 * v : m) : t + 24;
}

__device__ __forceinline__ void kv_load(const bf16* gk, const bf16* gv, const bf16* gs, uint32_t sb, int b, int r, int tid) {
  const int row = tid >> 2, col = 128 * r + 32 * (b & 3);
  const uint32_t a = sb + SM_RING + r * JOB_SZ + (row >> 3) * 80 + (tid & 3) * 16, ak = a + (row & 7) * 720, av = a + (row & 7) * 640 + JOB_V;
  const int o = (64 * (b >> 2) + row) * D_ + col + 8 * (tid & 3);
  cp16(ak + 80, gk + o);
  cp16(ak + 400, gk + o + 32 * D_);
  cp16(av, gv + o);
  cp16(av + 320, gv + o + 32 * D_);
  if (tid < 12) cp16z(ak + 3600, gk + (b < 4 ? o : o - 3 * D_), b < 4 ? 0 : 16);
  else if (tid >= 112) cp16(sb + SM_CB + 256 * r + 16 * (tid - 112), gs + 4 * col + 8 * (tid - 112));
}
__device__ __forceinline__ void load_kv(const Params& P, const bf16* gs, uint32_t sb, int b, int r) {
  const uint32_t a = sb + SM_RING + r * JOB_SZ, bar = sb + 8 * (B_B + r);
  const int cg = 4 * r + (b & 3);
  mbar_expect(bar, JOB_SZ + 256);
  tma4d(a, &P.mK, 0, cg, 8 * (b >> 2) - 1, 0, bar);
  tma4d(a + JOB_V, &P.mV, 0, cg, 8 * (b >> 2), 0, bar);
  bulk_g2s(sb + SM_CB + 256 * r, gs + 128 * cg, 256, bar);
}
__device__ __forceinline__ uint4* kv_dst(Scr* G, int b, int r, int tid) {
  return (uint4*)(G->kvT + (128 * r + 32 * (b & 3) + 8 * (tid >> 5) + 2 * (tid & 3)) * S_ + 2040 - 64 * (b >> 2)) - ((tid >> 2) & 7);
}
__device__ __forceinline__ void kv_job(Scr* G, uint32_t sb, int b, int r, int tid, uint32_t e1) {
  const int cp = 4 * (tid >> 5) + (tid & 3);
  const uint32_t ka = sb + SM_RING + r * JOB_SZ + ((tid >> 2) & 7) * 80 + cp * 4;
  mbar_wait(sb + 8 * (B_B + r), 0);
  STAMPIF(tid == 0, 56 + r);
  uint32_t kk[11], vv[8], o[8];
  if (KVV) {
#pragma unroll
    for (int i = 0; i < 11; i++) kk[i] = ldv32(ka + 720 * ((i + 5) & 7) + 80 * ((i + 5) >> 3));
#pragma unroll
    for (int i = 0; i < 8; i++) vv[i] = ldv32(ka + JOB_V + 640 * i);
  }
  const uint4 sk = ldv128(sb + SM_CB + 256 * r + 16 * cp);
  const uint32_t s0 = __byte_perm(sk.x, sk.z, 0x5410), s1 = __byte_perm(sk.x, sk.z, 0x7632), s2 = __byte_perm(sk.y, sk.w, 0x5410), s3 = __byte_perm(sk.y, sk.w, 0x7632);
#pragma unroll
  for (int i = 0; i < 11; i++) if (!KVV) kk[i] = lds32(ka + 720 * ((i + 5) & 7) + 80 * ((i + 5) >> 3));
#pragma unroll
  for (int i = 0; i < 8; i++) {
    uint32_t v = KVV ? vv[i] : lds32(ka + JOB_V + 640 * i);
    o[i] = hmul(hfma(kk[i + 3], s0, hfma(kk[i + 2], s1, hfma(kk[i + 1], s2, hmul(kk[i], s3)))), v);
  }
  uint4* dst = kv_dst(G, b, r, tid);
  dst[0] = make_uint4(__byte_perm(o[7], o[6], 0x5410), __byte_perm(o[5], o[4], 0x5410), __byte_perm(o[3], o[2], 0x5410), tagged(__byte_perm(o[1], o[0], 0x5410), e1));
  dst[256] = make_uint4(__byte_perm(o[7], o[6], 0x7632), __byte_perm(o[5], o[4], 0x7632), __byte_perm(o[3], o[2], 0x7632), tagged(__byte_perm(o[1], o[0], 0x7632), e1));
  if (tid == 0) { sts32(sb + SM_SMALL + SMALL_TS + 4 * r, clk()); mbar_arrive(sb + 8 * (B_KJ + r)); }
}
__device__ __forceinline__ void u_wait(uint4& a, uint4& c, const void* p) {
  asm volatile("{\n.reg .pred p;\n.reg .b32 t, n;\nmov.b32 n, 0;\n"
               "L0:\nlop3.b32 t, %3, %7, 1, 0x80;\nsetp.eq.b32 p, t, 0;\nvote.sync.any.pred p, p, 0xffffffff;\n@!p bra.uni L1;\n"
               "ld.relaxed.gpu.global.v4.u32 {%0, %1, %2, %3}, [%8];\nld.relaxed.gpu.global.v4.u32 {%4, %5, %6, %7}, [%8+2048];\n"
               "add.u32 n, n, 1;\nsetp.lt.u32 p, n, 1000000;\n@p bra.uni L0;\ntrap;\nL1:\n}"
               : "+r"(a.x), "+r"(a.y), "+r"(a.z), "+r"(a.w), "+r"(c.x), "+r"(c.y), "+r"(c.z), "+r"(c.w) : "l"(p) : "memory");
}
__device__ __forceinline__ void u_fix(uint4 a, uint4 c, const void* p, uint32_t sa, uint32_t e1) {
  asm volatile("{\n.reg .pred p;\n.reg .b32 t, n;\nmov.b32 n, 0;\n"
               "lop3.b32 t, %3, %7, %10, 0x81;\nand.b32 t, t, 1;\nsetp.eq.b32 p, t, 0;\nvote.sync.any.pred p, p, 0xffffffff;\n@!p bra.uni L2;\n"
               "L0:\nld.relaxed.gpu.global.v4.u32 {%0, %1, %2, %3}, [%8];\nld.relaxed.gpu.global.v4.u32 {%4, %5, %6, %7}, [%8+2048];\n"
               "lop3.b32 t, %3, %7, %10, 0x81;\nand.b32 t, t, 1;\nsetp.eq.b32 p, t, 0;\nvote.sync.any.pred p, p, 0xffffffff;\n@!p bra.uni L1;\n"
               "add.u32 n, n, 1;\nsetp.lt.u32 p, n, 1000000;\n@p bra.uni L0;\ntrap;\n"
               "L1:\nst.shared.v4.b32 [%9], {%0, %1, %2, %3};\nst.shared.v4.b32 [%9+2048], {%4, %5, %6, %7};\nL2:\n}"
               : "+r"(a.x), "+r"(a.y), "+r"(a.z), "+r"(a.w), "+r"(c.x), "+r"(c.y), "+r"(c.z), "+r"(c.w) : "l"(p), "r"(sa), "r"(e1) : "memory");
}
__device__ __forceinline__ void stv128(uint32_t a, uint4 v) { asm volatile("st.volatile.shared.v4.b32 [%0], {%1,%2,%3,%4};" ::"r"(a), "r"(v.x), "r"(v.y), "r"(v.z), "r"(v.w) : "memory"); }
__device__ __forceinline__ uint64_t box_a(uint32_t sb) { return mkdesc(sb + SM_RING + R_BOX, 256, 1024, 3); }
__device__ __forceinline__ uint64_t box_b(uint32_t sb) { return mkdesc(sb + SM_STAT, 64, 128, 0); }
__device__ __forceinline__ void mod_put(Scr* G, uint32_t sb, const float* a, int b, int j, uint32_t e1, int tid) {
  const uint32_t red = sb + SM_STAT + 1536;
  if ((tid & 3) == tid >> 6) sts64(red + 32 * ((tid >> 2) & 7) + 8 * (tid >> 5), __float_as_uint((tid & 32) ? a[1] : a[0]), __float_as_uint((tid & 32) ? a[3] : a[2]));
  bar_sync(j > (BX3 >= 3) ? 4 : 5, 128);
  if (tid < 16) {
    const uint4 u = lds128(red + 32 * (tid & 7)), v = lds128(red + 32 * (tid & 7) + 16);
    asm volatile("" : "+r"(b));
    const int grp = mod_grp(b, j);
    const uint32_t one = (grp >= 40 && grp < 80) || (grp >= 160 && grp < 200) ? 0x3f803f80u : 0u;
    const float lo = __uint_as_float(u.x) + __uint_as_float(u.z) + __uint_as_float(v.x) + __uint_as_float(v.z);
    const float hi = __uint_as_float(u.y) + __uint_as_float(u.w) + __uint_as_float(v.y) + __uint_as_float(v.w);
    asm volatile("st.relaxed.gpu.global.u32 [%0], %1;" ::"l"(G->mv + 8 * grp + 256 * (tid & 8) + (tid & 7)),
                 "r"(((tid >> 3) ^ e1) & 1 ? 0 : ~hadd(pack2(lo, hi), one)) : "memory");
  }
}
__device__ __forceinline__ void mod_box(Scr* G, uint32_t sb, int b, int j, uint32_t e1, int tid) {
  float a[4];
  uint64_t da = box_a(sb), db = box_b(sb);
#pragma unroll
  for (int h = 0; h < 2; h++) {
    mbar_wait(sb + 8 * (B_BOX + 2 * j + h), 0);
    STAMPIF(tid == 0 && j == 0, 71 + h);
    wg_fence();
#pragma unroll
    for (int n = 5 * h; n < 5 * h + 5; n++) wgmma_ss_n8<1, 0>(a, da + 128 * n, db + 8 * n, n != 0);
    wg_commit();
  }
  wg_wait<0>();
#pragma unroll
  for (int i = 0; i < 4; i++) asm volatile("" : "+f"(a[i])::"memory");
  mod_put(G, sb, a, b, j, e1, tid);
}
__device__ __forceinline__ void a_check(uint32_t sa, const void* ga, uint32_t tag) {
  asm volatile("{\n.reg .pred p;\n.reg .b32 t, n, x, y, z;\n.reg .b64 g;\n"
               "ld.shared.b32 t, [%0];\nlop3.b32 t, t, %2, 1, 0x28;\nsetp.ne.b32 p, t, 0;\nvote.sync.any.pred p, p, 0xffffffff;\n@!p bra.uni L1;\nmov.b32 n, 0;\n"
               "L0:\nld.relaxed.gpu.global.b32 t, [%1];\nlop3.b32 t, t, %2, 1, 0x28;\nsetp.ne.b32 p, t, 0;\nvote.sync.any.pred p, p, 0xffffffff;\n@!p bra.uni L2;\n"
               "add.u32 n, n, 1;\nsetp.lt.u32 p, n, 1000000;\n@p bra.uni L0;\ntrap;\nL2:\n"
               "and.b64 g, %1, -32;\nand.b32 n, %0, -32;\n"
               "ld.relaxed.gpu.global.v4.b32 {t, x, y, z}, [g];\nst.shared.v4.b32 [n], {t, x, y, z};\n"
               "ld.relaxed.gpu.global.v4.b32 {t, x, y, z}, [g+16];\nst.shared.v4.b32 [n+16], {t, x, y, z};\n"
               "fence.proxy.async.shared::cta;\nbar.warp.sync 0xffffffff;\nL1:\n}" ::"r"(sa), "l"(ga), "r"(tag) : "memory");
}
__device__ __forceinline__ void z_wait(uint4& a, uint4& c, uint32_t* v, const void* G, uint32_t zo, uint32_t co, uint32_t e1) {
  asm volatile("{\n.reg .pred p;\n.reg .b32 t, n;\n.reg .b64 x, y;\nmov.b32 n, 0;\n"
               "L0:\nlop3.b32 t, %3, %7, %14, 0x81;\nand.b32 t, t, 1;\nmin.u32 t, t, %8;\nmin.u32 t, t, %9;\nmin.u32 t, t, %10;\nmin.u32 t, t, %11;\n"
               "setp.eq.b32 p, t, 0;\nvote.sync.any.pred p, p, 0xffffffff;\n@!p bra.uni L1;\n"
               "shr.u32 t, n, 31;\nadd.u32 t, t, %12;\ncvt.u64.u32 x, t;\nadd.s64 x, x, %15;\nshr.u32 t, n, 30;\nadd.u32 t, t, %13;\ncvt.u64.u32 y, t;\nadd.s64 y, y, %15;\n"
               "ld.relaxed.gpu.global.v4.u32 {%0, %1, %2, %3}, [x];\nld.relaxed.gpu.global.v4.u32 {%4, %5, %6, %7}, [x+32768];\n"
               "ld.relaxed.gpu.global.u32 %8, [y];\nld.relaxed.gpu.global.u32 %9, [y+1280];\nld.relaxed.gpu.global.u32 %10, [y+2560];\nld.relaxed.gpu.global.u32 %11, [y+5120];\n"
               "add.u32 n, n, 1;\nsetp.lt.u32 p, n, 1000000;\n@p bra.uni L0;\ntrap;\nL1:\n}"
               : "+r"(a.x), "+r"(a.y), "+r"(a.z), "+r"(a.w), "+r"(c.x), "+r"(c.y), "+r"(c.z), "+r"(c.w), "+r"(v[0]), "+r"(v[1]), "+r"(v[2]), "+r"(v[3])
               : "r"(zo), "r"(co), "r"(e1), "l"(G) : "memory");
}
__device__ __forceinline__ void load_x(const Params& P, uint32_t sb, int b, int h) {
  const uint32_t bar = sb + 8 * (B_X + h);
  mbar_expect(bar, 10240);
  tma5d(sb + SM_X + h * 10240, &P.mX, 0, 0, 0, 5 * h, tbase(b), bar);
}
__device__ __forceinline__ uint32_t x_addr(uint32_t sb, int w, int lane) {
  const int rho = 15 - (4 * (lane >> 3) + 2 * (lane & 1) + ((lane >> 1) & 1));
  return sb + SM_X + (w >> 1) * 2048 + rho * 128 + (((2 * (w & 1) + (lane & 4)) ^ (rho & 7)) << 4);
}
__device__ __forceinline__ void ln1_half(uint32_t sb, int tid, int h, int dry, float& s1, float& s2, float& pv) {
  const uint32_t xr = sb + SM_X + 16 * tid;
  float s3 = 0.f;
  if (ITW == 8) STAMPIF(tid == 0, 102 + 2 * h);
  if (!dry) mbar_wait(sb + 8 * (B_X + h), 0);
  STAMPIF(tid == 0, 25);
  if (ITW == 8) STAMPIF(tid == 0, 103 + 2 * h);
  uint4 v[5];
#pragma unroll
  for (int n = 0; n < 5; n++) v[n] = n < LV ? ldv128(xr + 10240 * h + 2048 * n) : lds128(xr + 10240 * h + 2048 * n);
  pv = blo(ldv32(xr & ~127u));
#pragma unroll
  for (int n = 0; n < 5; n++) {
    const uint32_t u[4] = {v[n].x, v[n].y, v[n].z, v[n].w};
#pragma unroll
    for (int j = 0; j < 4; j++) {
      const float a = blo(u[j]) - pv, c = bhi(u[j]) - pv;
      s1 += a + c; s2 += a * a; s3 += c * c;
    }
  }
  s2 += s3;
}
__device__ __forceinline__ void ln1_end(uint32_t sb, int tid, float s1, float s2, float pv) {
#pragma unroll
  for (int o = 1; o < 8; o <<= 1) { s1 += __shfl_xor_sync(0xffffffffu, s1, o); s2 += __shfl_xor_sync(0xffffffffu, s2, o); }
  if (ITW == 8) { asm volatile("" : "+f"(s1), "+f"(s2)); STAMPIF(tid == 0, 107); }
  const float mu = s1 * (1.f / D_), var = fmaxf(s2 * (1.f / D_) - mu * mu, 0.f);
  float rs;
  asm("rcp.approx.ftz.f32 %0, %1;" : "=f"(rs) : "f"(sdev(var)));
  const int i = 15 - (tid >> 3), j = tid & 7;
  if (j < 2) sts16(sb + SM_SMALL + SMALL_LN + 32 * j + 16 * (i & 1) + (i & 14), pack2(j ? rs : pv + mu, 0.f));
  if (ITW == 8) STAMPIF(tid == 0, 108);
  bar_sync(5, 128);
  STAMPIF(tid == 0, 75);
}
__device__ __forceinline__ void load_box(const Params& P, uint32_t sb, int b, int cls) {
  const uint32_t bar = sb + 8 * (B_BOX + cls);
  mbar_expect(bar, 10240);
  tma3d(sb + SM_RING + R_BOX + 10240 * (cls & 1), &P.mWm, 16 * mod_grp(b, cls >> 1), 0, 5 * (cls & 1), bar);
}
__device__ __forceinline__ void load_ssm(const Params& P, uint32_t sb, int b, int r) {
  const uint32_t bar = sb + 8 * (B_S + r);
  mbar_expect(bar, 16 * 288);
  tma3d(chan_base(sb, r) + 128, &P.mS, 0, 0, 128 * r + b, bar);
}
__device__ __forceinline__ void k1_job(uint32_t sb, int r, int tid, uint32_t dv) {
  const uint32_t a0 = chan_base(sb, r) + 128 + 16 * tid + 32 * (tid >> 4);
  mbar_wait(sb + 8 * (B_S + r), 0);
  uint4 v[2];
  uint32_t pv[2];
#pragma unroll
  for (int n = 0; n < 2; n++) { v[n] = lds128(a0 + 2304 * n); pv[n] = lds32(a0 + 2304 * n - ((tid & 15) ? 4 : 36)); }
  if (tid == 0) { v[0].x = hadd(v[0].x, dv); sts32(a0, v[0].x); }
#pragma unroll
  for (int n = 0; n < 2; n++)
    sts128(a0 + 2304 * n + K1OFF, make_uint4(__byte_perm(pv[n], v[n].x, 0x5432), __byte_perm(v[n].x, v[n].y, 0x5432), __byte_perm(v[n].y, v[n].z, 0x5432), __byte_perm(v[n].z, v[n].w, 0x5432)));
}

__device__ __forceinline__ int out_blk(int s, int p) { const int t = p + (s >> 1); return t < 5 ? t : t - 5; }
__device__ __forceinline__ void l2_prefetch(const void* p, int bytes) { asm volatile("cp.async.bulk.prefetch.L2.global [%0], %1;" ::"l"(p), "r"(bytes) : "memory"); }
__device__ __forceinline__ void pf_line(const void* p) { asm volatile("prefetch.global.L2 [%0];" ::"l"(p) : "memory"); }
__device__ __forceinline__ int role(int bx) {
  const int c = bx >> 1, d = c - 36, q = (d * 37) >> 8, k = d - 7 * q;
  const int rank = c < 4 ? 12 + c : c < 36 ? ((c - 4) & 7) * 8 + ((c - 4) >> 3) : (k ? k + 1 : 0) * 8 + 4 + q;
  return 8 * (rank & 15) + 2 * (rank >> 4) + (bx & 1);
}
enum { K_KV, K_SSM, K_BOX, K_PW, K_PD, K_PKV, K_PSSM, K_PBOX, K_W, K_X, K_ST, K_END = 15 };
#define E(t, bar, kind, r) ((t) << 16 | (bar) << 8 | (kind) << 4 | (r))
#define SCHED E(2800, 255, K_BOX, 0), E(0, 255, K_BOX, 1), E(3700, 255, K_KV, 2), E(4400, 255, K_SSM, 2), E(4800, 255, XO ? K_X : K_KV, XO ? 0 : 3), E(5500, 255, XO ? K_KV : K_X, XO ? 3 : 0), \
              E(6400, 255, XP ? K_X : K_KV, XP ? 1 : 4), E(7100, 255, XP ? K_KV : K_X, XP ? 4 : 1), E(7900, 255, K_SSM, 3), E(8300, 255, K_SSM, 4), E(8600, 255, K_BOX, 2), E(9500, 255, K_PW, 0), \
              E(10100, 255, K_BOX, 3)
#define XPF 2
#define XBOTH 0
#define XI 8
#define XW 0
#define PWM 0x3c
#define STM 0x7c0
#define PDM 0x3800
#define KV4C 3
#define CVT 1
#define UPOS 4
#define UD 1000
#define UD1 6400
#define NP 6
#define NQ 6
#define SPOS(i) (2 * ((i) - NQ) + 13)
#define LH0 4
#define LH1 5
#define LM 0
#define PT 1
#define ZP 0
#define BD 1200
#define ER 0
#define PL 1
#define K1N 1
#define ZD 10100
#define PK 0
#define ZF 1
constexpr uint32_t kSched[] = {SCHED, E(0, 255, K_END, 0)};
struct In { const bf16 *k, *v, *sk, *Wg, *Wu, *Wd, *ss; };
__device__ __forceinline__ void load_w(const Params& P, uint32_t sb, int s, int it) {
  const int st = it % 5;
  mbar_wait(sb + 8 * (B_E1 + st), (it / 5) & 1);
  const uint32_t a = sb + SM_RING + st * 32768 + 8192, fb = sb + 8 * (B_F1 + st);
  mbar_expect(fb, 24576);
#pragma unroll
  for (int j = 0; j < 3; j++) {
    tma2d(a + 8192 * j, &P.mG, 192 * s + 64 * j, 32 * it, fb);
    tma2d(a + 8192 * j + 4096, &P.mU, 192 * s + 64 * j, 32 * it, fb);
  }
}

template <int I> __device__ __forceinline__ int sched_run(const Params& P, const In& in, uint32_t sb, int b, int lane, uint32_t t_0) {
  constexpr uint32_t e = kSched[I];
  constexpr int kind = (e >> 4) & 15, r = e & 15, bar = (e >> 8) & 255;
  if constexpr (kind == K_END) return 0;
  else {
    if constexpr ((e >> 16) != 0) while (clk() - t_0 < (e >> 16));
    if (bar != 255) mbar_wait(sb + 8 * bar, 0);
    if (kind == K_BOX && r == 2) mbar_wait(sb + 8 * B_BD, 0);
    if (kind == K_PKV) {
      const bf16* kvp = (lane < 16 ? in.k : in.v) + (16 * b + (lane & 15)) * D_ + 128 * r;
      pf_line(kvp); pf_line(kvp + 64);
    } else {
      if (elect()) {
        if (kind == K_KV) load_kv(P, in.sk, sb, b, r);
        if (kind == K_X) load_x(P, sb, b, r);
        if (kind == K_SSM) load_ssm(P, sb, b, r);
        if (kind == K_BOX && (r > 1 || mod_first(b))) load_box(P, sb, b, r);
        if (kind == K_PW) { l2_prefetch(in.Wg + (128 * r + b) * F_, 2 * F_); l2_prefetch(in.Wu + (128 * r + b) * F_, 2 * F_); }
        if (kind == K_PSSM) l2_prefetch(in.ss + (128 * r + b) * S_, 4096);
      }
      __syncwarp();
    }
    return sched_run<I + 1>(P, in, sb, b, lane, t_0) + (kind == K_PW);
  }
}

__global__ void __launch_bounds__(512, 1) fused_kernel(const bf16* __restrict__ gk, const bf16* __restrict__ gv, const bf16* __restrict__ gsk,
                                                       const bf16* __restrict__ gD, const bf16* __restrict__ gc, Scr* G, const bf16* gWg, const bf16* gWu,
                                                       const bf16* gWd, bf16* gout, const bf16* gss, const __grid_constant__ Params P) {
  extern __shared__ __align__(1024) char smem_raw[];
  const uint32_t sb = smem_u32(smem_raw), ring = sb + SM_RING;
  const int b = role(blockIdx.x), m = b >> 3, s = b & 7;
  const uint32_t t_0 = clk();
  const int wg = __shfl_sync(0xffffffffu, threadIdx.x >> 7, 0);
  const int tid = threadIdx.x & 127, lane = tid & 31;
  const int w = __shfl_sync(0xffffffffu, tid >> 5, 0);
  uint32_t e1 = 0;
  if (wg < 2) {
    kv_load(gk, gv, gsk, sb, b, wg, tid);
    if (TG == 1) e1 = rdback(G->flag + 8 * m + 4);
  } else {
    if (wg == 2) {
      if (tid < 40) {
        int c = tid & 7;
        sts128(chan_base(sb, tid >> 3) + (c < 2 ? 80 + c * K1OFF : KSZ + 4096 + (c - 2) * 16), make_uint4(0, 0, 0, 0));
      }
    }
    if (elect()) {
      const int j = 4 * (3 - wg) + w - 1;
      if (j < 4) asm volatile("prefetch.tensormap [%0];" ::"l"(&P.mX + j) : "memory");
      if (j < 0) {
#pragma unroll
        for (int i = 0; i < 5; i++) mbar_init(sb + 8 * (B_S + i), 1);
        fence_async_s();
        if (XPF > 0) load_ssm(P, sb, b, 0);
        if (XPF > 1) load_ssm(P, sb, b, 1);
      } else {
        const int c = j < 3 ? 1 : j < 4 ? 2 : 4;
#pragma unroll
        for (int i = 0; i < 16; i++) mbar_init(sb + 128 * j + 8 * i, i < 10 || j < 6 ? c : i < 12 ? 128 : 1);
      }
    }
    fence_async_s();
  }
  __syncthreads();
  STAMPIF(threadIdx.x == 0, 55);

  if (wg < 2) {
    cp_arrive(sb + 8 * (B_B + wg));
    asm volatile("setmaxnreg.inc.sync.aligned.u32 224;");
    STAMPIF(threadIdx.x == 0, 82);
    const int g = lane >> 2, q = lane & 3;
    constexpr int NB = UT < 5 ? 288 : 256;
    if (wg == 1) bar_arrive(1, NB);
    const uint32_t dv = *(const uint16_t*)(gD + 128 * wg + b);
    if (TG == 3) e1 = rdback(G->flag + 8 * m + 4 + (__shfl_sync(0xffffffffu, tid, tid) >> 8));
    e1 = (e1 >> 5) + 1;
    {
      const int tid = (OPQ & 4) ? __shfl_sync(0xffffffffu, threadIdx.x & 127, threadIdx.x) : threadIdx.x & 127, lane = tid & 31, g = lane >> 2, q = lane & 3;
      const int b0 = (g >> 1) & 1, b1 = g >> 2, u = q + 4 * b0 - w;
      const uint32_t fo = 128 + (g & 1) * K1OFF + 288 * b1 + 4 * u, fo0 = fo - (u < 0 ? 32 : 0);
      const bool wrap = b0 && q == 0;
      const int src1 = b0 ? ((lane & 20) | ((q - 1) & 3)) : (lane | 8);
      const uint2* pu = (const uint2*)(G->kvT + (128 * wg + b) * S_ + 8 * tid);
      uint4 u0 = make_uint4(0, 0, 0, 0), u1 = make_uint4(0, 0, 0, 1);
#pragma unroll 1
      for (int ch = wg; ch < 5; ch += 2) {
        const uint32_t base = chan_base(sb, ch);
        if (ch < 2 || ch == KV4C) {
          kv_job(G, sb, b, ch < 2 ? ch : 4, tid, TG ? e1 : 1);
          if (ER && ch > 1) { __syncwarp(); if (lane == 0) mbar_arrive(sb + 8 * B_KV4); }
          STAMPIF(tid == 0, ch < 2 ? 1 + ch : 24);
        }
        if (ch < 2) {
          k1_job(sb, wg, tid, dv);
          bar_sync(3 + wg, 128);
        } else {
          mbar_wait(sb + 8 * (B_K + ch - 2), 0);
          if (UT == 5) {
            u0 = ld_tag2(pu); u1 = ld_tag2(pu + 256);
            if (BS) mbar_wait(sb + 8 * (B_S + ch), 0);
          }
        }
        const uint32_t fa = base + fo, fa0 = base + fo0;
        uint32_t af[16][4];
        auto afl = [&](int j) {
          const int o = 64 * (j & 1) + 576 * (j >> 1);
          if (UF) { af[j][0] = ldv32(((j & 1) ? fa : fa0) + o); af[j][1] = ldv32(fa + o + 128); af[j][2] = ldv32(fa + o + 32); af[j][3] = ldv32(fa + o + 160); }
          else { af[j][0] = lds32(((j & 1) ? fa : fa0) + o); af[j][1] = lds32(fa + o + 128); af[j][2] = lds32(fa + o + 32); af[j][3] = lds32(fa + o + 160); }
        };
#pragma unroll
        for (int j = 0; j < NA; j++) afl(j);
        if (UF) {
          stv128(base + KSZ + 16 * tid, u0);
          stv128(base + KSZ + 2048 + 16 * tid, u1);
#pragma unroll
          for (int j = NA; j < 16; j++) afl(j);
        }
        STAMPIF(tid == 0, 40 + ch);
        const uint32_t tg = e1;
        if (!(TG & 1) && (!EH || ch < 2)) { mbar_wait(sb + 8 * B_E0, 0); e1 = epoch(sb); }
        if (ch < UT) {
          if (UD2 ? ch < 2 : ch == 1) spin(t_0, ch ? UD1 : UD2);
          if (UT == 2) u0.w = 0;
          if (UF) u_fix(u0, u1, pu, base + KSZ + 16 * tid, TG ? tg : 1);
          else u_wait(u0, u1, pu);
          if (ITW == 5) STAMPIF(tid == 0, 105 + ch);
          if (!UF) {
            sts128(base + KSZ + 16 * tid, u0);
            sts128(base + KSZ + 2048 + 16 * tid, u1);
#pragma unroll
            for (int j = NA; j < 16; j++) afl(j);
          }
          fence_async_s();
        }
        float acc[128];
        const uint64_t db = mkdesc(base + KSZ, 32, 128, 0);
        bar_sync(1 + wg, NB);
        if (ITW == 5) STAMPIF(tid == 0, 115 + ch);
        wg_fence();
        wgmma_rs_n64<0>(acc + 96, af[0], db + 192, 0);
        wgmma_rs_n192<0>(acc, af[0], db, 0);
        wgmma_rs_n64<0>(acc + 96, af[1], db + 196, 1);
        wgmma_rs_n192<0>(acc, af[1], db + 4, 1);
        wgmma_rs_n32<0>(acc + 96, af[2], db + 224, 1);
        wgmma_rs_n192<0>(acc, af[2], db + 32, 1);
        wgmma_rs_n32<0>(acc + 96, af[3], db + 228, 1);
        wgmma_rs_n192<0>(acc, af[3], db + 36, 1);
        wgmma_rs_n192<0>(acc, af[4], db + 64, 1);
        wgmma_rs_n192<0>(acc, af[5], db + 68, 1);
        wgmma_rs_n160<0>(acc, af[6], db + 96, 1);
        wgmma_rs_n160<0>(acc, af[7], db + 100, 1);
        if (CVT == 2) wg_commit();
        wgmma_rs_n128<0>(acc, af[8], db + 128, 1);
        wgmma_rs_n128<0>(acc, af[9], db + 132, 1);
        if (CVT == 1) wg_commit();
        wgmma_rs_n96<0>(acc, af[10], db + 160, 1);
        wgmma_rs_n96<0>(acc, af[11], db + 164, 1);
        if (CVT == 0) bar_arrive(2 - wg, NB);
        wgmma_rs_n64<0>(acc, af[12], db + 192, 1);
        wgmma_rs_n64<0>(acc, af[13], db + 196, 1);
        wgmma_rs_n32<0>(acc, af[14], db + 224, 1);
        wgmma_rs_n32<0>(acc, af[15], db + 228, 1);
        wg_commit();
        if ((!TG || TG == 2 && ch < 2) && ZP == 0 && ch < UT) {
          stg128((void*)pu, make_uint4(0, 0, 0, 0));
          stg128((void*)(pu + 256), make_uint4(0, 0, 0, 0));
        }
        if (tid < 2 && ch == (!ER && wg == (KV4C & 1) && KV4C < 5 ? KV4C : wg)) mbar_arrive(sb + 8 * (B_E1 + tid));
        auto go = [&](int k) {
          int mk = 0;
#pragma unroll
          for (int c = 0; c < 4; c++) if (((GT >> 4 * c) & 15) == k) mk |= 1 << c;
          if (mk) asm volatile("{\n.reg .pred p;\nsetp.ne.b32 p, %1, 0;\n@p bar.arrive %0, %2;\n}" ::"r"(2 - wg), "r"((mk >> ch) & 1), "n"(NB) : "memory");
        };
        if (CVT) { wg_wait<1>(); go(0); }
        STAMPIF(tid == 0, 3 + ch);
        if (BX3 == 2 && ch == 3) {
          mod_box(G, sb, b, 1, e1, tid);
          __syncwarp();
          if (lane == 0) mbar_arrive(sb + 8 * (B_BD + 1));
          STAMPIF(tid == 0, 73);
        }
        if (ZP == 1) {
          stg128((void*)pu, make_uint4(0, 0, 0, 0));
          stg128((void*)(pu + 256), make_uint4(0, 0, 0, 0));
        }
        wg_wait<0>();
#pragma unroll
        for (int i = 0; i < 128; i++) asm volatile("" : "+f"(acc[i])::"memory");
        if (!RL) {
          bar_sync(3 + wg, 128);
          if (tid <= (ch >> 2)) mbar_arrive(sb + 8 * (B_E1 + 2 + (ch >> 1)));
        }
        if (RL == 2 && lane == 0) mbar_arrive(sb + 8 * (B_Z + ch));
        go(1);
        float S0[33], T[34];
#pragma unroll
        for (int i = 0; i < 31; i++) S0[i] = acc[4 * i] + acc[4 * i + 6];
        S0[31] = acc[124]; S0[32] = 0.f;
        if (PK & 1) {
#pragma unroll
          for (int i = 0; i < 32; i += 2) {
            const uint32_t v = __shfl_sync(0xffffffffu, pack2(acc[4 * i + 1] + acc[4 * i + 7], i < 30 ? acc[4 * i + 5] + acc[4 * i + 11] : acc[125]), src1);
            T[i] = (wrap ? S0[i + 1] : S0[i]) + blo(v);
            T[i + 1] = (wrap ? S0[i + 2] : S0[i + 1]) + bhi(v);
          }
        } else {
#pragma unroll
          for (int i = 0; i < 32; i++) {
            float s1 = i < 31 ? acc[4 * i + 1] + acc[4 * i + 7] : acc[125];
            T[i] = (wrap ? S0[i + 1] : S0[i]) + __shfl_sync(0xffffffffu, s1, src1);
          }
        }
        T[32] = 0.f; T[33] = 0.f;
        go(2);
        uint4* pz = (uint4*)(G->zT + (128 * ch + b) * S_) + ((tid & 120) | (2 * q) | (g & 1));
#pragma unroll
        for (int h = 0; h < 2; h++) {
          float y[8];
          if (PK & 2) {
#pragma unroll
            for (int mu = 0; mu < 8; mu += 2) {
              const uint32_t v = __shfl_xor_sync(0xffffffffu, pack2(T[4 * mu + 2 + h], T[4 * mu + 6 + h]), 16);
              y[mu] = (b1 ? T[4 * mu + 4 + h] : T[4 * mu + h]) + blo(v);
              y[mu + 1] = (b1 ? T[4 * mu + 8 + h] : T[4 * mu + 4 + h]) + bhi(v);
            }
          } else {
#pragma unroll
            for (int mu = 0; mu < 8; mu++) y[mu] = (b1 ? T[4 * mu + 4 + h] : T[4 * mu + h]) + __shfl_xor_sync(0xffffffffu, T[4 * mu + 2 + h], 16);
          }
          pz[128 * h] = make_uint4(pack2(y[0], y[1]), pack2(y[2], y[3]), pack2(y[4], y[5]), tagged(pack2(y[6], y[7]), e1));
        }
        go(3);
        if (RL == 1 && lane == 0) mbar_arrive(sb + 8 * (B_Z + ch));
        if (ZP == 2) {
          stg128((void*)pu, make_uint4(0, 0, 0, 0));
          stg128((void*)(pu + 256), make_uint4(0, 0, 0, 0));
        }
        pu += 128 * S_ / 2;
        STAMPIF(tid == 0, 8 + ch);
      }
    }
    uint32_t hh[96];
    {
      float ga[192];
      float* ua = ga + 96;
      const uint64_t da0 = mkdesc(ring + wg * 2048, 512, 256, 3), db0 = mkdesc(ring + 8192, 4096, 1024, 1);
      int st = PL, ph = 0, ps = 0;
      if (ITW == 7) STAMPIF(tid == 0, 110 + wg);
      float bx[4];
      if (wg && BX3 < 2) {
        mbar_wait(sb + 8 * (B_BOX + 2), 0);
        mbar_wait(sb + 8 * (B_BOX + 3), 0);
        wg_fence();
#pragma unroll
        for (int n = 0; n < 10; n++) wgmma_ss_n8<1, 0>(bx, box_a(sb) + 128 * n, box_b(sb) + 8 * n, n != 0);
        wg_commit();
        if (ITW == 7) STAMPIF(tid == 0, 120);
      }
      auto put = [&]() {
#pragma unroll
        for (int i = 0; i < 4; i++) asm volatile("" : "+f"(bx[i])::"memory");
        mod_put(G, sb, bx, b, 1, e1, tid);
        __syncwarp();
        if (lane == 0) mbar_arrive(sb + 8 * (B_BD + 1));
        STAMPIF(tid == 0, 73);
      };
      if (wg && BX3 == 0) { wg_wait<0>(); put(); }
      mbar_wait(sb + 8 * B_F1, 0);
      STAMPIF(tid == 0, 13 + wg);
      bool nf = PG == 1 && mbar_test(sb + 8 * (B_F1 + 1), 0);
      wg_fence();
      wgmma_ss_n192<1, 1>(ga, da0, db0, 0);
      wgmma_ss_n192<1, 1>(ua, da0, db0 + 768, 0);
      wgmma_ss_n192<1, 1>(ga, da0 + 256, db0 + 128, 1);
      wgmma_ss_n192<1, 1>(ua, da0 + 256, db0 + 128 + 768, 1);
      wg_commit();
      if (wg && BX3 == 1) { wg_wait<1>(); put(); }
      if (!PG) mbar_wait(sb + 8 * B_BD, 0);
      if (ITW == 7) STAMPIF(tid == 0, 112 + wg);
      const bool cs = b < 96;
      const int x0 = wg ? XI : 99,
                x1 = x0 + (cs ? 4 : 2), xs = cs ? 4 : 8;
      uint64_t xa = cs ? mkdesc(sb + SM_EXT, 4096, 1024, 1) : box_a(sb), xb = cs ? mkdesc(sb + SM_CB, 32, 128, 0) : box_b(sb);
      uint64_t ya = xa + (cs ? (SM_RING + R_X - SM_EXT) / 16 : 256), yb = xb + 16;
      if (ITW == 7) STAMPIF(tid == 0, 114 + wg);
#pragma unroll 1
      for (int it = PL; it < 19; it++) {
        if (it == x0) {
          mbar_wait(sb + 8 * (cs ? B_F : B_BOX + 4), 0);
          mbar_wait(sb + 8 * (cs ? B_ST0 : B_BOX + 5), 0);
          STAMPIF(tid == 0, 76);
        }
        if (it == x1 + XW) {
          wg_wait<XW>();
#pragma unroll
          for (int i = 0; i < 4; i++) asm volatile("" : "+f"(bx[i])::"memory");
          if (!cs) mod_put(G, sb, bx, b, 2, e1, tid);
          else {
            const int row = (m < 6 ? 0 : 4) + q;
            uint16_t* dst = (uint16_t*)G->cimg + s * 3072 + (m % 6) * 512 + row * 64 + g;
#pragma unroll
            for (int j = 0; j < 2; j++) {
              const float c1 = __shfl_sync(0xffffffffu, bx[2 * j], lane & 28), c2 = __shfl_sync(0xffffffffu, bx[2 * j + 1], lane & 28);
              const float t = (lane & 2) ? c2 : c1, hi = rbf(t);
              dst[((2 * w + j) ^ row) << 3] = (uint16_t)pack2((lane & 1) ? t - hi : hi, 0.f);
            }
          }
          __syncwarp();
          if (lane == 0) mbar_arrive(sb + 8 * (B_BD + 2));
          STAMPIF(tid == 0, 77);
        }
        if (ITW == 7) STAMPIF(tid == 0 && it == 0, 116 + wg);
        if (!nf) mbar_wait(sb + 8 * (B_F1 + st), ph);
        const int nx = st == 4 ? 0 : st + 1;
        if (st == 4) ph ^= 1;
        if (ITW == 1) STAMPIF(tid == 0 && it >= 10, 90 + it + 10 * wg);
        else if (ITW == 2) STAMPIF(tid == 0 && it < 10, 100 + it + 10 * wg);
        else if (ITW < 3) STAMPIF(threadIdx.x == ITW, 100 + it);
        const uint64_t da = da0 + st * 2048, db = db0 + st * 2048;
        if (it >= x0 && it < x1) {
          if (PG == 1) nf = mbar_test(sb + 8 * (B_F1 + nx), ph);
          wg_fence();
          wgmma_ss_n8<1, 0>(bx, xa, xb, it != x0);
          wgmma_ss_n192<1, 1>(ga, da, db, 1);
          wgmma_ss_n8<1, 0>(bx, ya, yb, 1);
          wgmma_ss_n192<1, 1>(ua, da, db + 768, 1);
          wgmma_ss_n8<1, 0>(bx, ya + 128, yb + xs, 1);
          wgmma_ss_n192<1, 1>(ga, da + 256, db + 128, 1);
          wgmma_ss_n8<1, 0>(bx, ya + 256, yb + 2 * xs, 1);
          wgmma_ss_n192<1, 1>(ua, da + 256, db + 128 + 768, 1);
          wgmma_ss_n8<1, 0>(bx, ya + 384, yb + 3 * xs, 1);
          wg_commit();
          xa += 128; xb += xs; ya += 512; yb += 4 * xs;
        } else {
          if (PG == 1) nf = mbar_test(sb + 8 * (B_F1 + nx), ph);
          wg_fence();
          wgmma_ss_n192<1, 1>(ga, da, db, PL || it != 0);
          wgmma_ss_n192<1, 1>(ua, da, db + 768, PL || it != 0);
          wgmma_ss_n192<1, 1>(ga, da + 256, db + 128, 1);
          wgmma_ss_n192<1, 1>(ua, da + 256, db + 128 + 768, 1);
          wg_commit();
        }
        wg_wait<1>();
        if (PG) { if (w == 0 && elect()) mbar_arrive(sb + 8 * (B_E1 + ps)); }
        else if (tid == 0) mbar_arrive(sb + 8 * (B_E1 + (st == 0 ? 4 : st - 1)));
        ps = st; st = nx;
      }
      const uint32_t la = ring + wg * 2048 + tid * 16, ra = mapa(la, (b & 1) ^ 1), rp = mapa(sb + 8 * (B_PEER + 2 * wg), (b & 1) ^ 1), rb = rp + 8 * (B_RECV - B_PEER);
      uint32_t sa[24];
      auto addr = [&](int j) {
        sa[2 * j] = ra + (j < 2 ? 5 : (j >> 1) - 1) * 32768 + (j & 1) * 4096;
        sa[2 * j + 1] = (sa[2 * j] >> 31) + (rb + 8 * (j / 6));
        asm volatile("" : "+r"(sa[2 * j]), "+r"(sa[2 * j + 1]));
      };
      auto send = [&](int j) { st_async4(sa[2 * j], hh + 4 * j, sa[2 * j + 1]); };
      auto pack = [&](int c) {
#pragma unroll
        for (int i = 0; i < 64; i++) asm volatile("" : "+f"(ga[64 * c + i])::"memory");
#pragma unroll
        for (int i = 0; i < 4; i++) addr(4 * c + i);
#pragma unroll
        for (int i = 0; i < 16; i++) {
          const int j = 64 * c + 2 * i;
          hh[16 * c + i] = pack2(ga[j] * ga[j + 32], ga[j + 1] * ga[j + 33]);
          asm volatile("" : "+r"(hh[16 * c + i])::"memory");
          if ((i & 3) == 3 && 4 * c + i / 4 < NP) send(4 * c + i / 4);
          if (c == 2 && NQ > NP && i == 0) mbar_wait(sb + 8 * (B_PEER + 2 * wg), 0);
          if (c == 2 && (i & 3) == 3 && NP + i / 4 < NQ) send(NP + i / 4);
        }
      };
      STAMPIF(threadIdx.x == 0, 61);
      if (!nf) mbar_wait(sb + 8 * (B_F1 + 4), 1);
      mbar_wait(sb + 8 * B_EXT, 0);
      mbar_wait(sb + 8 * B_ST2, 0);
      const uint64_t de = mkdesc(sb + SM_EXT, 1024, 0, 1), ds = mkdesc(sb + SM_STAT + wg * 1024, 0, 128, 0);
#pragma unroll
      for (int c = 0; c < 2; c++) {
        wg_fence();
        wgmma_ss_n192<1, 1>(ga + 96 * c, da0 + 8192, db0 + 8192 + 768 * c, 1);
        wgmma_ss_n192<1, 1>(ga + 96 * c, da0 + 8192 + 256, db0 + 8192 + 128 + 768 * c, 1);
        wgmma_ss_n192<0, 1>(ga + 96 * c, ds, de + 192 * c, 1);
        wg_commit();
        if (c == 0) { mbar_wait(sb + 8 * B_P0, 0); mbar_wait(sb + 8 * B_FB, 0); }
        wg_wait<1>();
        if (c == 0 && tid == 0) {
          mbar_arrive(sb + 8 * (B_E1 + 3));
          mbar_arrive_remote(rp);
        }
      }
      STAMPIF(tid == 0, 15 + wg);
      float acc[64], rs[2] = {};
      uint4 pf[4], gb = {};
      uint32_t ln, os, ol, og, oz;
      const char *po, *pq;
      const uint64_t dd0 = mkdesc(ring + 8192, 0, 1024, 1);
      bool ok = false;
#pragma unroll
      for (int c = 0; c < 3; c++) {
        pack(c);
        if (c == 1) ok = mbar_try(sb + 8 * (B_FB + 1), 0);
        STAMPIF(tid == 0 && c == 0, wg ? 89 : 121);
        if (ITW == 3) STAMPIF(tid == 0 && c > 0, 99 + c + 10 * wg);
        wg_fence();
#pragma unroll
        for (int k = 4 * c; k < 4 * c + 4; k++) wgmma_rs_n64<1>(acc, hh + 4 * k, dd0 + 5 * 2048 + 128 * k, k);
        wg_commit();
        if (c == 0) {
          wg_wait<1>();
          if (tid == 0) {
            mbar_arrive(sb + 8 * (B_E1 + 4));
            mbar_arrive_remote(rp + 8);
          }
        }
        if (c == 1 && !ok) mbar_wait(sb + 8 * (B_FB + 1), 0);
      }
      auto recv = [&](int j) {
        const uint4 v = lds128(la + (j < 2 ? 5 : (j >> 1) - 1) * 32768 + (j & 1) * 4096);
        hh[48 + 4 * j] = v.x; hh[49 + 4 * j] = v.y; hh[50 + 4 * j] = v.z; hh[51 + 4 * j] = v.w;
      };
      auto stage = [&](const float* a, int i, int p) {
        const uint32_t v[4] = {pack2(a[8 * i] * rs[0], a[8 * i + 1] * rs[0]), pack2(a[8 * i + 2] * rs[1], a[8 * i + 3] * rs[1]),
                               pack2(a[8 * i + 4] * rs[0], a[8 * i + 5] * rs[0]), pack2(a[8 * i + 6] * rs[1], a[8 * i + 7] * rs[1])};
        stsm4(OF && p % 4 ? (oz ^ 32 * i) + 65536 * (p - 1) : os + 32 * i, v);
      };
      auto fetch = [&](int p) {
        __syncwarp();
#pragma unroll
        for (int i = 0; i < 4; i++) pf[i] = lds128(ol + 576 * i);
      };
      auto next = [&](int p) {
        gb = lds128(og + 256 * out_blk(s, p));
        pq = po + 128 * out_blk(s, p);
        asm volatile("" : "+l"(pq));
      };
      auto add = [&](int p, int i) {
        if (RX == 1 && p < 4) return;
        if (RX == 2) { stg128((uint4*)(pq - (i & 1) * 2048 * D_ - (i >> 1) * 2 * D_), make_uint4(hmul(pf[i].x, gb.x), hmul(pf[i].y, gb.y), hmul(pf[i].z, gb.z), hmul(pf[i].w, gb.w))); return; }
        asm volatile("red.relaxed.gpu.global.add.noftz.v4.bf16x2 [%0], {%1, %2, %3, %4};" ::"l"(pq - (i & 1) * 2048 * D_ - (i >> 1) * 2 * D_),
                     "r"(hmul(pf[i].x, gb.x)), "r"(hmul(pf[i].y, gb.y)), "r"(hmul(pf[i].z, gb.z)), "r"(hmul(pf[i].w, gb.w)) : "memory");
      };
#pragma unroll
      for (int h = 2; h < 20; h++) {
        const int gr = h >> 1, pe = gr < 4 ? gr >> 1 : gr & 1, ac = (gr < 4 ? gr : gr >> 1) & 1;
        const int ep = h == 7 || h == 8 ? 0 : h > 8 && (h & 3) == 1 || h > 8 && (h & 3) == 2 ? (h >> 2) - 1 : -1;
        const int es = h == 6 ? 0 : h > 6 && !(h & 3) ? (h >> 2) - 1 : -1;
        if (!(h & 1) && h > 2 && !(PT && ok)) mbar_wait(sb + 8 * (B_FB + gr), 0);
        if (h == LH0 || h == LH1) mbar_wait(sb + 8 * (B_RECV + 2 * wg + (h == LH1)), 0);
        if (h == LH0 && (h == 4 || !LM) || h == LH1 && (h == 5 || !LM)) {
#pragma unroll
          for (int j = 0; j < 6; j++) recv(6 * (h == LH1) + j);
        }
        if (h == SPOS(6) / 6 && NQ <= 6) mbar_wait(sb + 8 * (B_PEER + 2 * wg), 0);
        if (h == SPOS(10) / 6) mbar_wait(sb + 8 * (B_PEER + 2 * wg + 1), 0);
        if (OF && h == OH) mbar_wait(sb + 8 * B_OF, 0);
        if (h == (ES ? RH : 6)) {
          if (!OF) { mbar_wait(sb + 8 * B_X1, 0); mbar_wait(sb + 8 * B_GB, 0); }
          asm volatile("mov.u32 %0, %%laneid;" : "=r"(ln));
#pragma unroll
          for (int i = 0; i < 2; i++) rs[i] = blo(lds32(sb + SM_STAT + (4 * wg + w) * 256 + (ln & 28) * 4 + 128 * i + 4));
        }
        STAMPIF(tid == 0 && h % 4 == 0 && h < 16, (wg ? 89 : 121) + h / 4);
        STAMPIF(tid == 0 && h == 16, wg ? 97 : 96);
        if (ITW == 3) STAMPIF(tid == 0 && h < 10, 100 + h + 10 * wg);
        if (ITW == 4) STAMPIF(tid == 0 && h >= 10, 90 + h + 10 * wg);
        const uint64_t db = dd0 + (((gr + 5) % 6) * 2048 + (gr << 16));
        if (PT && (h & 1) && h < 19) ok = mbar_try(sb + 8 * (B_FB + gr + 1), 0);
        wg_fence();
#pragma unroll
        for (int j = 0; j < 6; j++) {
          const int k = 6 * (h & 1) + j;
          wgmma_rs_n64<1>(acc + 32 * ac, hh + 48 * pe + 4 * k, db + 128 * k, pe || k);
#pragma unroll
          for (int i = NQ; i < 12; i++) if (SPOS(i) == 6 * h + j) send(i);
          if (LM && h == LH0 && h < 4) { recv(j); wg_fence(); }
          if (LM && h == LH1 && h < 5) { recv(6 + j); wg_fence(); }
          if (ES && es >= 0) {
            if (j == ES - 1) {
              wg_commit();
              wg_wait<1>();
              if (h < 12 && tid == 0) mbar_arrive(sb + 8 * (B_EB + gr - 1));
#pragma unroll
              for (int i = 0; i < 32; i++) asm volatile("" : "+f"(acc[32 * (1 - ac) + i])::"memory");
            }
#pragma unroll
            for (int i = 0; i < 4; i++) if (j == min(5, ES - 1 + i * SI / 2)) {
              stage(acc + 32 * (1 - ac), i, es);
              if (i == 3) { __syncwarp(); if (ln == 0) mbar_arrive(sb + 8 * (B_OS + 4 * wg + es)); }
            }
            if (j == ES - 1 && j < 5) wg_fence();
          }
          if (!ES && ep >= 0 && (h & 1)) {
            if (j < 4) stage(acc + 32 * (1 - ac), j, ep);
            if (j == 4 && !OF) fetch(ep);
            if (j == 3 && OF) { __syncwarp(); if (ln == 0) mbar_arrive(sb + 8 * (B_OS + 4 * wg + ep)); }
          }
          if (!OF && ep >= 0 && !(h & 1) && j > 0 && j < 5) add(ep, j - 1);
          if (!OF && ep >= 0 && !(h & 1) && j == 5) next(ep + 1);
        }
        if (!(ES == 6 && es >= 0)) wg_commit();
        STAMPIF(tid == 0 && h == 3, 81);
        if (h == (ES ? RH : 6)) {
#pragma unroll
          for (int i = 0; i < 2; i++) rs[i] = __fdividef(0.25f, rs[i] * rs[i]);
          const uint32_t ob = sb + SM_X + (4 * wg + w) * 2304;
          os = ob + (ln & 15) * 144 + (ln & 16);
          oz = ring + (4 * wg + w) * 512 + (ln & 8) * 4096 + (ln & 4) * 1024 + (ln & 3) * 128 + ((ln >> 4) ^ (ln & 7)) * 16;
          asm volatile("" : "+r"(os), "+r"(oz));
        }
        if (h == (OF ? OH : 6)) {
          ol = sb + SM_X + (4 * wg + w) * 2304 + (ln >> 3) * 16 + ln * 16;
          po = (const char*)(gout + (1793 + 2 * tbase(8 * m + 4 * wg + w)) * D_) + (int)(640 * (s & 1) + 16 * ln - (ln >> 3) * (512 * D_ + 128));
          og = sb + SM_CB + 32 * (ln & 7);
          asm volatile("" : "+r"(ol), "+r"(og), "+l"(po));
          next(OF ? 4 : 0);
        }
        if (h == 2 || h == 4 || !ES && es >= 0) {
          wg_wait<1>();
          if (h < 12 && tid == 0) mbar_arrive(sb + 8 * (B_EB + gr - 1));
          if (h >= 6) {
#pragma unroll
            for (int j = 0; j < 32; j++) asm volatile("" : "+f"(acc[32 * (1 - ac) + j])::"memory");
          }
        }
      }
      STAMPIF(tid == 0, wg ? 95 : 93);
      wg_wait<0>();
#pragma unroll
      for (int i = 0; i < 32; i++) asm volatile("" : "+f"(acc[i])::"memory");
      STAMPIF(tid == 0, wg ? 50 : 18);
#pragma unroll
      for (int i = 0; i < 4; i++) stage(acc, i, 4);
      fetch(4);
#pragma unroll
      for (int i = 0; i < 4; i++) add(4, i);
    }
  } else if (wg == 2) {
    asm volatile("setmaxnreg.dec.sync.aligned.u32 40;");
    const uint32_t e1 = (rdback(G->flag + 8 * m + 4) >> 5) + 1;
    if (tid < 80) {
      uint4 c = ((const uint4*)gc)[tid];
#pragma unroll 1
      for (int i = 0; i < 4; i++) {
        const float lo = blo(c.x), hi = bhi(c.x);
        sts32(sb + SM_STAT + 16 * tid + 4 * i, pack2(__fdividef(lo, 1.f + __expf(-lo)), __fdividef(hi, 1.f + __expf(-hi))));
        c.x = c.y; c.y = c.z; c.z = c.w;
      }
    }
    if (tid == 0) { sts32(sb + SM_SMALL + SMALL_E, e1); mbar_arrive(sb + 8 * B_E0); }
    fence_async_s();
    bar_sync(5, 128);
    if (mod_first(b)) mod_box(G, sb, b, 0, e1, tid);
    __syncwarp();
    if (lane == 0) mbar_arrive(sb + 8 * B_BD);
    STAMPIF(tid == 0, 27);
    float s1 = 0.f, s2 = 0.f, pv;
    int tl = (OPQ & 1) ? __shfl_sync(0xffffffffu, tid, tid) : tid;
#pragma unroll 1
    for (int r = 2 - DR; r < 5 - XO; r++) {
      asm volatile("" : "+r"(tl));
      if (DR && r == 2) s1 = s2 = 0.f;
      if ((XO || r < 4) && r > 1) {
        kv_job(G, sb, b, r, tl, TG ? e1 : 1);
        STAMPIF(tid == 0, 20 + r);
      }
      if (r == 3) { __syncwarp(); if (elect()) mbar_arrive(sb + 8 * B_KVS); }
      if (XO || r != 2) ln1_half(sb, tl, (r - 3 + XO) & 1, r < 2, s1, s2, pv);
    }
    {
      const int lane = tl & 31, cg = 4 * (w >> 1) + (lane & 2) + (w & 1), g = lane >> 2;
      uint32_t zo = offsetof(Scr, zT) + 2 * ((16 * cg + g) * S_ + 16 * b + 8 * (lane & 1)), co = offsetof(Scr, mv) + 4 * (2048 * (e1 & 1) + 8 * cg + g);
      uint4 z[2];
      uint32_t c[4];
      auto zld = [&]() {
        asm volatile("" : "+r"(zo), "+r"(co));
        const uint2* pz = (const uint2*)((const char*)G + zo);
        const uint32_t* pc = (const uint32_t*)((const char*)G + co);
        z[0] = ld_tag2(pz); z[1] = ld_tag2(pz + 4096);
        c[0] = rdback(pc); c[1] = rdback(pc + 320); c[2] = rdback(pc + 640); c[3] = rdback(pc + 1280);
      };
      STAMPIF(tid == 0, 28);
      if (ZF < 2 && !ZA) { spin(t_0, ZD); zld(); spin(t_0, ZS); }
      if (ITW == 8) STAMPIF(tid == 0, 106);
      ln1_end(sb, tl, s1, s2, pv);
      if (ZF < 2 && ZA) { spin(t_0, ZD); zld(); }
#pragma unroll 1
      for (int r = 0; r < 5; r++) {
        asm volatile("" : "+r"(tl));
        const int lane = tl & 31;
        if (ITW == 6) STAMPIF(tid == 0 && r < 2, 100 + 10 * r);
        if (ZF == 3) { if (r == 2 + MG) { mbar_wait(sb + 8 * (B_BD + 1), 0); spin(clk(), BD); } if (r == 0) spin(t_0, ZD); zld(); }
        const uint32_t la = sb + SM_SMALL + SMALL_LN + 16 * (lane & 1);
        uint32_t xa = x_addr(sb, w, lane) + 4096 * r, xv[8];
        const uint4 m4 = lds128(la), s4 = lds128(la + 32);
        const uint32_t m_[4] = {m4.x, m4.y, m4.z, m4.w}, s_[4] = {s4.x, s4.y, s4.z, s4.w};
        ldsm4t(xv, xa);
        ldsm4t(xv + 4, xa ^ 16);
        if (ZF == 2) { if (r == 2 + MG) { mbar_wait(sb + 8 * (B_BD + 1), 0); spin(clk(), BD); } if (r == 0) spin(t_0, ZD); zld(); }
        if (ITW == 6) STAMPIF(tid == 0 && r < 2, 104 + 10 * r);
        if (ITW == 8) STAMPIF(tid == 0 && r == 0, 109);
        z_wait(z[0], z[1], c, G, zo, co, e1);
        asm volatile("" : "+r"(xa));
        const uint32_t zc = (zo - (uint32_t)offsetof(Scr, zT)) >> 11, ao = (320 * m + s) * 32 + ((zc & ~31u) << 3) + (zc & 14) + (((zo >> 4) ^ (zc >> 3)) & 1);
        STAMPIF(tid == 0 && r == 0, 83);
        if (ITW == 6) STAMPIF(tid == 0 && r < 2, 105 + 10 * r);
        uint32_t h[8];
        {
          const uint32_t sa = ~c[0], ca1 = ~c[1];
#pragma unroll
          for (int j = 0; j < 8; j++) {
            const uint32_t z_[8] = {z[0].x, z[0].y, z[0].z, z[0].w, z[1].x, z[1].y, z[1].z, z[1].w}, sel = j > 3 ? 0x3232 : 0x1010;
            h[j] = hmul(hfma(hmul(hsub(xv[j], m_[j & 3]), s_[j & 3]), __byte_perm(ca1, 0, sel), __byte_perm(sa, 0, sel)), z_[j]);
            asm volatile("" : "+r"(h[j]));
          }
        }
        uint4* pa = (uint4*)G->AT + ao;
        uint32_t oo[8];
#pragma unroll
        for (int n = 0; n < 2; n++) {
          const uint32_t sel = n ? 0x3232 : 0x1010, ga = __byte_perm(~c[2], 0, sel), cb1 = __byte_perm(~c[3], 0, sel);
          uint32_t* o = oo + 4 * n, a[4];
#pragma unroll
          for (int j = 0; j < 4; j++) {
            o[j] = hfma(ga, h[4 * n + j], xv[4 * n + j]);
            a[j] = hmul(o[j], cb1);
          }
          a[2 * n + 1] = tagged(a[2 * n + 1], e1);
          pa[16 * n] = make_uint4(a[0], a[1], a[2], a[3]);
          if (n) { __syncwarp(); if (elect()) { flag_add(G, 8 * m + r); if (EA && r == 0) mbar_arrive(sb + 8 * (B_EW + 5)); } }
          if (ITW == 6) STAMPIF(tid == 0 && r < 2, 106 + n + 10 * r);
          if (ITW == 8) STAMPIF(lane == 0 && r == 0 && n, 110 + w);
          if (!SL) stsm4t(xa ^ (16 * n), o);
        }
        if (SL) { stsm4t(xa, oo); stsm4t(xa ^ 16, oo + 4); }
        if (r < 4) { zo += 256 * S_; co += 256; }
        auto x1st = [&]() {
          __syncwarp();
          int lane = tl & 31;
          if (!(OPQ & 2)) asm volatile("mov.u32 %0, %%laneid;" : "=r"(lane));
          const int c = 2 * (w & 1) + (lane & 1) + 2 * (lane & 2), g = lane >> 2;
          const uint32_t a = sb + SM_X + 4096 * r + (w >> 1) * 2048 + g * 128 + ((c ^ g) << 4);
          const uint4 v0 = lds128(a), v1 = lds128(a + 1024);
          char* po = (char*)gout + (2 * tbase(b) + 128 * (g & 6) + (g & 1)) * 2 * D_ + 256 * r + 64 * (w & 2) + 16 * c;
          if (ITW == 6) STAMPIF(tid == 0 && r < 2, 108 + 10 * r);
          stg128(po, v0);
          stg128(po + 2048 * D_, v1);
        };
        auto box1 = [&]() {
          if (BX3 >= 3) {
            mod_box(G, sb, b, 1, e1, tl);
            __syncwarp();
            if (elect()) mbar_arrive(sb + 8 * (B_BD + 1));
            STAMPIF(tid == 0, 73);
          } else mbar_wait(sb + 8 * (B_BD + 1), 0);
          if (BX3 < 4) spin(clk(), BD);
        };
        if (ZF == 1) {
          if (BX3 < 4 && r == 1 + MG) { if (XE) x1st(); box1(); }
          if (BX3 == 5 && r == 0) box1();
          zld();
        }
        if (BX3 == 6 && r == 0) box1();
        if (BX3 > 3 || ZF != 1 || !XE || r != 1 + MG) x1st();
        if (BX3 == 4 && r == 0) box1();
        __syncwarp();
        if (elect()) mbar_arrive(sb + 8 * (B_EW + r));
        STAMPIF(tid == 0, 29 + r);
        if (ZF == 0) { if (r == 1 + MG) box1(); zld(); }
      }
    }
    asm volatile("" : "+r"(tl));
    {
      const int lane = tl & 31;
      const uint4 m4 = lds128(sb + SM_SMALL + SMALL_LN + 16 * (lane & 1));
      const uint32_t m_[4] = {m4.x, m4.y, m4.z, m4.w}, xa = x_addr(sb, w, lane);
      float a[16];
#pragma unroll
      for (int i = 0; i < 16; i++) a[i] = 0.f;
#pragma unroll 2
      for (int n = 0; n < 10; n++) {
        uint32_t x_[4];
        ldsm4t(x_, (xa ^ (16 * (n & 1))) + 2048 * (n & 14));
#pragma unroll
        for (int i = 0; i < 4; i++) {
          const float d0 = blo(x_[i]) - blo(m_[i]), d1 = bhi(x_[i]) - bhi(m_[i]);
          a[4 * i] += d0; a[4 * i + 1] += d0 * d0; a[4 * i + 2] += d1; a[4 * i + 3] += d1 * d1;
        }
      }
      STAMPIF(lane == 0, 67 + (w & 1) + 11 * (w >> 1));
      bfly<16>(a, 16, lane & 16); bfly<8>(a, 8, lane & 8); bfly<4>(a, 4, lane & 4); bfly<2>(a, 2, lane & 2);
      if (lane == 0) mbar_arrive(sb + 8 * B_XF);
      STAMPIF(tid == 0, 88);
      sts32(sb + SM_SMALL + SMALL_RED + 16 * lane + 4 * w, __float_as_uint(a[0]));
      bar_sync(5, 128);
      if (w == 0) {
        const uint4 v = lds128(sb + SM_SMALL + SMALL_RED + 16 * lane);
        const float s1 = __uint_as_float(v.x) + __uint_as_float(v.y) + __uint_as_float(v.z) + __uint_as_float(v.w), s2 = __shfl_xor_sync(0xffffffffu, s1, 2);
        const int p = 8 * (lane & 1) + (lane >> 2);
        const float pv = blo(lds32(sb + SM_SMALL + SMALL_LN + 4 * (p >> 1)) >> (16 * (p & 1)));
        const float mu = s1 * (1.f / D_), var = fmaxf(s2 * (1.f / D_) - mu * mu, 0.f);
        const float sd = sdev(var);
        if (!(lane & 2)) st_tag(G->st2 + 16 * b + p, pack2(-0.5f * (pv + mu), 0.5f * sd), e1);
      }
      STAMPIF(tid == 0, 87);
    }
    {
      uint2 v;
      spin(clk(), SD);
      mbar_wait(sb + 8 * (B_BD + 2), 0);
#pragma unroll 1
      for (int i = 0;; i++) {
        v = ld_tag(G->st2 + 128 * m + tl);
        if (__all_sync(0xffffffffu, v.y == e1)) break;
        if (i > (1 << 20)) __trap();
      }
      const uint32_t hm = __byte_perm(v.x, 0, 0x1010), hs = __byte_perm(v.x, 0, 0x3232);
      sts128(sb + SM_STAT + 16 * tl, make_uint4(hm, hs, hm, hs));
      fence_async_s();
      __syncwarp();
      if (elect()) mbar_arrive(sb + 8 * B_ST2);
      STAMPIF(tid == 0, 21);
    }
    if (OF) {
      uint32_t ln, w, s;
      asm volatile("mov.u32 %0, %%laneid;\n\tmov.u32 %1, %%tid.x;\n\tmov.u32 %2, %%ctaid.x;" : "=r"(ln), "=r"(w), "=r"(s));
      w = (w >> 5) & 3; s = role(s);
      const int m = s >> 3;
      s &= 7;
      mbar_wait(sb + 8 * B_X1, 0);
      mbar_wait(sb + 8 * B_GB, 0);
      const uint32_t ol = sb + SM_X + w * 2304 + (ln >> 3) * 16 + ln * 16, oz = ring - 65536 + w * 512 + (ln >> 3) * 128 + ((ln >> 3) ^ (ln & 7)) * 16;
      const char* po = (const char*)(gout + 1793 * D_) + (int)(640 * (s & 1) + 16 * ln - (ln >> 3) * (512 * D_ + 128));
#pragma unroll 1
      for (int n = 0; n < 8; n++) {
        const int p = n >> 1, c = n & 1, ob = out_blk(s, p);
        const uint4 gb = lds128(sb + SM_CB + 32 * (ln & 7) + 256 * ob);
        const char* pq = po + (128 * ob + 4 * D_ * tbase(8 * m + 4 * c + w));
        const uint32_t a0 = p ? oz + 65536 * p + 2048 * c : ol + 9216 * c, a1 = p ? (a0 ^ 64) + 4096 : a0 + 576, d = p ? 32768 : 1152;
        mbar_wait(sb + 8 * (B_OS + 4 * c + p), 0);
        const uint4 pf[4] = {lds128(a0), lds128(a1), lds128(a0 + d), lds128(a1 + d)};
#pragma unroll
        for (int i = 0; i < 4; i++)
          asm volatile("red.relaxed.gpu.global.add.noftz.v4.bf16x2 [%0], {%1, %2, %3, %4};" ::"l"(pq - (i & 1) * 2048 * D_ - (i >> 1) * 2 * D_),
                       "r"(hmul(pf[i].x, gb.x)), "r"(hmul(pf[i].y, gb.y)), "r"(hmul(pf[i].z, gb.z)), "r"(hmul(pf[i].w, gb.w)) : "memory");
        if (n == 1) { __syncwarp(); if (ln == 0) mbar_arrive(sb + 8 * B_OF); }
      }
    }
  } else {
    asm volatile("setmaxnreg.dec.sync.aligned.u32 24;");
    if (w != 0) {
    if (w == 2 && lane < 3) asm volatile("prefetch.tensormap [%0];" ::"l"(&P.mG + lane) : "memory");
    if (w & 1) {
      const uint32_t dv = *(const uint16_t*)(gD + 128 * min(lane, 4) + b);
#pragma unroll 1
      for (int j = 4; j < 10; j++) {
        k1_job(sb, j >> 1, 64 * (j & 1) + 16 * (w & 2) + lane, K1N ? __shfl_sync(0xffffffffu, dv, j >> 1) : *(const uint16_t*)(gD + 64 * (j & 14) + b));
        if (ITW == 5) STAMPIF(tid == 32, 98 + (j >> 1));
        if (UT == 5 && UD && w == 1 && (j & 1)) {
          mbar_wait(sb + 8 * (B_KJ + (j >> 1)), 0);
          const uint32_t t = lds32(sb + SM_SMALL + SMALL_TS + 4 * (j >> 1));
          while (clk() - t < UD);
        }
        __syncwarp();
        if (lane == 0) mbar_arrive(sb + 8 * (B_K + (j >> 1) - 2));
      }
      STAMPIF(tid == 32, 74);
    }
    if (w == 1) {
     {
      mbar_wait(sb + 8 * B_KVS, 0);
      const uint32_t e1 = epoch(sb);
      if (elect()) {
        if (P3) { const uint32_t v = e1 * 32 - 32; sts128(sb + SM_SMALL + SMALL_H, make_uint4(v, v, v, v)); sts32(sb + SM_SMALL + SMALL_H + 16, v); }
        if (ER) mbar_wait(sb + 8 * B_KV4, 0);
        mbar_wait(sb + 8 * (B_EW + 5 * EA), 0);
        spin(clk(), AD);
#pragma unroll 1
        for (int it = NS; it < 20; it++) {
          int st = it % 5;
          if ((it & 3) == 0 || it == NS) { if (P3) hint_wait(G, sb + SM_SMALL + SMALL_H, 8 * m + (it >> 2), e1 * 32); else flag_wait(G, 8 * m + (it >> 2), e1 * 32); STAMP(45 + (it >> 2)); }
          if (NS && it == NS) mbar_arrive(sb + 8 * B_FS);
          mbar_wait(sb + 8 * (B_E1 + st), (it / 5) & 1);
          uint32_t fb = sb + 8 * (B_A + st);
          mbar_expect(fb, 8192);
          bulk_g2s(ring + st * 32768, G->AT + (20 * m + it) * 4096, 8192, fb);
        }
        mbar_wait(sb + 8 * B_XF, 0);
        flag_wait(G, 8 * m + FL_X, e1 * 8);
        mbar_arrive(sb + 8 * B_X1);
        STAMP(86);
      }
     }
    } else if (w == 2) {
      if (lane < 4) mbar_expect(sb + 8 * (B_RECV + lane), 12288);
      if (UT == 2) { bar_arrive(1, 288); bar_arrive(2, 288); }
      int ph = 0;
#pragma unroll 1
      for (int ch = UT; ch < 5; ch++) {
        const uint32_t ub = chan_base(sb, ch) + KSZ;
        uint4* pu = (uint4*)(G->kvT + (128 * ch + b) * S_);
        mbar_wait(sb + 8 * (B_KJ + ch), 0);
        const uint32_t t0 = lds32(sb + SM_SMALL + SMALL_TS + 4 * ch);
        while (clk() - t0 < (ch ? UD : UD0));
#pragma unroll 1
        for (int i = 0;; i++) {
          if (elect()) { mbar_expect(sb + 8 * B_U, 4096); bulk_g2s(ub, pu, 4096, sb + 8 * B_U); }
          if (ITW == 5) STAMPIF(lane == 0, 110 + ch);
          mbar_wait(sb + 8 * B_U, ph);
          ph ^= 1;
          uint32_t t = 1;
#pragma unroll
          for (int j = 0; j < 8; j++) t &= lds32(ub + 16 * lane + 512 * j + 12);
          if (__all_sync(0xffffffffu, t)) break;
          if (i > (1 << 20)) __trap();
        }
        if (ITW == 5) STAMPIF(lane == 0, 105 + ch);
        if (ch > 1) mbar_wait(sb + 8 * (B_Z + ch - 2), 0);
        bar_arrive(1 + (ch & 1), 288);
#pragma unroll
        for (int j = 0; j < 8; j++) stg128(pu + lane + 32 * j, make_uint4(0, 0, 0, 0));
      }
      if (ITW == 8) { mbar_wait(sb + 8 * B_X, 0); STAMPIF(lane == 0, 100); mbar_wait(sb + 8 * (B_X + 1), 0); STAMPIF(lane == 0, 101); }
      mbar_wait(sb + 8 * B_BD, 0);
      const uint32_t e1 = epoch(sb), ao = 256 * (lane & 16) + 32 * (lane & 15) + 4 * (lane & 4) + (lane & 8) + 4;
      int it = 0;
      uint32_t pm = (1 << NS) - 1;
      bool ok = false;
      if (NS) {
        if (lane < NS) mbar_expect(sb + 8 * (B_A + lane), 8192);
        mbar_wait(sb + 8 * (lane < NS ? B_E1 + lane : B_EW + 5), 0);
        __syncwarp();
        spin(clk(), AT1);
        spin(t_0, AT0);
        if (elect()) {
#pragma unroll
          for (int i = 0; i < NS; i++) bulk_g2s(ring + i * 32768, G->AT + (20 * m + i) * 4096, 8192, sb + 8 * (B_A + i));
        }
        __syncwarp();
        STAMPIF(lane == 0, 84);
#pragma unroll 1
        for (; it < NS; it++) {
          if (!ok) mbar_wait(sb + 8 * (B_A + it), 0);
          uint32_t t = 0, v[8];
          if (PC) ok = mbar_test(sb + 8 * (B_A + it + 1), 0);
#pragma unroll
          for (int j = 0; j < 8; j++) v[j] = ldv32(ring + it * 32768 + ao + 512 * j);
#pragma unroll
          for (int j = 0; j < 8; j++) t |= v[7 - j] ^ e1;
          if (__any_sync(0xffffffffu, t & 1)) {
            ok = false;
            fence_async_s();
            mbar_wait(sb + 8 * (lane > it && lane < NS ? B_A + lane : B_FS), 0);
            __syncwarp();
            if (lane >= it && lane < NS) mbar_expect(sb + 8 * (B_A + lane), 8192);
            __syncwarp();
            if (elect()) {
#pragma unroll
              for (int i = 0; i < NS; i++)
                if (i >= it) bulk_g2s(ring + i * 32768, G->AT + (20 * m + i) * 4096, 8192, sb + 8 * (B_A + i));
            }
            __syncwarp();
            STAMPIF(lane == 0, 85);
            break;
          }
          if (lane == 0) mbar_arrive(sb + 8 * (B_F1 + it));
        }
      }
#pragma unroll 1
      for (int st = it; it < 20; it++) {
        const uint32_t a = ring + st * 32768 + ao;
        if (!ok) mbar_wait(sb + 8 * (B_A + st), (pm >> st) & 1);
        pm ^= 1 << st;
        const int nx = st == 4 ? 0 : st + 1;
        if (ITW == 7) STAMPIF(lane == 0 && it < 4, 100 + it);
        if (ITW == 8) STAMPIF(lane == 0 && it < 2, 114 + it);
        uint32_t t = 0, v[8];
        if (PC) ok = mbar_test(sb + 8 * (B_A + nx), (pm >> nx) & 1);
#pragma unroll
        for (int j = 0; j < 8; j++) v[j] = ldv32(a + 512 * j);
#pragma unroll
        for (int j = 0; j < 8; j++) t |= v[7 - j] ^ e1;
        if (__any_sync(0xffffffffu, t & 1)) {
#pragma unroll 1
          for (int j = 0; j < 8; j++) a_check(a + 512 * j, (const char*)G->AT + (20 * m + it) * 8192 + ao + 512 * j, e1);
        }
        if (lane == 0) mbar_arrive(sb + 8 * (B_F1 + st));
        if (ITW == 7) STAMPIF(lane == 0 && it < 4, 104 + it);
        if (ITW == 8) STAMPIF(lane == 0 && it < 2, 116 + it);
        st = nx;
      }
    } else {
      mbar_wait(sb + 8 * B_KVS, 0);
      auto rel = [&](int ch) { mbar_wait(sb + 8 * (B_Z + ch), 0); if (lane <= (ch >> 2)) mbar_arrive(sb + 8 * (B_E1 + 2 + (ch >> 1))); };
      if (RL) { rel(0); rel(1); rel(2); }
      mbar_wait(sb + 8 * (B_BD + 1), 0);
      if (!BI && b >= 96 && elect()) { load_box(P, sb, b, 4); load_box(P, sb, b, 5); }
      const uint32_t t1 = clk();
      if (RL) { rel(3); rel(4); }
      spin(t1, CD);
      __syncwarp();
      const uint32_t e1 = epoch(sb);
#pragma unroll 1
      for (int n = 0; n < 5; n++) {
        int lane;
        asm volatile("mov.u32 %0, %%laneid;" : "=r"(lane));
        if (n == 3) {
          fence_async_s();
          __syncwarp();
          if (lane == 0) mbar_arrive(sb + 8 * B_F);
          STAMPIF(lane == 0, 34);
          {
            mbar_wait(sb + 8 * (B_EW + 4), 0);
            const char* po = (char*)gout + (2 * tbase(b) + 64 * (lane & 28) + ((lane >> 1) & 1)) * 2 * D_ + (lane & 1) * 640;
            uint32_t v = 0;
#pragma unroll
            for (int r = 0; r < 5; r++) v ^= rdback(po + 128 * r);
            rdwait(sb, v);
            __syncwarp();
            if (lane == 0) flag_add(G, 8 * m + FL_X);
            STAMPIF(lane == 0, 94);
          }
          mbar_wait(sb + 8 * (B_BD + 2), 0);
          if (lane < 2) mbar_arrive(sb + 8 * (B_E1 + 5));
          if (m < 12) {
            rdwait(sb, rdback(G->cimg + s * 3072 + (m % 6) * 512 + (m < 6 ? 0 : 256) + 64 * (lane & 3)));
            __syncwarp();
            if (lane == 0) flag_add(G, FL_C + 8 * s);
            STAMPIF(lane == 0, 35);
          }
          if (elect()) {
            flag_wait(G, FL_C + 8 * s, e1 * 12);
            fence_async_g();
            STAMP(54);
            mbar_expect(sb + 8 * B_EXT, 6144);
            bulk_g2s(sb + SM_EXT, G->cimg + s * 3072, 6144, sb + 8 * B_EXT);
          }
          __syncwarp();
          mbar_wait(sb + 8 * B_ST2, 0);
        }
        const int j = n < 3 ? min(16 * n + (lane >> 1), 39) : min(16 * n - 8 + (lane >> 1), 59), k = j < 20 ? j : j < 40 ? j - 20 : j - 40;
        const uint2* pj = (const uint2*)(G->mv + 2048 * (e1 & 1) + 4 * (lane & 1) + 8 * (k + (j < 40 ? (j < 20 ? 160 : 120) + (m < 6 ? 0 : 20) : 200 + 20 * (s & 1))));
        uint4 a;
#pragma unroll 1
        for (int i = 0;; i++) {
          a = ld_tag2(pj);
          if (__all_sync(0xffffffffu, a.x != 0)) break;
          if (i > (1 << 20)) __trap();
        }
        const uint32_t d = sb + SM_CB + 64 * k + 8 * (lane & 1) + (j >= 20 && j < 40 ? 16 : 0);
        sts64(d, ~__byte_perm(a.x, a.y, 0x5410), ~__byte_perm(a.z, a.w, 0x5410));
        sts64(d + 32, ~__byte_perm(a.x, a.y, 0x7632), ~__byte_perm(a.z, a.w, 0x7632));
      }
      __syncwarp();
      if (lane == 0) mbar_arrive(sb + 8 * B_GB);
      STAMPIF(lane == 0, 39);
    }
    } else {
      STAMPIF(lane == 0, 62);
      int rw = sched_run<0>(P, In{gk, gv, gsk, gWg, gWu, gWd, gss}, sb, b, lane, __shfl_sync(0xffffffffu, t_0, 0));
      if (elect()) {
        STAMP(69);
        mbar_wait(sb + 8 * B_KVS, 0);
        if (ER) mbar_wait(sb + 8 * B_KV4, 0);
        STAMP(70);
        int rd = 0, c = 0;
#pragma unroll 1
        for (int it = 0; it < 20; it++) {
          load_w(P, sb, s, it);
          if ((PWM >> it) & 1) { l2_prefetch(gWg + (128 * rw + b) * F_, 2 * F_); l2_prefetch(gWu + (128 * rw + b) * F_, 2 * F_); rw++; }
          if ((PDM >> it) & 1) { l2_prefetch(gWd + (512 * rd + 4 * b) * D_, 8 * D_); rd++; }
          if (BI && it == BI && b >= 96) { mbar_wait(sb + 8 * (B_BD + 1), 0); load_box(P, sb, b, 4); load_box(P, sb, b, 5); }
          if (((STM >> it) & 1) && b < 96) {
            const int grp = m % 6;
            if (c == 4) mbar_wait(sb + 8 * (B_BD + 1), 0);
            if (c == 0) mbar_expect(sb + 8 * B_ST0, 40960);
#pragma unroll
            for (int j = 0; j < 2; j++, c++)
              tma2d(sb + (c < 2 ? SM_EXT : SM_RING + R_X - 8192) + 4096 * c, &P.mG + (grp & 1), 192 * s + 64 * (grp >> 1), (m < 6 ? 0 : 320) + 32 * c, sb + 8 * B_ST0);
          }
        }
#pragma unroll
        for (int k = 0; k < 10; k++) {
          const int st = (k + 5) % 6, pe = k < 4 ? k >> 1 : k & 1, ps = k < 4 ? k & 1 : k >> 1;
          mbar_wait(sb + 8 * (k < 6 ? B_E1 + st : B_EB + k - 6), 0);
          if (k == 2) mbar_arrive_remote(mapa(sb + 8 * B_P0, (b & 1) ^ 1));
          mbar_expect(sb + 8 * (B_FB + k), 24576);
          tma2d(ring + st * 32768 + 8192, &P.mD, 320 * (s & 1) + 64 * out_blk(s, ps), 192 * (s ^ pe), sb + 8 * (B_FB + k));
        }
      }
    }
  }
}

typedef CUresult (*EncFn)(CUtensorMap*, CUtensorMapDataType, cuuint32_t, void*, const cuuint64_t*, const cuuint64_t*, const cuuint32_t*, const cuuint32_t*,
                          CUtensorMapInterleave, CUtensorMapSwizzle, CUtensorMapL2promotion, CUtensorMapFloatOOBfill);
static void mkmap(EncFn enc, CUtensorMap* m, const void* p, int rank, const cuuint64_t* dims, const cuuint64_t* strides, const cuuint32_t* box, CUtensorMapSwizzle sw) {
  cuuint32_t es[5] = {1, 1, 1, 1, 1};
  CUresult r = enc(m, CU_TENSOR_MAP_DATA_TYPE_BFLOAT16, rank, (void*)p, dims, strides, box, es, CU_TENSOR_MAP_INTERLEAVE_NONE, sw,
                   CU_TENSOR_MAP_L2_PROMOTION_L2_128B, CU_TENSOR_MAP_FLOAT_OOB_FILL_NONE);
  if (r != CUDA_SUCCESS) fprintf(stderr, "tensor map encode failed: %d\n", (int)r);
}

extern "C" void kernel_launch(void* const* d_in, const int* in_sizes, int n_in, void* d_out, int out_size) {
  void* fn = nullptr;
  cudaDriverEntryPointQueryResult qr;
  cudaGetDriverEntryPoint("cuTensorMapEncodeTiled", &fn, cudaEnableDefault, &qr);
  EncFn enc = (EncFn)fn;
  Scr* G;
  cudaGetSymbolAddress((void**)&G, g_scr);
  Params P;
  { cuuint64_t d[] = {128, 16, 640}, st[] = {256, 4096}; cuuint32_t bx[] = {144, 16, 1}; mkmap(enc, &P.mS, d_in[4], 3, d, st, bx, CU_TENSOR_MAP_SWIZZLE_NONE); }
  { cuuint64_t d[] = {3840, 64, 10}, st[] = {7680, 64 * 7680}; cuuint32_t bx[] = {16, 64, 5}; mkmap(enc, &P.mWm, d_in[11], 3, d, st, bx, CU_TENSOR_MAP_SWIZZLE_32B); }
  { cuuint64_t d[] = {32, 20, 256, 8}, st[] = {64, 10240, 1280}; cuuint32_t bx[] = {40, 1, 9, 8}, bx2[] = {40, 1, 8, 8};
    mkmap(enc, &P.mK, d_in[1], 4, d, st, bx, CU_TENSOR_MAP_SWIZZLE_NONE); mkmap(enc, &P.mV, d_in[2], 4, d, st, bx2, CU_TENSOR_MAP_SWIZZLE_NONE); }
  { cuuint64_t d[] = {1536, 640}, st[] = {3072}; cuuint32_t bx[] = {64, 32};
    mkmap(enc, &P.mG, d_in[7], 2, d, st, bx, CU_TENSOR_MAP_SWIZZLE_128B); mkmap(enc, &P.mU, d_in[8], 2, d, st, bx, CU_TENSOR_MAP_SWIZZLE_128B); }
  { cuuint64_t d[] = {640, 1536}, st[] = {1280}; cuuint32_t bx[] = {64, 192}; mkmap(enc, &P.mD, d_in[9], 2, d, st, bx, CU_TENSOR_MAP_SWIZZLE_128B); }
  { cuuint64_t d[] = {64, 2, 8, 10, 128}, st[] = {1280, 256 * 1280, 128, 2560}; cuuint32_t bx[] = {64, 2, 8, 5, 1}; mkmap(enc, &P.mX, d_in[0], 5, d, st, bx, CU_TENSOR_MAP_SWIZZLE_128B); }
  cudaFuncSetAttribute(fused_kernel, cudaFuncAttributeMaxDynamicSharedMemorySize, SM_TOTAL + DEVSM);
  cudaLaunchConfig_t cfg = {};
  cfg.gridDim = dim3(128); cfg.blockDim = dim3(512); cfg.dynamicSmemBytes = SM_TOTAL + DEVSM; cfg.stream = cudaStreamPerThread;
  cudaLaunchAttribute at[1];
  at[0].id = cudaLaunchAttributeClusterDimension; at[0].val.clusterDim.x = 2; at[0].val.clusterDim.y = 1; at[0].val.clusterDim.z = 1;
  cfg.attrs = at; cfg.numAttrs = 1;
  cudaLaunchKernelEx(&cfg, fused_kernel, (const bf16*)d_in[1], (const bf16*)d_in[2], (const bf16*)d_in[3], (const bf16*)d_in[5], (const bf16*)d_in[10], G,
                     (const bf16*)d_in[7], (const bf16*)d_in[8], (const bf16*)d_in[9], (bf16*)d_out, (const bf16*)d_in[4], P);
}
```

```cpp
#include <cuda_runtime.h>
#include <cuda.h>
#include <cuda_bf16.h>
#include <stdio.h>
#include <stdint.h>
typedef __nv_bfloat16 bf16;
__device__ __forceinline__ uint32_t smem_u32(const void* p) { return (uint32_t)__cvta_generic_to_shared(p); }
__device__ __forceinline__ void mbar_init(uint32_t bar, int cnt) { asm volatile("mbarrier.init.shared::cta.b64 [%0], %1;" ::"r"(bar), "r"(cnt) : "memory"); }
__device__ __forceinline__ void mbar_expect(uint32_t bar, int bytes) { asm volatile("mbarrier.arrive.expect_tx.shared::cta.b64 _, [%0], %1;" ::"r"(bar), "r"(bytes) : "memory"); }
__device__ __forceinline__ void mbar_arrive(uint32_t bar) { asm volatile("mbarrier.arrive.shared::cta.b64 _, [%0];" ::"r"(bar) : "memory"); }
__device__ __forceinline__ void mbar_arrive_remote(uint32_t bar) { asm volatile("mbarrier.arrive.relaxed.cluster.shared::cluster.b64 _, [%0];" ::"r"(bar) : "memory"); }
__device__ __forceinline__ uint32_t mapa(uint32_t a, uint32_t cta) { uint32_t r; asm("mapa.shared::cluster.u32 %0, %1, %2;" : "=r"(r) : "r"(a), "r"(cta)); return r; }
__device__ __forceinline__ bool mbar_try(uint32_t bar, int parity) {
  uint32_t ok;
  asm volatile("{\n.reg .pred p;\nmbarrier.try_wait.parity.shared::cta.b64 p, [%1], %2;\nselp.u32 %0, 1, 0, p;\n}" : "=r"(ok) : "r"(bar), "r"(parity) : "memory");
  return ok;
}
__device__ __forceinline__ void mbar_wait(uint32_t bar, int parity) {
#pragma unroll 1
  for (int i = 0; i < (1 << 20); i++) { if (mbar_try(bar, parity)) return; }
  __trap();
}
__device__ __forceinline__ bool elect() {
  uint32_t p;
  asm volatile("{\n.reg .pred P;\nelect.sync _|P, 0xffffffff;\nselp.u32 %0, 1, 0, P;\n}" : "=r"(p));
  return p;
}
__device__ __forceinline__ void tma2d(uint32_t dst, const CUtensorMap* m, int c0, int c1, uint32_t bar) {
  asm volatile("cp.async.bulk.tensor.2d.shared::cluster.global.mbarrier::complete_tx::bytes [%0], [%1, {%3, %4}], [%2];" ::"r"(dst), "l"(m), "r"(bar), "r"(c0), "r"(c1) : "memory");
}
__device__ __forceinline__ void tma3d(uint32_t dst, const CUtensorMap* m, int c0, int c1, int c2, uint32_t bar) {
  asm volatile("cp.async.bulk.tensor.3d.shared::cluster.global.mbarrier::complete_tx::bytes [%0], [%1, {%3, %4, %5}], [%2];" ::"r"(dst), "l"(m), "r"(bar), "r"(c0), "r"(c1), "r"(c2) : "memory");
}
__device__ __forceinline__ void tma4d(uint32_t dst, const CUtensorMap* m, int c0, int c1, int c2, int c3, uint32_t bar) {
  asm volatile("cp.async.bulk.tensor.4d.shared::cluster.global.mbarrier::complete_tx::bytes [%0], [%1, {%3, %4, %5, %6}], [%2];" ::"r"(dst), "l"(m), "r"(bar), "r"(c0), "r"(c1), "r"(c2), "r"(c3) : "memory");
}
__device__ __forceinline__ void tma5d(uint32_t dst, const CUtensorMap* m, int c0, int c1, int c2, int c3, int c4, uint32_t bar) {
  asm volatile("cp.async.bulk.tensor.5d.shared::cluster.global.mbarrier::complete_tx::bytes [%0], [%1, {%3, %4, %5, %6, %7}], [%2];" ::"r"(dst), "l"(m), "r"(bar), "r"(c0), "r"(c1), "r"(c2), "r"(c3), "r"(c4) : "memory");
}
__device__ __forceinline__ void tma_store2d(const CUtensorMap* m, uint32_t src, int c0, int c1) {
  asm volatile("cp.async.bulk.tensor.2d.global.shared::cta.bulk_group [%0, {%2, %3}], [%1];" ::"l"(m), "r"(src), "r"(c0), "r"(c1) : "memory");
}
__device__ __forceinline__ void tma_store4d(const CUtensorMap* m, uint32_t src, int c0, int c1, int c2, int c3) {
  asm volatile("cp.async.bulk.tensor.4d.global.shared::cta.bulk_group [%0, {%2, %3, %4, %5}], [%1];" ::"l"(m), "r"(src), "r"(c0), "r"(c1), "r"(c2), "r"(c3) : "memory");
}
__device__ __forceinline__ void tma_prefetch2d(const CUtensorMap* m, int c0, int c1) {
  asm volatile("cp.async.bulk.prefetch.tensor.2d.L2.global [%0, {%1, %2}];" ::"l"(m), "r"(c0), "r"(c1) : "memory");
}
__device__ __forceinline__ void bulk_g2s(uint32_t dst, const void* src, int bytes, uint32_t bar) {
  asm volatile("cp.async.bulk.shared::cluster.global.mbarrier::complete_tx::bytes [%0], [%1], %2, [%3];" ::"r"(dst), "l"(src), "r"(bytes), "r"(bar) : "memory");
}
__device__ __forceinline__ void bulk_s2g(void* dst, uint32_t src, int bytes) {
  asm volatile("cp.async.bulk.global.shared::cta.bulk_group [%0], [%1], %2;" ::"l"(dst), "r"(src), "r"(bytes) : "memory");
}
__device__ __forceinline__ void cp16(uint32_t dst, const void* src) { asm volatile("cp.async.cg.shared.global [%0], [%1], 16;" ::"r"(dst), "l"(src) : "memory"); }
__device__ __forceinline__ void cp16z(uint32_t dst, const void* src, int n) { asm volatile("cp.async.cg.shared.global [%0], [%1], 16, %2;" ::"r"(dst), "l"(src), "r"(n) : "memory"); }
__device__ __forceinline__ void cp_arrive(uint32_t bar) { asm volatile("cp.async.mbarrier.arrive.noinc.shared::cta.b64 [%0];" ::"r"(bar) : "memory"); }
__device__ __forceinline__ void st_async4(uint32_t dst, const uint32_t* v, uint32_t bar) {
  asm volatile("st.async.weak.shared::cluster.mbarrier::complete_tx::bytes.v4.b32 [%0], {%1, %2, %3, %4}, [%5];" ::"r"(dst), "r"(v[0]), "r"(v[1]), "r"(v[2]), "r"(v[3]), "r"(bar) : "memory");
}
__device__ __forceinline__ void wg_fence() { asm volatile("wgmma.fence.sync.aligned;" ::: "memory"); }
__device__ __forceinline__ void wg_commit() { asm volatile("wgmma.commit_group.sync.aligned;" ::: "memory"); }
template <int N> __device__ __forceinline__ void wg_wait() { asm volatile("wgmma.wait_group.sync.aligned %0;" ::"n"(N) : "memory"); }
__device__ __forceinline__ uint64_t mkdesc(uint32_t addr, uint32_t lbo, uint32_t sbo, uint32_t swz) {
  return (uint64_t)((addr & 0x3FFFF) >> 4) | ((uint64_t)(lbo >> 4) << 16) | ((uint64_t)(sbo >> 4) << 32) | ((uint64_t)swz << 62);
}
__device__ __forceinline__ void ldsm4t(uint32_t* r, uint32_t a) {
  asm volatile("ldmatrix.sync.aligned.m8n8.x4.trans.shared.b16 {%0,%1,%2,%3}, [%4];" : "=r"(r[0]), "=r"(r[1]), "=r"(r[2]), "=r"(r[3]) : "r"(a) : "memory");
}
__device__ __forceinline__ void stsm4(uint32_t a, const uint32_t* r) {
  asm volatile("stmatrix.sync.aligned.m8n8.x4.shared.b16 [%0], {%1,%2,%3,%4};" ::"r"(a), "r"(r[0]), "r"(r[1]), "r"(r[2]), "r"(r[3]) : "memory");
}
__device__ __forceinline__ void stsm4t(uint32_t a, const uint32_t* r) {
  asm volatile("stmatrix.sync.aligned.m8n8.x4.trans.shared.b16 [%0], {%1,%2,%3,%4};" ::"r"(a), "r"(r[0]), "r"(r[1]), "r"(r[2]), "r"(r[3]) : "memory");
}
__device__ __forceinline__ void bar_sync(int id, int n) { asm volatile("bar.sync %0, %1;" ::"r"(id), "r"(n) : "memory"); }
__device__ __forceinline__ void bar_arrive(int id, int n) { asm volatile("bar.arrive %0, %1;" ::"r"(id), "r"(n) : "memory"); }
__device__ __forceinline__ uint32_t lds32(uint32_t a) { uint32_t v; asm volatile("ld.shared.b32 %0, [%1];" : "=r"(v) : "r"(a) : "memory"); return v; }
__device__ __forceinline__ uint2 lds64(uint32_t a) { uint2 v; asm volatile("ld.shared.v2.b32 {%0,%1}, [%2];" : "=r"(v.x), "=r"(v.y) : "r"(a) : "memory"); return v; }
__device__ __forceinline__ uint4 lds128(uint32_t a) { uint4 v; asm volatile("ld.shared.v4.b32 {%0,%1,%2,%3}, [%4];" : "=r"(v.x), "=r"(v.y), "=r"(v.z), "=r"(v.w) : "r"(a) : "memory"); return v; }
__device__ __forceinline__ void sts16(uint32_t a, uint32_t v) { asm volatile("st.shared.b16 [%0], %1;" ::"r"(a), "h"((uint16_t)v) : "memory"); }
__device__ __forceinline__ void sts32(uint32_t a, uint32_t v) { asm volatile("st.shared.b32 [%0], %1;" ::"r"(a), "r"(v) : "memory"); }
__device__ __forceinline__ void sts64(uint32_t a, uint32_t x, uint32_t y) { asm volatile("st.shared.v2.b32 [%0], {%1,%2};" ::"r"(a), "r"(x), "r"(y) : "memory"); }
__device__ __forceinline__ void sts128(uint32_t a, uint4 v) { asm volatile("st.shared.v4.b32 [%0], {%1,%2,%3,%4};" ::"r"(a), "r"(v.x), "r"(v.y), "r"(v.z), "r"(v.w) : "memory"); }
template<int TB> __device__ __forceinline__ void wgmma_rs_n128(float* d, const uint32_t* a, uint64_t db, int sd) {
  asm volatile("{\n.reg .pred p;\nsetp.ne.b32 p, %69, 0;\n"
    "wgmma.mma_async.sync.aligned.m64n128k16.f32.bf16.bf16 {%0, %1, %2, %3, %4, %5, %6, %7, %8, %9, %10, %11, %12, %13, %14, %15, %16, %17, %18, %19, %20, %21, %22, %23, %24, %25, %26, %27, %28, %29, %30, %31, %32, %33, %34, %35, %36, %37, %38, %39, %40, %41, %42, %43, %44, %45, %46, %47, %48, %49, %50, %51, %52, %53, %54, %55, %56, %57, %58, %59, %60, %61, %62, %63}, {%64, %65, %66, %67}, %68, p, 1, 1, %70;\n}"
    : "+f"(d[0]), "+f"(d[1]), "+f"(d[2]), "+f"(d[3]), "+f"(d[4]), "+f"(d[5]), "+f"(d[6]), "+f"(d[7]), "+f"(d[8]), "+f"(d[9]), "+f"(d[10]), "+f"(d[11]), "+f"(d[12]), "+f"(d[13]), "+f"(d[14]), "+f"(d[15]), "+f"(d[16]), "+f"(d[17]), "+f"(d[18]), "+f"(d[19]), "+f"(d[20]), "+f"(d[21]), "+f"(d[22]), "+f"(d[23]), "+f"(d[24]), "+f"(d[25]), "+f"(d[26]), "+f"(d[27]), "+f"(d[28]), "+f"(d[29]), "+f"(d[30]), "+f"(d[31]), "+f"(d[32]), "+f"(d[33]), "+f"(d[34]), "+f"(d[35]), "+f"(d[36]), "+f"(d[37]), "+f"(d[38]), "+f"(d[39]), "+f"(d[40]), "+f"(d[41]), "+f"(d[42]), "+f"(d[43]), "+f"(d[44]), "+f"(d[45]), "+f"(d[46]), "+f"(d[47]), "+f"(d[48]), "+f"(d[49]), "+f"(d[50]), "+f"(d[51]), "+f"(d[52]), "+f"(d[53]), "+f"(d[54]), "+f"(d[55]), "+f"(d[56]), "+f"(d[57]), "+f"(d[58]), "+f"(d[59]), "+f"(d[60]), "+f"(d[61]), "+f"(d[62]), "+f"(d[63])
    : "r"(a[0]), "r"(a[1]), "r"(a[2]), "r"(a[3]), "l"(db), "r"(sd), "n"(TB));
}

template<int TB> __device__ __forceinline__ void wgmma_rs_n160(float* d, const uint32_t* a, uint64_t db, int sd) {
  asm volatile("{\n.reg .pred p;\nsetp.ne.b32 p, %85, 0;\n"
    "wgmma.mma_async.sync.aligned.m64n160k16.f32.bf16.bf16 {%0, %1, %2, %3, %4, %5, %6, %7, %8, %9, %10, %11, %12, %13, %14, %15, %16, %17, %18, %19, %20, %21, %22, %23, %24, %25, %26, %27, %28, %29, %30, %31, %32, %33, %34, %35, %36, %37, %38, %39, %40, %41, %42, %43, %44, %45, %46, %47, %48, %49, %50, %51, %52, %53, %54, %55, %56, %57, %58, %59, %60, %61, %62, %63, %64, %65, %66, %67, %68, %69, %70, %71, %72, %73, %74, %75, %76, %77, %78, %79}, {%80, %81, %82, %83}, %84, p, 1, 1, %86;\n}"
    : "+f"(d[0]), "+f"(d[1]), "+f"(d[2]), "+f"(d[3]), "+f"(d[4]), "+f"(d[5]), "+f"(d[6]), "+f"(d[7]), "+f"(d[8]), "+f"(d[9]), "+f"(d[10]), "+f"(d[11]), "+f"(d[12]), "+f"(d[13]), "+f"(d[14]), "+f"(d[15]), "+f"(d[16]), "+f"(d[17]), "+f"(d[18]), "+f"(d[19]), "+f"(d[20]), "+f"(d[21]), "+f"(d[22]), "+f"(d[23]), "+f"(d[24]), "+f"(d[25]), "+f"(d[26]), "+f"(d[27]), "+f"(d[28]), "+f"(d[29]), "+f"(d[30]), "+f"(d[31]), "+f"(d[32]), "+f"(d[33]), "+f"(d[34]), "+f"(d[35]), "+f"(d[36]), "+f"(d[37]), "+f"(d[38]), "+f"(d[39]), "+f"(d[40]), "+f"(d[41]), "+f"(d[42]), "+f"(d[43]), "+f"(d[44]), "+f"(d[45]), "+f"(d[46]), "+f"(d[47]), "+f"(d[48]), "+f"(d[49]), "+f"(d[50]), "+f"(d[51]), "+f"(d[52]), "+f"(d[53]), "+f"(d[54]), "+f"(d[55]), "+f"(d[56]), "+f"(d[57]), "+f"(d[58]), "+f"(d[59]), "+f"(d[60]), "+f"(d[61]), "+f"(d[62]), "+f"(d[63]), "+f"(d[64]), "+f"(d[65]), "+f"(d[66]), "+f"(d[67]), "+f"(d[68]), "+f"(d[69]), "+f"(d[70]), "+f"(d[71]), "+f"(d[72]), "+f"(d[73]), "+f"(d[74]), "+f"(d[75]), "+f"(d[76]), "+f"(d[77]), "+f"(d[78]), "+f"(d[79])
    : "r"(a[0]), "r"(a[1]), "r"(a[2]), "r"(a[3]), "l"(db), "r"(sd), "n"(TB));
}

template<int TB> __device__ __forceinline__ void wgmma_rs_n192(float* d, const uint32_t* a, uint64_t db, int sd) {
  asm volatile("{\n.reg .pred p;\nsetp.ne.b32 p, %101, 0;\n"
    "wgmma.mma_async.sync.aligned.m64n192k16.f32.bf16.bf16 {%0, %1, %2, %3, %4, %5, %6, %7, %8, %9, %10, %11, %12, %13, %14, %15, %16, %17, %18, %19, %20, %21, %22, %23, %24, %25, %26, %27, %28, %29, %30, %31, %32, %33, %34, %35, %36, %37, %38, %39, %40, %41, %42, %43, %44, %45, %46, %47, %48, %49, %50, %51, %52, %53, %54, %55, %56, %57, %58, %59, %60, %61, %62, %63, %64, %65, %66, %67, %68, %69, %70, %71, %72, %73, %74, %75, %76, %77, %78, %79, %80, %81, %82, %83, %84, %85, %86, %87, %88, %89, %90, %91, %92, %93, %94, %95}, {%96, %97, %98, %99}, %100, p, 1, 1, %102;\n}"
    : "+f"(d[0]), "+f"(d[1]), "+f"(d[2]), "+f"(d[3]), "+f"(d[4]), "+f"(d[5]), "+f"(d[6]), "+f"(d[7]), "+f"(d[8]), "+f"(d[9]), "+f"(d[10]), "+f"(d[11]), "+f"(d[12]), "+f"(d[13]), "+f"(d[14]), "+f"(d[15]), "+f"(d[16]), "+f"(d[17]), "+f"(d[18]), "+f"(d[19]), "+f"(d[20]), "+f"(d[21]), "+f"(d[22]), "+f"(d[23]), "+f"(d[24]), "+f"(d[25]), "+f"(d[26]), "+f"(d[27]), "+f"(d[28]), "+f"(d[29]), "+f"(d[30]), "+f"(d[31]), "+f"(d[32]), "+f"(d[33]), "+f"(d[34]), "+f"(d[35]), "+f"(d[36]), "+f"(d[37]), "+f"(d[38]), "+f"(d[39]), "+f"(d[40]), "+f"(d[41]), "+f"(d[42]), "+f"(d[43]), "+f"(d[44]), "+f"(d[45]), "+f"(d[46]), "+f"(d[47]), "+f"(d[48]), "+f"(d[49]), "+f"(d[50]), "+f"(d[51]), "+f"(d[52]), "+f"(d[53]), "+f"(d[54]), "+f"(d[55]), "+f"(d[56]), "+f"(d[57]), "+f"(d[58]), "+f"(d[59]), "+f"(d[60]), "+f"(d[61]), "+f"(d[62]), "+f"(d[63]), "+f"(d[64]), "+f"(d[65]), "+f"(d[66]), "+f"(d[67]), "+f"(d[68]), "+f"(d[69]), "+f"(d[70]), "+f"(d[71]), "+f"(d[72]), "+f"(d[73]), "+f"(d[74]), "+f"(d[75]), "+f"(d[76]), "+f"(d[77]), "+f"(d[78]), "+f"(d[79]), "+f"(d[80]), "+f"(d[81]), "+f"(d[82]), "+f"(d[83]), "+f"(d[84]), "+f"(d[85]), "+f"(d[86]), "+f"(d[87]), "+f"(d[88]), "+f"(d[89]), "+f"(d[90]), "+f"(d[91]), "+f"(d[92]), "+f"(d[93]), "+f"(d[94]), "+f"(d[95])
    : "r"(a[0]), "r"(a[1]), "r"(a[2]), "r"(a[3]), "l"(db), "r"(sd), "n"(TB));
}

template<int TB> __device__ __forceinline__ void wgmma_rs_n32(float* d, const uint32_t* a, uint64_t db, int sd) {
  asm volatile("{\n.reg .pred p;\nsetp.ne.b32 p, %21, 0;\n"
    "wgmma.mma_async.sync.aligned.m64n32k16.f32.bf16.bf16 {%0, %1, %2, %3, %4, %5, %6, %7, %8, %9, %10, %11, %12, %13, %14, %15}, {%16, %17, %18, %19}, %20, p, 1, 1, %22;\n}"
    : "+f"(d[0]), "+f"(d[1]), "+f"(d[2]), "+f"(d[3]), "+f"(d[4]), "+f"(d[5]), "+f"(d[6]), "+f"(d[7]), "+f"(d[8]), "+f"(d[9]), "+f"(d[10]), "+f"(d[11]), "+f"(d[12]), "+f"(d[13]), "+f"(d[14]), "+f"(d[15])
    : "r"(a[0]), "r"(a[1]), "r"(a[2]), "r"(a[3]), "l"(db), "r"(sd), "n"(TB));
}

template<int TB> __device__ __forceinline__ void wgmma_rs_n64(float* d, const uint32_t* a, uint64_t db, int sd) {
  asm volatile("{\n.reg .pred p;\nsetp.ne.b32 p, %37, 0;\n"
    "wgmma.mma_async.sync.aligned.m64n64k16.f32.bf16.bf16 {%0, %1, %2, %3, %4, %5, %6, %7, %8, %9, %10, %11, %12, %13, %14, %15, %16, %17, %18, %19, %20, %21, %22, %23, %24, %25, %26, %27, %28, %29, %30, %31}, {%32, %33, %34, %35}, %36, p, 1, 1, %38;\n}"
    : "+f"(d[0]), "+f"(d[1]), "+f"(d[2]), "+f"(d[3]), "+f"(d[4]), "+f"(d[5]), "+f"(d[6]), "+f"(d[7]), "+f"(d[8]), "+f"(d[9]), "+f"(d[10]), "+f"(d[11]), "+f"(d[12]), "+f"(d[13]), "+f"(d[14]), "+f"(d[15]), "+f"(d[16]), "+f"(d[17]), "+f"(d[18]), "+f"(d[19]), "+f"(d[20]), "+f"(d[21]), "+f"(d[22]), "+f"(d[23]), "+f"(d[24]), "+f"(d[25]), "+f"(d[26]), "+f"(d[27]), "+f"(d[28]), "+f"(d[29]), "+f"(d[30]), "+f"(d[31])
    : "r"(a[0]), "r"(a[1]), "r"(a[2]), "r"(a[3]), "l"(db), "r"(sd), "n"(TB));
}

template<int TB> __device__ __forceinline__ void wgmma_rs_n96(float* d, const uint32_t* a, uint64_t db, int sd) {
  asm volatile("{\n.reg .pred p;\nsetp.ne.b32 p, %53, 0;\n"
    "wgmma.mma_async.sync.aligned.m64n96k16.f32.bf16.bf16 {%0, %1, %2, %3, %4, %5, %6, %7, %8, %9, %10, %11, %12, %13, %14, %15, %16, %17, %18, %19, %20, %21, %22, %23, %24, %25, %26, %27, %28, %29, %30, %31, %32, %33, %34, %35, %36, %37, %38, %39, %40, %41, %42, %43, %44, %45, %46, %47}, {%48, %49, %50, %51}, %52, p, 1, 1, %54;\n}"
    : "+f"(d[0]), "+f"(d[1]), "+f"(d[2]), "+f"(d[3]), "+f"(d[4]), "+f"(d[5]), "+f"(d[6]), "+f"(d[7]), "+f"(d[8]), "+f"(d[9]), "+f"(d[10]), "+f"(d[11]), "+f"(d[12]), "+f"(d[13]), "+f"(d[14]), "+f"(d[15]), "+f"(d[16]), "+f"(d[17]), "+f"(d[18]), "+f"(d[19]), "+f"(d[20]), "+f"(d[21]), "+f"(d[22]), "+f"(d[23]), "+f"(d[24]), "+f"(d[25]), "+f"(d[26]), "+f"(d[27]), "+f"(d[28]), "+f"(d[29]), "+f"(d[30]), "+f"(d[31]), "+f"(d[32]), "+f"(d[33]), "+f"(d[34]), "+f"(d[35]), "+f"(d[36]), "+f"(d[37]), "+f"(d[38]), "+f"(d[39]), "+f"(d[40]), "+f"(d[41]), "+f"(d[42]), "+f"(d[43]), "+f"(d[44]), "+f"(d[45]), "+f"(d[46]), "+f"(d[47])
    : "r"(a[0]), "r"(a[1]), "r"(a[2]), "r"(a[3]), "l"(db), "r"(sd), "n"(TB));
}

template<int TA, int TB> __device__ __forceinline__ void wgmma_ss_n192(float* d, uint64_t da, uint64_t db, int sd) {
  asm volatile("{\n.reg .pred p;\nsetp.ne.b32 p, %98, 0;\n"
    "wgmma.mma_async.sync.aligned.m64n192k16.f32.bf16.bf16 {%0, %1, %2, %3, %4, %5, %6, %7, %8, %9, %10, %11, %12, %13, %14, %15, %16, %17, %18, %19, %20, %21, %22, %23, %24, %25, %26, %27, %28, %29, %30, %31, %32, %33, %34, %35, %36, %37, %38, %39, %40, %41, %42, %43, %44, %45, %46, %47, %48, %49, %50, %51, %52, %53, %54, %55, %56, %57, %58, %59, %60, %61, %62, %63, %64, %65, %66, %67, %68, %69, %70, %71, %72, %73, %74, %75, %76, %77, %78, %79, %80, %81, %82, %83, %84, %85, %86, %87, %88, %89, %90, %91, %92, %93, %94, %95}, %96, %97, p, 1, 1, %99, %100;\n}"
    : "+f"(d[0]), "+f"(d[1]), "+f"(d[2]), "+f"(d[3]), "+f"(d[4]), "+f"(d[5]), "+f"(d[6]), "+f"(d[7]), "+f"(d[8]), "+f"(d[9]), "+f"(d[10]), "+f"(d[11]), "+f"(d[12]), "+f"(d[13]), "+f"(d[14]), "+f"(d[15]), "+f"(d[16]), "+f"(d[17]), "+f"(d[18]), "+f"(d[19]), "+f"(d[20]), "+f"(d[21]), "+f"(d[22]), "+f"(d[23]), "+f"(d[24]), "+f"(d[25]), "+f"(d[26]), "+f"(d[27]), "+f"(d[28]), "+f"(d[29]), "+f"(d[30]), "+f"(d[31]), "+f"(d[32]), "+f"(d[33]), "+f"(d[34]), "+f"(d[35]), "+f"(d[36]), "+f"(d[37]), "+f"(d[38]), "+f"(d[39]), "+f"(d[40]), "+f"(d[41]), "+f"(d[42]), "+f"(d[43]), "+f"(d[44]), "+f"(d[45]), "+f"(d[46]), "+f"(d[47]), "+f"(d[48]), "+f"(d[49]), "+f"(d[50]), "+f"(d[51]), "+f"(d[52]), "+f"(d[53]), "+f"(d[54]), "+f"(d[55]), "+f"(d[56]), "+f"(d[57]), "+f"(d[58]), "+f"(d[59]), "+f"(d[60]), "+f"(d[61]), "+f"(d[62]), "+f"(d[63]), "+f"(d[64]), "+f"(d[65]), "+f"(d[66]), "+f"(d[67]), "+f"(d[68]), "+f"(d[69]), "+f"(d[70]), "+f"(d[71]), "+f"(d[72]), "+f"(d[73]), "+f"(d[74]), "+f"(d[75]), "+f"(d[76]), "+f"(d[77]), "+f"(d[78]), "+f"(d[79]), "+f"(d[80]), "+f"(d[81]), "+f"(d[82]), "+f"(d[83]), "+f"(d[84]), "+f"(d[85]), "+f"(d[86]), "+f"(d[87]), "+f"(d[88]), "+f"(d[89]), "+f"(d[90]), "+f"(d[91]), "+f"(d[92]), "+f"(d[93]), "+f"(d[94]), "+f"(d[95])
    : "l"(da), "l"(db), "r"(sd), "n"(TA), "n"(TB));
}

template<int TA, int TB> __device__ __forceinline__ void wgmma_ss_n8(float* d, uint64_t da, uint64_t db, int sd) {
  asm volatile("{\n.reg .pred p;\nsetp.ne.b32 p, %6, 0;\n"
    "wgmma.mma_async.sync.aligned.m64n8k16.f32.bf16.bf16 {%0, %1, %2, %3}, %4, %5, p, 1, 1, %7, %8;\n}"
    : "+f"(d[0]), "+f"(d[1]), "+f"(d[2]), "+f"(d[3])
    : "l"(da), "l"(db), "r"(sd), "n"(TA), "n"(TB));
}

constexpr int S_ = 2048, D_ = 640, F_ = 1536;

struct Scr {
  uint32_t flag[32 * 8];
  uint32_t mv[2 * 2048];
  bf16 cimg[8 * 6 * 512];
  uint2 st2[S_];
  bf16 kvT[D_ * S_];
  bf16 zT[D_ * S_];
  bf16 AT[D_ * S_];
};
__device__ __align__(1024) Scr g_scr;
__device__ __forceinline__ uint32_t clk() { uint32_t c; asm volatile("mov.u32 %0, %%clock;" : "=r"(c) :: "memory"); return c; }
#define DEVSM 0
#define STAMP(id)
#define STAMPIF(c, id)
#define ITW 0
#define P3 0
constexpr int FL_X = 5, FL_C = 128;
#define CD 600
#define SD 1000

constexpr int SM_X = 1024, SM_EXT = 21504, SM_SMALL = 29696, SM_STAT = 30720, SM_CB = 32768, SM_RING = 34816, SM_TOTAL = SM_RING + 6 * 32768;
constexpr int SMALL_LN = 224, SMALL_RED = 320, SMALL_DUMMY = 1008, SMALL_E = 1012, SMALL_TS = 160, SMALL_H = 864;
constexpr int JOB_SZ = 10880, JOB_V = 5760, R_X = 5 * 32768, R_BOX = R_X + 12288;
constexpr int K1OFF = 4672, KSZ = 9472, CSZ = KSZ + 4224;
enum { B_KJ = 0, B_X = 5, B_EXT = 7, B_X1 = 8, B_P0 = 9, B_FB = 10, B_PEER = 20, B_RECV = 24, B_U = 28, B_A = 30, B_E0 = 35, B_FS = 37, B_BOX = 38, B_F = 44, B_ST0 = 45, B_GB = 46,
       B_F1 = 48, B_E1 = 54, B_EB = 60,
       B_OS = 64, B_OF = 72, B_Z = 80, B_K = 85, B_EW = 88, B_ST2 = 94, B_XF = 95, B_KV4 = 96, B_KVS = 98, B_BD = 99,
       B_B = 106, B_S = 112 };
__device__ __forceinline__ uint32_t chan_base(uint32_t sb, int ch) { return sb + SM_RING + (2 + (ch >> 1)) * 32768 + (ch & 1) * CSZ; }

struct Params { CUtensorMap mS, mX, mWm, mK, mV, mG, mU, mD; };

__device__ __forceinline__ void flag_add(Scr* G, int id) { asm volatile("red.relaxed.gpu.global.add.u32 [%0], 1;" ::"l"(G->flag + id) : "memory"); }
__device__ __forceinline__ uint32_t rdback(const void* p) { uint32_t v; asm volatile("ld.relaxed.gpu.global.u32 %0, [%1];" : "=r"(v) : "l"(p) : "memory"); return v; }
__device__ __forceinline__ void st_tag(uint2* p, uint32_t v, uint32_t t) { asm volatile("st.relaxed.gpu.global.v2.u32 [%0], {%1, %2};" ::"l"(p), "r"(v), "r"(t) : "memory"); }
__device__ __forceinline__ void spin(uint32_t t, uint32_t d) { if (d) while (clk() - t < d); }
__device__ __forceinline__ uint2 ld_tag(const uint2* p) { uint2 v; asm volatile("ld.relaxed.gpu.global.v2.u32 {%0, %1}, [%2];" : "=r"(v.x), "=r"(v.y) : "l"(p) : "memory"); return v; }
__device__ __forceinline__ uint4 ld_tag2(const uint2* p) {
  uint4 v;
  asm volatile("ld.relaxed.gpu.global.v4.u32 {%0, %1, %2, %3}, [%4];" : "=r"(v.x), "=r"(v.y), "=r"(v.z), "=r"(v.w) : "l"(p) : "memory");
  return v;
}
__device__ __forceinline__ void stg128(void* p, uint4 v) { asm volatile("st.global.v4.b32 [%0], {%1, %2, %3, %4};" ::"l"(p), "r"(v.x), "r"(v.y), "r"(v.z), "r"(v.w) : "memory"); }
__device__ __forceinline__ uint32_t ldv32(uint32_t a) { uint32_t v; asm volatile("ld.volatile.shared.b32 %0, [%1];" : "=r"(v) : "r"(a) : "memory"); return v; }
__device__ __forceinline__ uint4 ldv128(uint32_t a) { uint4 v; asm volatile("ld.volatile.shared.v4.b32 {%0,%1,%2,%3}, [%4];" : "=r"(v.x), "=r"(v.y), "=r"(v.z), "=r"(v.w) : "r"(a) : "memory"); return v; }
__device__ __forceinline__ bool mbar_test(uint32_t bar, int parity) {
  uint32_t ok;
  asm volatile("{\n.reg .pred P;\nmbarrier.test_wait.parity.shared::cta.b64 P, [%1], %2;\nselp.u32 %0, 1, 0, P;\n}" : "=r"(ok) : "r"(bar), "r"(parity) : "memory");
  return ok;
}
__device__ __forceinline__ uint32_t epoch(uint32_t sb) { return lds32(sb + SM_SMALL + SMALL_E); }
__device__ __forceinline__ void rdwait(uint32_t sb, uint32_t v) { sts32(sb + SM_SMALL + SMALL_DUMMY, v); }
__device__ __forceinline__ void fence_async_s() { asm volatile("fence.proxy.async.shared::cta;" ::: "memory"); }
__device__ __forceinline__ void fence_async_g() { asm volatile("fence.proxy.async.global;" ::: "memory"); }
__device__ __forceinline__ void bulk_done() { asm volatile("cp.async.bulk.commit_group;\n\tcp.async.bulk.wait_group 0;" ::: "memory"); }
__device__ __forceinline__ void flag_wait(Scr* G, int id, uint32_t target) {
  const uint32_t* p = G->flag + id;
#pragma unroll 1
  for (int i = 0; i < (1 << 20); i++) {
    uint32_t v;
    asm volatile("ld.relaxed.gpu.global.u32 %0, [%1];" : "=r"(v) : "l"(p) : "memory");
    if ((int)(v - target) >= 0) return;
  }
  __trap();
}
__device__ __forceinline__ void hint_wait(Scr* G, uint32_t sa, int id, uint32_t target) {
#pragma unroll 1
  for (int i = 0; i < (1 << 20); i++) {
    const uint32_t t = clk();
    cp16(sa + 4 * (id & 4), G->flag + (id & ~3));
    spin(t, P3);
    if ((int)(lds32(sa + 4 * (id & 7)) - target) >= 0) return;
  }
  __trap();
}
__device__ __forceinline__ int tbase(int pb) { return 127 - (32 * (pb >> 6) + 8 * (pb & 8) + 4 * ((2 * (pb & 3) - ((pb >> 2) & 1)) & 7) + ((pb >> 4) & 3)); }
__device__ __forceinline__ uint32_t hmul(uint32_t a, uint32_t b) { uint32_t d; asm("mul.rn.bf16x2 %0, %1, %2;" : "=r"(d) : "r"(a), "r"(b)); return d; }
__device__ __forceinline__ uint32_t hadd(uint32_t a, uint32_t b) { uint32_t d; asm("add.rn.bf16x2 %0, %1, %2;" : "=r"(d) : "r"(a), "r"(b)); return d; }
__device__ __forceinline__ uint32_t hsub(uint32_t a, uint32_t b) { uint32_t d; asm("sub.rn.bf16x2 %0, %1, %2;" : "=r"(d) : "r"(a), "r"(b)); return d; }
__device__ __forceinline__ uint32_t hfma(uint32_t a, uint32_t b, uint32_t c) { uint32_t d; asm("fma.rn.bf16x2 %0, %1, %2, %3;" : "=r"(d) : "r"(a), "r"(b), "r"(c)); return d; }
__device__ __forceinline__ uint32_t pack2(float lo, float hi) { uint32_t d; asm("cvt.rn.bf16x2.f32 %0, %1, %2;" : "=r"(d) : "f"(hi), "f"(lo)); return d; }
__device__ __forceinline__ float blo(uint32_t v) { return __uint_as_float(v << 16); }
__device__ __forceinline__ float bhi(uint32_t v) { return __uint_as_float(v & 0xffff0000u); }
__device__ __forceinline__ uint32_t tagged(uint32_t v, uint32_t e1) { return (v & ~1u) | (e1 & 1); }
__device__ __forceinline__ float rbf(float v) { return blo(pack2(v, 0.f)); }
__device__ __forceinline__ float sdev(float var) { float d; asm("sqrt.approx.ftz.f32 %0, %1;" : "=f"(d) : "f"(rbf(rbf(var) + 1e-5f))); return rbf(d); }
template <int N> __device__ __forceinline__ void bfly(float* v, int mask, bool up) {
#pragma unroll
  for (int i = 0; i < N / 2; i++) {
    float send = up ? v[i] : v[i + N / 2], keep = up ? v[i + N / 2] : v[i];
    v[i] = keep + __shfl_xor_sync(0xffffffffu, send, mask);
  }
}
#define BX3 2
#define XO 0
#define ZA 0
#define XE 0
#define EA 1
#define AD 300
#define XP 0
#define DR 0
#define KVV 0
#define OPQ 4
#define SL 1
#define UT 5
#define UD0 1000
#define EH 1
#define NA 16
#define BS 0
#define UF 1
#define ZS 1
#define LV 5
#define TG 2
#define RL 2
#define OF 1
#define OH 16
#define ES 2
#define SI 1
#define RH 5
#define NS 0
#define AT0 14200
#define AT1 0
#define BI 4
#define PC 1
#define PG 1
#define UD2 5000
#define GT 0x111
#define K3 0
#define KW 0
#define RX 0
#define MG 0
__device__ __forceinline__ bool mod_first(int b) { return MG ? (b & 3) != 3 : !(b & 1) || !(b & 6); }
__device__ __forceinline__ int mod_grp(int b, int j) {
  if (MG) {
  const int m = b >> 3, s = b & 7, t = 16 * (j ? min(s, 6) : s - (s >> 2)) + m, v = j ? s : (t * 43) >> 10;
  if (j == 2) return b + 112;
  return v < 4 ? (v == 3 ? 160 : 40 * v) + (j ? 24 + m : t - 24 * v) : t + (t < 104 ? 56 : 96);
  }
  const int m = b >> 3, s = b & 7, t = 16 * s + m, v = j ? (t * 43) >> 10 : s >> 1;
  if (j == 2) return b + 112;
  if (j == 0 && s == 1) return m + (m < 8 ? 152 : 192);
  return v < 4 ? (v == 3 ? 160 : 40 * v) + (j ? 16 + t - 24 * v : m) : t + 24;
}

__device__ __forceinline__ void kv_load(const bf16* gk, const bf16* gv, const bf16* gs, uint32_t sb, int b, int r, int tid) {
  const int row = tid >> 2, col = 128 * r + 32 * (b & 3);
  const uint32_t a = sb + SM_RING + r * JOB_SZ + (row >> 3) * 80 + (tid & 3) * 16, ak = a + (row & 7) * 720, av = a + (row & 7) * 640 + JOB_V;
  const int o = (64 * (b >> 2) + row) * D_ + col + 8 * (tid & 3);
  cp16(ak + 80, gk + o);
  cp16(ak + 400, gk + o + 32 * D_);
  cp16(av, gv + o);
  cp16(av + 320, gv + o + 32 * D_);
  if (tid < 12) cp16z(ak + 3600, gk + (b < 4 ? o : o - 3 * D_), b < 4 ? 0 : 16);
  else if (tid >= 112) cp16(sb + SM_CB + 256 * r + 16 * (tid - 112), gs + 4 * col + 8 * (tid - 112));
}
__device__ __forceinline__ void load_kv(const Params& P, const bf16* gs, uint32_t sb, int b, int r) {
  const uint32_t a = sb + SM_RING + r * JOB_SZ, bar = sb + 8 * (B_B + r);
  const int cg = 4 * r + (b & 3);
  mbar_expect(bar, JOB_SZ + 256);
  tma4d(a, &P.mK, 0, cg, 8 * (b >> 2) - 1, 0, bar);
  tma4d(a + JOB_V, &P.mV, 0, cg, 8 * (b >> 2), 0, bar);
  bulk_g2s(sb + SM_CB + 256 * r, gs + 128 * cg, 256, bar);
}
__device__ __forceinline__ uint4* kv_dst(Scr* G, int b, int r, int tid) {
  return (uint4*)(G->kvT + (128 * r + 32 * (b & 3) + 8 * (tid >> 5) + 2 * (tid & 3)) * S_ + 2040 - 64 * (b >> 2)) - ((tid >> 2) & 7);
}
__device__ __forceinline__ void kv_job(Scr* G, uint32_t sb, int b, int r, int tid, uint32_t e1) {
  const int cp = 4 * (tid >> 5) + (tid & 3);
  const uint32_t ka = sb + SM_RING + r * JOB_SZ + ((tid >> 2) & 7) * 80 + cp * 4;
  mbar_wait(sb + 8 * (B_B + r), 0);
  STAMPIF(tid == 0, 56 + r);
  uint32_t kk[11], vv[8], o[8];
  if (KVV) {
#pragma unroll
    for (int i = 0; i < 11; i++) kk[i] = ldv32(ka + 720 * ((i + 5) & 7) + 80 * ((i + 5) >> 3));
#pragma unroll
    for (int i = 0; i < 8; i++) vv[i] = ldv32(ka + JOB_V + 640 * i);
  }
  const uint4 sk = ldv128(sb + SM_CB + 256 * r + 16 * cp);
  const uint32_t s0 = __byte_perm(sk.x, sk.z, 0x5410), s1 = __byte_perm(sk.x, sk.z, 0x7632), s2 = __byte_perm(sk.y, sk.w, 0x5410), s3 = __byte_perm(sk.y, sk.w, 0x7632);
#pragma unroll
  for (int i = 0; i < 11; i++) if (!KVV) kk[i] = lds32(ka + 720 * ((i + 5) & 7) + 80 * ((i + 5) >> 3));
#pragma unroll
  for (int i = 0; i < 8; i++) {
    uint32_t v = KVV ? vv[i] : lds32(ka + JOB_V + 640 * i);
    o[i] = hmul(hfma(kk[i + 3], s0, hfma(kk[i + 2], s1, hfma(kk[i + 1], s2, hmul(kk[i], s3)))), v);
  }
  uint4* dst = kv_dst(G, b, r, tid);
  dst[0] = make_uint4(__byte_perm(o[7], o[6], 0x5410), __byte_perm(o[5], o[4], 0x5410), __byte_perm(o[3], o[2], 0x5410), tagged(__byte_perm(o[1], o[0], 0x5410), e1));
  dst[256] = make_uint4(__byte_perm(o[7], o[6], 0x7632), __byte_perm(o[5], o[4], 0x7632), __byte_perm(o[3], o[2], 0x7632), tagged(__byte_perm(o[1], o[0], 0x7632), e1));
  if (tid == 0) { sts32(sb + SM_SMALL + SMALL_TS + 4 * r, clk()); mbar_arrive(sb + 8 * (B_KJ + r)); }
}
__device__ __forceinline__ void u_wait(uint4& a, uint4& c, const void* p) {
  asm volatile("{\n.reg .pred p;\n.reg .b32 t, n;\nmov.b32 n, 0;\n"
               "L0:\nlop3.b32 t, %3, %7, 1, 0x80;\nsetp.eq.b32 p, t, 0;\nvote.sync.any.pred p, p, 0xffffffff;\n@!p bra.uni L1;\n"
               "ld.relaxed.gpu.global.v4.u32 {%0, %1, %2, %3}, [%8];\nld.relaxed.gpu.global.v4.u32 {%4, %5, %6, %7}, [%8+2048];\n"
               "add.u32 n, n, 1;\nsetp.lt.u32 p, n, 1000000;\n@p bra.uni L0;\ntrap;\nL1:\n}"
               : "+r"(a.x), "+r"(a.y), "+r"(a.z), "+r"(a.w), "+r"(c.x), "+r"(c.y), "+r"(c.z), "+r"(c.w) : "l"(p) : "memory");
}
__device__ __forceinline__ void u_fix(uint4 a, uint4 c, const void* p, uint32_t sa, uint32_t e1) {
  asm volatile("{\n.reg .pred p;\n.reg .b32 t, n;\nmov.b32 n, 0;\n"
               "lop3.b32 t, %3, %7, %10, 0x81;\nand.b32 t, t, 1;\nsetp.eq.b32 p, t, 0;\nvote.sync.any.pred p, p, 0xffffffff;\n@!p bra.uni L2;\n"
               "L0:\nld.relaxed.gpu.global.v4.u32 {%0, %1, %2, %3}, [%8];\nld.relaxed.gpu.global.v4.u32 {%4, %5, %6, %7}, [%8+2048];\n"
               "lop3.b32 t, %3, %7, %10, 0x81;\nand.b32 t, t, 1;\nsetp.eq.b32 p, t, 0;\nvote.sync.any.pred p, p, 0xffffffff;\n@!p bra.uni L1;\n"
               "add.u32 n, n, 1;\nsetp.lt.u32 p, n, 1000000;\n@p bra.uni L0;\ntrap;\n"
               "L1:\nst.shared.v4.b32 [%9], {%0, %1, %2, %3};\nst.shared.v4.b32 [%9+2048], {%4, %5, %6, %7};\nL2:\n}"
               : "+r"(a.x), "+r"(a.y), "+r"(a.z), "+r"(a.w), "+r"(c.x), "+r"(c.y), "+r"(c.z), "+r"(c.w) : "l"(p), "r"(sa), "r"(e1) : "memory");
}
__device__ __forceinline__ void stv128(uint32_t a, uint4 v) { asm volatile("st.volatile.shared.v4.b32 [%0], {%1,%2,%3,%4};" ::"r"(a), "r"(v.x), "r"(v.y), "r"(v.z), "r"(v.w) : "memory"); }
__device__ __forceinline__ uint64_t box_a(uint32_t sb) { return mkdesc(sb + SM_RING + R_BOX, 256, 1024, 3); }
__device__ __forceinline__ uint64_t box_b(uint32_t sb) { return mkdesc(sb + SM_STAT, 64, 128, 0); }
__device__ __forceinline__ void mod_put(Scr* G, uint32_t sb, const float* a, int b, int j, uint32_t e1, int tid) {
  const uint32_t red = sb + SM_STAT + 1536;
  if ((tid & 3) == tid >> 6) sts64(red + 32 * ((tid >> 2) & 7) + 8 * (tid >> 5), __float_as_uint((tid & 32) ? a[1] : a[0]), __float_as_uint((tid & 32) ? a[3] : a[2]));
  bar_sync(j > (BX3 >= 3) ? 4 : 5, 128);
  if (tid < 16) {
    const uint4 u = lds128(red + 32 * (tid & 7)), v = lds128(red + 32 * (tid & 7) + 16);
    asm volatile("" : "+r"(b));
    const int grp = mod_grp(b, j);
    const uint32_t one = (grp >= 40 && grp < 80) || (grp >= 160 && grp < 200) ? 0x3f803f80u : 0u;
    const float lo = __uint_as_float(u.x) + __uint_as_float(u.z) + __uint_as_float(v.x) + __uint_as_float(v.z);
    const float hi = __uint_as_float(u.y) + __uint_as_float(u.w) + __uint_as_float(v.y) + __uint_as_float(v.w);
    asm volatile("st.relaxed.gpu.global.u32 [%0], %1;" ::"l"(G->mv + 8 * grp + 256 * (tid & 8) + (tid & 7)),
                 "r"(((tid >> 3) ^ e1) & 1 ? 0 : ~hadd(pack2(lo, hi), one)) : "memory");
  }
}
__device__ __forceinline__ void mod_box(Scr* G, uint32_t sb, int b, int j, uint32_t e1, int tid) {
  float a[4];
  uint64_t da = box_a(sb), db = box_b(sb);
#pragma unroll
  for (int h = 0; h < 2; h++) {
    mbar_wait(sb + 8 * (B_BOX + 2 * j + h), 0);
    STAMPIF(tid == 0 && j == 0, 71 + h);
    wg_fence();
#pragma unroll
    for (int n = 5 * h; n < 5 * h + 5; n++) wgmma_ss_n8<1, 0>(a, da + 128 * n, db + 8 * n, n != 0);
    wg_commit();
  }
  wg_wait<0>();
#pragma unroll
  for (int i = 0; i < 4; i++) asm volatile("" : "+f"(a[i])::"memory");
  mod_put(G, sb, a, b, j, e1, tid);
}
__device__ __forceinline__ void a_check(uint32_t sa, const void* ga, uint32_t tag) {
  asm volatile("{\n.reg .pred p;\n.reg .b32 t, n, x, y, z;\n.reg .b64 g;\n"
               "ld.shared.b32 t, [%0];\nlop3.b32 t, t, %2, 1, 0x28;\nsetp.ne.b32 p, t, 0;\nvote.sync.any.pred p, p, 0xffffffff;\n@!p bra.uni L1;\nmov.b32 n, 0;\n"
               "L0:\nld.relaxed.gpu.global.b32 t, [%1];\nlop3.b32 t, t, %2, 1, 0x28;\nsetp.ne.b32 p, t, 0;\nvote.sync.any.pred p, p, 0xffffffff;\n@!p bra.uni L2;\n"
               "add.u32 n, n, 1;\nsetp.lt.u32 p, n, 1000000;\n@p bra.uni L0;\ntrap;\nL2:\n"
               "and.b64 g, %1, -32;\nand.b32 n, %0, -32;\n"
               "ld.relaxed.gpu.global.v4.b32 {t, x, y, z}, [g];\nst.shared.v4.b32 [n], {t, x, y, z};\n"
               "ld.relaxed.gpu.global.v4.b32 {t, x, y, z}, [g+16];\nst.shared.v4.b32 [n+16], {t, x, y, z};\n"
               "fence.proxy.async.shared::cta;\nbar.warp.sync 0xffffffff;\nL1:\n}" ::"r"(sa), "l"(ga), "r"(tag) : "memory");
}
__device__ __forceinline__ void z_wait(uint4& a, uint4& c, uint32_t* v, const void* G, uint32_t zo, uint32_t co, uint32_t e1) {
  asm volatile("{\n.reg .pred p;\n.reg .b32 t, n;\n.reg .b64 x, y;\nmov.b32 n, 0;\n"
               "L0:\nlop3.b32 t, %3, %7, %14, 0x81;\nand.b32 t, t, 1;\nmin.u32 t, t, %8;\nmin.u32 t, t, %9;\nmin.u32 t, t, %10;\nmin.u32 t, t, %11;\n"
               "setp.eq.b32 p, t, 0;\nvote.sync.any.pred p, p, 0xffffffff;\n@!p bra.uni L1;\n"
               "shr.u32 t, n, 31;\nadd.u32 t, t, %12;\ncvt.u64.u32 x, t;\nadd.s64 x, x, %15;\nshr.u32 t, n, 30;\nadd.u32 t, t, %13;\ncvt.u64.u32 y, t;\nadd.s64 y, y, %15;\n"
               "ld.relaxed.gpu.global.v4.u32 {%0, %1, %2, %3}, [x];\nld.relaxed.gpu.global.v4.u32 {%4, %5, %6, %7}, [x+32768];\n"
               "ld.relaxed.gpu.global.u32 %8, [y];\nld.relaxed.gpu.global.u32 %9, [y+1280];\nld.relaxed.gpu.global.u32 %10, [y+2560];\nld.relaxed.gpu.global.u32 %11, [y+5120];\n"
               "add.u32 n, n, 1;\nsetp.lt.u32 p, n, 1000000;\n@p bra.uni L0;\ntrap;\nL1:\n}"
               : "+r"(a.x), "+r"(a.y), "+r"(a.z), "+r"(a.w), "+r"(c.x), "+r"(c.y), "+r"(c.z), "+r"(c.w), "+r"(v[0]), "+r"(v[1]), "+r"(v[2]), "+r"(v[3])
               : "r"(zo), "r"(co), "r"(e1), "l"(G) : "memory");
}
__device__ __forceinline__ void load_x(const Params& P, uint32_t sb, int b, int h) {
  const uint32_t bar = sb + 8 * (B_X + h);
  mbar_expect(bar, 10240);
  tma5d(sb + SM_X + h * 10240, &P.mX, 0, 0, 0, 5 * h, tbase(b), bar);
}
__device__ __forceinline__ uint32_t x_addr(uint32_t sb, int w, int lane) {
  const int rho = 15 - (4 * (lane >> 3) + 2 * (lane & 1) + ((lane >> 1) & 1));
  return sb + SM_X + (w >> 1) * 2048 + rho * 128 + (((2 * (w & 1) + (lane & 4)) ^ (rho & 7)) << 4);
}
__device__ __forceinline__ void ln1_half(uint32_t sb, int tid, int h, int dry, float& s1, float& s2, float& pv) {
  const uint32_t xr = sb + SM_X + 16 * tid;
  float s3 = 0.f;
  if (ITW == 8) STAMPIF(tid == 0, 102 + 2 * h);
  if (!dry) mbar_wait(sb + 8 * (B_X + h), 0);
  STAMPIF(tid == 0, 25);
  if (ITW == 8) STAMPIF(tid == 0, 103 + 2 * h);
  uint4 v[5];
#pragma unroll
  for (int n = 0; n < 5; n++) v[n] = n < LV ? ldv128(xr + 10240 * h + 2048 * n) : lds128(xr + 10240 * h + 2048 * n);
  pv = blo(ldv32(xr & ~127u));
#pragma unroll
  for (int n = 0; n < 5; n++) {
    const uint32_t u[4] = {v[n].x, v[n].y, v[n].z, v[n].w};
#pragma unroll
    for (int j = 0; j < 4; j++) {
      const float a = blo(u[j]) - pv, c = bhi(u[j]) - pv;
      s1 += a + c; s2 += a * a; s3 += c * c;
    }
  }
  s2 += s3;
}
__device__ __forceinline__ void ln1_end(uint32_t sb, int tid, float s1, float s2, float pv) {
#pragma unroll
  for (int o = 1; o < 8; o <<= 1) { s1 += __shfl_xor_sync(0xffffffffu, s1, o); s2 += __shfl_xor_sync(0xffffffffu, s2, o); }
  if (ITW == 8) { asm volatile("" : "+f"(s1), "+f"(s2)); STAMPIF(tid == 0, 107); }
  const float mu = s1 * (1.f / D_), var = fmaxf(s2 * (1.f / D_) - mu * mu, 0.f);
  float rs;
  asm("rcp.approx.ftz.f32 %0, %1;" : "=f"(rs) : "f"(sdev(var)));
  const int i = 15 - (tid >> 3), j = tid & 7;
  if (j < 2) sts16(sb + SM_SMALL + SMALL_LN + 32 * j + 16 * (i & 1) + (i & 14), pack2(j ? rs : pv + mu, 0.f));
  if (ITW == 8) STAMPIF(tid == 0, 108);
  bar_sync(5, 128);
  STAMPIF(tid == 0, 75);
}
__device__ __forceinline__ void load_box(const Params& P, uint32_t sb, int b, int cls) {
  const uint32_t bar = sb + 8 * (B_BOX + cls);
  mbar_expect(bar, 10240);
  tma3d(sb + SM_RING + R_BOX + 10240 * (cls & 1), &P.mWm, 16 * mod_grp(b, cls >> 1), 0, 5 * (cls & 1), bar);
}
__device__ __forceinline__ void load_ssm(const Params& P, uint32_t sb, int b, int r) {
  const uint32_t bar = sb + 8 * (B_S + r);
  mbar_expect(bar, 16 * 288);
  tma3d(chan_base(sb, r) + 128, &P.mS, 0, 0, 128 * r + b, bar);
}
__device__ __forceinline__ void k1_job(uint32_t sb, int r, int tid, uint32_t dv) {
  const uint32_t a0 = chan_base(sb, r) + 128 + 16 * tid + 32 * (tid >> 4);
  mbar_wait(sb + 8 * (B_S + r), 0);
  uint4 v[2];
  uint32_t pv[2];
#pragma unroll
  for (int n = 0; n < 2; n++) { v[n] = lds128(a0 + 2304 * n); pv[n] = lds32(a0 + 2304 * n - ((tid & 15) ? 4 : 36)); }
  if (tid == 0) { v[0].x = hadd(v[0].x, dv); sts32(a0, v[0].x); }
#pragma unroll
  for (int n = 0; n < 2; n++)
    sts128(a0 + 2304 * n + K1OFF, make_uint4(__byte_perm(pv[n], v[n].x, 0x5432), __byte_perm(v[n].x, v[n].y, 0x5432), __byte_perm(v[n].y, v[n].z, 0x5432), __byte_perm(v[n].z, v[n].w, 0x5432)));
}

__device__ __forceinline__ int out_blk(int s, int p) { const int t = p + (s >> 1); return t < 5 ? t : t - 5; }
__device__ __forceinline__ void l2_prefetch(const void* p, int bytes) { asm volatile("cp.async.bulk.prefetch.L2.global [%0], %1;" ::"l"(p), "r"(bytes) : "memory"); }
__device__ __forceinline__ void pf_line(const void* p) { asm volatile("prefetch.global.L2 [%0];" ::"l"(p) : "memory"); }
__device__ __forceinline__ int role(int bx) {
  const int c = bx >> 1, d = c - 36, q = (d * 37) >> 8, k = d - 7 * q;
  const int rank = c < 4 ? 12 + c : c < 36 ? ((c - 4) & 7) * 8 + ((c - 4) >> 3) : (k ? k + 1 : 0) * 8 + 4 + q;
  return 8 * (rank & 15) + 2 * (rank >> 4) + (bx & 1);
}
enum { K_KV, K_SSM, K_BOX, K_PW, K_PD, K_PKV, K_PSSM, K_PBOX, K_W, K_X, K_ST, K_END = 15 };
#define E(t, bar, kind, r) ((t) << 16 | (bar) << 8 | (kind) << 4 | (r))
#define SCHED E(2800, 255, K_BOX, 0), E(0, 255, K_BOX, 1), E(3700, 255, K_KV, 2), E(4400, 255, K_SSM, 2), E(4800, 255, XO ? K_X : K_KV, XO ? 0 : 3), E(5500, 255, XO ? K_KV : K_X, XO ? 3 : 0), \
              E(6400, 255, XP ? K_X : K_KV, XP ? 1 : 4), E(7100, 255, XP ? K_KV : K_X, XP ? 4 : 1), E(7900, 255, K_SSM, 3), E(8300, 255, K_SSM, 4), E(8600, 255, K_BOX, 2), E(9500, 255, K_PW, 0), \
              E(10100, 255, K_BOX, 3)
#define XPF 2
#define XBOTH 0
#define XI 8
#define XW 0
#define PWM 0x3c
#define STM 0x7c0
#define PDM 0x3800
#define KV4C 3
#define CVT 1
#define UPOS 4
#define UD 1000
#define UD1 6400
#define NP 6
#define NQ 6
#define SPOS(i) (2 * ((i) - NQ) + 13)
#define LH0 4
#define LH1 5
#define LM 0
#define PT 1
#define ZP 0
#define BD 1200
#define ER 0
#define PL 1
#define K1N 1
#define ZD 10100
#define PK 0
#define ZF 1
constexpr uint32_t kSched[] = {SCHED, E(0, 255, K_END, 0)};
struct In { const bf16 *k, *v, *sk, *Wg, *Wu, *Wd, *ss; };
__device__ __forceinline__ void load_w(const Params& P, uint32_t sb, int s, int it) {
  const int st = it % 5;
  mbar_wait(sb + 8 * (B_E1 + st), (it / 5) & 1);
  const uint32_t a = sb + SM_RING + st * 32768 + 8192, fb = sb + 8 * (B_F1 + st);
  mbar_expect(fb, 24576);
#pragma unroll
  for (int j = 0; j < 3; j++) {
    tma2d(a + 8192 * j, &P.mG, 192 * s + 64 * j, 32 * it, fb);
    tma2d(a + 8192 * j + 4096, &P.mU, 192 * s + 64 * j, 32 * it, fb);
  }
}

template <int I> __device__ __forceinline__ int sched_run(const Params& P, const In& in, uint32_t sb, int b, int lane, uint32_t t_0) {
  constexpr uint32_t e = kSched[I];
  constexpr int kind = (e >> 4) & 15, r = e & 15, bar = (e >> 8) & 255;
  if constexpr (kind == K_END) return 0;
  else {
    if constexpr ((e >> 16) != 0) while (clk() - t_0 < (e >> 16));
    if (bar != 255) mbar_wait(sb + 8 * bar, 0);
    if (kind == K_BOX && r == 2) mbar_wait(sb + 8 * B_BD, 0);
    if (kind == K_PKV) {
      const bf16* kvp = (lane < 16 ? in.k : in.v) + (16 * b + (lane & 15)) * D_ + 128 * r;
      pf_line(kvp); pf_line(kvp + 64);
    } else {
      if (elect()) {
        if (kind == K_KV) load_kv(P, in.sk, sb, b, r);
        if (kind == K_X) load_x(P, sb, b, r);
        if (kind == K_SSM) load_ssm(P, sb, b, r);
        if (kind == K_BOX && (r > 1 || mod_first(b))) load_box(P, sb, b, r);
        if (kind == K_PW) { l2_prefetch(in.Wg + (128 * r + b) * F_, 2 * F_); l2_prefetch(in.Wu + (128 * r + b) * F_, 2 * F_); }
        if (kind == K_PSSM) l2_prefetch(in.ss + (128 * r + b) * S_, 4096);
      }
      __syncwarp();
    }
    return sched_run<I + 1>(P, in, sb, b, lane, t_0) + (kind == K_PW);
  }
}

__global__ void __launch_bounds__(512, 1) fused_kernel(const bf16* __restrict__ gk, const bf16* __restrict__ gv, const bf16* __restrict__ gsk,
                                                       const bf16* __restrict__ gD, const bf16* __restrict__ gc, Scr* G, const bf16* gWg, const bf16* gWu,
                                                       const bf16* gWd, bf16* gout, const bf16* gss, const __grid_constant__ Params P) {
  extern __shared__ __align__(1024) char smem_raw[];
  const uint32_t sb = smem_u32(smem_raw), ring = sb + SM_RING;
  const int b = role(blockIdx.x), m = b >> 3, s = b & 7;
  const uint32_t t_0 = clk();
  const int wg = __shfl_sync(0xffffffffu, threadIdx.x >> 7, 0);
  const int tid = threadIdx.x & 127, lane = tid & 31;
  const int w = __shfl_sync(0xffffffffu, tid >> 5, 0);
  uint32_t e1 = 0;
  if (wg < 2) {
    kv_load(gk, gv, gsk, sb, b, wg, tid);
    if (TG == 1) e1 = rdback(G->flag + 8 * m + 4);
  } else {
    if (wg == 2) {
      if (tid < 40) {
        int c = tid & 7;
        sts128(chan_base(sb, tid >> 3) + (c < 2 ? 80 + c * K1OFF : KSZ + 4096 + (c - 2) * 16), make_uint4(0, 0, 0, 0));
      }
    }
    if (elect()) {
      const int j = 4 * (3 - wg) + w - 1;
      if (j < 4) asm volatile("prefetch.tensormap [%0];" ::"l"(&P.mX + j) : "memory");
      if (j < 0) {
#pragma unroll
        for (int i = 0; i < 5; i++) mbar_init(sb + 8 * (B_S + i), 1);
        fence_async_s();
        if (XPF > 0) load_ssm(P, sb, b, 0);
        if (XPF > 1) load_ssm(P, sb, b, 1);
      } else {
        const int c = j < 3 ? 1 : j < 4 ? 2 : 4;
#pragma unroll
        for (int i = 0; i < 16; i++) mbar_init(sb + 128 * j + 8 * i, i < 10 || j < 6 ? c : i < 12 ? 128 : 1);
      }
    }
    fence_async_s();
  }
  __syncthreads();
  STAMPIF(threadIdx.x == 0, 55);

  if (wg < 2) {
    cp_arrive(sb + 8 * (B_B + wg));
    asm volatile("setmaxnreg.inc.sync.aligned.u32 224;");
    STAMPIF(threadIdx.x == 0, 82);
    const int g = lane >> 2, q = lane & 3;
    constexpr int NB = UT < 5 ? 288 : 256;
    if (wg == 1) bar_arrive(1, NB);
    const uint32_t dv = *(const uint16_t*)(gD + 128 * wg + b);
    if (TG == 3) e1 = rdback(G->flag + 8 * m + 4 + (__shfl_sync(0xffffffffu, tid, tid) >> 8));
    e1 = (e1 >> 5) + 1;
    {
      const int tid = (OPQ & 4) ? __shfl_sync(0xffffffffu, threadIdx.x & 127, threadIdx.x) : threadIdx.x & 127, lane = tid & 31, g = lane >> 2, q = lane & 3;
      const int b0 = (g >> 1) & 1, b1 = g >> 2, u = q + 4 * b0 - w;
      const uint32_t fo = 128 + (g & 1) * K1OFF + 288 * b1 + 4 * u, fo0 = fo - (u < 0 ? 32 : 0);
      const bool wrap = b0 && q == 0;
      const int src1 = b0 ? ((lane & 20) | ((q - 1) & 3)) : (lane | 8);
      const uint2* pu = (const uint2*)(G->kvT + (128 * wg + b) * S_ + 8 * tid);
      uint4 u0 = make_uint4(0, 0, 0, 0), u1 = make_uint4(0, 0, 0, 1);
#pragma unroll 1
      for (int ch = wg; ch < 5; ch += 2) {
        const uint32_t base = chan_base(sb, ch);
        if (KW) {
          if (ch < 2) {
#pragma unroll 1
            for (int n = 0; n <= ch; n++) {
              kv_job(G, sb, b, ch + n, tid, e1);
              STAMPIF(tid == 0, n ? 22 : 1 + ch);
              if (n == 0) {
                k1_job(sb, wg, tid, dv);
                bar_sync(3 + wg, 128);
                mbar_wait(sb + 8 * B_E0, 0);
                e1 = epoch(sb);
              }
            }
            if (ch) spin(t_0, UD1);
          } else mbar_wait(sb + 8 * (B_K + ch - 2), 0);
          if (ch) { u0 = ld_tag2(pu); u1 = ld_tag2(pu + 256); }
        }
        if (!KW && (ch < 2 || ch == KV4C)) {
          kv_job(G, sb, b, ch < 2 ? ch : 4, tid, TG ? e1 : 1);
          if (ER && ch > 1) { __syncwarp(); if (lane == 0) mbar_arrive(sb + 8 * B_KV4); }
          STAMPIF(tid == 0, ch < 2 ? 1 + ch : 24);
        }
        if (KW) {
        } else if (ch < 2) {
          k1_job(sb, wg, tid, dv);
          bar_sync(3 + wg, 128);
        } else {
          mbar_wait(sb + 8 * (B_K + ch - 2), 0);
          if (UT == 5) {
            u0 = ld_tag2(pu); u1 = ld_tag2(pu + 256);
            if (BS) mbar_wait(sb + 8 * (B_S + ch), 0);
          }
        }
        const uint32_t fa = base + fo, fa0 = base + fo0;
        uint32_t af[16][4];
        auto afl = [&](int j) {
          const int o = 64 * (j & 1) + 576 * (j >> 1);
          if (UF) { af[j][0] = ldv32(((j & 1) ? fa : fa0) + o); af[j][1] = ldv32(fa + o + 128); af[j][2] = ldv32(fa + o + 32); af[j][3] = ldv32(fa + o + 160); }
          else { af[j][0] = lds32(((j & 1) ? fa : fa0) + o); af[j][1] = lds32(fa + o + 128); af[j][2] = lds32(fa + o + 32); af[j][3] = lds32(fa + o + 160); }
        };
#pragma unroll
        for (int j = 0; j < NA; j++) afl(j);
        if (UF) {
          stv128(base + KSZ + 16 * tid, u0);
          stv128(base + KSZ + 2048 + 16 * tid, u1);
#pragma unroll
          for (int j = NA; j < 16; j++) afl(j);
        }
        STAMPIF(tid == 0, 40 + ch);
        const uint32_t tg = KW && ch < 2 ? 1 : e1;
        if (!KW && !(TG & 1) && (!EH || ch < 2)) { mbar_wait(sb + 8 * B_E0, 0); e1 = epoch(sb); }
        if (ch < UT) {
          if (KW) { if (ch == 0) spin(t_0, UD2); }
          else if (UD2 ? ch < 2 : ch == 1) spin(t_0, ch ? UD1 : UD2);
          if (UT == 2) u0.w = 0;
          if (UF) u_fix(u0, u1, pu, base + KSZ + 16 * tid, TG ? tg : 1);
          else u_wait(u0, u1, pu);
          if (ITW == 5) STAMPIF(tid == 0, 105 + ch);
          if (!UF) {
            sts128(base + KSZ + 16 * tid, u0);
            sts128(base + KSZ + 2048 + 16 * tid, u1);
#pragma unroll
            for (int j = NA; j < 16; j++) afl(j);
          }
          fence_async_s();
        }
        float acc[128];
        const uint64_t db = mkdesc(base + KSZ, 32, 128, 0);
        bar_sync(1 + wg, NB);
        if (ITW == 5) STAMPIF(tid == 0, 115 + ch);
        wg_fence();
        wgmma_rs_n64<0>(acc + 96, af[0], db + 192, 0);
        wgmma_rs_n192<0>(acc, af[0], db, 0);
        wgmma_rs_n64<0>(acc + 96, af[1], db + 196, 1);
        wgmma_rs_n192<0>(acc, af[1], db + 4, 1);
        wgmma_rs_n32<0>(acc + 96, af[2], db + 224, 1);
        wgmma_rs_n192<0>(acc, af[2], db + 32, 1);
        wgmma_rs_n32<0>(acc + 96, af[3], db + 228, 1);
        wgmma_rs_n192<0>(acc, af[3], db + 36, 1);
        wgmma_rs_n192<0>(acc, af[4], db + 64, 1);
        wgmma_rs_n192<0>(acc, af[5], db + 68, 1);
        wgmma_rs_n160<0>(acc, af[6], db + 96, 1);
        wgmma_rs_n160<0>(acc, af[7], db + 100, 1);
        if (CVT == 2) wg_commit();
        wgmma_rs_n128<0>(acc, af[8], db + 128, 1);
        wgmma_rs_n128<0>(acc, af[9], db + 132, 1);
        if (CVT == 1) wg_commit();
        wgmma_rs_n96<0>(acc, af[10], db + 160, 1);
        wgmma_rs_n96<0>(acc, af[11], db + 164, 1);
        if (CVT == 0) bar_arrive(2 - wg, NB);
        wgmma_rs_n64<0>(acc, af[12], db + 192, 1);
        wgmma_rs_n64<0>(acc, af[13], db + 196, 1);
        wgmma_rs_n32<0>(acc, af[14], db + 224, 1);
        wgmma_rs_n32<0>(acc, af[15], db + 228, 1);
        wg_commit();
        if ((!TG || TG == 2 && ch < 2) && ZP == 0 && ch < UT) {
          stg128((void*)pu, make_uint4(0, 0, 0, 0));
          stg128((void*)(pu + 256), make_uint4(0, 0, 0, 0));
        }
        if (tid < 2 && ch == (!ER && wg == (KV4C & 1) && KV4C < 5 ? KV4C : wg)) mbar_arrive(sb + 8 * (B_E1 + tid));
        auto go = [&](int k) {
          int mk = 0;
#pragma unroll
          for (int c = 0; c < 4; c++) if (((GT >> 4 * c) & 15) == k) mk |= 1 << c;
          if (mk) asm volatile("{\n.reg .pred p;\nsetp.ne.b32 p, %1, 0;\n@p bar.arrive %0, %2;\n}" ::"r"(2 - wg), "r"((mk >> ch) & 1), "n"(NB) : "memory");
        };
        if (CVT) { wg_wait<1>(); go(0); }
        STAMPIF(tid == 0, 3 + ch);
        if (BX3 == 2 && ch == 3) {
          mod_box(G, sb, b, 1, e1, tid);
          __syncwarp();
          if (lane == 0) mbar_arrive(sb + 8 * (B_BD + 1));
          STAMPIF(tid == 0, 73);
        }
        if (ZP == 1) {
          stg128((void*)pu, make_uint4(0, 0, 0, 0));
          stg128((void*)(pu + 256), make_uint4(0, 0, 0, 0));
        }
        wg_wait<0>();
#pragma unroll
        for (int i = 0; i < 128; i++) asm volatile("" : "+f"(acc[i])::"memory");
        if (!RL) {
          bar_sync(3 + wg, 128);
          if (tid <= (ch >> 2)) mbar_arrive(sb + 8 * (B_E1 + 2 + (ch >> 1)));
        }
        if (RL == 2 && lane == 0) mbar_arrive(sb + 8 * (B_Z + ch));
        go(1);
        float S0[33], T[34];
#pragma unroll
        for (int i = 0; i < 31; i++) S0[i] = acc[4 * i] + acc[4 * i + 6];
        S0[31] = acc[124]; S0[32] = 0.f;
        if (PK & 1) {
#pragma unroll
          for (int i = 0; i < 32; i += 2) {
            const uint32_t v = __shfl_sync(0xffffffffu, pack2(acc[4 * i + 1] + acc[4 * i + 7], i < 30 ? acc[4 * i + 5] + acc[4 * i + 11] : acc[125]), src1);
            T[i] = (wrap ? S0[i + 1] : S0[i]) + blo(v);
            T[i + 1] = (wrap ? S0[i + 2] : S0[i + 1]) + bhi(v);
          }
        } else {
#pragma unroll
          for (int i = 0; i < 32; i++) {
            float s1 = i < 31 ? acc[4 * i + 1] + acc[4 * i + 7] : acc[125];
            T[i] = (wrap ? S0[i + 1] : S0[i]) + __shfl_sync(0xffffffffu, s1, src1);
          }
        }
        T[32] = 0.f; T[33] = 0.f;
        go(2);
        uint4* pz = (uint4*)(G->zT + (128 * ch + b) * S_) + ((tid & 120) | (2 * q) | (g & 1));
#pragma unroll
        for (int h = 0; h < 2; h++) {
          float y[8];
          if (PK & 2) {
#pragma unroll
            for (int mu = 0; mu < 8; mu += 2) {
              const uint32_t v = __shfl_xor_sync(0xffffffffu, pack2(T[4 * mu + 2 + h], T[4 * mu + 6 + h]), 16);
              y[mu] = (b1 ? T[4 * mu + 4 + h] : T[4 * mu + h]) + blo(v);
              y[mu + 1] = (b1 ? T[4 * mu + 8 + h] : T[4 * mu + 4 + h]) + bhi(v);
            }
          } else {
#pragma unroll
            for (int mu = 0; mu < 8; mu++) y[mu] = (b1 ? T[4 * mu + 4 + h] : T[4 * mu + h]) + __shfl_xor_sync(0xffffffffu, T[4 * mu + 2 + h], 16);
          }
          pz[128 * h] = make_uint4(pack2(y[0], y[1]), pack2(y[2], y[3]), pack2(y[4], y[5]), tagged(pack2(y[6], y[7]), e1));
        }
        go(3);
        if (RL == 1 && lane == 0) mbar_arrive(sb + 8 * (B_Z + ch));
        if (ZP == 2) {
          stg128((void*)pu, make_uint4(0, 0, 0, 0));
          stg128((void*)(pu + 256), make_uint4(0, 0, 0, 0));
        }
        pu += 128 * S_ / 2;
        STAMPIF(tid == 0, 8 + ch);
      }
    }
    uint32_t hh[96];
    {
      float ga[192];
      float* ua = ga + 96;
      const uint64_t da0 = mkdesc(ring + wg * 2048, 512, 256, 3), db0 = mkdesc(ring + 8192, 4096, 1024, 1);
      int st = PL, ph = 0, ps = 0;
      if (ITW == 7) STAMPIF(tid == 0, 110 + wg);
      float bx[4];
      if (wg && BX3 < 2) {
        mbar_wait(sb + 8 * (B_BOX + 2), 0);
        mbar_wait(sb + 8 * (B_BOX + 3), 0);
        wg_fence();
#pragma unroll
        for (int n = 0; n < 10; n++) wgmma_ss_n8<1, 0>(bx, box_a(sb) + 128 * n, box_b(sb) + 8 * n, n != 0);
        wg_commit();
        if (ITW == 7) STAMPIF(tid == 0, 120);
      }
      auto put = [&]() {
#pragma unroll
        for (int i = 0; i < 4; i++) asm volatile("" : "+f"(bx[i])::"memory");
        mod_put(G, sb, bx, b, 1, e1, tid);
        __syncwarp();
        if (lane == 0) mbar_arrive(sb + 8 * (B_BD + 1));
        STAMPIF(tid == 0, 73);
      };
      if (wg && BX3 == 0) { wg_wait<0>(); put(); }
      mbar_wait(sb + 8 * B_F1, 0);
      STAMPIF(tid == 0, 13 + wg);
      bool nf = PG == 1 && mbar_test(sb + 8 * (B_F1 + 1), 0);
      wg_fence();
      wgmma_ss_n192<1, 1>(ga, da0, db0, 0);
      wgmma_ss_n192<1, 1>(ua, da0, db0 + 768, 0);
      wgmma_ss_n192<1, 1>(ga, da0 + 256, db0 + 128, 1);
      wgmma_ss_n192<1, 1>(ua, da0 + 256, db0 + 128 + 768, 1);
      wg_commit();
      if (wg && BX3 == 1) { wg_wait<1>(); put(); }
      if (!PG) mbar_wait(sb + 8 * B_BD, 0);
      if (ITW == 7) STAMPIF(tid == 0, 112 + wg);
      const bool cs = b < 96;
      const int x0 = wg ? XI : 99,
                x1 = x0 + (cs ? 4 : 2), xs = cs ? 4 : 8;
      uint64_t xa = cs ? mkdesc(sb + SM_EXT, 4096, 1024, 1) : box_a(sb), xb = cs ? mkdesc(sb + SM_CB, 32, 128, 0) : box_b(sb);
      uint64_t ya = xa + (cs ? (SM_RING + R_X - SM_EXT) / 16 : 256), yb = xb + 16;
      if (ITW == 7) STAMPIF(tid == 0, 114 + wg);
#pragma unroll 1
      for (int it = PL; it < 19; it++) {
        if (it == x0) {
          mbar_wait(sb + 8 * (cs ? B_F : B_BOX + 4), 0);
          mbar_wait(sb + 8 * (cs ? B_ST0 : B_BOX + 5), 0);
          STAMPIF(tid == 0, 76);
        }
        if (it == x1 + XW) {
          wg_wait<XW>();
#pragma unroll
          for (int i = 0; i < 4; i++) asm volatile("" : "+f"(bx[i])::"memory");
          if (!cs) mod_put(G, sb, bx, b, 2, e1, tid);
          else {
            const int row = (m < 6 ? 0 : 4) + q;
            uint16_t* dst = (uint16_t*)G->cimg + s * 3072 + (m % 6) * 512 + row * 64 + g;
#pragma unroll
            for (int j = 0; j < 2; j++) {
              const float c1 = __shfl_sync(0xffffffffu, bx[2 * j], lane & 28), c2 = __shfl_sync(0xffffffffu, bx[2 * j + 1], lane & 28);
              const float t = (lane & 2) ? c2 : c1, hi = rbf(t);
              dst[((2 * w + j) ^ row) << 3] = (uint16_t)pack2((lane & 1) ? t - hi : hi, 0.f);
            }
          }
          __syncwarp();
          if (lane == 0) mbar_arrive(sb + 8 * (B_BD + 2));
          STAMPIF(tid == 0, 77);
        }
        if (ITW == 7) STAMPIF(tid == 0 && it == 0, 116 + wg);
        if (!nf) mbar_wait(sb + 8 * (B_F1 + st), ph);
        const int nx = st == 4 ? 0 : st + 1;
        if (st == 4) ph ^= 1;
        if (ITW == 1) STAMPIF(tid == 0 && it >= 10, 90 + it + 10 * wg);
        else if (ITW == 2) STAMPIF(tid == 0 && it < 10, 100 + it + 10 * wg);
        else if (ITW < 3) STAMPIF(threadIdx.x == ITW, 100 + it);
        const uint64_t da = da0 + st * 2048, db = db0 + st * 2048;
        if (it >= x0 && it < x1) {
          if (PG == 1) nf = mbar_test(sb + 8 * (B_F1 + nx), ph);
          wg_fence();
          wgmma_ss_n8<1, 0>(bx, xa, xb, it != x0);
          wgmma_ss_n192<1, 1>(ga, da, db, 1);
          wgmma_ss_n8<1, 0>(bx, ya, yb, 1);
          wgmma_ss_n192<1, 1>(ua, da, db + 768, 1);
          wgmma_ss_n8<1, 0>(bx, ya + 128, yb + xs, 1);
          wgmma_ss_n192<1, 1>(ga, da + 256, db + 128, 1);
          wgmma_ss_n8<1, 0>(bx, ya + 256, yb + 2 * xs, 1);
          wgmma_ss_n192<1, 1>(ua, da + 256, db + 128 + 768, 1);
          wgmma_ss_n8<1, 0>(bx, ya + 384, yb + 3 * xs, 1);
          wg_commit();
          xa += 128; xb += xs; ya += 512; yb += 4 * xs;
        } else {
          if (PG == 1) nf = mbar_test(sb + 8 * (B_F1 + nx), ph);
          wg_fence();
          wgmma_ss_n192<1, 1>(ga, da, db, PL || it != 0);
          wgmma_ss_n192<1, 1>(ua, da, db + 768, PL || it != 0);
          wgmma_ss_n192<1, 1>(ga, da + 256, db + 128, 1);
          wgmma_ss_n192<1, 1>(ua, da + 256, db + 128 + 768, 1);
          wg_commit();
        }
        wg_wait<1>();
        if (PG) { if (w == 0 && elect()) mbar_arrive(sb + 8 * (B_E1 + ps)); }
        else if (tid == 0) mbar_arrive(sb + 8 * (B_E1 + (st == 0 ? 4 : st - 1)));
        ps = st; st = nx;
      }
      const uint32_t la = ring + wg * 2048 + tid * 16, ra = mapa(la, (b & 1) ^ 1), rp = mapa(sb + 8 * (B_PEER + 2 * wg), (b & 1) ^ 1), rb = rp + 8 * (B_RECV - B_PEER);
      uint32_t sa[24];
      auto addr = [&](int j) {
        sa[2 * j] = ra + (j < 2 ? 5 : (j >> 1) - 1) * 32768 + (j & 1) * 4096;
        sa[2 * j + 1] = (sa[2 * j] >> 31) + (rb + 8 * (j / 6));
        asm volatile("" : "+r"(sa[2 * j]), "+r"(sa[2 * j + 1]));
      };
      auto send = [&](int j) { st_async4(sa[2 * j], hh + 4 * j, sa[2 * j + 1]); };
      auto pack = [&](int c) {
#pragma unroll
        for (int i = 0; i < 64; i++) asm volatile("" : "+f"(ga[64 * c + i])::"memory");
#pragma unroll
        for (int i = 0; i < 4; i++) addr(4 * c + i);
#pragma unroll
        for (int i = 0; i < 16; i++) {
          const int j = 64 * c + 2 * i;
          hh[16 * c + i] = pack2(ga[j] * ga[j + 32], ga[j + 1] * ga[j + 33]);
          asm volatile("" : "+r"(hh[16 * c + i])::"memory");
          if ((i & 3) == 3 && 4 * c + i / 4 < NP) send(4 * c + i / 4);
          if (c == 2 && NQ > NP && i == 0) mbar_wait(sb + 8 * (B_PEER + 2 * wg), 0);
          if (c == 2 && (i & 3) == 3 && NP + i / 4 < NQ) send(NP + i / 4);
        }
      };
      STAMPIF(threadIdx.x == 0, 61);
      if (!nf) mbar_wait(sb + 8 * (B_F1 + 4), 1);
      mbar_wait(sb + 8 * B_EXT, 0);
      mbar_wait(sb + 8 * B_ST2, 0);
      const uint64_t de = mkdesc(sb + SM_EXT, 1024, 0, 1), ds = mkdesc(sb + SM_STAT + wg * 1024, 0, 128, 0);
#pragma unroll
      for (int c = 0; c < 2; c++) {
        wg_fence();
        wgmma_ss_n192<1, 1>(ga + 96 * c, da0 + 8192, db0 + 8192 + 768 * c, 1);
        wgmma_ss_n192<1, 1>(ga + 96 * c, da0 + 8192 + 256, db0 + 8192 + 128 + 768 * c, 1);
        wgmma_ss_n192<0, 1>(ga + 96 * c, ds, de + 192 * c, 1);
        wg_commit();
        if (c == 0) { mbar_wait(sb + 8 * B_P0, 0); mbar_wait(sb + 8 * B_FB, 0); }
        wg_wait<1>();
        if (c == 0 && tid == 0) {
          mbar_arrive(sb + 8 * (B_E1 + 3));
          mbar_arrive_remote(rp);
        }
      }
      STAMPIF(tid == 0, 15 + wg);
      float acc[64], rs[2] = {};
      uint4 pf[4], gb = {};
      uint32_t ln, os, ol, og, oz;
      const char *po, *pq;
      const uint64_t dd0 = mkdesc(ring + 8192, 0, 1024, 1);
      bool ok = false;
#pragma unroll
      for (int c = 0; c < 3; c++) {
        pack(c);
        if (c == 1) ok = mbar_try(sb + 8 * (B_FB + 1), 0);
        STAMPIF(tid == 0 && c == 0, wg ? 89 : 121);
        if (ITW == 3) STAMPIF(tid == 0 && c > 0, 99 + c + 10 * wg);
        wg_fence();
#pragma unroll
        for (int k = 4 * c; k < 4 * c + 4; k++) wgmma_rs_n64<1>(acc, hh + 4 * k, dd0 + 5 * 2048 + 128 * k, k);
        wg_commit();
        if (c == 0) {
          wg_wait<1>();
          if (tid == 0) {
            mbar_arrive(sb + 8 * (B_E1 + 4));
            mbar_arrive_remote(rp + 8);
          }
        }
        if (c == 1 && !ok) mbar_wait(sb + 8 * (B_FB + 1), 0);
      }
      auto recv = [&](int j) {
        const uint4 v = lds128(la + (j < 2 ? 5 : (j >> 1) - 1) * 32768 + (j & 1) * 4096);
        hh[48 + 4 * j] = v.x; hh[49 + 4 * j] = v.y; hh[50 + 4 * j] = v.z; hh[51 + 4 * j] = v.w;
      };
      auto stage = [&](const float* a, int i, int p) {
        const uint32_t v[4] = {pack2(a[8 * i] * rs[0], a[8 * i + 1] * rs[0]), pack2(a[8 * i + 2] * rs[1], a[8 * i + 3] * rs[1]),
                               pack2(a[8 * i + 4] * rs[0], a[8 * i + 5] * rs[0]), pack2(a[8 * i + 6] * rs[1], a[8 * i + 7] * rs[1])};
        stsm4(OF && p % 4 ? (oz ^ 32 * i) + 65536 * (p - 1) : os + 32 * i, v);
      };
      auto fetch = [&](int p) {
        __syncwarp();
#pragma unroll
        for (int i = 0; i < 4; i++) pf[i] = lds128(ol + 576 * i);
      };
      auto next = [&](int p) {
        gb = lds128(og + 256 * out_blk(s, p));
        pq = po + 128 * out_blk(s, p);
        asm volatile("" : "+l"(pq));
      };
      auto add = [&](int p, int i) {
        if (RX == 1 && p < 4) return;
        if (RX == 2) { stg128((uint4*)(pq - (i & 1) * 2048 * D_ - (i >> 1) * 2 * D_), make_uint4(hmul(pf[i].x, gb.x), hmul(pf[i].y, gb.y), hmul(pf[i].z, gb.z), hmul(pf[i].w, gb.w))); return; }
        asm volatile("red.relaxed.gpu.global.add.noftz.v4.bf16x2 [%0], {%1, %2, %3, %4};" ::"l"(pq - (i & 1) * 2048 * D_ - (i >> 1) * 2 * D_),
                     "r"(hmul(pf[i].x, gb.x)), "r"(hmul(pf[i].y, gb.y)), "r"(hmul(pf[i].z, gb.z)), "r"(hmul(pf[i].w, gb.w)) : "memory");
      };
#pragma unroll
      for (int h = 2; h < 20; h++) {
        const int gr = h >> 1, pe = gr < 4 ? gr >> 1 : gr & 1, ac = (gr < 4 ? gr : gr >> 1) & 1;
        const int ep = h == 7 || h == 8 ? 0 : h > 8 && (h & 3) == 1 || h > 8 && (h & 3) == 2 ? (h >> 2) - 1 : -1;
        const int es = h == 6 ? 0 : h > 6 && !(h & 3) ? (h >> 2) - 1 : -1;
        if (!(h & 1) && h > 2 && !(PT && ok)) mbar_wait(sb + 8 * (B_FB + gr), 0);
        if (h == LH0 || h == LH1) mbar_wait(sb + 8 * (B_RECV + 2 * wg + (h == LH1)), 0);
        if (h == LH0 && (h == 4 || !LM) || h == LH1 && (h == 5 || !LM)) {
#pragma unroll
          for (int j = 0; j < 6; j++) recv(6 * (h == LH1) + j);
        }
        if (h == SPOS(6) / 6 && NQ <= 6) mbar_wait(sb + 8 * (B_PEER + 2 * wg), 0);
        if (h == SPOS(10) / 6) mbar_wait(sb + 8 * (B_PEER + 2 * wg + 1), 0);
        if (OF && h == OH) mbar_wait(sb + 8 * B_OF, 0);
        if (h == (ES ? RH : 6)) {
          if (!OF) { mbar_wait(sb + 8 * B_X1, 0); mbar_wait(sb + 8 * B_GB, 0); }
          asm volatile("mov.u32 %0, %%laneid;" : "=r"(ln));
#pragma unroll
          for (int i = 0; i < 2; i++) rs[i] = blo(lds32(sb + SM_STAT + (4 * wg + w) * 256 + (ln & 28) * 4 + 128 * i + 4));
        }
        STAMPIF(tid == 0 && h % 4 == 0 && h < 16, (wg ? 89 : 121) + h / 4);
        STAMPIF(tid == 0 && h == 16, wg ? 97 : 96);
        if (ITW == 3) STAMPIF(tid == 0 && h < 10, 100 + h + 10 * wg);
        if (ITW == 4) STAMPIF(tid == 0 && h >= 10, 90 + h + 10 * wg);
        const uint64_t db = dd0 + (((gr + 5) % 6) * 2048 + (gr << 16));
        if (PT && (h & 1) && h < 19) ok = mbar_try(sb + 8 * (B_FB + gr + 1), 0);
        wg_fence();
#pragma unroll
        for (int j = 0; j < 6; j++) {
          const int k = 6 * (h & 1) + j;
          wgmma_rs_n64<1>(acc + 32 * ac, hh + 48 * pe + 4 * k, db + 128 * k, pe || k);
#pragma unroll
          for (int i = NQ; i < 12; i++) if (SPOS(i) == 6 * h + j) send(i);
          if (LM && h == LH0 && h < 4) { recv(j); wg_fence(); }
          if (LM && h == LH1 && h < 5) { recv(6 + j); wg_fence(); }
          if (ES && es >= 0) {
            if (j == ES - 1) {
              wg_commit();
              wg_wait<1>();
              if (h < 12 && tid == 0) mbar_arrive(sb + 8 * (B_EB + gr - 1));
#pragma unroll
              for (int i = 0; i < 32; i++) asm volatile("" : "+f"(acc[32 * (1 - ac) + i])::"memory");
            }
#pragma unroll
            for (int i = 0; i < 4; i++) if (j == min(5, ES - 1 + i * SI / 2)) {
              stage(acc + 32 * (1 - ac), i, es);
              if (i == 3) { __syncwarp(); if (ln == 0) mbar_arrive(sb + 8 * (B_OS + 4 * wg + es)); }
            }
            if (j == ES - 1 && j < 5) wg_fence();
          }
          if (!ES && ep >= 0 && (h & 1)) {
            if (j < 4) stage(acc + 32 * (1 - ac), j, ep);
            if (j == 4 && !OF) fetch(ep);
            if (j == 3 && OF) { __syncwarp(); if (ln == 0) mbar_arrive(sb + 8 * (B_OS + 4 * wg + ep)); }
          }
          if (!OF && ep >= 0 && !(h & 1) && j > 0 && j < 5) add(ep, j - 1);
          if (!OF && ep >= 0 && !(h & 1) && j == 5) next(ep + 1);
        }
        if (!(ES == 6 && es >= 0)) wg_commit();
        STAMPIF(tid == 0 && h == 3, 81);
        if (h == (ES ? RH : 6)) {
#pragma unroll
          for (int i = 0; i < 2; i++) rs[i] = __fdividef(0.25f, rs[i] * rs[i]);
          const uint32_t ob = sb + SM_X + (4 * wg + w) * 2304;
          os = ob + (ln & 15) * 144 + (ln & 16);
          oz = ring + (4 * wg + w) * 512 + (ln & 8) * 4096 + (ln & 4) * 1024 + (ln & 3) * 128 + ((ln >> 4) ^ (ln & 7)) * 16;
          asm volatile("" : "+r"(os), "+r"(oz));
        }
        if (h == (OF ? OH : 6)) {
          ol = sb + SM_X + (4 * wg + w) * 2304 + (ln >> 3) * 16 + ln * 16;
          po = (const char*)(gout + (1793 + 2 * tbase(8 * m + 4 * wg + w)) * D_) + (int)(640 * (s & 1) + 16 * ln - (ln >> 3) * (512 * D_ + 128));
          og = sb + SM_CB + 32 * (ln & 7);
          asm volatile("" : "+r"(ol), "+r"(og), "+l"(po));
          next(OF ? 4 : 0);
        }
        if (h == 2 || h == 4 || !ES && es >= 0) {
          wg_wait<1>();
          if (h < 12 && tid == 0) mbar_arrive(sb + 8 * (B_EB + gr - 1));
          if (h >= 6) {
#pragma unroll
            for (int j = 0; j < 32; j++) asm volatile("" : "+f"(acc[32 * (1 - ac) + j])::"memory");
          }
        }
      }
      STAMPIF(tid == 0, wg ? 95 : 93);
      wg_wait<0>();
#pragma unroll
      for (int i = 0; i < 32; i++) asm volatile("" : "+f"(acc[i])::"memory");
      STAMPIF(tid == 0, wg ? 50 : 18);
#pragma unroll
      for (int i = 0; i < 4; i++) stage(acc, i, 4);
      fetch(4);
#pragma unroll
      for (int i = 0; i < 4; i++) add(4, i);
    }
  } else if (wg == 2) {
    asm volatile("setmaxnreg.dec.sync.aligned.u32 40;");
    const uint32_t e1 = (rdback(G->flag + 8 * m + 4) >> 5) + 1;
    if (tid < 80) {
      uint4 c = ((const uint4*)gc)[tid];
#pragma unroll 1
      for (int i = 0; i < 4; i++) {
        const float lo = blo(c.x), hi = bhi(c.x);
        sts32(sb + SM_STAT + 16 * tid + 4 * i, pack2(__fdividef(lo, 1.f + __expf(-lo)), __fdividef(hi, 1.f + __expf(-hi))));
        c.x = c.y; c.y = c.z; c.z = c.w;
      }
    }
    if (tid == 0) { sts32(sb + SM_SMALL + SMALL_E, e1); mbar_arrive(sb + 8 * B_E0); }
    fence_async_s();
    bar_sync(5, 128);
    if (mod_first(b)) mod_box(G, sb, b, 0, e1, tid);
    __syncwarp();
    if (lane == 0) mbar_arrive(sb + 8 * B_BD);
    STAMPIF(tid == 0, 27);
    float s1 = 0.f, s2 = 0.f, pv;
    int tl = (OPQ & 1) ? __shfl_sync(0xffffffffu, tid, tid) : tid;
#pragma unroll 1
    for (int r = KW == 1 ? 3 : 2 - DR; r < 5 - XO; r++) {
      asm volatile("" : "+r"(tl));
      if (DR && r == 2) s1 = s2 = 0.f;
      if (KW == 1 || (XO || r < 4) && r > 1) {
        kv_job(G, sb, b, r + (KW == 2), tl, TG ? e1 : 1);
        STAMPIF(tid == 0, 20 + r + (KW == 2));
      }
      if (r == (KW == 1 ? 4 : 3)) { __syncwarp(); if (elect()) mbar_arrive(sb + 8 * B_KVS); }
      if (XO || r != 2) ln1_half(sb, tl, (r - 3 + XO) & 1, r < 2, s1, s2, pv);
    }
    {
      const int lane = tl & 31, cg = 4 * (w >> 1) + (lane & 2) + (w & 1), g = lane >> 2;
      uint32_t zo = offsetof(Scr, zT) + 2 * ((16 * cg + g) * S_ + 16 * b + 8 * (lane & 1)), co = offsetof(Scr, mv) + 4 * (2048 * (e1 & 1) + 8 * cg + g);
      uint4 z[2];
      uint32_t c[4];
      auto zld = [&]() {
        asm volatile("" : "+r"(zo), "+r"(co));
        const uint2* pz = (const uint2*)((const char*)G + zo);
        const uint32_t* pc = (const uint32_t*)((const char*)G + co);
        z[0] = ld_tag2(pz); z[1] = ld_tag2(pz + 4096);
        c[0] = rdback(pc); c[1] = rdback(pc + 320); c[2] = rdback(pc + 640); c[3] = rdback(pc + 1280);
      };
      STAMPIF(tid == 0, 28);
      if (ZF < 2 && !ZA) { spin(t_0, ZD); zld(); spin(t_0, ZS); }
      if (ITW == 8) STAMPIF(tid == 0, 106);
      ln1_end(sb, tl, s1, s2, pv);
      if (ZF < 2 && ZA) { spin(t_0, ZD); zld(); }
#pragma unroll 1
      for (int r = 0; r < 5; r++) {
        asm volatile("" : "+r"(tl));
        const int lane = tl & 31;
        if (ITW == 6) STAMPIF(tid == 0 && r < 2, 100 + 10 * r);
        if (ZF == 3) { if (r == 2 + MG) { mbar_wait(sb + 8 * (B_BD + 1), 0); spin(clk(), BD); } if (r == 0) spin(t_0, ZD); zld(); }
        const uint32_t la = sb + SM_SMALL + SMALL_LN + 16 * (lane & 1);
        uint32_t xa = x_addr(sb, w, lane) + 4096 * r, xv[8];
        const uint4 m4 = lds128(la), s4 = lds128(la + 32);
        const uint32_t m_[4] = {m4.x, m4.y, m4.z, m4.w}, s_[4] = {s4.x, s4.y, s4.z, s4.w};
        ldsm4t(xv, xa);
        ldsm4t(xv + 4, xa ^ 16);
        if (ZF == 2) { if (r == 2 + MG) { mbar_wait(sb + 8 * (B_BD + 1), 0); spin(clk(), BD); } if (r == 0) spin(t_0, ZD); zld(); }
        if (ITW == 6) STAMPIF(tid == 0 && r < 2, 104 + 10 * r);
        if (ITW == 8) STAMPIF(tid == 0 && r == 0, 109);
        z_wait(z[0], z[1], c, G, zo, co, e1);
        asm volatile("" : "+r"(xa));
        const uint32_t zc = (zo - (uint32_t)offsetof(Scr, zT)) >> 11, ao = (320 * m + s) * 32 + ((zc & ~31u) << 3) + (zc & 14) + (((zo >> 4) ^ (zc >> 3)) & 1);
        STAMPIF(tid == 0 && r == 0, 83);
        if (ITW == 6) STAMPIF(tid == 0 && r < 2, 105 + 10 * r);
        uint32_t h[8];
        {
          const uint32_t sa = ~c[0], ca1 = ~c[1];
#pragma unroll
          for (int j = 0; j < 8; j++) {
            const uint32_t z_[8] = {z[0].x, z[0].y, z[0].z, z[0].w, z[1].x, z[1].y, z[1].z, z[1].w}, sel = j > 3 ? 0x3232 : 0x1010;
            h[j] = hmul(hfma(hmul(hsub(xv[j], m_[j & 3]), s_[j & 3]), __byte_perm(ca1, 0, sel), __byte_perm(sa, 0, sel)), z_[j]);
            asm volatile("" : "+r"(h[j]));
          }
        }
        uint4* pa = (uint4*)G->AT + ao;
        uint32_t oo[8];
#pragma unroll
        for (int n = 0; n < 2; n++) {
          const uint32_t sel = n ? 0x3232 : 0x1010, ga = __byte_perm(~c[2], 0, sel), cb1 = __byte_perm(~c[3], 0, sel);
          uint32_t* o = oo + 4 * n, a[4];
#pragma unroll
          for (int j = 0; j < 4; j++) {
            o[j] = hfma(ga, h[4 * n + j], xv[4 * n + j]);
            a[j] = hmul(o[j], cb1);
          }
          a[2 * n + 1] = tagged(a[2 * n + 1], e1);
          pa[16 * n] = make_uint4(a[0], a[1], a[2], a[3]);
          if (n) { __syncwarp(); if (elect()) { flag_add(G, 8 * m + r); if (EA && r == 0) mbar_arrive(sb + 8 * (B_EW + 5)); } }
          if (ITW == 6) STAMPIF(tid == 0 && r < 2, 106 + n + 10 * r);
          if (ITW == 8) STAMPIF(lane == 0 && r == 0 && n, 110 + w);
          if (!SL) stsm4t(xa ^ (16 * n), o);
        }
        if (SL) { stsm4t(xa, oo); stsm4t(xa ^ 16, oo + 4); }
        if (r < 4) { zo += 256 * S_; co += 256; }
        auto x1st = [&]() {
          __syncwarp();
          int lane = tl & 31;
          if (!(OPQ & 2)) asm volatile("mov.u32 %0, %%laneid;" : "=r"(lane));
          const int c = 2 * (w & 1) + (lane & 1) + 2 * (lane & 2), g = lane >> 2;
          const uint32_t a = sb + SM_X + 4096 * r + (w >> 1) * 2048 + g * 128 + ((c ^ g) << 4);
          const uint4 v0 = lds128(a), v1 = lds128(a + 1024);
          char* po = (char*)gout + (2 * tbase(b) + 128 * (g & 6) + (g & 1)) * 2 * D_ + 256 * r + 64 * (w & 2) + 16 * c;
          if (ITW == 6) STAMPIF(tid == 0 && r < 2, 108 + 10 * r);
          stg128(po, v0);
          stg128(po + 2048 * D_, v1);
        };
        auto box1 = [&]() {
          if (BX3 >= 3) {
            mod_box(G, sb, b, 1, e1, tl);
            __syncwarp();
            if (elect()) mbar_arrive(sb + 8 * (B_BD + 1));
            STAMPIF(tid == 0, 73);
          } else mbar_wait(sb + 8 * (B_BD + 1), 0);
          if (BX3 < 4) spin(clk(), BD);
        };
        if (ZF == 1) {
          if (BX3 < 4 && r == 1 + MG) { if (XE) x1st(); box1(); }
          if (BX3 == 5 && r == 0) box1();
          zld();
        }
        if (BX3 == 6 && r == 0) box1();
        if (BX3 > 3 || ZF != 1 || !XE || r != 1 + MG) x1st();
        if (BX3 == 4 && r == 0) box1();
        __syncwarp();
        if (elect()) mbar_arrive(sb + 8 * (B_EW + r));
        STAMPIF(tid == 0, 29 + r);
        if (ZF == 0) { if (r == 1 + MG) box1(); zld(); }
      }
    }
    asm volatile("" : "+r"(tl));
    {
      const int lane = tl & 31;
      const uint4 m4 = lds128(sb + SM_SMALL + SMALL_LN + 16 * (lane & 1));
      const uint32_t m_[4] = {m4.x, m4.y, m4.z, m4.w}, xa = x_addr(sb, w, lane);
      float a[16];
#pragma unroll
      for (int i = 0; i < 16; i++) a[i] = 0.f;
#pragma unroll 2
      for (int n = 0; n < 10; n++) {
        uint32_t x_[4];
        ldsm4t(x_, (xa ^ (16 * (n & 1))) + 2048 * (n & 14));
#pragma unroll
        for (int i = 0; i < 4; i++) {
          const float d0 = blo(x_[i]) - blo(m_[i]), d1 = bhi(x_[i]) - bhi(m_[i]);
          a[4 * i] += d0; a[4 * i + 1] += d0 * d0; a[4 * i + 2] += d1; a[4 * i + 3] += d1 * d1;
        }
      }
      STAMPIF(lane == 0, 67 + (w & 1) + 11 * (w >> 1));
      bfly<16>(a, 16, lane & 16); bfly<8>(a, 8, lane & 8); bfly<4>(a, 4, lane & 4); bfly<2>(a, 2, lane & 2);
      if (lane == 0) mbar_arrive(sb + 8 * B_XF);
      STAMPIF(tid == 0, 88);
      sts32(sb + SM_SMALL + SMALL_RED + 16 * lane + 4 * w, __float_as_uint(a[0]));
      bar_sync(5, 128);
      if (w == 0) {
        const uint4 v = lds128(sb + SM_SMALL + SMALL_RED + 16 * lane);
        const float s1 = __uint_as_float(v.x) + __uint_as_float(v.y) + __uint_as_float(v.z) + __uint_as_float(v.w), s2 = __shfl_xor_sync(0xffffffffu, s1, 2);
        const int p = 8 * (lane & 1) + (lane >> 2);
        const float pv = blo(lds32(sb + SM_SMALL + SMALL_LN + 4 * (p >> 1)) >> (16 * (p & 1)));
        const float mu = s1 * (1.f / D_), var = fmaxf(s2 * (1.f / D_) - mu * mu, 0.f);
        const float sd = sdev(var);
        if (!(lane & 2)) st_tag(G->st2 + 16 * b + p, pack2(-0.5f * (pv + mu), 0.5f * sd), e1);
      }
      STAMPIF(tid == 0, 87);
    }
    {
      uint2 v;
      spin(clk(), SD);
      mbar_wait(sb + 8 * (B_BD + 2), 0);
#pragma unroll 1
      for (int i = 0;; i++) {
        v = ld_tag(G->st2 + 128 * m + tl);
        if (__all_sync(0xffffffffu, v.y == e1)) break;
        if (i > (1 << 20)) __trap();
      }
      const uint32_t hm = __byte_perm(v.x, 0, 0x1010), hs = __byte_perm(v.x, 0, 0x3232);
      sts128(sb + SM_STAT + 16 * tl, make_uint4(hm, hs, hm, hs));
      fence_async_s();
      __syncwarp();
      if (elect()) mbar_arrive(sb + 8 * B_ST2);
      STAMPIF(tid == 0, 21);
    }
    if (OF) {
      uint32_t ln, w, s;
      asm volatile("mov.u32 %0, %%laneid;\n\tmov.u32 %1, %%tid.x;\n\tmov.u32 %2, %%ctaid.x;" : "=r"(ln), "=r"(w), "=r"(s));
      w = (w >> 5) & 3; s = role(s);
      const int m = s >> 3;
      s &= 7;
      mbar_wait(sb + 8 * B_X1, 0);
      mbar_wait(sb + 8 * B_GB, 0);
      const uint32_t ol = sb + SM_X + w * 2304 + (ln >> 3) * 16 + ln * 16, oz = ring - 65536 + w * 512 + (ln >> 3) * 128 + ((ln >> 3) ^ (ln & 7)) * 16;
      const char* po = (const char*)(gout + 1793 * D_) + (int)(640 * (s & 1) + 16 * ln - (ln >> 3) * (512 * D_ + 128));
#pragma unroll 1
      for (int n = 0; n < 8; n++) {
        const int p = n >> 1, c = n & 1, ob = out_blk(s, p);
        const uint4 gb = lds128(sb + SM_CB + 32 * (ln & 7) + 256 * ob);
        const char* pq = po + (128 * ob + 4 * D_ * tbase(8 * m + 4 * c + w));
        const uint32_t a0 = p ? oz + 65536 * p + 2048 * c : ol + 9216 * c, a1 = p ? (a0 ^ 64) + 4096 : a0 + 576, d = p ? 32768 : 1152;
        mbar_wait(sb + 8 * (B_OS + 4 * c + p), 0);
        const uint4 pf[4] = {lds128(a0), lds128(a1), lds128(a0 + d), lds128(a1 + d)};
#pragma unroll
        for (int i = 0; i < 4; i++)
          asm volatile("red.relaxed.gpu.global.add.noftz.v4.bf16x2 [%0], {%1, %2, %3, %4};" ::"l"(pq - (i & 1) * 2048 * D_ - (i >> 1) * 2 * D_),
                       "r"(hmul(pf[i].x, gb.x)), "r"(hmul(pf[i].y, gb.y)), "r"(hmul(pf[i].z, gb.z)), "r"(hmul(pf[i].w, gb.w)) : "memory");
        if (n == 1) { __syncwarp(); if (ln == 0) mbar_arrive(sb + 8 * B_OF); }
      }
    }
  } else {
    asm volatile("setmaxnreg.dec.sync.aligned.u32 24;");
    if (w != 0) {
    if (w == 2 && lane < 3) asm volatile("prefetch.tensormap [%0];" ::"l"(&P.mG + lane) : "memory");
    if (K3) {
      const uint32_t dv = *(const uint16_t*)(gD + 128 * min(lane, 4) + b);
#pragma unroll 1
      for (int j = 7 + w; j < 20; j += 3) {
        k1_job(sb, j >> 2, 32 * (j & 3) + lane, __shfl_sync(0xffffffffu, dv, j >> 2));
        if ((j & 3) == (K3 & 3)) {
          mbar_wait(sb + 8 * (B_KJ + (j >> 2)), 0);
          const uint32_t t = lds32(sb + SM_SMALL + SMALL_TS + 4 * (j >> 2));
          while (clk() - t < UD);
        }
        __syncwarp();
        if (lane == 0) mbar_arrive(sb + 8 * (B_K + (j >> 2) - 2));
      }
      STAMPIF(lane == 0 && w == 3, 74);
    } else if (w & 1) {
      const uint32_t dv = *(const uint16_t*)(gD + 128 * min(lane, 4) + b);
#pragma unroll 1
      for (int j = 4; j < 10; j++) {
        k1_job(sb, j >> 1, 64 * (j & 1) + 16 * (w & 2) + lane, K1N ? __shfl_sync(0xffffffffu, dv, j >> 1) : *(const uint16_t*)(gD + 64 * (j & 14) + b));
        if (ITW == 5) STAMPIF(tid == 32, 98 + (j >> 1));
        if (UT == 5 && UD && w == 1 && (j & 1)) {
          mbar_wait(sb + 8 * (B_KJ + (j >> 1)), 0);
          const uint32_t t = lds32(sb + SM_SMALL + SMALL_TS + 4 * (j >> 1));
          while (clk() - t < UD);
        }
        __syncwarp();
        if (lane == 0) mbar_arrive(sb + 8 * (B_K + (j >> 1) - 2));
      }
      STAMPIF(tid == 32, 74);
    }
    if (w == 1) {
     {
      mbar_wait(sb + 8 * B_KVS, 0);
      const uint32_t e1 = epoch(sb);
      if (elect()) {
        if (P3) { const uint32_t v = e1 * 32 - 32; sts128(sb + SM_SMALL + SMALL_H, make_uint4(v, v, v, v)); sts32(sb + SM_SMALL + SMALL_H + 16, v); }
        if (ER) mbar_wait(sb + 8 * B_KV4, 0);
        mbar_wait(sb + 8 * (B_EW + 5 * EA), 0);
        spin(clk(), AD);
#pragma unroll 1
        for (int it = NS; it < 20; it++) {
          int st = it % 5;
          if ((it & 3) == 0 || it == NS) { if (P3) hint_wait(G, sb + SM_SMALL + SMALL_H, 8 * m + (it >> 2), e1 * 32); else flag_wait(G, 8 * m + (it >> 2), e1 * 32); STAMP(45 + (it >> 2)); }
          if (NS && it == NS) mbar_arrive(sb + 8 * B_FS);
          mbar_wait(sb + 8 * (B_E1 + st), (it / 5) & 1);
          uint32_t fb = sb + 8 * (B_A + st);
          mbar_expect(fb, 8192);
          bulk_g2s(ring + st * 32768, G->AT + (20 * m + it) * 4096, 8192, fb);
        }
        mbar_wait(sb + 8 * B_XF, 0);
        flag_wait(G, 8 * m + FL_X, e1 * 8);
        mbar_arrive(sb + 8 * B_X1);
        STAMP(86);
      }
     }
    } else if (w == 2) {
      if (lane < 4) mbar_expect(sb + 8 * (B_RECV + lane), 12288);
      if (UT == 2) { bar_arrive(1, 288); bar_arrive(2, 288); }
      int ph = 0;
#pragma unroll 1
      for (int ch = UT; ch < 5; ch++) {
        const uint32_t ub = chan_base(sb, ch) + KSZ;
        uint4* pu = (uint4*)(G->kvT + (128 * ch + b) * S_);
        mbar_wait(sb + 8 * (B_KJ + ch), 0);
        const uint32_t t0 = lds32(sb + SM_SMALL + SMALL_TS + 4 * ch);
        while (clk() - t0 < (ch ? UD : UD0));
#pragma unroll 1
        for (int i = 0;; i++) {
          if (elect()) { mbar_expect(sb + 8 * B_U, 4096); bulk_g2s(ub, pu, 4096, sb + 8 * B_U); }
          if (ITW == 5) STAMPIF(lane == 0, 110 + ch);
          mbar_wait(sb + 8 * B_U, ph);
          ph ^= 1;
          uint32_t t = 1;
#pragma unroll
          for (int j = 0; j < 8; j++) t &= lds32(ub + 16 * lane + 512 * j + 12);
          if (__all_sync(0xffffffffu, t)) break;
          if (i > (1 << 20)) __trap();
        }
        if (ITW == 5) STAMPIF(lane == 0, 105 + ch);
        if (ch > 1) mbar_wait(sb + 8 * (B_Z + ch - 2), 0);
        bar_arrive(1 + (ch & 1), 288);
#pragma unroll
        for (int j = 0; j < 8; j++) stg128(pu + lane + 32 * j, make_uint4(0, 0, 0, 0));
      }
      if (ITW == 8) { mbar_wait(sb + 8 * B_X, 0); STAMPIF(lane == 0, 100); mbar_wait(sb + 8 * (B_X + 1), 0); STAMPIF(lane == 0, 101); }
      mbar_wait(sb + 8 * B_BD, 0);
      const uint32_t e1 = epoch(sb), ao = 256 * (lane & 16) + 32 * (lane & 15) + 4 * (lane & 4) + (lane & 8) + 4;
      int it = 0;
      uint32_t pm = (1 << NS) - 1;
      bool ok = false;
      if (NS) {
        if (lane < NS) mbar_expect(sb + 8 * (B_A + lane), 8192);
        mbar_wait(sb + 8 * (lane < NS ? B_E1 + lane : B_EW + 5), 0);
        __syncwarp();
        spin(clk(), AT1);
        spin(t_0, AT0);
        if (elect()) {
#pragma unroll
          for (int i = 0; i < NS; i++) bulk_g2s(ring + i * 32768, G->AT + (20 * m + i) * 4096, 8192, sb + 8 * (B_A + i));
        }
        __syncwarp();
        STAMPIF(lane == 0, 84);
#pragma unroll 1
        for (; it < NS; it++) {
          if (!ok) mbar_wait(sb + 8 * (B_A + it), 0);
          uint32_t t = 0, v[8];
          if (PC) ok = mbar_test(sb + 8 * (B_A + it + 1), 0);
#pragma unroll
          for (int j = 0; j < 8; j++) v[j] = ldv32(ring + it * 32768 + ao + 512 * j);
#pragma unroll
          for (int j = 0; j < 8; j++) t |= v[7 - j] ^ e1;
          if (__any_sync(0xffffffffu, t & 1)) {
            ok = false;
            fence_async_s();
            mbar_wait(sb + 8 * (lane > it && lane < NS ? B_A + lane : B_FS), 0);
            __syncwarp();
            if (lane >= it && lane < NS) mbar_expect(sb + 8 * (B_A + lane), 8192);
            __syncwarp();
            if (elect()) {
#pragma unroll
              for (int i = 0; i < NS; i++)
                if (i >= it) bulk_g2s(ring + i * 32768, G->AT + (20 * m + i) * 4096, 8192, sb + 8 * (B_A + i));
            }
            __syncwarp();
            STAMPIF(lane == 0, 85);
            break;
          }
          if (lane == 0) mbar_arrive(sb + 8 * (B_F1 + it));
        }
      }
#pragma unroll 1
      for (int st = it; it < 20; it++) {
        const uint32_t a = ring + st * 32768 + ao;
        if (!ok) mbar_wait(sb + 8 * (B_A + st), (pm >> st) & 1);
        pm ^= 1 << st;
        const int nx = st == 4 ? 0 : st + 1;
        if (ITW == 7) STAMPIF(lane == 0 && it < 4, 100 + it);
        if (ITW == 8) STAMPIF(lane == 0 && it < 2, 114 + it);
        uint32_t t = 0, v[8];
        if (PC) ok = mbar_test(sb + 8 * (B_A + nx), (pm >> nx) & 1);
#pragma unroll
        for (int j = 0; j < 8; j++) v[j] = ldv32(a + 512 * j);
#pragma unroll
        for (int j = 0; j < 8; j++) t |= v[7 - j] ^ e1;
        if (__any_sync(0xffffffffu, t & 1)) {
#pragma unroll 1
          for (int j = 0; j < 8; j++) a_check(a + 512 * j, (const char*)G->AT + (20 * m + it) * 8192 + ao + 512 * j, e1);
        }
        if (lane == 0) mbar_arrive(sb + 8 * (B_F1 + st));
        if (ITW == 7) STAMPIF(lane == 0 && it < 4, 104 + it);
        if (ITW == 8) STAMPIF(lane == 0 && it < 2, 116 + it);
        st = nx;
      }
    } else {
      mbar_wait(sb + 8 * B_KVS, 0);
      auto rel = [&](int ch) { mbar_wait(sb + 8 * (B_Z + ch), 0); if (lane <= (ch >> 2)) mbar_arrive(sb + 8 * (B_E1 + 2 + (ch >> 1))); };
      if (RL) { rel(0); rel(1); rel(2); }
      mbar_wait(sb + 8 * (B_BD + 1), 0);
      if (!BI && b >= 96 && elect()) { load_box(P, sb, b, 4); load_box(P, sb, b, 5); }
      const uint32_t t1 = clk();
      if (RL) { rel(3); rel(4); }
      spin(t1, CD);
      __syncwarp();
      const uint32_t e1 = epoch(sb);
#pragma unroll 1
      for (int n = 0; n < 5; n++) {
        int lane;
        asm volatile("mov.u32 %0, %%laneid;" : "=r"(lane));
        if (n == 3) {
          fence_async_s();
          __syncwarp();
          if (lane == 0) mbar_arrive(sb + 8 * B_F);
          STAMPIF(lane == 0, 34);
          {
            mbar_wait(sb + 8 * (B_EW + 4), 0);
            const char* po = (char*)gout + (2 * tbase(b) + 64 * (lane & 28) + ((lane >> 1) & 1)) * 2 * D_ + (lane & 1) * 640;
            uint32_t v = 0;
#pragma unroll
            for (int r = 0; r < 5; r++) v ^= rdback(po + 128 * r);
            rdwait(sb, v);
            __syncwarp();
            if (lane == 0) flag_add(G, 8 * m + FL_X);
            STAMPIF(lane == 0, 94);
          }
          mbar_wait(sb + 8 * (B_BD + 2), 0);
          if (lane < 2) mbar_arrive(sb + 8 * (B_E1 + 5));
          if (m < 12) {
            rdwait(sb, rdback(G->cimg + s * 3072 + (m % 6) * 512 + (m < 6 ? 0 : 256) + 64 * (lane & 3)));
            __syncwarp();
            if (lane == 0) flag_add(G, FL_C + 8 * s);
            STAMPIF(lane == 0, 35);
          }
          if (elect()) {
            flag_wait(G, FL_C + 8 * s, e1 * 12);
            fence_async_g();
            STAMP(54);
            mbar_expect(sb + 8 * B_EXT, 6144);
            bulk_g2s(sb + SM_EXT, G->cimg + s * 3072, 6144, sb + 8 * B_EXT);
          }
          __syncwarp();
          mbar_wait(sb + 8 * B_ST2, 0);
        }
        const int j = n < 3 ? min(16 * n + (lane >> 1), 39) : min(16 * n - 8 + (lane >> 1), 59), k = j < 20 ? j : j < 40 ? j - 20 : j - 40;
        const uint2* pj = (const uint2*)(G->mv + 2048 * (e1 & 1) + 4 * (lane & 1) + 8 * (k + (j < 40 ? (j < 20 ? 160 : 120) + (m < 6 ? 0 : 20) : 200 + 20 * (s & 1))));
        uint4 a;
#pragma unroll 1
        for (int i = 0;; i++) {
          a = ld_tag2(pj);
          if (__all_sync(0xffffffffu, a.x != 0)) break;
          if (i > (1 << 20)) __trap();
        }
        const uint32_t d = sb + SM_CB + 64 * k + 8 * (lane & 1) + (j >= 20 && j < 40 ? 16 : 0);
        sts64(d, ~__byte_perm(a.x, a.y, 0x5410), ~__byte_perm(a.z, a.w, 0x5410));
        sts64(d + 32, ~__byte_perm(a.x, a.y, 0x7632), ~__byte_perm(a.z, a.w, 0x7632));
      }
      __syncwarp();
      if (lane == 0) mbar_arrive(sb + 8 * B_GB);
      STAMPIF(lane == 0, 39);
    }
    } else {
      STAMPIF(lane == 0, 62);
      int rw = sched_run<0>(P, In{gk, gv, gsk, gWg, gWu, gWd, gss}, sb, b, lane, __shfl_sync(0xffffffffu, t_0, 0));
      if (elect()) {
        STAMP(69);
        mbar_wait(sb + 8 * B_KVS, 0);
        if (ER) mbar_wait(sb + 8 * B_KV4, 0);
        STAMP(70);
        int rd = 0, c = 0;
#pragma unroll 1
        for (int it = 0; it < 20; it++) {
          load_w(P, sb, s, it);
          if ((PWM >> it) & 1) { l2_prefetch(gWg + (128 * rw + b) * F_, 2 * F_); l2_prefetch(gWu + (128 * rw + b) * F_, 2 * F_); rw++; }
          if ((PDM >> it) & 1) { l2_prefetch(gWd + (512 * rd + 4 * b) * D_, 8 * D_); rd++; }
          if (BI && it == BI && b >= 96) { mbar_wait(sb + 8 * (B_BD + 1), 0); load_box(P, sb, b, 4); load_box(P, sb, b, 5); }
          if (((STM >> it) & 1) && b < 96) {
            const int grp = m % 6;
            if (c == 4) mbar_wait(sb + 8 * (B_BD + 1), 0);
            if (c == 0) mbar_expect(sb + 8 * B_ST0, 40960);
#pragma unroll
            for (int j = 0; j < 2; j++, c++)
              tma2d(sb + (c < 2 ? SM_EXT : SM_RING + R_X - 8192) + 4096 * c, &P.mG + (grp & 1), 192 * s + 64 * (grp >> 1), (m < 6 ? 0 : 320) + 32 * c, sb + 8 * B_ST0);
          }
        }
#pragma unroll
        for (int k = 0; k < 10; k++) {
          const int st = (k + 5) % 6, pe = k < 4 ? k >> 1 : k & 1, ps = k < 4 ? k & 1 : k >> 1;
          mbar_wait(sb + 8 * (k < 6 ? B_E1 + st : B_EB + k - 6), 0);
          if (k == 2) mbar_arrive_remote(mapa(sb + 8 * B_P0, (b & 1) ^ 1));
          mbar_expect(sb + 8 * (B_FB + k), 24576);
          tma2d(ring + st * 32768 + 8192, &P.mD, 320 * (s & 1) + 64 * out_blk(s, ps), 192 * (s ^ pe), sb + 8 * (B_FB + k));
        }
      }
    }
  }
}

typedef CUresult (*EncFn)(CUtensorMap*, CUtensorMapDataType, cuuint32_t, void*, const cuuint64_t*, const cuuint64_t*, const cuuint32_t*, const cuuint32_t*,
                          CUtensorMapInterleave, CUtensorMapSwizzle, CUtensorMapL2promotion, CUtensorMapFloatOOBfill);
static void mkmap(EncFn enc, CUtensorMap* m, const void* p, int rank, const cuuint64_t* dims, const cuuint64_t* strides, const cuuint32_t* box, CUtensorMapSwizzle sw) {
  cuuint32_t es[5] = {1, 1, 1, 1, 1};
  CUresult r = enc(m, CU_TENSOR_MAP_DATA_TYPE_BFLOAT16, rank, (void*)p, dims, strides, box, es, CU_TENSOR_MAP_INTERLEAVE_NONE, sw,
                   CU_TENSOR_MAP_L2_PROMOTION_L2_128B, CU_TENSOR_MAP_FLOAT_OOB_FILL_NONE);
  if (r != CUDA_SUCCESS) fprintf(stderr, "tensor map encode failed: %d\n", (int)r);
}

extern "C" void kernel_launch(void* const* d_in, const int* in_sizes, int n_in, void* d_out, int out_size) {
  void* fn = nullptr;
  cudaDriverEntryPointQueryResult qr;
  cudaGetDriverEntryPoint("cuTensorMapEncodeTiled", &fn, cudaEnableDefault, &qr);
  EncFn enc = (EncFn)fn;
  Scr* G;
  cudaGetSymbolAddress((void**)&G, g_scr);
  Params P;
  { cuuint64_t d[] = {128, 16, 640}, st[] = {256, 4096}; cuuint32_t bx[] = {144, 16, 1}; mkmap(enc, &P.mS, d_in[4], 3, d, st, bx, CU_TENSOR_MAP_SWIZZLE_NONE); }
  { cuuint64_t d[] = {3840, 64, 10}, st[] = {7680, 64 * 7680}; cuuint32_t bx[] = {16, 64, 5}; mkmap(enc, &P.mWm, d_in[11], 3, d, st, bx, CU_TENSOR_MAP_SWIZZLE_32B); }
  { cuuint64_t d[] = {32, 20, 256, 8}, st[] = {64, 10240, 1280}; cuuint32_t bx[] = {40, 1, 9, 8}, bx2[] = {40, 1, 8, 8};
    mkmap(enc, &P.mK, d_in[1], 4, d, st, bx, CU_TENSOR_MAP_SWIZZLE_NONE); mkmap(enc, &P.mV, d_in[2], 4, d, st, bx2, CU_TENSOR_MAP_SWIZZLE_NONE); }
  { cuuint64_t d[] = {1536, 640}, st[] = {3072}; cuuint32_t bx[] = {64, 32};
    mkmap(enc, &P.mG, d_in[7], 2, d, st, bx, CU_TENSOR_MAP_SWIZZLE_128B); mkmap(enc, &P.mU, d_in[8], 2, d, st, bx, CU_TENSOR_MAP_SWIZZLE_128B); }
  { cuuint64_t d[] = {640, 1536}, st[] = {1280}; cuuint32_t bx[] = {64, 192}; mkmap(enc, &P.mD, d_in[9], 2, d, st, bx, CU_TENSOR_MAP_SWIZZLE_128B); }
  { cuuint64_t d[] = {64, 2, 8, 10, 128}, st[] = {1280, 256 * 1280, 128, 2560}; cuuint32_t bx[] = {64, 2, 8, 5, 1}; mkmap(enc, &P.mX, d_in[0], 5, d, st, bx, CU_TENSOR_MAP_SWIZZLE_128B); }
  cudaFuncSetAttribute(fused_kernel, cudaFuncAttributeMaxDynamicSharedMemorySize, SM_TOTAL + DEVSM);
  cudaLaunchConfig_t cfg = {};
  cfg.gridDim = dim3(128); cfg.blockDim = dim3(512); cfg.dynamicSmemBytes = SM_TOTAL + DEVSM; cfg.stream = cudaStreamPerThread;
  cudaLaunchAttribute at[1];
  at[0].id = cudaLaunchAttributeClusterDimension; at[0].val.clusterDim.x = 2; at[0].val.clusterDim.y = 1; at[0].val.clusterDim.z = 1;
  cfg.attrs = at; cfg.numAttrs = 1;
  cudaLaunchKernelEx(&cfg, fused_kernel, (const bf16*)d_in[1], (const bf16*)d_in[2], (const bf16*)d_in[3], (const bf16*)d_in[5], (const bf16*)d_in[10], G,
                     (const bf16*)d_in[7], (const bf16*)d_in[8], (const bf16*)d_in[9], (bf16*)d_out, (const bf16*)d_in[4], P);
}
```

```cpp
#include <cuda_runtime.h>
#include <cuda.h>
#include <cuda_bf16.h>
#include <stdio.h>
#include <stdint.h>
typedef __nv_bfloat16 bf16;
__device__ __forceinline__ uint32_t smem_u32(const void* p) { return (uint32_t)__cvta_generic_to_shared(p); }
__device__ __forceinline__ void mbar_init(uint32_t bar, int cnt) { asm volatile("mbarrier.init.shared::cta.b64 [%0], %1;" ::"r"(bar), "r"(cnt) : "memory"); }
__device__ __forceinline__ void mbar_expect(uint32_t bar, int bytes) { asm volatile("mbarrier.arrive.expect_tx.shared::cta.b64 _, [%0], %1;" ::"r"(bar), "r"(bytes) : "memory"); }
__device__ __forceinline__ void mbar_arrive(uint32_t bar) { asm volatile("mbarrier.arrive.shared::cta.b64 _, [%0];" ::"r"(bar) : "memory"); }
__device__ __forceinline__ void mbar_arrive_remote(uint32_t bar) { asm volatile("mbarrier.arrive.relaxed.cluster.shared::cluster.b64 _, [%0];" ::"r"(bar) : "memory"); }
__device__ __forceinline__ uint32_t mapa(uint32_t a, uint32_t cta) { uint32_t r; asm("mapa.shared::cluster.u32 %0, %1, %2;" : "=r"(r) : "r"(a), "r"(cta)); return r; }
__device__ __forceinline__ bool mbar_try(uint32_t bar, int parity) {
  uint32_t ok;
  asm volatile("{\n.reg .pred p;\nmbarrier.try_wait.parity.shared::cta.b64 p, [%1], %2;\nselp.u32 %0, 1, 0, p;\n}" : "=r"(ok) : "r"(bar), "r"(parity) : "memory");
  return ok;
}
__device__ __forceinline__ void mbar_wait(uint32_t bar, int parity) {
#pragma unroll 1
  for (int i = 0; i < (1 << 20); i++) { if (mbar_try(bar, parity)) return; }
  __trap();
}
__device__ __forceinline__ bool elect() {
  uint32_t p;
  asm volatile("{\n.reg .pred P;\nelect.sync _|P, 0xffffffff;\nselp.u32 %0, 1, 0, P;\n}" : "=r"(p));
  return p;
}
__device__ __forceinline__ void tma2d(uint32_t dst, const CUtensorMap* m, int c0, int c1, uint32_t bar) {
  asm volatile("cp.async.bulk.tensor.2d.shared::cluster.global.mbarrier::complete_tx::bytes [%0], [%1, {%3, %4}], [%2];" ::"r"(dst), "l"(m), "r"(bar), "r"(c0), "r"(c1) : "memory");
}
__device__ __forceinline__ void tma3d(uint32_t dst, const CUtensorMap* m, int c0, int c1, int c2, uint32_t bar) {
  asm volatile("cp.async.bulk.tensor.3d.shared::cluster.global.mbarrier::complete_tx::bytes [%0], [%1, {%3, %4, %5}], [%2];" ::"r"(dst), "l"(m), "r"(bar), "r"(c0), "r"(c1), "r"(c2) : "memory");
}
__device__ __forceinline__ void tma4d(uint32_t dst, const CUtensorMap* m, int c0, int c1, int c2, int c3, uint32_t bar) {
  asm volatile("cp.async.bulk.tensor.4d.shared::cluster.global.mbarrier::complete_tx::bytes [%0], [%1, {%3, %4, %5, %6}], [%2];" ::"r"(dst), "l"(m), "r"(bar), "r"(c0), "r"(c1), "r"(c2), "r"(c3) : "memory");
}
__device__ __forceinline__ void tma5d(uint32_t dst, const CUtensorMap* m, int c0, int c1, int c2, int c3, int c4, uint32_t bar) {
  asm volatile("cp.async.bulk.tensor.5d.shared::cluster.global.mbarrier::complete_tx::bytes [%0], [%1, {%3, %4, %5, %6, %7}], [%2];" ::"r"(dst), "l"(m), "r"(bar), "r"(c0), "r"(c1), "r"(c2), "r"(c3), "r"(c4) : "memory");
}
__device__ __forceinline__ void tma_store2d(const CUtensorMap* m, uint32_t src, int c0, int c1) {
  asm volatile("cp.async.bulk.tensor.2d.global.shared::cta.bulk_group [%0, {%2, %3}], [%1];" ::"l"(m), "r"(src), "r"(c0), "r"(c1) : "memory");
}
__device__ __forceinline__ void tma_store4d(const CUtensorMap* m, uint32_t src, int c0, int c1, int c2, int c3) {
  asm volatile("cp.async.bulk.tensor.4d.global.shared::cta.bulk_group [%0, {%2, %3, %4, %5}], [%1];" ::"l"(m), "r"(src), "r"(c0), "r"(c1), "r"(c2), "r"(c3) : "memory");
}
__device__ __forceinline__ void tma_prefetch2d(const CUtensorMap* m, int c0, int c1) {
  asm volatile("cp.async.bulk.prefetch.tensor.2d.L2.global [%0, {%1, %2}];" ::"l"(m), "r"(c0), "r"(c1) : "memory");
}
__device__ __forceinline__ void bulk_g2s(uint32_t dst, const void* src, int bytes, uint32_t bar) {
  asm volatile("cp.async.bulk.shared::cluster.global.mbarrier::complete_tx::bytes [%0], [%1], %2, [%3];" ::"r"(dst), "l"(src), "r"(bytes), "r"(bar) : "memory");
}
__device__ __forceinline__ void bulk_s2g(void* dst, uint32_t src, int bytes) {
  asm volatile("cp.async.bulk.global.shared::cta.bulk_group [%0], [%1], %2;" ::"l"(dst), "r"(src), "r"(bytes) : "memory");
}
__device__ __forceinline__ void cp16(uint32_t dst, const void* src) { asm volatile("cp.async.cg.shared.global [%0], [%1], 16;" ::"r"(dst), "l"(src) : "memory"); }
__device__ __forceinline__ void cp16z(uint32_t dst, const void* src, int n) { asm volatile("cp.async.cg.shared.global [%0], [%1], 16, %2;" ::"r"(dst), "l"(src), "r"(n) : "memory"); }
__device__ __forceinline__ void cp_arrive(uint32_t bar) { asm volatile("cp.async.mbarrier.arrive.noinc.shared::cta.b64 [%0];" ::"r"(bar) : "memory"); }
__device__ __forceinline__ void st_async4(uint32_t dst, const uint32_t* v, uint32_t bar) {
  asm volatile("st.async.weak.shared::cluster.mbarrier::complete_tx::bytes.v4.b32 [%0], {%1, %2, %3, %4}, [%5];" ::"r"(dst), "r"(v[0]), "r"(v[1]), "r"(v[2]), "r"(v[3]), "r"(bar) : "memory");
}
__device__ __forceinline__ void wg_fence() { asm volatile("wgmma.fence.sync.aligned;" ::: "memory"); }
__device__ __forceinline__ void wg_commit() { asm volatile("wgmma.commit_group.sync.aligned;" ::: "memory"); }
template <int N> __device__ __forceinline__ void wg_wait() { asm volatile("wgmma.wait_group.sync.aligned %0;" ::"n"(N) : "memory"); }
__device__ __forceinline__ uint64_t mkdesc(uint32_t addr, uint32_t lbo, uint32_t sbo, uint32_t swz) {
  return (uint64_t)((addr & 0x3FFFF) >> 4) | ((uint64_t)(lbo >> 4) << 16) | ((uint64_t)(sbo >> 4) << 32) | ((uint64_t)swz << 62);
}
__device__ __forceinline__ void ldsm4t(uint32_t* r, uint32_t a) {
  asm volatile("ldmatrix.sync.aligned.m8n8.x4.trans.shared.b16 {%0,%1,%2,%3}, [%4];" : "=r"(r[0]), "=r"(r[1]), "=r"(r[2]), "=r"(r[3]) : "r"(a) : "memory");
}
__device__ __forceinline__ void stsm4(uint32_t a, const uint32_t* r) {
  asm volatile("stmatrix.sync.aligned.m8n8.x4.shared.b16 [%0], {%1,%2,%3,%4};" ::"r"(a), "r"(r[0]), "r"(r[1]), "r"(r[2]), "r"(r[3]) : "memory");
}
__device__ __forceinline__ void stsm4t(uint32_t a, const uint32_t* r) {
  asm volatile("stmatrix.sync.aligned.m8n8.x4.trans.shared.b16 [%0], {%1,%2,%3,%4};" ::"r"(a), "r"(r[0]), "r"(r[1]), "r"(r[2]), "r"(r[3]) : "memory");
}
__device__ __forceinline__ void bar_sync(int id, int n) { asm volatile("bar.sync %0, %1;" ::"r"(id), "r"(n) : "memory"); }
__device__ __forceinline__ void bar_arrive(int id, int n) { asm volatile("bar.arrive %0, %1;" ::"r"(id), "r"(n) : "memory"); }
__device__ __forceinline__ uint32_t lds32(uint32_t a) { uint32_t v; asm volatile("ld.shared.b32 %0, [%1];" : "=r"(v) : "r"(a) : "memory"); return v; }
__device__ __forceinline__ uint2 lds64(uint32_t a) { uint2 v; asm volatile("ld.shared.v2.b32 {%0,%1}, [%2];" : "=r"(v.x), "=r"(v.y) : "r"(a) : "memory"); return v; }
__device__ __forceinline__ uint4 lds128(uint32_t a) { uint4 v; asm volatile("ld.shared.v4.b32 {%0,%1,%2,%3}, [%4];" : "=r"(v.x), "=r"(v.y), "=r"(v.z), "=r"(v.w) : "r"(a) : "memory"); return v; }
__device__ __forceinline__ void sts16(uint32_t a, uint32_t v) { asm volatile("st.shared.b16 [%0], %1;" ::"r"(a), "h"((uint16_t)v) : "memory"); }
__device__ __forceinline__ void sts32(uint32_t a, uint32_t v) { asm volatile("st.shared.b32 [%0], %1;" ::"r"(a), "r"(v) : "memory"); }
__device__ __forceinline__ void sts64(uint32_t a, uint32_t x, uint32_t y) { asm volatile("st.shared.v2.b32 [%0], {%1,%2};" ::"r"(a), "r"(x), "r"(y) : "memory"); }
__device__ __forceinline__ void sts128(uint32_t a, uint4 v) { asm volatile("st.shared.v4.b32 [%0], {%1,%2,%3,%4};" ::"r"(a), "r"(v.x), "r"(v.y), "r"(v.z), "r"(v.w) : "memory"); }
template<int TB> __device__ __forceinline__ void wgmma_rs_n128(float* d, const uint32_t* a, uint64_t db, int sd) {
  asm volatile("{\n.reg .pred p;\nsetp.ne.b32 p, %69, 0;\n"
    "wgmma.mma_async.sync.aligned.m64n128k16.f32.bf16.bf16 {%0, %1, %2, %3, %4, %5, %6, %7, %8, %9, %10, %11, %12, %13, %14, %15, %16, %17, %18, %19, %20, %21, %22, %23, %24, %25, %26, %27, %28, %29, %30, %31, %32, %33, %34, %35, %36, %37, %38, %39, %40, %41, %42, %43, %44, %45, %46, %47, %48, %49, %50, %51, %52, %53, %54, %55, %56, %57, %58, %59, %60, %61, %62, %63}, {%64, %65, %66, %67}, %68, p, 1, 1, %70;\n}"
    : "+f"(d[0]), "+f"(d[1]), "+f"(d[2]), "+f"(d[3]), "+f"(d[4]), "+f"(d[5]), "+f"(d[6]), "+f"(d[7]), "+f"(d[8]), "+f"(d[9]), "+f"(d[10]), "+f"(d[11]), "+f"(d[12]), "+f"(d[13]), "+f"(d[14]), "+f"(d[15]), "+f"(d[16]), "+f"(d[17]), "+f"(d[18]), "+f"(d[19]), "+f"(d[20]), "+f"(d[21]), "+f"(d[22]), "+f"(d[23]), "+f"(d[24]), "+f"(d[25]), "+f"(d[26]), "+f"(d[27]), "+f"(d[28]), "+f"(d[29]), "+f"(d[30]), "+f"(d[31]), "+f"(d[32]), "+f"(d[33]), "+f"(d[34]), "+f"(d[35]), "+f"(d[36]), "+f"(d[37]), "+f"(d[38]), "+f"(d[39]), "+f"(d[40]), "+f"(d[41]), "+f"(d[42]), "+f"(d[43]), "+f"(d[44]), "+f"(d[45]), "+f"(d[46]), "+f"(d[47]), "+f"(d[48]), "+f"(d[49]), "+f"(d[50]), "+f"(d[51]), "+f"(d[52]), "+f"(d[53]), "+f"(d[54]), "+f"(d[55]), "+f"(d[56]), "+f"(d[57]), "+f"(d[58]), "+f"(d[59]), "+f"(d[60]), "+f"(d[61]), "+f"(d[62]), "+f"(d[63])
    : "r"(a[0]), "r"(a[1]), "r"(a[2]), "r"(a[3]), "l"(db), "r"(sd), "n"(TB));
}

template<int TB> __device__ __forceinline__ void wgmma_rs_n160(float* d, const uint32_t* a, uint64_t db, int sd) {
  asm volatile("{\n.reg .pred p;\nsetp.ne.b32 p, %85, 0;\n"
    "wgmma.mma_async.sync.aligned.m64n160k16.f32.bf16.bf16 {%0, %1, %2, %3, %4, %5, %6, %7, %8, %9, %10, %11, %12, %13, %14, %15, %16, %17, %18, %19, %20, %21, %22, %23, %24, %25, %26, %27, %28, %29, %30, %31, %32, %33, %34, %35, %36, %37, %38, %39, %40, %41, %42, %43, %44, %45, %46, %47, %48, %49, %50, %51, %52, %53, %54, %55, %56, %57, %58, %59, %60, %61, %62, %63, %64, %65, %66, %67, %68, %69, %70, %71, %72, %73, %74, %75, %76, %77, %78, %79}, {%80, %81, %82, %83}, %84, p, 1, 1, %86;\n}"
    : "+f"(d[0]), "+f"(d[1]), "+f"(d[2]), "+f"(d[3]), "+f"(d[4]), "+f"(d[5]), "+f"(d[6]), "+f"(d[7]), "+f"(d[8]), "+f"(d[9]), "+f"(d[10]), "+f"(d[11]), "+f"(d[12]), "+f"(d[13]), "+f"(d[14]), "+f"(d[15]), "+f"(d[16]), "+f"(d[17]), "+f"(d[18]), "+f"(d[19]), "+f"(d[20]), "+f"(d[21]), "+f"(d[22]), "+f"(d[23]), "+f"(d[24]), "+f"(d[25]), "+f"(d[26]), "+f"(d[27]), "+f"(d[28]), "+f"(d[29]), "+f"(d[30]), "+f"(d[31]), "+f"(d[32]), "+f"(d[33]), "+f"(d[34]), "+f"(d[35]), "+f"(d[36]), "+f"(d[37]), "+f"(d[38]), "+f"(d[39]), "+f"(d[40]), "+f"(d[41]), "+f"(d[42]), "+f"(d[43]), "+f"(d[44]), "+f"(d[45]), "+f"(d[46]), "+f"(d[47]), "+f"(d[48]), "+f"(d[49]), "+f"(d[50]), "+f"(d[51]), "+f"(d[52]), "+f"(d[53]), "+f"(d[54]), "+f"(d[55]), "+f"(d[56]), "+f"(d[57]), "+f"(d[58]), "+f"(d[59]), "+f"(d[60]), "+f"(d[61]), "+f"(d[62]), "+f"(d[63]), "+f"(d[64]), "+f"(d[65]), "+f"(d[66]), "+f"(d[67]), "+f"(d[68]), "+f"(d[69]), "+f"(d[70]), "+f"(d[71]), "+f"(d[72]), "+f"(d[73]), "+f"(d[74]), "+f"(d[75]), "+f"(d[76]), "+f"(d[77]), "+f"(d[78]), "+f"(d[79])
    : "r"(a[0]), "r"(a[1]), "r"(a[2]), "r"(a[3]), "l"(db), "r"(sd), "n"(TB));
}

template<int TB> __device__ __forceinline__ void wgmma_rs_n192(float* d, const uint32_t* a, uint64_t db, int sd) {
  asm volatile("{\n.reg .pred p;\nsetp.ne.b32 p, %101, 0;\n"
    "wgmma.mma_async.sync.aligned.m64n192k16.f32.bf16.bf16 {%0, %1, %2, %3, %4, %5, %6, %7, %8, %9, %10, %11, %12, %13, %14, %15, %16, %17, %18, %19, %20, %21, %22, %23, %24, %25, %26, %27, %28, %29, %30, %31, %32, %33, %34, %35, %36, %37, %38, %39, %40, %41, %42, %43, %44, %45, %46, %47, %48, %49, %50, %51, %52, %53, %54, %55, %56, %57, %58, %59, %60, %61, %62, %63, %64, %65, %66, %67, %68, %69, %70, %71, %72, %73, %74, %75, %76, %77, %78, %79, %80, %81, %82, %83, %84, %85, %86, %87, %88, %89, %90, %91, %92, %93, %94, %95}, {%96, %97, %98, %99}, %100, p, 1, 1, %102;\n}"
    : "+f"(d[0]), "+f"(d[1]), "+f"(d[2]), "+f"(d[3]), "+f"(d[4]), "+f"(d[5]), "+f"(d[6]), "+f"(d[7]), "+f"(d[8]), "+f"(d[9]), "+f"(d[10]), "+f"(d[11]), "+f"(d[12]), "+f"(d[13]), "+f"(d[14]), "+f"(d[15]), "+f"(d[16]), "+f"(d[17]), "+f"(d[18]), "+f"(d[19]), "+f"(d[20]), "+f"(d[21]), "+f"(d[22]), "+f"(d[23]), "+f"(d[24]), "+f"(d[25]), "+f"(d[26]), "+f"(d[27]), "+f"(d[28]), "+f"(d[29]), "+f"(d[30]), "+f"(d[31]), "+f"(d[32]), "+f"(d[33]), "+f"(d[34]), "+f"(d[35]), "+f"(d[36]), "+f"(d[37]), "+f"(d[38]), "+f"(d[39]), "+f"(d[40]), "+f"(d[41]), "+f"(d[42]), "+f"(d[43]), "+f"(d[44]), "+f"(d[45]), "+f"(d[46]), "+f"(d[47]), "+f"(d[48]), "+f"(d[49]), "+f"(d[50]), "+f"(d[51]), "+f"(d[52]), "+f"(d[53]), "+f"(d[54]), "+f"(d[55]), "+f"(d[56]), "+f"(d[57]), "+f"(d[58]), "+f"(d[59]), "+f"(d[60]), "+f"(d[61]), "+f"(d[62]), "+f"(d[63]), "+f"(d[64]), "+f"(d[65]), "+f"(d[66]), "+f"(d[67]), "+f"(d[68]), "+f"(d[69]), "+f"(d[70]), "+f"(d[71]), "+f"(d[72]), "+f"(d[73]), "+f"(d[74]), "+f"(d[75]), "+f"(d[76]), "+f"(d[77]), "+f"(d[78]), "+f"(d[79]), "+f"(d[80]), "+f"(d[81]), "+f"(d[82]), "+f"(d[83]), "+f"(d[84]), "+f"(d[85]), "+f"(d[86]), "+f"(d[87]), "+f"(d[88]), "+f"(d[89]), "+f"(d[90]), "+f"(d[91]), "+f"(d[92]), "+f"(d[93]), "+f"(d[94]), "+f"(d[95])
    : "r"(a[0]), "r"(a[1]), "r"(a[2]), "r"(a[3]), "l"(db), "r"(sd), "n"(TB));
}

template<int TB> __device__ __forceinline__ void wgmma_rs_n32(float* d, const uint32_t* a, uint64_t db, int sd) {
  asm volatile("{\n.reg .pred p;\nsetp.ne.b32 p, %21, 0;\n"
    "wgmma.mma_async.sync.aligned.m64n32k16.f32.bf16.bf16 {%0, %1, %2, %3, %4, %5, %6, %7, %8, %9, %10, %11, %12, %13, %14, %15}, {%16, %17, %18, %19}, %20, p, 1, 1, %22;\n}"
    : "+f"(d[0]), "+f"(d[1]), "+f"(d[2]), "+f"(d[3]), "+f"(d[4]), "+f"(d[5]), "+f"(d[6]), "+f"(d[7]), "+f"(d[8]), "+f"(d[9]), "+f"(d[10]), "+f"(d[11]), "+f"(d[12]), "+f"(d[13]), "+f"(d[14]), "+f"(d[15])
    : "r"(a[0]), "r"(a[1]), "r"(a[2]), "r"(a[3]), "l"(db), "r"(sd), "n"(TB));
}

template<int TB> __device__ __forceinline__ void wgmma_rs_n64(float* d, const uint32_t* a, uint64_t db, int sd) {
  asm volatile("{\n.reg .pred p;\nsetp.ne.b32 p, %37, 0;\n"
    "wgmma.mma_async.sync.aligned.m64n64k16.f32.bf16.bf16 {%0, %1, %2, %3, %4, %5, %6, %7, %8, %9, %10, %11, %12, %13, %14, %15, %16, %17, %18, %19, %20, %21, %22, %23, %24, %25, %26, %27, %28, %29, %30, %31}, {%32, %33, %34, %35}, %36, p, 1, 1, %38;\n}"
    : "+f"(d[0]), "+f"(d[1]), "+f"(d[2]), "+f"(d[3]), "+f"(d[4]), "+f"(d[5]), "+f"(d[6]), "+f"(d[7]), "+f"(d[8]), "+f"(d[9]), "+f"(d[10]), "+f"(d[11]), "+f"(d[12]), "+f"(d[13]), "+f"(d[14]), "+f"(d[15]), "+f"(d[16]), "+f"(d[17]), "+f"(d[18]), "+f"(d[19]), "+f"(d[20]), "+f"(d[21]), "+f"(d[22]), "+f"(d[23]), "+f"(d[24]), "+f"(d[25]), "+f"(d[26]), "+f"(d[27]), "+f"(d[28]), "+f"(d[29]), "+f"(d[30]), "+f"(d[31])
    : "r"(a[0]), "r"(a[1]), "r"(a[2]), "r"(a[3]), "l"(db), "r"(sd), "n"(TB));
}

template<int TB> __device__ __forceinline__ void wgmma_rs_n96(float* d, const uint32_t* a, uint64_t db, int sd) {
  asm volatile("{\n.reg .pred p;\nsetp.ne.b32 p, %53, 0;\n"
    "wgmma.mma_async.sync.aligned.m64n96k16.f32.bf16.bf16 {%0, %1, %2, %3, %4, %5, %6, %7, %8, %9, %10, %11, %12, %13, %14, %15, %16, %17, %18, %19, %20, %21, %22, %23, %24, %25, %26, %27, %28, %29, %30, %31, %32, %33, %34, %35, %36, %37, %38, %39, %40, %41, %42, %43, %44, %45, %46, %47}, {%48, %49, %50, %51}, %52, p, 1, 1, %54;\n}"
    : "+f"(d[0]), "+f"(d[1]), "+f"(d[2]), "+f"(d[3]), "+f"(d[4]), "+f"(d[5]), "+f"(d[6]), "+f"(d[7]), "+f"(d[8]), "+f"(d[9]), "+f"(d[10]), "+f"(d[11]), "+f"(d[12]), "+f"(d[13]), "+f"(d[14]), "+f"(d[15]), "+f"(d[16]), "+f"(d[17]), "+f"(d[18]), "+f"(d[19]), "+f"(d[20]), "+f"(d[21]), "+f"(d[22]), "+f"(d[23]), "+f"(d[24]), "+f"(d[25]), "+f"(d[26]), "+f"(d[27]), "+f"(d[28]), "+f"(d[29]), "+f"(d[30]), "+f"(d[31]), "+f"(d[32]), "+f"(d[33]), "+f"(d[34]), "+f"(d[35]), "+f"(d[36]), "+f"(d[37]), "+f"(d[38]), "+f"(d[39]), "+f"(d[40]), "+f"(d[41]), "+f"(d[42]), "+f"(d[43]), "+f"(d[44]), "+f"(d[45]), "+f"(d[46]), "+f"(d[47])
    : "r"(a[0]), "r"(a[1]), "r"(a[2]), "r"(a[3]), "l"(db), "r"(sd), "n"(TB));
}

template<int TA, int TB> __device__ __forceinline__ void wgmma_ss_n192(float* d, uint64_t da, uint64_t db, int sd) {
  asm volatile("{\n.reg .pred p;\nsetp.ne.b32 p, %98, 0;\n"
    "wgmma.mma_async.sync.aligned.m64n192k16.f32.bf16.bf16 {%0, %1, %2, %3, %4, %5, %6, %7, %8, %9, %10, %11, %12, %13, %14, %15, %16, %17, %18, %19, %20, %21, %22, %23, %24, %25, %26, %27, %28, %29, %30, %31, %32, %33, %34, %35, %36, %37, %38, %39, %40, %41, %42, %43, %44, %45, %46, %47, %48, %49, %50, %51, %52, %53, %54, %55, %56, %57, %58, %59, %60, %61, %62, %63, %64, %65, %66, %67, %68, %69, %70, %71, %72, %73, %74, %75, %76, %77, %78, %79, %80, %81, %82, %83, %84, %85, %86, %87, %88, %89, %90, %91, %92, %93, %94, %95}, %96, %97, p, 1, 1, %99, %100;\n}"
    : "+f"(d[0]), "+f"(d[1]), "+f"(d[2]), "+f"(d[3]), "+f"(d[4]), "+f"(d[5]), "+f"(d[6]), "+f"(d[7]), "+f"(d[8]), "+f"(d[9]), "+f"(d[10]), "+f"(d[11]), "+f"(d[12]), "+f"(d[13]), "+f"(d[14]), "+f"(d[15]), "+f"(d[16]), "+f"(d[17]), "+f"(d[18]), "+f"(d[19]), "+f"(d[20]), "+f"(d[21]), "+f"(d[22]), "+f"(d[23]), "+f"(d[24]), "+f"(d[25]), "+f"(d[26]), "+f"(d[27]), "+f"(d[28]), "+f"(d[29]), "+f"(d[30]), "+f"(d[31]), "+f"(d[32]), "+f"(d[33]), "+f"(d[34]), "+f"(d[35]), "+f"(d[36]), "+f"(d[37]), "+f"(d[38]), "+f"(d[39]), "+f"(d[40]), "+f"(d[41]), "+f"(d[42]), "+f"(d[43]), "+f"(d[44]), "+f"(d[45]), "+f"(d[46]), "+f"(d[47]), "+f"(d[48]), "+f"(d[49]), "+f"(d[50]), "+f"(d[51]), "+f"(d[52]), "+f"(d[53]), "+f"(d[54]), "+f"(d[55]), "+f"(d[56]), "+f"(d[57]), "+f"(d[58]), "+f"(d[59]), "+f"(d[60]), "+f"(d[61]), "+f"(d[62]), "+f"(d[63]), "+f"(d[64]), "+f"(d[65]), "+f"(d[66]), "+f"(d[67]), "+f"(d[68]), "+f"(d[69]), "+f"(d[70]), "+f"(d[71]), "+f"(d[72]), "+f"(d[73]), "+f"(d[74]), "+f"(d[75]), "+f"(d[76]), "+f"(d[77]), "+f"(d[78]), "+f"(d[79]), "+f"(d[80]), "+f"(d[81]), "+f"(d[82]), "+f"(d[83]), "+f"(d[84]), "+f"(d[85]), "+f"(d[86]), "+f"(d[87]), "+f"(d[88]), "+f"(d[89]), "+f"(d[90]), "+f"(d[91]), "+f"(d[92]), "+f"(d[93]), "+f"(d[94]), "+f"(d[95])
    : "l"(da), "l"(db), "r"(sd), "n"(TA), "n"(TB));
}

template<int TA, int TB> __device__ __forceinline__ void wgmma_ss_n8(float* d, uint64_t da, uint64_t db, int sd) {
  asm volatile("{\n.reg .pred p;\nsetp.ne.b32 p, %6, 0;\n"
    "wgmma.mma_async.sync.aligned.m64n8k16.f32.bf16.bf16 {%0, %1, %2, %3}, %4, %5, p, 1, 1, %7, %8;\n}"
    : "+f"(d[0]), "+f"(d[1]), "+f"(d[2]), "+f"(d[3])
    : "l"(da), "l"(db), "r"(sd), "n"(TA), "n"(TB));
}

constexpr int S_ = 2048, D_ = 640, F_ = 1536;

struct Scr {
  uint32_t flag[32 * 8];
  uint32_t mv[2 * 2048];
  bf16 cimg[8 * 6 * 512];
  uint2 st2[S_];
  bf16 kvT[D_ * S_];
  bf16 zT[D_ * S_];
  bf16 AT[D_ * S_];
};
__device__ __align__(1024) Scr g_scr;
__device__ __forceinline__ uint32_t clk() { uint32_t c; asm volatile("mov.u32 %0, %%clock;" : "=r"(c) :: "memory"); return c; }
#define DEVSM 0
#define STAMP(id)
#define STAMPIF(c, id)
#define ITW 0
#define P3 0
constexpr int FL_X = 5, FL_C = 128;
#define CD 600
#define SD 1000

constexpr int SM_X = 1024, SM_EXT = 21504, SM_SMALL = 29696, SM_STAT = 30720, SM_CB = 32768, SM_RING = 34816, SM_TOTAL = SM_RING + 6 * 32768;
constexpr int SMALL_LN = 224, SMALL_RED = 320, SMALL_DUMMY = 1008, SMALL_E = 1012, SMALL_TS = 160, SMALL_H = 864;
constexpr int JOB_SZ = 10880, JOB_V = 5760, R_X = 5 * 32768, R_BOX = R_X + 12288;
constexpr int K1OFF = 4672, KSZ = 9472, CSZ = KSZ + 4224;
enum { B_KJ = 0, B_X = 5, B_EXT = 7, B_X1 = 8, B_P0 = 9, B_FB = 10, B_PEER = 20, B_RECV = 24, B_U = 28, B_A = 30, B_E0 = 35, B_FS = 37, B_BOX = 38, B_F = 44, B_ST0 = 45, B_GB = 46,
       B_F1 = 48, B_E1 = 54, B_EB = 60,
       B_OS = 64, B_OF = 72, B_Z = 80, B_K = 85, B_EW = 88, B_ST2 = 94, B_XF = 95, B_KV4 = 96, B_KVS = 98, B_BD = 99,
       B_B = 106, B_S = 112 };
__device__ __forceinline__ uint32_t chan_base(uint32_t sb, int ch) { return sb + SM_RING + (2 + (ch >> 1)) * 32768 + (ch & 1) * CSZ; }

struct Params { CUtensorMap mS, mX, mWm, mK, mV, mG, mU, mD; };

__device__ __forceinline__ void flag_add(Scr* G, int id) { asm volatile("red.relaxed.gpu.global.add.u32 [%0], 1;" ::"l"(G->flag + id) : "memory"); }
__device__ __forceinline__ uint32_t rdback(const void* p) { uint32_t v; asm volatile("ld.relaxed.gpu.global.u32 %0, [%1];" : "=r"(v) : "l"(p) : "memory"); return v; }
__device__ __forceinline__ void st_tag(uint2* p, uint32_t v, uint32_t t) { asm volatile("st.relaxed.gpu.global.v2.u32 [%0], {%1, %2};" ::"l"(p), "r"(v), "r"(t) : "memory"); }
__device__ __forceinline__ void spin(uint32_t t, uint32_t d) { if (d) while (clk() - t < d); }
__device__ __forceinline__ uint2 ld_tag(const uint2* p) { uint2 v; asm volatile("ld.relaxed.gpu.global.v2.u32 {%0, %1}, [%2];" : "=r"(v.x), "=r"(v.y) : "l"(p) : "memory"); return v; }
__device__ __forceinline__ uint4 ld_tag2(const uint2* p) {
  uint4 v;
  asm volatile("ld.relaxed.gpu.global.v4.u32 {%0, %1, %2, %3}, [%4];" : "=r"(v.x), "=r"(v.y), "=r"(v.z), "=r"(v.w) : "l"(p) : "memory");
  return v;
}
__device__ __forceinline__ void stg128(void* p, uint4 v) { asm volatile("st.global.v4.b32 [%0], {%1, %2, %3, %4};" ::"l"(p), "r"(v.x), "r"(v.y), "r"(v.z), "r"(v.w) : "memory"); }
__device__ __forceinline__ uint32_t ldv32(uint32_t a) { uint32_t v; asm volatile("ld.volatile.shared.b32 %0, [%1];" : "=r"(v) : "r"(a) : "memory"); return v; }
__device__ __forceinline__ uint4 ldv128(uint32_t a) { uint4 v; asm volatile("ld.volatile.shared.v4.b32 {%0,%1,%2,%3}, [%4];" : "=r"(v.x), "=r"(v.y), "=r"(v.z), "=r"(v.w) : "r"(a) : "memory"); return v; }
__device__ __forceinline__ bool mbar_test(uint32_t bar, int parity) {
  uint32_t ok;
  asm volatile("{\n.reg .pred P;\nmbarrier.test_wait.parity.shared::cta.b64 P, [%1], %2;\nselp.u32 %0, 1, 0, P;\n}" : "=r"(ok) : "r"(bar), "r"(parity) : "memory");
  return ok;
}
__device__ __forceinline__ uint32_t epoch(uint32_t sb) { return lds32(sb + SM_SMALL + SMALL_E); }
__device__ __forceinline__ void rdwait(uint32_t sb, uint32_t v) { sts32(sb + SM_SMALL + SMALL_DUMMY, v); }
__device__ __forceinline__ void fence_async_s() { asm volatile("fence.proxy.async.shared::cta;" ::: "memory"); }
__device__ __forceinline__ void fence_async_g() { asm volatile("fence.proxy.async.global;" ::: "memory"); }
__device__ __forceinline__ void bulk_done() { asm volatile("cp.async.bulk.commit_group;\n\tcp.async.bulk.wait_group 0;" ::: "memory"); }
__device__ __forceinline__ void flag_wait(Scr* G, int id, uint32_t target) {
  const uint32_t* p = G->flag + id;
#pragma unroll 1
  for (int i = 0; i < (1 << 20); i++) {
    uint32_t v;
    asm volatile("ld.relaxed.gpu.global.u32 %0, [%1];" : "=r"(v) : "l"(p) : "memory");
    if ((int)(v - target) >= 0) return;
  }
  __trap();
}
__device__ __forceinline__ void hint_wait(Scr* G, uint32_t sa, int id, uint32_t target) {
#pragma unroll 1
  for (int i = 0; i < (1 << 20); i++) {
    const uint32_t t = clk();
    cp16(sa + 4 * (id & 4), G->flag + (id & ~3));
    spin(t, P3);
    if ((int)(lds32(sa + 4 * (id & 7)) - target) >= 0) return;
  }
  __trap();
}
__device__ __forceinline__ int tbase(int pb) { return 127 - (32 * (pb >> 6) + 8 * (pb & 8) + 4 * ((2 * (pb & 3) - ((pb >> 2) & 1)) & 7) + ((pb >> 4) & 3)); }
__device__ __forceinline__ uint32_t hmul(uint32_t a, uint32_t b) { uint32_t d; asm("mul.rn.bf16x2 %0, %1, %2;" : "=r"(d) : "r"(a), "r"(b)); return d; }
__device__ __forceinline__ uint32_t hadd(uint32_t a, uint32_t b) { uint32_t d; asm("add.rn.bf16x2 %0, %1, %2;" : "=r"(d) : "r"(a), "r"(b)); return d; }
__device__ __forceinline__ uint32_t hsub(uint32_t a, uint32_t b) { uint32_t d; asm("sub.rn.bf16x2 %0, %1, %2;" : "=r"(d) : "r"(a), "r"(b)); return d; }
__device__ __forceinline__ uint32_t hfma(uint32_t a, uint32_t b, uint32_t c) { uint32_t d; asm("fma.rn.bf16x2 %0, %1, %2, %3;" : "=r"(d) : "r"(a), "r"(b), "r"(c)); return d; }
__device__ __forceinline__ uint32_t pack2(float lo, float hi) { uint32_t d; asm("cvt.rn.bf16x2.f32 %0, %1, %2;" : "=r"(d) : "f"(hi), "f"(lo)); return d; }
__device__ __forceinline__ float blo(uint32_t v) { return __uint_as_float(v << 16); }
__device__ __forceinline__ float bhi(uint32_t v) { return __uint_as_float(v & 0xffff0000u); }
__device__ __forceinline__ uint32_t tagged(uint32_t v, uint32_t e1) { return (v & ~1u) | (e1 & 1); }
__device__ __forceinline__ float rbf(float v) { return blo(pack2(v, 0.f)); }
__device__ __forceinline__ float sdev(float var) { float d; asm("sqrt.approx.ftz.f32 %0, %1;" : "=f"(d) : "f"(rbf(rbf(var) + 1e-5f))); return rbf(d); }
template <int N> __device__ __forceinline__ void bfly(float* v, int mask, bool up) {
#pragma unroll
  for (int i = 0; i < N / 2; i++) {
    float send = up ? v[i] : v[i + N / 2], keep = up ? v[i + N / 2] : v[i];
    v[i] = keep + __shfl_xor_sync(0xffffffffu, send, mask);
  }
}
#define BX3 2
#define XO 0
#define ZA 0
#define XE 0
#define EA 1
#define AD 300
#define XP 0
#define DR 0
#define KVV 0
#define OPQ 4
#define SL 1
#define UT 5
#define UD0 1000
#define EH 2
#define NA 16
#define BS 0
#define UF 1
#define ZS 1
#define LV 5
#define TG 2
#define RL 2
#define OF 1
#define OH 16
#define ES 2
#define SI 1
#define RH 5
#define NS 0
#define AT0 14200
#define AT1 0
#define BI 4
#define PC 1
#define PG 1
#define UD2 3700
#define GT 0x111
#define K3 0
#define FS 31
#define KW 0
#define RX 0
#define MG 0
__device__ __forceinline__ bool mod_first(int b) { return MG ? (b & 3) != 3 : !(b & 1) || !(b & 6); }
__device__ __forceinline__ int mod_grp(int b, int j) {
  if (MG) {
  const int m = b >> 3, s = b & 7, t = 16 * (j ? min(s, 6) : s - (s >> 2)) + m, v = j ? s : (t * 43) >> 10;
  if (j == 2) return b + 112;
  return v < 4 ? (v == 3 ? 160 : 40 * v) + (j ? 24 + m : t - 24 * v) : t + (t < 104 ? 56 : 96);
  }
  const int m = b >> 3, s = b & 7, t = 16 * s + m, v = j ? (t * 43) >> 10 : s >> 1;
  if (j == 2) return b + 112;
  if (j == 0 && s == 1) return m + (m < 8 ? 152 : 192);
  return v < 4 ? (v == 3 ? 160 : 40 * v) + (j ? 16 + t - 24 * v : m) : t + 24;
}

__device__ __forceinline__ void kv_load(const bf16* gk, const bf16* gv, const bf16* gs, uint32_t sb, int b, int r, int tid) {
  const int row = tid >> 2, col = 128 * r + 32 * (b & 3);
  const uint32_t a = sb + SM_RING + r * JOB_SZ + (row >> 3) * 80 + (tid & 3) * 16, ak = a + (row & 7) * 720, av = a + (row & 7) * 640 + JOB_V;
  const int o = (64 * (b >> 2) + row) * D_ + col + 8 * (tid & 3);
  if (FS & 16) {
    uint32_t oo = 2 * o;
    asm volatile("" : "+r"(oo));
    const char *pk = (const char*)gk + oo, *pv = (const char*)gv + oo;
    cp16(ak + 80, pk);
    cp16(av, pv);
    cp16(ak + 400, pk + 64 * D_);
    cp16(av + 320, pv + 64 * D_);
    if (tid < 12) cp16z(ak + 3600, pk - (b < 4 ? 0 : 6 * D_), b < 4 ? 0 : 16);
    if (tid >= 112) cp16(sb + SM_CB + 256 * r + 16 * (tid - 112), (const char*)gs + (uint32_t)(8 * col + 16 * (tid - 112)));
    return;
  } else {
    cp16(ak + 80, gk + o);
    cp16(ak + 400, gk + o + 32 * D_);
    cp16(av, gv + o);
    cp16(av + 320, gv + o + 32 * D_);
  }
  if (tid < 12) cp16z(ak + 3600, gk + (b < 4 ? o : o - 3 * D_), b < 4 ? 0 : 16);
  else if (tid >= 112) cp16(sb + SM_CB + 256 * r + 16 * (tid - 112), gs + 4 * col + 8 * (tid - 112));
}
__device__ __forceinline__ void kv_load0(const bf16* gk, const bf16* gv, const bf16* gs, uint32_t sb, int b, int t) {
  const int r = t >> 7, tid = t & 127, row = tid >> 2, col = 128 * r + 32 * (b & 3);
  const uint32_t a = sb + SM_RING + r * JOB_SZ + (row >> 3) * 80 + (tid & 3) * 16, ak = a + (row & 7) * 720, av = a + (row & 7) * 640 + JOB_V;
  const uint32_t o = 2 * ((64 * (b >> 2) + row) * D_ + col + 8 * (tid & 3));
  asm volatile("{\n.reg .pred p;\n.reg .b64 x, y, z;\ncvt.u64.u32 z, %4;\nadd.s64 x, %2, z;\nadd.s64 y, %3, z;\nsetp.lt.s32 p, %5, 256;\n"
               "@p cp.async.cg.shared.global [%0+80], [x], 16;\n@p cp.async.cg.shared.global [%1], [y], 16;\n"
               "@p cp.async.cg.shared.global [%0+400], [x+40960], 16;\n@p cp.async.cg.shared.global [%1+320], [y+40960], 16;\n}"
               ::"r"(ak), "r"(av), "l"(gk), "l"(gv), "r"(o), "r"(t) : "memory");
  asm volatile("{\n.reg .pred p, q;\n.reg .b64 x, y;\ncvt.u64.u32 x, %4;\nadd.s64 x, x, %2;\ncvt.u64.u32 y, %5;\nadd.s64 y, y, %3;\nsetp.lt.s32 p, %7, 12;\nsetp.eq.s32 q, %8, 112;\n"
               "@p cp.async.cg.shared.global [%0+3600], [x], 16, %6;\n@q cp.async.cg.shared.global [%1], [y], 16;\n}"
               ::"r"(ak), "r"(sb + SM_CB + 256 * r + 16 * (tid - 112)), "l"(gk), "l"(gs), "r"(b < 4 ? o : o - 6 * D_), "r"(8 * col + 16 * (tid & 15)), "r"(b < 4 ? 0 : 16),
                 "r"(t & 0x17f), "r"(t & 0x170) : "memory");
}
__device__ __forceinline__ void load_kv(const Params& P, const bf16* gs, uint32_t sb, int b, int r) {
  const uint32_t a = sb + SM_RING + r * JOB_SZ, bar = sb + 8 * (B_B + r);
  const int cg = 4 * r + (b & 3);
  mbar_expect(bar, JOB_SZ + 256);
  tma4d(a, &P.mK, 0, cg, 8 * (b >> 2) - 1, 0, bar);
  tma4d(a + JOB_V, &P.mV, 0, cg, 8 * (b >> 2), 0, bar);
  bulk_g2s(sb + SM_CB + 256 * r, gs + 128 * cg, 256, bar);
}
__device__ __forceinline__ uint4* kv_dst(Scr* G, int b, int r, int tid) {
  return (uint4*)(G->kvT + (128 * r + 32 * (b & 3) + 8 * (tid >> 5) + 2 * (tid & 3)) * S_ + 2040 - 64 * (b >> 2)) - ((tid >> 2) & 7);
}
__device__ __forceinline__ void kv_job(Scr* G, uint32_t sb, int b, int r, int tid, uint32_t e1) {
  const int cp = 4 * (tid >> 5) + (tid & 3);
  const uint32_t ka = sb + SM_RING + r * JOB_SZ + ((tid >> 2) & 7) * 80 + cp * 4;
  mbar_wait(sb + 8 * (B_B + r), 0);
  STAMPIF(tid == 0, 56 + r);
  uint32_t kk[11], vv[8], o[8];
  if (KVV) {
#pragma unroll
    for (int i = 0; i < 11; i++) kk[i] = ldv32(ka + 720 * ((i + 5) & 7) + 80 * ((i + 5) >> 3));
#pragma unroll
    for (int i = 0; i < 8; i++) vv[i] = ldv32(ka + JOB_V + 640 * i);
  }
  const uint4 sk = ldv128(sb + SM_CB + 256 * r + 16 * cp);
  const uint32_t s0 = __byte_perm(sk.x, sk.z, 0x5410), s1 = __byte_perm(sk.x, sk.z, 0x7632), s2 = __byte_perm(sk.y, sk.w, 0x5410), s3 = __byte_perm(sk.y, sk.w, 0x7632);
#pragma unroll
  for (int i = 0; i < 11; i++) if (!KVV) kk[i] = lds32(ka + 720 * ((i + 5) & 7) + 80 * ((i + 5) >> 3));
#pragma unroll
  for (int i = 0; i < 8; i++) {
    uint32_t v = KVV ? vv[i] : lds32(ka + JOB_V + 640 * i);
    o[i] = hmul(hfma(kk[i + 3], s0, hfma(kk[i + 2], s1, hfma(kk[i + 1], s2, hmul(kk[i], s3)))), v);
  }
  uint4* dst = kv_dst(G, b, r, tid);
  dst[0] = make_uint4(__byte_perm(o[7], o[6], 0x5410), __byte_perm(o[5], o[4], 0x5410), __byte_perm(o[3], o[2], 0x5410), tagged(__byte_perm(o[1], o[0], 0x5410), e1));
  dst[256] = make_uint4(__byte_perm(o[7], o[6], 0x7632), __byte_perm(o[5], o[4], 0x7632), __byte_perm(o[3], o[2], 0x7632), tagged(__byte_perm(o[1], o[0], 0x7632), e1));
  if (tid == 0) { sts32(sb + SM_SMALL + SMALL_TS + 4 * r, clk()); mbar_arrive(sb + 8 * (B_KJ + r)); }
}
__device__ __forceinline__ void u_wait(uint4& a, uint4& c, const void* p) {
  asm volatile("{\n.reg .pred p;\n.reg .b32 t, n;\nmov.b32 n, 0;\n"
               "L0:\nlop3.b32 t, %3, %7, 1, 0x80;\nsetp.eq.b32 p, t, 0;\nvote.sync.any.pred p, p, 0xffffffff;\n@!p bra.uni L1;\n"
               "ld.relaxed.gpu.global.v4.u32 {%0, %1, %2, %3}, [%8];\nld.relaxed.gpu.global.v4.u32 {%4, %5, %6, %7}, [%8+2048];\n"
               "add.u32 n, n, 1;\nsetp.lt.u32 p, n, 1000000;\n@p bra.uni L0;\ntrap;\nL1:\n}"
               : "+r"(a.x), "+r"(a.y), "+r"(a.z), "+r"(a.w), "+r"(c.x), "+r"(c.y), "+r"(c.z), "+r"(c.w) : "l"(p) : "memory");
}
__device__ __forceinline__ void u_fix(uint4 a, uint4 c, const void* p, uint32_t sa, uint32_t e1) {
  asm volatile("{\n.reg .pred p;\n.reg .b32 t, n;\nmov.b32 n, 0;\n"
               "lop3.b32 t, %3, %7, %10, 0x81;\nand.b32 t, t, 1;\nsetp.eq.b32 p, t, 0;\nvote.sync.any.pred p, p, 0xffffffff;\n@!p bra.uni L2;\n"
               "L0:\nld.relaxed.gpu.global.v4.u32 {%0, %1, %2, %3}, [%8];\nld.relaxed.gpu.global.v4.u32 {%4, %5, %6, %7}, [%8+2048];\n"
               "lop3.b32 t, %3, %7, %10, 0x81;\nand.b32 t, t, 1;\nsetp.eq.b32 p, t, 0;\nvote.sync.any.pred p, p, 0xffffffff;\n@!p bra.uni L1;\n"
               "add.u32 n, n, 1;\nsetp.lt.u32 p, n, 1000000;\n@p bra.uni L0;\ntrap;\n"
               "L1:\nst.shared.v4.b32 [%9], {%0, %1, %2, %3};\nst.shared.v4.b32 [%9+2048], {%4, %5, %6, %7};\nL2:\n}"
               : "+r"(a.x), "+r"(a.y), "+r"(a.z), "+r"(a.w), "+r"(c.x), "+r"(c.y), "+r"(c.z), "+r"(c.w) : "l"(p), "r"(sa), "r"(e1) : "memory");
}
__device__ __forceinline__ void stv128(uint32_t a, uint4 v) { asm volatile("st.volatile.shared.v4.b32 [%0], {%1,%2,%3,%4};" ::"r"(a), "r"(v.x), "r"(v.y), "r"(v.z), "r"(v.w) : "memory"); }
__device__ __forceinline__ uint64_t box_a(uint32_t sb) { return mkdesc(sb + SM_RING + R_BOX, 256, 1024, 3); }
__device__ __forceinline__ uint64_t box_b(uint32_t sb) { return mkdesc(sb + SM_STAT, 64, 128, 0); }
__device__ __forceinline__ void mod_put(Scr* G, uint32_t sb, const float* a, int b, int j, uint32_t e1, int tid) {
  const uint32_t red = sb + SM_STAT + 1536;
  if ((tid & 3) == tid >> 6) sts64(red + 32 * ((tid >> 2) & 7) + 8 * (tid >> 5), __float_as_uint((tid & 32) ? a[1] : a[0]), __float_as_uint((tid & 32) ? a[3] : a[2]));
  bar_sync(j > (BX3 >= 3) ? 4 : 5, 128);
  if (tid < 16) {
    const uint4 u = lds128(red + 32 * (tid & 7)), v = lds128(red + 32 * (tid & 7) + 16);
    asm volatile("" : "+r"(b));
    const int grp = mod_grp(b, j);
    const uint32_t one = (grp >= 40 && grp < 80) || (grp >= 160 && grp < 200) ? 0x3f803f80u : 0u;
    const float lo = __uint_as_float(u.x) + __uint_as_float(u.z) + __uint_as_float(v.x) + __uint_as_float(v.z);
    const float hi = __uint_as_float(u.y) + __uint_as_float(u.w) + __uint_as_float(v.y) + __uint_as_float(v.w);
    asm volatile("st.relaxed.gpu.global.u32 [%0], %1;" ::"l"(G->mv + 8 * grp + 256 * (tid & 8) + (tid & 7)),
                 "r"(((tid >> 3) ^ e1) & 1 ? 0 : ~hadd(pack2(lo, hi), one)) : "memory");
  }
}
__device__ __forceinline__ void mod_box(Scr* G, uint32_t sb, int b, int j, uint32_t e1, int tid) {
  float a[4];
  uint64_t da = box_a(sb), db = box_b(sb);
#pragma unroll
  for (int h = 0; h < 2; h++) {
    mbar_wait(sb + 8 * (B_BOX + 2 * j + h), 0);
    STAMPIF(tid == 0 && j == 0, 71 + h);
    wg_fence();
#pragma unroll
    for (int n = 5 * h; n < 5 * h + 5; n++) wgmma_ss_n8<1, 0>(a, da + 128 * n, db + 8 * n, n != 0);
    wg_commit();
  }
  wg_wait<0>();
#pragma unroll
  for (int i = 0; i < 4; i++) asm volatile("" : "+f"(a[i])::"memory");
  mod_put(G, sb, a, b, j, e1, tid);
}
__device__ __forceinline__ void a_check(uint32_t sa, const void* ga, uint32_t tag) {
  asm volatile("{\n.reg .pred p;\n.reg .b32 t, n, x, y, z;\n.reg .b64 g;\n"
               "ld.shared.b32 t, [%0];\nlop3.b32 t, t, %2, 1, 0x28;\nsetp.ne.b32 p, t, 0;\nvote.sync.any.pred p, p, 0xffffffff;\n@!p bra.uni L1;\nmov.b32 n, 0;\n"
               "L0:\nld.relaxed.gpu.global.b32 t, [%1];\nlop3.b32 t, t, %2, 1, 0x28;\nsetp.ne.b32 p, t, 0;\nvote.sync.any.pred p, p, 0xffffffff;\n@!p bra.uni L2;\n"
               "add.u32 n, n, 1;\nsetp.lt.u32 p, n, 1000000;\n@p bra.uni L0;\ntrap;\nL2:\n"
               "and.b64 g, %1, -32;\nand.b32 n, %0, -32;\n"
               "ld.relaxed.gpu.global.v4.b32 {t, x, y, z}, [g];\nst.shared.v4.b32 [n], {t, x, y, z};\n"
               "ld.relaxed.gpu.global.v4.b32 {t, x, y, z}, [g+16];\nst.shared.v4.b32 [n+16], {t, x, y, z};\n"
               "fence.proxy.async.shared::cta;\nbar.warp.sync 0xffffffff;\nL1:\n}" ::"r"(sa), "l"(ga), "r"(tag) : "memory");
}
__device__ __forceinline__ void z_wait(uint4& a, uint4& c, uint32_t* v, const void* G, uint32_t zo, uint32_t co, uint32_t e1) {
  asm volatile("{\n.reg .pred p;\n.reg .b32 t, n;\n.reg .b64 x, y;\nmov.b32 n, 0;\n"
               "L0:\nlop3.b32 t, %3, %7, %14, 0x81;\nand.b32 t, t, 1;\nmin.u32 t, t, %8;\nmin.u32 t, t, %9;\nmin.u32 t, t, %10;\nmin.u32 t, t, %11;\n"
               "setp.eq.b32 p, t, 0;\nvote.sync.any.pred p, p, 0xffffffff;\n@!p bra.uni L1;\n"
               "shr.u32 t, n, 31;\nadd.u32 t, t, %12;\ncvt.u64.u32 x, t;\nadd.s64 x, x, %15;\nshr.u32 t, n, 30;\nadd.u32 t, t, %13;\ncvt.u64.u32 y, t;\nadd.s64 y, y, %15;\n"
               "ld.relaxed.gpu.global.v4.u32 {%0, %1, %2, %3}, [x];\nld.relaxed.gpu.global.v4.u32 {%4, %5, %6, %7}, [x+32768];\n"
               "ld.relaxed.gpu.global.u32 %8, [y];\nld.relaxed.gpu.global.u32 %9, [y+1280];\nld.relaxed.gpu.global.u32 %10, [y+2560];\nld.relaxed.gpu.global.u32 %11, [y+5120];\n"
               "add.u32 n, n, 1;\nsetp.lt.u32 p, n, 1000000;\n@p bra.uni L0;\ntrap;\nL1:\n}"
               : "+r"(a.x), "+r"(a.y), "+r"(a.z), "+r"(a.w), "+r"(c.x), "+r"(c.y), "+r"(c.z), "+r"(c.w), "+r"(v[0]), "+r"(v[1]), "+r"(v[2]), "+r"(v[3])
               : "r"(zo), "r"(co), "r"(e1), "l"(G) : "memory");
}
__device__ __forceinline__ void load_x(const Params& P, uint32_t sb, int b, int h) {
  const uint32_t bar = sb + 8 * (B_X + h);
  mbar_expect(bar, 10240);
  tma5d(sb + SM_X + h * 10240, &P.mX, 0, 0, 0, 5 * h, tbase(b), bar);
}
__device__ __forceinline__ uint32_t x_addr(uint32_t sb, int w, int lane) {
  const int rho = 15 - (4 * (lane >> 3) + 2 * (lane & 1) + ((lane >> 1) & 1));
  return sb + SM_X + (w >> 1) * 2048 + rho * 128 + (((2 * (w & 1) + (lane & 4)) ^ (rho & 7)) << 4);
}
__device__ __forceinline__ void ln1_half(uint32_t sb, int tid, int h, int dry, float& s1, float& s2, float& pv) {
  const uint32_t xr = sb + SM_X + 16 * tid;
  float s3 = 0.f;
  if (ITW == 8) STAMPIF(tid == 0, 102 + 2 * h);
  if (!dry) mbar_wait(sb + 8 * (B_X + h), 0);
  STAMPIF(tid == 0, 25);
  if (ITW == 8) STAMPIF(tid == 0, 103 + 2 * h);
  uint4 v[5];
#pragma unroll
  for (int n = 0; n < 5; n++) v[n] = n < LV ? ldv128(xr + 10240 * h + 2048 * n) : lds128(xr + 10240 * h + 2048 * n);
  pv = blo(ldv32(xr & ~127u));
#pragma unroll
  for (int n = 0; n < 5; n++) {
    const uint32_t u[4] = {v[n].x, v[n].y, v[n].z, v[n].w};
#pragma unroll
    for (int j = 0; j < 4; j++) {
      const float a = blo(u[j]) - pv, c = bhi(u[j]) - pv;
      s1 += a + c; s2 += a * a; s3 += c * c;
    }
  }
  s2 += s3;
}
__device__ __forceinline__ void ln1_end(uint32_t sb, int tid, float s1, float s2, float pv) {
#pragma unroll
  for (int o = 1; o < 8; o <<= 1) { s1 += __shfl_xor_sync(0xffffffffu, s1, o); s2 += __shfl_xor_sync(0xffffffffu, s2, o); }
  if (ITW == 8) { asm volatile("" : "+f"(s1), "+f"(s2)); STAMPIF(tid == 0, 107); }
  const float mu = s1 * (1.f / D_), var = fmaxf(s2 * (1.f / D_) - mu * mu, 0.f);
  float rs;
  asm("rcp.approx.ftz.f32 %0, %1;" : "=f"(rs) : "f"(sdev(var)));
  const int i = 15 - (tid >> 3), j = tid & 7;
  if (j < 2) sts16(sb + SM_SMALL + SMALL_LN + 32 * j + 16 * (i & 1) + (i & 14), pack2(j ? rs : pv + mu, 0.f));
  if (ITW == 8) STAMPIF(tid == 0, 108);
  bar_sync(5, 128);
  STAMPIF(tid == 0, 75);
}
__device__ __forceinline__ void load_box(const Params& P, uint32_t sb, int b, int cls) {
  const uint32_t bar = sb + 8 * (B_BOX + cls);
  mbar_expect(bar, 10240);
  tma3d(sb + SM_RING + R_BOX + 10240 * (cls & 1), &P.mWm, 16 * mod_grp(b, cls >> 1), 0, 5 * (cls & 1), bar);
}
__device__ __forceinline__ void load_ssm(const Params& P, uint32_t sb, int b, int r) {
  const uint32_t bar = sb + 8 * (B_S + r);
  mbar_expect(bar, 16 * 288);
  tma3d(chan_base(sb, r) + 128, &P.mS, 0, 0, 128 * r + b, bar);
}
__device__ __forceinline__ void k1_job(uint32_t sb, int r, int tid, uint32_t dv) {
  const uint32_t a0 = chan_base(sb, r) + 128 + 16 * tid + 32 * (tid >> 4);
  mbar_wait(sb + 8 * (B_S + r), 0);
  uint4 v[2];
  uint32_t pv[2];
#pragma unroll
  for (int n = 0; n < 2; n++) { v[n] = lds128(a0 + 2304 * n); pv[n] = lds32(a0 + 2304 * n - ((tid & 15) ? 4 : 36)); }
  if (tid == 0) { v[0].x = hadd(v[0].x, dv); sts32(a0, v[0].x); }
#pragma unroll
  for (int n = 0; n < 2; n++)
    sts128(a0 + 2304 * n + K1OFF, make_uint4(__byte_perm(pv[n], v[n].x, 0x5432), __byte_perm(v[n].x, v[n].y, 0x5432), __byte_perm(v[n].y, v[n].z, 0x5432), __byte_perm(v[n].z, v[n].w, 0x5432)));
}

__device__ __forceinline__ int out_blk(int s, int p) { const int t = p + (s >> 1); return t < 5 ? t : t - 5; }
__device__ __forceinline__ void l2_prefetch(const void* p, int bytes) { asm volatile("cp.async.bulk.prefetch.L2.global [%0], %1;" ::"l"(p), "r"(bytes) : "memory"); }
__device__ __forceinline__ void pf_line(const void* p) { asm volatile("prefetch.global.L2 [%0];" ::"l"(p) : "memory"); }
template <int BF> __device__ __forceinline__ int role(int bx) {
  const int c = bx >> 1, d = c - 36, q = (d * 37) >> 8, k = d - 7 * q;
  int rank;
  if (BF) {
    const int r1 = ((c - 4) & 7) * 8 + ((c - 4) >> 3), r2 = (k + min(k, 1)) * 8 + 4 + q;
    rank = r2 + ((d >> 31) & (r1 - r2)) + (((c - 4) >> 31) & (12 + c - r1));
  }
  else rank = c < 4 ? 12 + c : c < 36 ? ((c - 4) & 7) * 8 + ((c - 4) >> 3) : (k ? k + 1 : 0) * 8 + 4 + q;
  return 8 * (rank & 15) + 2 * (rank >> 4) + (bx & 1);
}
enum { K_KV, K_SSM, K_BOX, K_PW, K_PD, K_PKV, K_PSSM, K_PBOX, K_W, K_X, K_ST, K_END = 15 };
#define KD 600
#define S1T 2000
#define KP 0
#define Q0 2400
#define Q1 3100
#define Q2 4300
#define Q3 4600
#define Q4 5200
#define Q5 5900
#define Q6 6600
#define Q7 6900
#define Q8 7700
#define Q9 8100
#define QA 9000
#define QB 9600
#define SC 0
#define MO 0
#define QS 0
#define SH 300
#define E(t, bar, kind, r) (((t) ? (t) - SH : 0) << 16 | (bar) << 8 | (kind) << 4 | (r))
#define SCH0 E(S1T + SH, 255, K_SSM, 1),
#define SCHED SCH0 E(2800, 255, K_BOX, 0), E(0, 255, K_BOX, 1), E(3700, 255, K_KV, 2), E(4400, 255, K_SSM, 2), E(4800, 255, XO ? K_X : K_KV, XO ? 0 : 3), E(5500, 255, XO ? K_KV : K_X, XO ? 3 : 0), \
              E(6400, 255, XP ? K_X : K_KV, XP ? 1 : 4), E(7100, 255, XP ? K_KV : K_X, XP ? 4 : 1), E(7900, 255, K_SSM, 3), E(8300, 255, K_SSM, 4), E(8600, 255, K_BOX, 2), E(9500, 255, K_PW, 0), \
              E(10100, 255, K_BOX, 3)
#define XPF (S1T ? 1 : 2)
#define XBOTH 0
#define XI 8
#define XW 0
#define PWM 0x3c
#define STM 0x7c0
#define PDM 0x3800
#define KV4C 3
#define CVT 1
#define UPOS 4
#define UD 1200
#define UD1 5400
#define NP 6
#define NQ 6
#define SPOS(i) (2 * ((i) - NQ) + 13)
#define LH0 4
#define LH1 5
#define LM 0
#define PT 1
#define ZP 0
#define BD 1200
#define ER 0
#define PL 1
#define K1N 1
#define ZD 9900
#define PK 0
#define ZF 1
constexpr uint32_t kSched[] = {SCHED, E(0, 255, K_END, 0)};
struct In { const bf16 *k, *v, *sk, *Wg, *Wu, *Wd, *ss; };
__device__ __forceinline__ void load_w(const Params& P, uint32_t sb, int s, int it) {
  const int st = it % 5;
  mbar_wait(sb + 8 * (B_E1 + st), (it / 5) & 1);
  const uint32_t a = sb + SM_RING + st * 32768 + 8192, fb = sb + 8 * (B_F1 + st);
  mbar_expect(fb, 24576);
#pragma unroll
  for (int j = 0; j < 3; j++) {
    tma2d(a + 8192 * j, &P.mG, 192 * s + 64 * j, 32 * it, fb);
    tma2d(a + 8192 * j + 4096, &P.mU, 192 * s + 64 * j, 32 * it, fb);
  }
}

template <int I> __device__ __forceinline__ int sched_run(const Params& P, const In& in, uint32_t sb, int b, int lane, uint32_t t_0) {
  constexpr uint32_t e = kSched[I];
  constexpr int kind = (e >> 4) & 15, r = e & 15, bar = (e >> 8) & 255;
  if constexpr (kind == K_END) return 0;
  else {
    if constexpr ((e >> 16) != 0) while (clk() - t_0 < (e >> 16));
    if (bar != 255) mbar_wait(sb + 8 * bar, 0);
    if (kind == K_BOX && r == 2) mbar_wait(sb + 8 * B_BD, 0);
    if (kind == K_PKV) {
      const bf16* kvp = (lane < 16 ? in.k : in.v) + (16 * b + (lane & 15)) * D_ + 128 * r;
      pf_line(kvp); pf_line(kvp + 64);
    } else {
      if (elect()) {
        if (kind == K_KV) load_kv(P, in.sk, sb, b, r);
        if (kind == K_X) load_x(P, sb, b, r);
        if (kind == K_SSM) load_ssm(P, sb, b, r);
        if (kind == K_BOX && (r > 1 || mod_first(b))) load_box(P, sb, b, r);
        if (kind == K_PW) { l2_prefetch(in.Wg + (128 * r + b) * F_, 2 * F_); l2_prefetch(in.Wu + (128 * r + b) * F_, 2 * F_); }
        if (kind == K_PSSM) l2_prefetch(in.ss + (128 * r + b) * S_, 4096);
      }
      __syncwarp();
    }
    return sched_run<I + 1>(P, in, sb, b, lane, t_0) + (kind == K_PW);
  }
}

__global__ void __launch_bounds__(512, 1) fused_kernel(const bf16* __restrict__ gk, const bf16* __restrict__ gv, const bf16* __restrict__ gsk,
                                                       const bf16* __restrict__ gD, const bf16* __restrict__ gc, Scr* G, const bf16* gWg, const bf16* gWu,
                                                       const bf16* gWd, bf16* gout, const bf16* gss, const __grid_constant__ Params P) {
  extern __shared__ __align__(1024) char smem_raw[];
  const uint32_t sb = smem_u32(smem_raw), ring = sb + SM_RING;
  int t0 = 0;
  uint32_t t_0;
  if (FS & 2) asm volatile("mov.u32 %0, %%tid.x;" : "=r"(t0));
  if (FS & 4) t_0 = clk();
  if (FS & 32) {
    int bx;
    asm volatile("mov.u32 %0, %%ctaid.x;" : "=r"(bx));
    kv_load0(gk, gv, gsk, sb, bx, t0);
  } else if ((FS & 1) && t0 < (KP ? 128 : 256)) {
    int bx;
    if (!KP && KD && t0 >= 128) spin(t_0, KD);
    asm volatile("mov.u32 %0, %%ctaid.x;" : "=r"(bx));
    kv_load(gk, gv, gsk, sb, (FS & 8) ? bx : role<1>(bx), KP ? 0 : t0 >> 7, t0 & 127);
  }
  const int b = role<0>(blockIdx.x), m = b >> 3, s = b & 7;
  if (!(FS & 4)) t_0 = clk();
  if ((FS & 3) == 2 && t0 < 256) kv_load(gk, gv, gsk, sb, b, t0 >> 7, t0 & 127);
  const int wg = __shfl_sync(0xffffffffu, threadIdx.x >> 7, 0);
  const int tid = threadIdx.x & 127, lane = tid & 31;
  const int w = __shfl_sync(0xffffffffu, tid >> 5, 0);
  uint32_t e1 = 0;
  if (wg < 2) {
    if (!(FS & 2)) kv_load(gk, gv, gsk, sb, b, wg, tid);
    if (TG == 1) e1 = rdback(G->flag + 8 * m + 4);
  } else {
    if (wg == 2) {
      if (tid < 40) {
        int c = tid & 7;
        sts128(chan_base(sb, tid >> 3) + (c < 2 ? 80 + c * K1OFF : KSZ + 4096 + (c - 2) * 16), make_uint4(0, 0, 0, 0));
      }
    }
    if (elect()) {
      const int j = 4 * (3 - wg) + w - 1;
      if (j < 4) asm volatile("prefetch.tensormap [%0];" ::"l"(&P.mX + j) : "memory");
      if (j < 0) {
#pragma unroll
        for (int i = 0; i < 5; i++) mbar_init(sb + 8 * (B_S + i), 1);
        fence_async_s();
        if (XPF > 0) load_ssm(P, sb, b, 0);
        if (XPF > 1) load_ssm(P, sb, b, 1);
      } else {
        const int c = j < 3 ? 1 : j < 4 ? 2 : 4;
#pragma unroll
        for (int i = 0; i < 16; i++) mbar_init(sb + 128 * j + 8 * i, i < 10 || j < 6 ? c : i < 12 - KP ? 128 : 1);
      }
    }
    fence_async_s();
  }
  __syncthreads();
  STAMPIF(threadIdx.x == 0, 55);

  if (wg < 2) {
    if (!KP || !wg) cp_arrive(sb + 8 * (B_B + wg));
    asm volatile("setmaxnreg.inc.sync.aligned.u32 224;");
    STAMPIF(threadIdx.x == 0, 82);
    const int g = lane >> 2, q = lane & 3;
    constexpr int NB = UT < 5 ? 288 : 256;
    if (wg == 1) bar_arrive(1, NB);
    const uint32_t dv = *(const uint16_t*)(gD + 128 * wg + b);
    if (TG == 3) e1 = rdback(G->flag + 8 * m + 4 + (__shfl_sync(0xffffffffu, tid, tid) >> 8));
    e1 = (e1 >> 5) + 1;
    {
      const int tid = (OPQ & 4) ? __shfl_sync(0xffffffffu, threadIdx.x & 127, threadIdx.x) : threadIdx.x & 127, lane = tid & 31, g = lane >> 2, q = lane & 3;
      const int b0 = (g >> 1) & 1, b1 = g >> 2, u = q + 4 * b0 - w;
      const uint32_t fo = 128 + (g & 1) * K1OFF + 288 * b1 + 4 * u, fo0 = fo - (u < 0 ? 32 : 0);
      const bool wrap = b0 && q == 0;
      const int src1 = b0 ? ((lane & 20) | ((q - 1) & 3)) : (lane | 8);
      const uint2* pu = (const uint2*)(G->kvT + (128 * wg + b) * S_ + 8 * tid);
      uint4 u0 = make_uint4(0, 0, 0, 0), u1 = make_uint4(0, 0, 0, 1);
#pragma unroll 1
      for (int ch = wg; ch < 5; ch += 2) {
        const uint32_t base = chan_base(sb, ch);
        if (KW) {
#pragma unroll 1
          for (int n = ch > 1; n <= (ch & 1); n++) {
            int bx;
            asm volatile("mov.u32 %0, %%ctaid.x;" : "=r"(bx));
            kv_job(G, sb, n ? b : bx, ch + n, tid, e1);
            STAMPIF(tid == 0, n ? 21 + ch : 1 + ch);
            if (n == 0) {
              k1_job(sb, wg, tid, dv);
              bar_sync(3 + wg, 128);
              mbar_wait(sb + 8 * B_E0, 0);
              e1 = epoch(sb);
            }
          }
          if (ch > 1) mbar_wait(sb + 8 * (B_K + ch - 2), 0);
          else if (ch) spin(t_0, UD1);
          if (ch) { u0 = ld_tag2(pu); u1 = ld_tag2(pu + 256); }
        }
        if (!KW && (ch < 2 || ch == KV4C)) {
          int bx = b;
          if (FS & 8) { asm volatile("mov.u32 %0, %%ctaid.x;" : "=r"(bx)); bx = ch < 2 - KP ? bx : b; }
          kv_job(G, sb, bx, ch < 2 ? ch : 4, tid, TG ? e1 : 1);
          if (ER && ch > 1) { __syncwarp(); if (lane == 0) mbar_arrive(sb + 8 * B_KV4); }
          STAMPIF(tid == 0, ch < 2 ? 1 + ch : 24);
        }
        if (KW) {
        } else if (ch < 2) {
          k1_job(sb, wg, tid, dv);
          bar_sync(3 + wg, 128);
        } else {
          mbar_wait(sb + 8 * (B_K + ch - 2), 0);
          if (UT == 5) {
            u0 = ld_tag2(pu); u1 = ld_tag2(pu + 256);
            if (BS) mbar_wait(sb + 8 * (B_S + ch), 0);
          }
        }
        const uint32_t fa = base + fo, fa0 = base + fo0;
        uint32_t af[16][4];
        auto afl = [&](int j) {
          const int o = 64 * (j & 1) + 576 * (j >> 1);
          if (UF) { af[j][0] = ldv32(((j & 1) ? fa : fa0) + o); af[j][1] = ldv32(fa + o + 128); af[j][2] = ldv32(fa + o + 32); af[j][3] = ldv32(fa + o + 160); }
          else { af[j][0] = lds32(((j & 1) ? fa : fa0) + o); af[j][1] = lds32(fa + o + 128); af[j][2] = lds32(fa + o + 32); af[j][3] = lds32(fa + o + 160); }
        };
#pragma unroll
        for (int j = 0; j < NA; j++) afl(j);
        if (UF) {
          stv128(base + KSZ + 16 * tid, u0);
          stv128(base + KSZ + 2048 + 16 * tid, u1);
#pragma unroll
          for (int j = NA; j < 16; j++) afl(j);
        }
        STAMPIF(tid == 0, 40 + ch);
        const uint32_t tg = KW && ch < 2 ? 1 : e1;
        if (!KW && !(TG & 1) && EH < 2 && (!EH || ch < 2)) { mbar_wait(sb + 8 * B_E0, 0); e1 = epoch(sb); }
        if (ch < UT) {
          if (KW) { if (ch == 0) spin(t_0, UD2); }
          else if (UD2 ? ch < 2 : ch == 1) spin(t_0, ch ? UD1 : UD2);
          if (UT == 2) u0.w = 0;
          if (UF) u_fix(u0, u1, pu, base + KSZ + 16 * tid, TG ? tg : 1);
          else u_wait(u0, u1, pu);
          if (ITW == 5) STAMPIF(tid == 0, 105 + ch);
          if (!UF) {
            sts128(base + KSZ + 16 * tid, u0);
            sts128(base + KSZ + 2048 + 16 * tid, u1);
#pragma unroll
            for (int j = NA; j < 16; j++) afl(j);
          }
          fence_async_s();
        }
        float acc[128];
        const uint64_t db = mkdesc(base + KSZ, 32, 128, 0);
        bar_sync(1 + wg, NB);
        if (ITW == 5) STAMPIF(tid == 0, 115 + ch);
        wg_fence();
        wgmma_rs_n64<0>(acc + 96, af[0], db + 192, 0);
        wgmma_rs_n192<0>(acc, af[0], db, 0);
        wgmma_rs_n64<0>(acc + 96, af[1], db + 196, 1);
        wgmma_rs_n192<0>(acc, af[1], db + 4, 1);
        wgmma_rs_n32<0>(acc + 96, af[2], db + 224, 1);
        wgmma_rs_n192<0>(acc, af[2], db + 32, 1);
        wgmma_rs_n32<0>(acc + 96, af[3], db + 228, 1);
        wgmma_rs_n192<0>(acc, af[3], db + 36, 1);
        wgmma_rs_n192<0>(acc, af[4], db + 64, 1);
        wgmma_rs_n192<0>(acc, af[5], db + 68, 1);
        wgmma_rs_n160<0>(acc, af[6], db + 96, 1);
        wgmma_rs_n160<0>(acc, af[7], db + 100, 1);
        if (CVT == 2) wg_commit();
        wgmma_rs_n128<0>(acc, af[8], db + 128, 1);
        wgmma_rs_n128<0>(acc, af[9], db + 132, 1);
        if (CVT == 1) wg_commit();
        wgmma_rs_n96<0>(acc, af[10], db + 160, 1);
        wgmma_rs_n96<0>(acc, af[11], db + 164, 1);
        if (CVT == 0) bar_arrive(2 - wg, NB);
        wgmma_rs_n64<0>(acc, af[12], db + 192, 1);
        wgmma_rs_n64<0>(acc, af[13], db + 196, 1);
        wgmma_rs_n32<0>(acc, af[14], db + 224, 1);
        wgmma_rs_n32<0>(acc, af[15], db + 228, 1);
        wg_commit();
        if ((!TG || TG == 2 && ch < 2) && ZP == 0 && ch < UT) {
          stg128((void*)pu, make_uint4(0, 0, 0, 0));
          stg128((void*)(pu + 256), make_uint4(0, 0, 0, 0));
        }
        if (tid < 2 && ch == (!ER && wg == (KV4C & 1) && KV4C < 5 ? KV4C : wg)) mbar_arrive(sb + 8 * (B_E1 + tid));
        if (EH == 2 && ch < 2) { mbar_wait(sb + 8 * B_E0, 0); e1 = epoch(sb); }
        auto go = [&](int k) {
          int mk = 0;
#pragma unroll
          for (int c = 0; c < 4; c++) if (((GT >> 4 * c) & 15) == k) mk |= 1 << c;
          if (mk) asm volatile("{\n.reg .pred p;\nsetp.ne.b32 p, %1, 0;\n@p bar.arrive %0, %2;\n}" ::"r"(2 - wg), "r"((mk >> ch) & 1), "n"(NB) : "memory");
        };
        if (CVT) { wg_wait<1>(); go(0); }
        STAMPIF(tid == 0, 3 + ch);
        if (EH == 3 && ch < 2) { mbar_wait(sb + 8 * B_E0, 0); e1 = epoch(sb); }
        if (BX3 == 2 && ch == 3) {
          mod_box(G, sb, b, 1, e1, tid);
          __syncwarp();
          if (lane == 0) mbar_arrive(sb + 8 * (B_BD + 1));
          STAMPIF(tid == 0, 73);
        }
        if (ZP == 1) {
          stg128((void*)pu, make_uint4(0, 0, 0, 0));
          stg128((void*)(pu + 256), make_uint4(0, 0, 0, 0));
        }
        wg_wait<0>();
#pragma unroll
        for (int i = 0; i < 128; i++) asm volatile("" : "+f"(acc[i])::"memory");
        if (!RL) {
          bar_sync(3 + wg, 128);
          if (tid <= (ch >> 2)) mbar_arrive(sb + 8 * (B_E1 + 2 + (ch >> 1)));
        }
        if (RL == 2 && lane == 0) mbar_arrive(sb + 8 * (B_Z + ch));
        go(1);
        float S0[33], T[34];
#pragma unroll
        for (int i = 0; i < 31; i++) S0[i] = acc[4 * i] + acc[4 * i + 6];
        S0[31] = acc[124]; S0[32] = 0.f;
        if (PK & 1) {
#pragma unroll
          for (int i = 0; i < 32; i += 2) {
            const uint32_t v = __shfl_sync(0xffffffffu, pack2(acc[4 * i + 1] + acc[4 * i + 7], i < 30 ? acc[4 * i + 5] + acc[4 * i + 11] : acc[125]), src1);
            T[i] = (wrap ? S0[i + 1] : S0[i]) + blo(v);
            T[i + 1] = (wrap ? S0[i + 2] : S0[i + 1]) + bhi(v);
          }
        } else {
#pragma unroll
          for (int i = 0; i < 32; i++) {
            float s1 = i < 31 ? acc[4 * i + 1] + acc[4 * i + 7] : acc[125];
            T[i] = (wrap ? S0[i + 1] : S0[i]) + __shfl_sync(0xffffffffu, s1, src1);
          }
        }
        T[32] = 0.f; T[33] = 0.f;
        go(2);
        uint4* pz = (uint4*)(G->zT + (128 * ch + b) * S_) + ((tid & 120) | (2 * q) | (g & 1));
#pragma unroll
        for (int h = 0; h < 2; h++) {
          float y[8];
          if (PK & 2) {
#pragma unroll
            for (int mu = 0; mu < 8; mu += 2) {
              const uint32_t v = __shfl_xor_sync(0xffffffffu, pack2(T[4 * mu + 2 + h], T[4 * mu + 6 + h]), 16);
              y[mu] = (b1 ? T[4 * mu + 4 + h] : T[4 * mu + h]) + blo(v);
              y[mu + 1] = (b1 ? T[4 * mu + 8 + h] : T[4 * mu + 4 + h]) + bhi(v);
            }
          } else {
#pragma unroll
            for (int mu = 0; mu < 8; mu++) y[mu] = (b1 ? T[4 * mu + 4 + h] : T[4 * mu + h]) + __shfl_xor_sync(0xffffffffu, T[4 * mu + 2 + h], 16);
          }
          pz[128 * h] = make_uint4(pack2(y[0], y[1]), pack2(y[2], y[3]), pack2(y[4], y[5]), tagged(pack2(y[6], y[7]), e1));
        }
        go(3);
        if (RL == 1 && lane == 0) mbar_arrive(sb + 8 * (B_Z + ch));
        if (ZP == 2) {
          stg128((void*)pu, make_uint4(0, 0, 0, 0));
          stg128((void*)(pu + 256), make_uint4(0, 0, 0, 0));
        }
        pu += 128 * S_ / 2;
        STAMPIF(tid == 0, 8 + ch);
      }
    }
    uint32_t hh[96];
    {
      float ga[192];
      float* ua = ga + 96;
      const uint64_t da0 = mkdesc(ring + wg * 2048, 512, 256, 3), db0 = mkdesc(ring + 8192, 4096, 1024, 1);
      int st = PL, ph = 0, ps = 0;
      if (ITW == 7) STAMPIF(tid == 0, 110 + wg);
      float bx[4];
      if (wg && BX3 < 2) {
        mbar_wait(sb + 8 * (B_BOX + 2), 0);
        mbar_wait(sb + 8 * (B_BOX + 3), 0);
        wg_fence();
#pragma unroll
        for (int n = 0; n < 10; n++) wgmma_ss_n8<1, 0>(bx, box_a(sb) + 128 * n, box_b(sb) + 8 * n, n != 0);
        wg_commit();
        if (ITW == 7) STAMPIF(tid == 0, 120);
      }
      auto put = [&]() {
#pragma unroll
        for (int i = 0; i < 4; i++) asm volatile("" : "+f"(bx[i])::"memory");
        mod_put(G, sb, bx, b, 1, e1, tid);
        __syncwarp();
        if (lane == 0) mbar_arrive(sb + 8 * (B_BD + 1));
        STAMPIF(tid == 0, 73);
      };
      if (wg && BX3 == 0) { wg_wait<0>(); put(); }
      mbar_wait(sb + 8 * B_F1, 0);
      STAMPIF(tid == 0, 13 + wg);
      bool nf = PG == 1 && mbar_test(sb + 8 * (B_F1 + 1), 0);
      wg_fence();
      wgmma_ss_n192<1, 1>(ga, da0, db0, 0);
      wgmma_ss_n192<1, 1>(ua, da0, db0 + 768, 0);
      wgmma_ss_n192<1, 1>(ga, da0 + 256, db0 + 128, 1);
      wgmma_ss_n192<1, 1>(ua, da0 + 256, db0 + 128 + 768, 1);
      wg_commit();
      if (wg && BX3 == 1) { wg_wait<1>(); put(); }
      if (!PG) mbar_wait(sb + 8 * B_BD, 0);
      if (ITW == 7) STAMPIF(tid == 0, 112 + wg);
      const bool cs = b < 96;
      const int x0 = wg ? XI : 99,
                x1 = x0 + (cs ? 4 : 2), xs = cs ? 4 : 8;
      uint64_t xa = cs ? mkdesc(sb + SM_EXT, 4096, 1024, 1) : box_a(sb), xb = cs ? mkdesc(sb + SM_CB, 32, 128, 0) : box_b(sb);
      uint64_t ya = xa + (cs ? (SM_RING + R_X - SM_EXT) / 16 : 256), yb = xb + 16;
      if (ITW == 7) STAMPIF(tid == 0, 114 + wg);
#pragma unroll 1
      for (int it = PL; it < 19; it++) {
        if (it == x0) {
          mbar_wait(sb + 8 * (cs ? B_F : B_BOX + 4), 0);
          mbar_wait(sb + 8 * (cs ? B_ST0 : B_BOX + 5), 0);
          STAMPIF(tid == 0, 76);
        }
        if (it == x1 + XW) {
          wg_wait<XW>();
#pragma unroll
          for (int i = 0; i < 4; i++) asm volatile("" : "+f"(bx[i])::"memory");
          if (!cs) mod_put(G, sb, bx, b, 2, e1, tid);
          else {
            const int row = (m < 6 ? 0 : 4) + q;
            uint16_t* dst = (uint16_t*)G->cimg + s * 3072 + (m % 6) * 512 + row * 64 + g;
#pragma unroll
            for (int j = 0; j < 2; j++) {
              const float c1 = __shfl_sync(0xffffffffu, bx[2 * j], lane & 28), c2 = __shfl_sync(0xffffffffu, bx[2 * j + 1], lane & 28);
              const float t = (lane & 2) ? c2 : c1, hi = rbf(t);
              dst[((2 * w + j) ^ row) << 3] = (uint16_t)pack2((lane & 1) ? t - hi : hi, 0.f);
            }
          }
          __syncwarp();
          if (lane == 0) mbar_arrive(sb + 8 * (B_BD + 2));
          STAMPIF(tid == 0, 77);
        }
        if (ITW == 7) STAMPIF(tid == 0 && it == 0, 116 + wg);
        if (!nf) mbar_wait(sb + 8 * (B_F1 + st), ph);
        const int nx = st == 4 ? 0 : st + 1;
        if (st == 4) ph ^= 1;
        if (ITW == 1) STAMPIF(tid == 0 && it >= 10, 90 + it + 10 * wg);
        else if (ITW == 2) STAMPIF(tid == 0 && it < 10, 100 + it + 10 * wg);
        else if (ITW < 3) STAMPIF(threadIdx.x == ITW, 100 + it);
        const uint64_t da = da0 + st * 2048, db = db0 + st * 2048;
        if (it >= x0 && it < x1) {
          if (PG == 1) nf = mbar_test(sb + 8 * (B_F1 + nx), ph);
          wg_fence();
          wgmma_ss_n8<1, 0>(bx, xa, xb, it != x0);
          wgmma_ss_n192<1, 1>(ga, da, db, 1);
          wgmma_ss_n8<1, 0>(bx, ya, yb, 1);
          wgmma_ss_n192<1, 1>(ua, da, db + 768, 1);
          wgmma_ss_n8<1, 0>(bx, ya + 128, yb + xs, 1);
          wgmma_ss_n192<1, 1>(ga, da + 256, db + 128, 1);
          wgmma_ss_n8<1, 0>(bx, ya + 256, yb + 2 * xs, 1);
          wgmma_ss_n192<1, 1>(ua, da + 256, db + 128 + 768, 1);
          wgmma_ss_n8<1, 0>(bx, ya + 384, yb + 3 * xs, 1);
          wg_commit();
          xa += 128; xb += xs; ya += 512; yb += 4 * xs;
        } else {
          if (PG == 1) nf = mbar_test(sb + 8 * (B_F1 + nx), ph);
          wg_fence();
          wgmma_ss_n192<1, 1>(ga, da, db, PL || it != 0);
          wgmma_ss_n192<1, 1>(ua, da, db + 768, PL || it != 0);
          wgmma_ss_n192<1, 1>(ga, da + 256, db + 128, 1);
          wgmma_ss_n192<1, 1>(ua, da + 256, db + 128 + 768, 1);
          wg_commit();
        }
        wg_wait<1>();
        if (PG) { if (w == 0 && elect()) mbar_arrive(sb + 8 * (B_E1 + ps)); }
        else if (tid == 0) mbar_arrive(sb + 8 * (B_E1 + (st == 0 ? 4 : st - 1)));
        ps = st; st = nx;
      }
      const uint32_t la = ring + wg * 2048 + tid * 16, ra = mapa(la, (b & 1) ^ 1), rp = mapa(sb + 8 * (B_PEER + 2 * wg), (b & 1) ^ 1), rb = rp + 8 * (B_RECV - B_PEER);
      uint32_t sa[24];
      auto addr = [&](int j) {
        sa[2 * j] = ra + (j < 2 ? 5 : (j >> 1) - 1) * 32768 + (j & 1) * 4096;
        sa[2 * j + 1] = (sa[2 * j] >> 31) + (rb + 8 * (j / 6));
        asm volatile("" : "+r"(sa[2 * j]), "+r"(sa[2 * j + 1]));
      };
      auto send = [&](int j) { st_async4(sa[2 * j], hh + 4 * j, sa[2 * j + 1]); };
      auto pack = [&](int c) {
#pragma unroll
        for (int i = 0; i < 64; i++) asm volatile("" : "+f"(ga[64 * c + i])::"memory");
#pragma unroll
        for (int i = 0; i < 4; i++) addr(4 * c + i);
#pragma unroll
        for (int i = 0; i < 16; i++) {
          const int j = 64 * c + 2 * i;
          hh[16 * c + i] = pack2(ga[j] * ga[j + 32], ga[j + 1] * ga[j + 33]);
          asm volatile("" : "+r"(hh[16 * c + i])::"memory");
          if ((i & 3) == 3 && 4 * c + i / 4 < NP) send(4 * c + i / 4);
          if (c == 2 && NQ > NP && i == 0) mbar_wait(sb + 8 * (B_PEER + 2 * wg), 0);
          if (c == 2 && (i & 3) == 3 && NP + i / 4 < NQ) send(NP + i / 4);
        }
      };
      STAMPIF(threadIdx.x == 0, 61);
      if (!nf) mbar_wait(sb + 8 * (B_F1 + 4), 1);
      mbar_wait(sb + 8 * B_EXT, 0);
      mbar_wait(sb + 8 * B_ST2, 0);
      const uint64_t de = mkdesc(sb + SM_EXT, 1024, 0, 1), ds = mkdesc(sb + SM_STAT + wg * 1024, 0, 128, 0);
#pragma unroll
      for (int c = 0; c < 2; c++) {
        wg_fence();
        wgmma_ss_n192<1, 1>(ga + 96 * c, da0 + 8192, db0 + 8192 + 768 * c, 1);
        wgmma_ss_n192<1, 1>(ga + 96 * c, da0 + 8192 + 256, db0 + 8192 + 128 + 768 * c, 1);
        wgmma_ss_n192<0, 1>(ga + 96 * c, ds, de + 192 * c, 1);
        wg_commit();
        if (c == 0) { mbar_wait(sb + 8 * B_P0, 0); mbar_wait(sb + 8 * B_FB, 0); }
        wg_wait<1>();
        if (c == 0 && tid == 0) {
          mbar_arrive(sb + 8 * (B_E1 + 3));
          mbar_arrive_remote(rp);
        }
      }
      STAMPIF(tid == 0, 15 + wg);
      float acc[64], rs[2] = {};
      uint4 pf[4], gb = {};
      uint32_t ln, os, ol, og, oz;
      const char *po, *pq;
      const uint64_t dd0 = mkdesc(ring + 8192, 0, 1024, 1);
      bool ok = false;
#pragma unroll
      for (int c = 0; c < 3; c++) {
        pack(c);
        if (c == 1) ok = mbar_try(sb + 8 * (B_FB + 1), 0);
        STAMPIF(tid == 0 && c == 0, wg ? 89 : 121);
        if (ITW == 3) STAMPIF(tid == 0 && c > 0, 99 + c + 10 * wg);
        wg_fence();
#pragma unroll
        for (int k = 4 * c; k < 4 * c + 4; k++) wgmma_rs_n64<1>(acc, hh + 4 * k, dd0 + 5 * 2048 + 128 * k, k);
        wg_commit();
        if (c == 0) {
          wg_wait<1>();
          if (tid == 0) {
            mbar_arrive(sb + 8 * (B_E1 + 4));
            mbar_arrive_remote(rp + 8);
          }
        }
        if (c == 1 && !ok) mbar_wait(sb + 8 * (B_FB + 1), 0);
      }
      auto recv = [&](int j) {
        const uint4 v = lds128(la + (j < 2 ? 5 : (j >> 1) - 1) * 32768 + (j & 1) * 4096);
        hh[48 + 4 * j] = v.x; hh[49 + 4 * j] = v.y; hh[50 + 4 * j] = v.z; hh[51 + 4 * j] = v.w;
      };
      auto stage = [&](const float* a, int i, int p) {
        const uint32_t v[4] = {pack2(a[8 * i] * rs[0], a[8 * i + 1] * rs[0]), pack2(a[8 * i + 2] * rs[1], a[8 * i + 3] * rs[1]),
                               pack2(a[8 * i + 4] * rs[0], a[8 * i + 5] * rs[0]), pack2(a[8 * i + 6] * rs[1], a[8 * i + 7] * rs[1])};
        stsm4(OF && p % 4 ? (oz ^ 32 * i) + 65536 * (p - 1) : os + 32 * i, v);
      };
      auto fetch = [&](int p) {
        __syncwarp();
#pragma unroll
        for (int i = 0; i < 4; i++) pf[i] = lds128(ol + 576 * i);
      };
      auto next = [&](int p) {
        gb = lds128(og + 256 * out_blk(s, p));
        pq = po + 128 * out_blk(s, p);
        asm volatile("" : "+l"(pq));
      };
      auto add = [&](int p, int i) {
        if (RX == 1 && p < 4) return;
        if (RX == 2) { stg128((uint4*)(pq - (i & 1) * 2048 * D_ - (i >> 1) * 2 * D_), make_uint4(hmul(pf[i].x, gb.x), hmul(pf[i].y, gb.y), hmul(pf[i].z, gb.z), hmul(pf[i].w, gb.w))); return; }
        asm volatile("red.relaxed.gpu.global.add.noftz.v4.bf16x2 [%0], {%1, %2, %3, %4};" ::"l"(pq - (i & 1) * 2048 * D_ - (i >> 1) * 2 * D_),
                     "r"(hmul(pf[i].x, gb.x)), "r"(hmul(pf[i].y, gb.y)), "r"(hmul(pf[i].z, gb.z)), "r"(hmul(pf[i].w, gb.w)) : "memory");
      };
#pragma unroll
      for (int h = 2; h < 20; h++) {
        const int gr = h >> 1, pe = gr < 4 ? gr >> 1 : gr & 1, ac = (gr < 4 ? gr : gr >> 1) & 1;
        const int ep = h == 7 || h == 8 ? 0 : h > 8 && (h & 3) == 1 || h > 8 && (h & 3) == 2 ? (h >> 2) - 1 : -1;
        const int es = h == 6 ? 0 : h > 6 && !(h & 3) ? (h >> 2) - 1 : -1;
        if (!(h & 1) && h > 2 && !(PT && ok)) mbar_wait(sb + 8 * (B_FB + gr), 0);
        if (h == LH0 || h == LH1) mbar_wait(sb + 8 * (B_RECV + 2 * wg + (h == LH1)), 0);
        if (h == LH0 && (h == 4 || !LM) || h == LH1 && (h == 5 || !LM)) {
#pragma unroll
          for (int j = 0; j < 6; j++) recv(6 * (h == LH1) + j);
        }
        if (h == SPOS(6) / 6 && NQ <= 6) mbar_wait(sb + 8 * (B_PEER + 2 * wg), 0);
        if (h == SPOS(10) / 6) mbar_wait(sb + 8 * (B_PEER + 2 * wg + 1), 0);
        if (OF && h == OH) mbar_wait(sb + 8 * B_OF, 0);
        if (h == (ES ? RH : 6)) {
          if (!OF) { mbar_wait(sb + 8 * B_X1, 0); mbar_wait(sb + 8 * B_GB, 0); }
          asm volatile("mov.u32 %0, %%laneid;" : "=r"(ln));
#pragma unroll
          for (int i = 0; i < 2; i++) rs[i] = blo(lds32(sb + SM_STAT + (4 * wg + w) * 256 + (ln & 28) * 4 + 128 * i + 4));
        }
        STAMPIF(tid == 0 && h % 4 == 0 && h < 16, (wg ? 89 : 121) + h / 4);
        STAMPIF(tid == 0 && h == 16, wg ? 97 : 96);
        if (ITW == 3) STAMPIF(tid == 0 && h < 10, 100 + h + 10 * wg);
        if (ITW == 4) STAMPIF(tid == 0 && h >= 10, 90 + h + 10 * wg);
        const uint64_t db = dd0 + (((gr + 5) % 6) * 2048 + (gr << 16));
        if (PT && (h & 1) && h < 19) ok = mbar_try(sb + 8 * (B_FB + gr + 1), 0);
        wg_fence();
#pragma unroll
        for (int j = 0; j < 6; j++) {
          const int k = 6 * (h & 1) + j;
          wgmma_rs_n64<1>(acc + 32 * ac, hh + 48 * pe + 4 * k, db + 128 * k, pe || k);
#pragma unroll
          for (int i = NQ; i < 12; i++) if (SPOS(i) == 6 * h + j) send(i);
          if (LM && h == LH0 && h < 4) { recv(j); wg_fence(); }
          if (LM && h == LH1 && h < 5) { recv(6 + j); wg_fence(); }
          if (ES && es >= 0) {
            if (j == ES - 1) {
              wg_commit();
              wg_wait<1>();
              if (h < 12 && tid == 0) mbar_arrive(sb + 8 * (B_EB + gr - 1));
#pragma unroll
              for (int i = 0; i < 32; i++) asm volatile("" : "+f"(acc[32 * (1 - ac) + i])::"memory");
            }
#pragma unroll
            for (int i = 0; i < 4; i++) if (j == min(5, ES - 1 + i * SI / 2)) {
              stage(acc + 32 * (1 - ac), i, es);
              if (i == 3) { __syncwarp(); if (ln == 0) mbar_arrive(sb + 8 * (B_OS + 4 * wg + es)); }
            }
            if (j == ES - 1 && j < 5) wg_fence();
          }
          if (!ES && ep >= 0 && (h & 1)) {
            if (j < 4) stage(acc + 32 * (1 - ac), j, ep);
            if (j == 4 && !OF) fetch(ep);
            if (j == 3 && OF) { __syncwarp(); if (ln == 0) mbar_arrive(sb + 8 * (B_OS + 4 * wg + ep)); }
          }
          if (!OF && ep >= 0 && !(h & 1) && j > 0 && j < 5) add(ep, j - 1);
          if (!OF && ep >= 0 && !(h & 1) && j == 5) next(ep + 1);
        }
        if (!(ES == 6 && es >= 0)) wg_commit();
        STAMPIF(tid == 0 && h == 3, 81);
        if (h == (ES ? RH : 6)) {
#pragma unroll
          for (int i = 0; i < 2; i++) rs[i] = __fdividef(0.25f, rs[i] * rs[i]);
          const uint32_t ob = sb + SM_X + (4 * wg + w) * 2304;
          os = ob + (ln & 15) * 144 + (ln & 16);
          oz = ring + (4 * wg + w) * 512 + (ln & 8) * 4096 + (ln & 4) * 1024 + (ln & 3) * 128 + ((ln >> 4) ^ (ln & 7)) * 16;
          asm volatile("" : "+r"(os), "+r"(oz));
        }
        if (h == (OF ? OH : 6)) {
          ol = sb + SM_X + (4 * wg + w) * 2304 + (ln >> 3) * 16 + ln * 16;
          po = (const char*)(gout + (1793 + 2 * tbase(8 * m + 4 * wg + w)) * D_) + (int)(640 * (s & 1) + 16 * ln - (ln >> 3) * (512 * D_ + 128));
          og = sb + SM_CB + 32 * (ln & 7);
          asm volatile("" : "+r"(ol), "+r"(og), "+l"(po));
          next(OF ? 4 : 0);
        }
        if (h == 2 || h == 4 || !ES && es >= 0) {
          wg_wait<1>();
          if (h < 12 && tid == 0) mbar_arrive(sb + 8 * (B_EB + gr - 1));
          if (h >= 6) {
#pragma unroll
            for (int j = 0; j < 32; j++) asm volatile("" : "+f"(acc[32 * (1 - ac) + j])::"memory");
          }
        }
      }
      STAMPIF(tid == 0, wg ? 95 : 93);
      wg_wait<0>();
#pragma unroll
      for (int i = 0; i < 32; i++) asm volatile("" : "+f"(acc[i])::"memory");
      STAMPIF(tid == 0, wg ? 50 : 18);
#pragma unroll
      for (int i = 0; i < 4; i++) stage(acc, i, 4);
      fetch(4);
#pragma unroll
      for (int i = 0; i < 4; i++) add(4, i);
    }
  } else if (wg == 2) {
    asm volatile("setmaxnreg.dec.sync.aligned.u32 40;");
    const uint32_t e1 = (rdback(G->flag + 8 * m + 4) >> 5) + 1;
    if (tid < 80) {
      uint4 c = ((const uint4*)gc)[tid];
#pragma unroll 1
      for (int i = 0; i < 4; i++) {
        const float lo = blo(c.x), hi = bhi(c.x);
        sts32(sb + SM_STAT + 16 * tid + 4 * i, pack2(__fdividef(lo, 1.f + __expf(-lo)), __fdividef(hi, 1.f + __expf(-hi))));
        c.x = c.y; c.y = c.z; c.z = c.w;
      }
    }
    if (tid == 0) { sts32(sb + SM_SMALL + SMALL_E, e1); mbar_arrive(sb + 8 * B_E0); }
    fence_async_s();
    bar_sync(5, 128);
    auto mod0 = [&](int tid) {
      if (mod_first(b)) mod_box(G, sb, b, 0, e1, tid);
      __syncwarp();
      if (elect()) mbar_arrive(sb + 8 * B_BD);
      STAMPIF(tid == 0, 27);
    };
    if (MO == 2) { kv_job(G, sb, b, 2, tid, e1); STAMPIF(tid == 0, 22); }
    if (MO != 1) mod0(tid);
    float s1 = 0.f, s2 = 0.f, pv;
    int tl = (OPQ & 1) ? __shfl_sync(0xffffffffu, tid, tid) : tid;
#pragma unroll 1
    for (int r = KW || MO == 2 ? 3 : 2 - DR; r < 5 - XO; r++) {
      asm volatile("" : "+r"(tl));
      if (DR && r == 2) s1 = s2 = 0.f;
      if ((XO || r < 4) && r > 1) {
        kv_job(G, sb, b, r, tl, TG ? e1 : 1);
        STAMPIF(tid == 0, 20 + r);
      }
      if (r == 3) { __syncwarp(); if (elect()) mbar_arrive(sb + 8 * B_KVS); }
      if (XO || r != 2) ln1_half(sb, tl, (r - 3 + XO) & 1, r < 2, s1, s2, pv);
      else if (MO == 1) { mod0(tl); s1 = s2 = 0.f; }
    }
    {
      const int lane = tl & 31, cg = 4 * (w >> 1) + (lane & 2) + (w & 1), g = lane >> 2;
      uint32_t zo = offsetof(Scr, zT) + 2 * ((16 * cg + g) * S_ + 16 * b + 8 * (lane & 1)), co = offsetof(Scr, mv) + 4 * (2048 * (e1 & 1) + 8 * cg + g);
      uint4 z[2];
      uint32_t c[4];
      auto zld = [&]() {
        asm volatile("" : "+r"(zo), "+r"(co));
        const uint2* pz = (const uint2*)((const char*)G + zo);
        const uint32_t* pc = (const uint32_t*)((const char*)G + co);
        z[0] = ld_tag2(pz); z[1] = ld_tag2(pz + 4096);
        c[0] = rdback(pc); c[1] = rdback(pc + 320); c[2] = rdback(pc + 640); c[3] = rdback(pc + 1280);
      };
      STAMPIF(tid == 0, 28);
      if (ZF < 2 && !ZA) { spin(t_0, ZD); zld(); spin(t_0, ZS); }
      if (ITW == 8) STAMPIF(tid == 0, 106);
      ln1_end(sb, tl, s1, s2, pv);
      if (ZF < 2 && ZA) { spin(t_0, ZD); zld(); }
#pragma unroll 1
      for (int r = 0; r < 5; r++) {
        asm volatile("" : "+r"(tl));
        const int lane = tl & 31;
        if (ITW == 6) STAMPIF(tid == 0 && r < 2, 100 + 10 * r);
        if (ZF == 3) { if (r == 2 + MG) { mbar_wait(sb + 8 * (B_BD + 1), 0); spin(clk(), BD); } if (r == 0) spin(t_0, ZD); zld(); }
        const uint32_t la = sb + SM_SMALL + SMALL_LN + 16 * (lane & 1);
        uint32_t xa = x_addr(sb, w, lane) + 4096 * r, xv[8];
        const uint4 m4 = lds128(la), s4 = lds128(la + 32);
        const uint32_t m_[4] = {m4.x, m4.y, m4.z, m4.w}, s_[4] = {s4.x, s4.y, s4.z, s4.w};
        ldsm4t(xv, xa);
        ldsm4t(xv + 4, xa ^ 16);
        if (ZF == 2) { if (r == 2 + MG) { mbar_wait(sb + 8 * (B_BD + 1), 0); spin(clk(), BD); } if (r == 0) spin(t_0, ZD); zld(); }
        if (ITW == 6) STAMPIF(tid == 0 && r < 2, 104 + 10 * r);
        if (ITW == 8) STAMPIF(tid == 0 && r == 0, 109);
        z_wait(z[0], z[1], c, G, zo, co, e1);
        asm volatile("" : "+r"(xa));
        const uint32_t zc = (zo - (uint32_t)offsetof(Scr, zT)) >> 11, ao = (320 * m + s) * 32 + ((zc & ~31u) << 3) + (zc & 14) + (((zo >> 4) ^ (zc >> 3)) & 1);
        STAMPIF(tid == 0 && r == 0, 83);
        if (ITW == 6) STAMPIF(tid == 0 && r < 2, 105 + 10 * r);
        uint32_t h[8];
        {
          const uint32_t sa = ~c[0], ca1 = ~c[1];
#pragma unroll
          for (int j = 0; j < 8; j++) {
            const uint32_t z_[8] = {z[0].x, z[0].y, z[0].z, z[0].w, z[1].x, z[1].y, z[1].z, z[1].w}, sel = j > 3 ? 0x3232 : 0x1010;
            h[j] = hmul(hfma(hmul(hsub(xv[j], m_[j & 3]), s_[j & 3]), __byte_perm(ca1, 0, sel), __byte_perm(sa, 0, sel)), z_[j]);
            asm volatile("" : "+r"(h[j]));
          }
        }
        uint4* pa = (uint4*)G->AT + ao;
        uint32_t oo[8];
#pragma unroll
        for (int n = 0; n < 2; n++) {
          const uint32_t sel = n ? 0x3232 : 0x1010, ga = __byte_perm(~c[2], 0, sel), cb1 = __byte_perm(~c[3], 0, sel);
          uint32_t* o = oo + 4 * n, a[4];
#pragma unroll
          for (int j = 0; j < 4; j++) {
            o[j] = hfma(ga, h[4 * n + j], xv[4 * n + j]);
            a[j] = hmul(o[j], cb1);
          }
          a[2 * n + 1] = tagged(a[2 * n + 1], e1);
          pa[16 * n] = make_uint4(a[0], a[1], a[2], a[3]);
          if (n) { __syncwarp(); if (elect()) { flag_add(G, 8 * m + r); if (EA && r == 0) mbar_arrive(sb + 8 * (B_EW + 5)); } }
          if (ITW == 6) STAMPIF(tid == 0 && r < 2, 106 + n + 10 * r);
          if (ITW == 8) STAMPIF(lane == 0 && r == 0 && n, 110 + w);
          if (!SL) stsm4t(xa ^ (16 * n), o);
        }
        if (SL) { stsm4t(xa, oo); stsm4t(xa ^ 16, oo + 4); }
        if (r < 4) { zo += 256 * S_; co += 256; }
        auto x1st = [&]() {
          __syncwarp();
          int lane = tl & 31;
          if (!(OPQ & 2)) asm volatile("mov.u32 %0, %%laneid;" : "=r"(lane));
          const int c = 2 * (w & 1) + (lane & 1) + 2 * (lane & 2), g = lane >> 2;
          const uint32_t a = sb + SM_X + 4096 * r + (w >> 1) * 2048 + g * 128 + ((c ^ g) << 4);
          const uint4 v0 = lds128(a), v1 = lds128(a + 1024);
          char* po = (char*)gout + (2 * tbase(b) + 128 * (g & 6) + (g & 1)) * 2 * D_ + 256 * r + 64 * (w & 2) + 16 * c;
          if (ITW == 6) STAMPIF(tid == 0 && r < 2, 108 + 10 * r);
          stg128(po, v0);
          stg128(po + 2048 * D_, v1);
        };
        auto box1 = [&]() {
          if (BX3 >= 3) {
            mod_box(G, sb, b, 1, e1, tl);
            __syncwarp();
            if (elect()) mbar_arrive(sb + 8 * (B_BD + 1));
            STAMPIF(tid == 0, 73);
          } else mbar_wait(sb + 8 * (B_BD + 1), 0);
          if (BX3 < 4) spin(clk(), BD);
        };
        if (ZF == 1) {
          if (BX3 < 4 && r == 1 + MG) { if (XE) x1st(); box1(); }
          if (BX3 == 5 && r == 0) box1();
          zld();
        }
        if (BX3 == 6 && r == 0) box1();
        if (BX3 > 3 || ZF != 1 || !XE || r != 1 + MG) x1st();
        if (BX3 == 4 && r == 0) box1();
        __syncwarp();
        if (elect()) mbar_arrive(sb + 8 * (B_EW + r));
        STAMPIF(tid == 0, 29 + r);
        if (ZF == 0) { if (r == 1 + MG) box1(); zld(); }
      }
    }
    asm volatile("" : "+r"(tl));
    {
      const int lane = tl & 31;
      const uint4 m4 = lds128(sb + SM_SMALL + SMALL_LN + 16 * (lane & 1));
      const uint32_t m_[4] = {m4.x, m4.y, m4.z, m4.w}, xa = x_addr(sb, w, lane);
      float a[16];
#pragma unroll
      for (int i = 0; i < 16; i++) a[i] = 0.f;
#pragma unroll 2
      for (int n = 0; n < 10; n++) {
        uint32_t x_[4];
        ldsm4t(x_, (xa ^ (16 * (n & 1))) + 2048 * (n & 14));
#pragma unroll
        for (int i = 0; i < 4; i++) {
          const float d0 = blo(x_[i]) - blo(m_[i]), d1 = bhi(x_[i]) - bhi(m_[i]);
          a[4 * i] += d0; a[4 * i + 1] += d0 * d0; a[4 * i + 2] += d1; a[4 * i + 3] += d1 * d1;
        }
      }
      STAMPIF(lane == 0, 67 + (w & 1) + 11 * (w >> 1));
      bfly<16>(a, 16, lane & 16); bfly<8>(a, 8, lane & 8); bfly<4>(a, 4, lane & 4); bfly<2>(a, 2, lane & 2);
      if (lane == 0) mbar_arrive(sb + 8 * B_XF);
      STAMPIF(tid == 0, 88);
      sts32(sb + SM_SMALL + SMALL_RED + 16 * lane + 4 * w, __float_as_uint(a[0]));
      bar_sync(5, 128);
      if (w == 0) {
        const uint4 v = lds128(sb + SM_SMALL + SMALL_RED + 16 * lane);
        const float s1 = __uint_as_float(v.x) + __uint_as_float(v.y) + __uint_as_float(v.z) + __uint_as_float(v.w), s2 = __shfl_xor_sync(0xffffffffu, s1, 2);
        const int p = 8 * (lane & 1) + (lane >> 2);
        const float pv = blo(lds32(sb + SM_SMALL + SMALL_LN + 4 * (p >> 1)) >> (16 * (p & 1)));
        const float mu = s1 * (1.f / D_), var = fmaxf(s2 * (1.f / D_) - mu * mu, 0.f);
        const float sd = sdev(var);
        if (!(lane & 2)) st_tag(G->st2 + 16 * b + p, pack2(-0.5f * (pv + mu), 0.5f * sd), e1);
      }
      STAMPIF(tid == 0, 87);
    }
    {
      uint2 v;
      spin(clk(), SD);
      mbar_wait(sb + 8 * (B_BD + 2), 0);
#pragma unroll 1
      for (int i = 0;; i++) {
        v = ld_tag(G->st2 + 128 * m + tl);
        if (__all_sync(0xffffffffu, v.y == e1)) break;
        if (i > (1 << 20)) __trap();
      }
      const uint32_t hm = __byte_perm(v.x, 0, 0x1010), hs = __byte_perm(v.x, 0, 0x3232);
      sts128(sb + SM_STAT + 16 * tl, make_uint4(hm, hs, hm, hs));
      fence_async_s();
      __syncwarp();
      if (elect()) mbar_arrive(sb + 8 * B_ST2);
      STAMPIF(tid == 0, 21);
    }
    if (OF) {
      uint32_t ln, w, s;
      asm volatile("mov.u32 %0, %%laneid;\n\tmov.u32 %1, %%tid.x;\n\tmov.u32 %2, %%ctaid.x;" : "=r"(ln), "=r"(w), "=r"(s));
      w = (w >> 5) & 3; s = role<0>(s);
      const int m = s >> 3;
      s &= 7;
      mbar_wait(sb + 8 * B_X1, 0);
      mbar_wait(sb + 8 * B_GB, 0);
      const uint32_t ol = sb + SM_X + w * 2304 + (ln >> 3) * 16 + ln * 16, oz = ring - 65536 + w * 512 + (ln >> 3) * 128 + ((ln >> 3) ^ (ln & 7)) * 16;
      const char* po = (const char*)(gout + 1793 * D_) + (int)(640 * (s & 1) + 16 * ln - (ln >> 3) * (512 * D_ + 128));
#pragma unroll 1
      for (int n = 0; n < 8; n++) {
        const int p = n >> 1, c = n & 1, ob = out_blk(s, p);
        const uint4 gb = lds128(sb + SM_CB + 32 * (ln & 7) + 256 * ob);
        const char* pq = po + (128 * ob + 4 * D_ * tbase(8 * m + 4 * c + w));
        const uint32_t a0 = p ? oz + 65536 * p + 2048 * c : ol + 9216 * c, a1 = p ? (a0 ^ 64) + 4096 : a0 + 576, d = p ? 32768 : 1152;
        mbar_wait(sb + 8 * (B_OS + 4 * c + p), 0);
        const uint4 pf[4] = {lds128(a0), lds128(a1), lds128(a0 + d), lds128(a1 + d)};
#pragma unroll
        for (int i = 0; i < 4; i++)
          asm volatile("red.relaxed.gpu.global.add.noftz.v4.bf16x2 [%0], {%1, %2, %3, %4};" ::"l"(pq - (i & 1) * 2048 * D_ - (i >> 1) * 2 * D_),
                       "r"(hmul(pf[i].x, gb.x)), "r"(hmul(pf[i].y, gb.y)), "r"(hmul(pf[i].z, gb.z)), "r"(hmul(pf[i].w, gb.w)) : "memory");
        if (n == 1) { __syncwarp(); if (ln == 0) mbar_arrive(sb + 8 * B_OF); }
      }
    }
  } else {
    asm volatile("setmaxnreg.dec.sync.aligned.u32 24;");
    if (w != 0) {
    if (w == 2 && lane < 3) asm volatile("prefetch.tensormap [%0];" ::"l"(&P.mG + lane) : "memory");
    if (K3) {
      const uint32_t dv = *(const uint16_t*)(gD + 128 * min(lane, 4) + b);
#pragma unroll 1
      for (int j = 7 + w; j < 20; j += 3) {
        k1_job(sb, j >> 2, 32 * (j & 3) + lane, __shfl_sync(0xffffffffu, dv, j >> 2));
        if ((j & 3) == (K3 & 3)) {
          mbar_wait(sb + 8 * (B_KJ + (j >> 2)), 0);
          const uint32_t t = lds32(sb + SM_SMALL + SMALL_TS + 4 * (j >> 2));
          while (clk() - t < UD);
        }
        __syncwarp();
        if (lane == 0) mbar_arrive(sb + 8 * (B_K + (j >> 2) - 2));
      }
      STAMPIF(lane == 0 && w == 3, 74);
    } else if (w & 1) {
      const uint32_t dv = *(const uint16_t*)(gD + 128 * min(lane, 4) + b);
#pragma unroll 1
      for (int j = 4; j < 10; j++) {
        k1_job(sb, j >> 1, 64 * (j & 1) + 16 * (w & 2) + lane, K1N ? __shfl_sync(0xffffffffu, dv, j >> 1) : *(const uint16_t*)(gD + 64 * (j & 14) + b));
        if (ITW == 5) STAMPIF(tid == 32, 98 + (j >> 1));
        if (UT == 5 && UD && w == 1 && (j & 1)) {
          mbar_wait(sb + 8 * (B_KJ + (j >> 1)), 0);
          const uint32_t t = lds32(sb + SM_SMALL + SMALL_TS + 4 * (j >> 1));
          while (clk() - t < UD);
        }
        __syncwarp();
        if (lane == 0) mbar_arrive(sb + 8 * (B_K + (j >> 1) - 2));
      }
      STAMPIF(tid == 32, 74);
    }
    if (w == 1) {
     {
      mbar_wait(sb + 8 * B_KVS, 0);
      const uint32_t e1 = epoch(sb);
      if (elect()) {
        if (P3) { const uint32_t v = e1 * 32 - 32; sts128(sb + SM_SMALL + SMALL_H, make_uint4(v, v, v, v)); sts32(sb + SM_SMALL + SMALL_H + 16, v); }
        if (ER) mbar_wait(sb + 8 * B_KV4, 0);
        mbar_wait(sb + 8 * (B_EW + 5 * EA), 0);
        spin(clk(), AD);
#pragma unroll 1
        for (int it = NS; it < 20; it++) {
          int st = it % 5;
          if ((it & 3) == 0 || it == NS) { if (P3) hint_wait(G, sb + SM_SMALL + SMALL_H, 8 * m + (it >> 2), e1 * 32); else flag_wait(G, 8 * m + (it >> 2), e1 * 32); STAMP(45 + (it >> 2)); }
          if (NS && it == NS) mbar_arrive(sb + 8 * B_FS);
          mbar_wait(sb + 8 * (B_E1 + st), (it / 5) & 1);
          uint32_t fb = sb + 8 * (B_A + st);
          mbar_expect(fb, 8192);
          bulk_g2s(ring + st * 32768, G->AT + (20 * m + it) * 4096, 8192, fb);
        }
        mbar_wait(sb + 8 * B_XF, 0);
        flag_wait(G, 8 * m + FL_X, e1 * 8);
        mbar_arrive(sb + 8 * B_X1);
        STAMP(86);
      }
     }
    } else if (w == 2) {
      if (lane < 4) mbar_expect(sb + 8 * (B_RECV + lane), 12288);
      if (UT == 2) { bar_arrive(1, 288); bar_arrive(2, 288); }
      int ph = 0;
#pragma unroll 1
      for (int ch = UT; ch < 5; ch++) {
        const uint32_t ub = chan_base(sb, ch) + KSZ;
        uint4* pu = (uint4*)(G->kvT + (128 * ch + b) * S_);
        mbar_wait(sb + 8 * (B_KJ + ch), 0);
        const uint32_t t0 = lds32(sb + SM_SMALL + SMALL_TS + 4 * ch);
        while (clk() - t0 < (ch ? UD : UD0));
#pragma unroll 1
        for (int i = 0;; i++) {
          if (elect()) { mbar_expect(sb + 8 * B_U, 4096); bulk_g2s(ub, pu, 4096, sb + 8 * B_U); }
          if (ITW == 5) STAMPIF(lane == 0, 110 + ch);
          mbar_wait(sb + 8 * B_U, ph);
          ph ^= 1;
          uint32_t t = 1;
#pragma unroll
          for (int j = 0; j < 8; j++) t &= lds32(ub + 16 * lane + 512 * j + 12);
          if (__all_sync(0xffffffffu, t)) break;
          if (i > (1 << 20)) __trap();
        }
        if (ITW == 5) STAMPIF(lane == 0, 105 + ch);
        if (ch > 1) mbar_wait(sb + 8 * (B_Z + ch - 2), 0);
        bar_arrive(1 + (ch & 1), 288);
#pragma unroll
        for (int j = 0; j < 8; j++) stg128(pu + lane + 32 * j, make_uint4(0, 0, 0, 0));
      }
      if (ITW == 8) { mbar_wait(sb + 8 * B_X, 0); STAMPIF(lane == 0, 100); mbar_wait(sb + 8 * (B_X + 1), 0); STAMPIF(lane == 0, 101); }
      mbar_wait(sb + 8 * B_BD, 0);
      const uint32_t e1 = epoch(sb), ao = 256 * (lane & 16) + 32 * (lane & 15) + 4 * (lane & 4) + (lane & 8) + 4;
      int it = 0;
      uint32_t pm = (1 << NS) - 1;
      bool ok = false;
      if (NS) {
        if (lane < NS) mbar_expect(sb + 8 * (B_A + lane), 8192);
        mbar_wait(sb + 8 * (lane < NS ? B_E1 + lane : B_EW + 5), 0);
        __syncwarp();
        spin(clk(), AT1);
        spin(t_0, AT0);
        if (elect()) {
#pragma unroll
          for (int i = 0; i < NS; i++) bulk_g2s(ring + i * 32768, G->AT + (20 * m + i) * 4096, 8192, sb + 8 * (B_A + i));
        }
        __syncwarp();
        STAMPIF(lane == 0, 84);
#pragma unroll 1
        for (; it < NS; it++) {
          if (!ok) mbar_wait(sb + 8 * (B_A + it), 0);
          uint32_t t = 0, v[8];
          if (PC) ok = mbar_test(sb + 8 * (B_A + it + 1), 0);
#pragma unroll
          for (int j = 0; j < 8; j++) v[j] = ldv32(ring + it * 32768 + ao + 512 * j);
#pragma unroll
          for (int j = 0; j < 8; j++) t |= v[7 - j] ^ e1;
          if (__any_sync(0xffffffffu, t & 1)) {
            ok = false;
            fence_async_s();
            mbar_wait(sb + 8 * (lane > it && lane < NS ? B_A + lane : B_FS), 0);
            __syncwarp();
            if (lane >= it && lane < NS) mbar_expect(sb + 8 * (B_A + lane), 8192);
            __syncwarp();
            if (elect()) {
#pragma unroll
              for (int i = 0; i < NS; i++)
                if (i >= it) bulk_g2s(ring + i * 32768, G->AT + (20 * m + i) * 4096, 8192, sb + 8 * (B_A + i));
            }
            __syncwarp();
            STAMPIF(lane == 0, 85);
            break;
          }
          if (lane == 0) mbar_arrive(sb + 8 * (B_F1 + it));
        }
      }
#pragma unroll 1
      for (int st = it; it < 20; it++) {
        const uint32_t a = ring + st * 32768 + ao;
        if (!ok) mbar_wait(sb + 8 * (B_A + st), (pm >> st) & 1);
        pm ^= 1 << st;
        const int nx = st == 4 ? 0 : st + 1;
        if (ITW == 7) STAMPIF(lane == 0 && it < 4, 100 + it);
        if (ITW == 8) STAMPIF(lane == 0 && it < 2, 114 + it);
        uint32_t t = 0, v[8];
        if (PC) ok = mbar_test(sb + 8 * (B_A + nx), (pm >> nx) & 1);
#pragma unroll
        for (int j = 0; j < 8; j++) v[j] = ldv32(a + 512 * j);
#pragma unroll
        for (int j = 0; j < 8; j++) t |= v[7 - j] ^ e1;
        if (__any_sync(0xffffffffu, t & 1)) {
#pragma unroll 1
          for (int j = 0; j < 8; j++) a_check(a + 512 * j, (const char*)G->AT + (20 * m + it) * 8192 + ao + 512 * j, e1);
        }
        if (lane == 0) mbar_arrive(sb + 8 * (B_F1 + st));
        if (ITW == 7) STAMPIF(lane == 0 && it < 4, 104 + it);
        if (ITW == 8) STAMPIF(lane == 0 && it < 2, 116 + it);
        st = nx;
      }
    } else {
      mbar_wait(sb + 8 * B_KVS, 0);
      auto rel = [&](int ch) { mbar_wait(sb + 8 * (B_Z + ch), 0); if (lane <= (ch >> 2)) mbar_arrive(sb + 8 * (B_E1 + 2 + (ch >> 1))); };
      if (RL) { rel(0); rel(1); rel(2); }
      mbar_wait(sb + 8 * (B_BD + 1), 0);
      if (!BI && b >= 96 && elect()) { load_box(P, sb, b, 4); load_box(P, sb, b, 5); }
      const uint32_t t1 = clk();
      if (RL) { rel(3); rel(4); }
      spin(t1, CD);
      __syncwarp();
      const uint32_t e1 = epoch(sb);
#pragma unroll 1
      for (int n = 0; n < 5; n++) {
        int lane;
        asm volatile("mov.u32 %0, %%laneid;" : "=r"(lane));
        if (n == 3) {
          fence_async_s();
          __syncwarp();
          if (lane == 0) mbar_arrive(sb + 8 * B_F);
          STAMPIF(lane == 0, 34);
          {
            mbar_wait(sb + 8 * (B_EW + 4), 0);
            const char* po = (char*)gout + (2 * tbase(b) + 64 * (lane & 28) + ((lane >> 1) & 1)) * 2 * D_ + (lane & 1) * 640;
            uint32_t v = 0;
#pragma unroll
            for (int r = 0; r < 5; r++) v ^= rdback(po + 128 * r);
            rdwait(sb, v);
            __syncwarp();
            if (lane == 0) flag_add(G, 8 * m + FL_X);
            STAMPIF(lane == 0, 94);
          }
          mbar_wait(sb + 8 * (B_BD + 2), 0);
          if (lane < 2) mbar_arrive(sb + 8 * (B_E1 + 5));
          if (m < 12) {
            rdwait(sb, rdback(G->cimg + s * 3072 + (m % 6) * 512 + (m < 6 ? 0 : 256) + 64 * (lane & 3)));
            __syncwarp();
            if (lane == 0) flag_add(G, FL_C + 8 * s);
            STAMPIF(lane == 0, 35);
          }
          if (elect()) {
            flag_wait(G, FL_C + 8 * s, e1 * 12);
            fence_async_g();
            STAMP(54);
            mbar_expect(sb + 8 * B_EXT, 6144);
            bulk_g2s(sb + SM_EXT, G->cimg + s * 3072, 6144, sb + 8 * B_EXT);
          }
          __syncwarp();
          mbar_wait(sb + 8 * B_ST2, 0);
        }
        const int j = n < 3 ? min(16 * n + (lane >> 1), 39) : min(16 * n - 8 + (lane >> 1), 59), k = j < 20 ? j : j < 40 ? j - 20 : j - 40;
        const uint2* pj = (const uint2*)(G->mv + 2048 * (e1 & 1) + 4 * (lane & 1) + 8 * (k + (j < 40 ? (j < 20 ? 160 : 120) + (m < 6 ? 0 : 20) : 200 + 20 * (s & 1))));
        uint4 a;
#pragma unroll 1
        for (int i = 0;; i++) {
          a = ld_tag2(pj);
          if (__all_sync(0xffffffffu, a.x != 0)) break;
          if (i > (1 << 20)) __trap();
        }
        const uint32_t d = sb + SM_CB + 64 * k + 8 * (lane & 1) + (j >= 20 && j < 40 ? 16 : 0);
        sts64(d, ~__byte_perm(a.x, a.y, 0x5410), ~__byte_perm(a.z, a.w, 0x5410));
        sts64(d + 32, ~__byte_perm(a.x, a.y, 0x7632), ~__byte_perm(a.z, a.w, 0x7632));
      }
      __syncwarp();
      if (lane == 0) mbar_arrive(sb + 8 * B_GB);
      STAMPIF(lane == 0, 39);
    }
    } else {
      STAMPIF(lane == 0, 62);
      int rw = sched_run<0>(P, In{gk, gv, gsk, gWg, gWu, gWd, gss}, sb, b, lane, __shfl_sync(0xffffffffu, t_0, 0));
      if (elect()) {
        STAMP(69);
        mbar_wait(sb + 8 * B_KVS, 0);
        if (ER) mbar_wait(sb + 8 * B_KV4, 0);
        STAMP(70);
        int rd = 0, c = 0;
#pragma unroll 1
        for (int it = 0; it < 20; it++) {
          load_w(P, sb, s, it);
          if ((PWM >> it) & 1) { l2_prefetch(gWg + (128 * rw + b) * F_, 2 * F_); l2_prefetch(gWu + (128 * rw + b) * F_, 2 * F_); rw++; }
          if ((PDM >> it) & 1) { l2_prefetch(gWd + (512 * rd + 4 * b) * D_, 8 * D_); rd++; }
          if (BI && it == BI && b >= 96) { mbar_wait(sb + 8 * (B_BD + 1), 0); load_box(P, sb, b, 4); load_box(P, sb, b, 5); }
          if (((STM >> it) & 1) && b < 96) {
            const int grp = m % 6;
            if (c == 4) mbar_wait(sb + 8 * (B_BD + 1), 0);
            if (c == 0) mbar_expect(sb + 8 * B_ST0, 40960);
#pragma unroll
            for (int j = 0; j < 2; j++, c++)
              tma2d(sb + (c < 2 ? SM_EXT : SM_RING + R_X - 8192) + 4096 * c, &P.mG + (grp & 1), 192 * s + 64 * (grp >> 1), (m < 6 ? 0 : 320) + 32 * c, sb + 8 * B_ST0);
          }
        }
#pragma unroll
        for (int k = 0; k < 10; k++) {
          const int st = (k + 5) % 6, pe = k < 4 ? k >> 1 : k & 1, ps = k < 4 ? k & 1 : k >> 1;
          mbar_wait(sb + 8 * (k < 6 ? B_E1 + st : B_EB + k - 6), 0);
          if (k == 2) mbar_arrive_remote(mapa(sb + 8 * B_P0, (b & 1) ^ 1));
          mbar_expect(sb + 8 * (B_FB + k), 24576);
          tma2d(ring + st * 32768 + 8192, &P.mD, 320 * (s & 1) + 64 * out_blk(s, ps), 192 * (s ^ pe), sb + 8 * (B_FB + k));
        }
      }
    }
  }
}

typedef CUresult (*EncFn)(CUtensorMap*, CUtensorMapDataType, cuuint32_t, void*, const cuuint64_t*, const cuuint64_t*, const cuuint32_t*, const cuuint32_t*,
                          CUtensorMapInterleave, CUtensorMapSwizzle, CUtensorMapL2promotion, CUtensorMapFloatOOBfill);
static void mkmap(EncFn enc, CUtensorMap* m, const void* p, int rank, const cuuint64_t* dims, const cuuint64_t* strides, const cuuint32_t* box, CUtensorMapSwizzle sw) {
  cuuint32_t es[5] = {1, 1, 1, 1, 1};
  CUresult r = enc(m, CU_TENSOR_MAP_DATA_TYPE_BFLOAT16, rank, (void*)p, dims, strides, box, es, CU_TENSOR_MAP_INTERLEAVE_NONE, sw,
                   CU_TENSOR_MAP_L2_PROMOTION_L2_128B, CU_TENSOR_MAP_FLOAT_OOB_FILL_NONE);
  if (r != CUDA_SUCCESS) fprintf(stderr, "tensor map encode failed: %d\n", (int)r);
}

extern "C" void kernel_launch(void* const* d_in, const int* in_sizes, int n_in, void* d_out, int out_size) {
  void* fn = nullptr;
  cudaDriverEntryPointQueryResult qr;
  cudaGetDriverEntryPoint("cuTensorMapEncodeTiled", &fn, cudaEnableDefault, &qr);
  EncFn enc = (EncFn)fn;
  Scr* G;
  cudaGetSymbolAddress((void**)&G, g_scr);
  Params P;
  { cuuint64_t d[] = {128, 16, 640}, st[] = {256, 4096}; cuuint32_t bx[] = {144, 16, 1}; mkmap(enc, &P.mS, d_in[4], 3, d, st, bx, CU_TENSOR_MAP_SWIZZLE_NONE); }
  { cuuint64_t d[] = {3840, 64, 10}, st[] = {7680, 64 * 7680}; cuuint32_t bx[] = {16, 64, 5}; mkmap(enc, &P.mWm, d_in[11], 3, d, st, bx, CU_TENSOR_MAP_SWIZZLE_32B); }
  { cuuint64_t d[] = {32, 20, 256, 8}, st[] = {64, 10240, 1280}; cuuint32_t bx[] = {40, 1, 9, 8}, bx2[] = {40, 1, 8, 8};
    mkmap(enc, &P.mK, d_in[1], 4, d, st, bx, CU_TENSOR_MAP_SWIZZLE_NONE); mkmap(enc, &P.mV, d_in[2], 4, d, st, bx2, CU_TENSOR_MAP_SWIZZLE_NONE); }
  { cuuint64_t d[] = {1536, 640}, st[] = {3072}; cuuint32_t bx[] = {64, 32};
    mkmap(enc, &P.mG, d_in[7], 2, d, st, bx, CU_TENSOR_MAP_SWIZZLE_128B); mkmap(enc, &P.mU, d_in[8], 2, d, st, bx, CU_TENSOR_MAP_SWIZZLE_128B); }
  { cuuint64_t d[] = {640, 1536}, st[] = {1280}; cuuint32_t bx[] = {64, 192}; mkmap(enc, &P.mD, d_in[9], 2, d, st, bx, CU_TENSOR_MAP_SWIZZLE_128B); }
  { cuuint64_t d[] = {64, 2, 8, 10, 128}, st[] = {1280, 256 * 1280, 128, 2560}; cuuint32_t bx[] = {64, 2, 8, 5, 1}; mkmap(enc, &P.mX, d_in[0], 5, d, st, bx, CU_TENSOR_MAP_SWIZZLE_128B); }
  cudaFuncSetAttribute(fused_kernel, cudaFuncAttributeMaxDynamicSharedMemorySize, SM_TOTAL + DEVSM);
  cudaLaunchConfig_t cfg = {};
  cfg.gridDim = dim3(128); cfg.blockDim = dim3(512); cfg.dynamicSmemBytes = SM_TOTAL + DEVSM; cfg.stream = cudaStreamPerThread;
  cudaLaunchAttribute at[1];
  at[0].id = cudaLaunchAttributeClusterDimension; at[0].val.clusterDim.x = 2; at[0].val.clusterDim.y = 1; at[0].val.clusterDim.z = 1;
  cfg.attrs = at; cfg.numAttrs = 1;
  cudaLaunchKernelEx(&cfg, fused_kernel, (const bf16*)d_in[1], (const bf16*)d_in[2], (const bf16*)d_in[3], (const bf16*)d_in[5], (const bf16*)d_in[10], G,
                     (const bf16*)d_in[7], (const bf16*)d_in[8], (const bf16*)d_in[9], (bf16*)d_out, (const bf16*)d_in[4], P);
}
```

```cpp
#include <cuda_runtime.h>
#include <cuda.h>
#include <cuda_bf16.h>
#include <stdio.h>
#include <stdint.h>
typedef __nv_bfloat16 bf16;
__device__ __forceinline__ uint32_t smem_u32(const void* p) { return (uint32_t)__cvta_generic_to_shared(p); }
__device__ __forceinline__ void mbar_init(uint32_t bar, int cnt) { asm volatile("mbarrier.init.shared::cta.b64 [%0], %1;" ::"r"(bar), "r"(cnt) : "memory"); }
__device__ __forceinline__ void mbar_expect(uint32_t bar, int bytes) { asm volatile("mbarrier.arrive.expect_tx.shared::cta.b64 _, [%0], %1;" ::"r"(bar), "r"(bytes) : "memory"); }
__device__ __forceinline__ void mbar_arrive(uint32_t bar) { asm volatile("mbarrier.arrive.shared::cta.b64 _, [%0];" ::"r"(bar) : "memory"); }
__device__ __forceinline__ void mbar_arrive_remote(uint32_t bar) { asm volatile("mbarrier.arrive.relaxed.cluster.shared::cluster.b64 _, [%0];" ::"r"(bar) : "memory"); }
__device__ __forceinline__ uint32_t mapa(uint32_t a, uint32_t cta) { uint32_t r; asm("mapa.shared::cluster.u32 %0, %1, %2;" : "=r"(r) : "r"(a), "r"(cta)); return r; }
__device__ __forceinline__ bool mbar_try(uint32_t bar, int parity) {
  uint32_t ok;
  asm volatile("{\n.reg .pred p;\nmbarrier.try_wait.parity.shared::cta.b64 p, [%1], %2;\nselp.u32 %0, 1, 0, p;\n}" : "=r"(ok) : "r"(bar), "r"(parity) : "memory");
  return ok;
}
__device__ __forceinline__ void mbar_wait(uint32_t bar, int parity) {
#pragma unroll 1
  for (int i = 0; i < (1 << 20); i++) { if (mbar_try(bar, parity)) return; }
  __trap();
}
__device__ __forceinline__ bool elect() {
  uint32_t p;
  asm volatile("{\n.reg .pred P;\nelect.sync _|P, 0xffffffff;\nselp.u32 %0, 1, 0, P;\n}" : "=r"(p));
  return p;
}
__device__ __forceinline__ void tma2d(uint32_t dst, const CUtensorMap* m, int c0, int c1, uint32_t bar) {
  asm volatile("cp.async.bulk.tensor.2d.shared::cluster.global.mbarrier::complete_tx::bytes [%0], [%1, {%3, %4}], [%2];" ::"r"(dst), "l"(m), "r"(bar), "r"(c0), "r"(c1) : "memory");
}
__device__ __forceinline__ void tma3d(uint32_t dst, const CUtensorMap* m, int c0, int c1, int c2, uint32_t bar) {
  asm volatile("cp.async.bulk.tensor.3d.shared::cluster.global.mbarrier::complete_tx::bytes [%0], [%1, {%3, %4, %5}], [%2];" ::"r"(dst), "l"(m), "r"(bar), "r"(c0), "r"(c1), "r"(c2) : "memory");
}
__device__ __forceinline__ void tma4d(uint32_t dst, const CUtensorMap* m, int c0, int c1, int c2, int c3, uint32_t bar) {
  asm volatile("cp.async.bulk.tensor.4d.shared::cluster.global.mbarrier::complete_tx::bytes [%0], [%1, {%3, %4, %5, %6}], [%2];" ::"r"(dst), "l"(m), "r"(bar), "r"(c0), "r"(c1), "r"(c2), "r"(c3) : "memory");
}
__device__ __forceinline__ void tma5d(uint32_t dst, const CUtensorMap* m, int c0, int c1, int c2, int c3, int c4, uint32_t bar) {
  asm volatile("cp.async.bulk.tensor.5d.shared::cluster.global.mbarrier::complete_tx::bytes [%0], [%1, {%3, %4, %5, %6, %7}], [%2];" ::"r"(dst), "l"(m), "r"(bar), "r"(c0), "r"(c1), "r"(c2), "r"(c3), "r"(c4) : "memory");
}
__device__ __forceinline__ void tma_store2d(const CUtensorMap* m, uint32_t src, int c0, int c1) {
  asm volatile("cp.async.bulk.tensor.2d.global.shared::cta.bulk_group [%0, {%2, %3}], [%1];" ::"l"(m), "r"(src), "r"(c0), "r"(c1) : "memory");
}
__device__ __forceinline__ void tma_store4d(const CUtensorMap* m, uint32_t src, int c0, int c1, int c2, int c3) {
  asm volatile("cp.async.bulk.tensor.4d.global.shared::cta.bulk_group [%0, {%2, %3, %4, %5}], [%1];" ::"l"(m), "r"(src), "r"(c0), "r"(c1), "r"(c2), "r"(c3) : "memory");
}
__device__ __forceinline__ void tma_prefetch2d(const CUtensorMap* m, int c0, int c1) {
  asm volatile("cp.async.bulk.prefetch.tensor.2d.L2.global [%0, {%1, %2}];" ::"l"(m), "r"(c0), "r"(c1) : "memory");
}
__device__ __forceinline__ void bulk_g2s(uint32_t dst, const void* src, int bytes, uint32_t bar) {
  asm volatile("cp.async.bulk.shared::cluster.global.mbarrier::complete_tx::bytes [%0], [%1], %2, [%3];" ::"r"(dst), "l"(src), "r"(bytes), "r"(bar) : "memory");
}
__device__ __forceinline__ void bulk_s2g(void* dst, uint32_t src, int bytes) {
  asm volatile("cp.async.bulk.global.shared::cta.bulk_group [%0], [%1], %2;" ::"l"(dst), "r"(src), "r"(bytes) : "memory");
}
__device__ __forceinline__ void cp16(uint32_t dst, const void* src) { asm volatile("cp.async.cg.shared.global [%0], [%1], 16;" ::"r"(dst), "l"(src) : "memory"); }
__device__ __forceinline__ void cp16z(uint32_t dst, const void* src, int n) { asm volatile("cp.async.cg.shared.global [%0], [%1], 16, %2;" ::"r"(dst), "l"(src), "r"(n) : "memory"); }
__device__ __forceinline__ void cp_arrive(uint32_t bar) { asm volatile("cp.async.mbarrier.arrive.noinc.shared::cta.b64 [%0];" ::"r"(bar) : "memory"); }
__device__ __forceinline__ void st_async4(uint32_t dst, const uint32_t* v, uint32_t bar) {
  asm volatile("st.async.weak.shared::cluster.mbarrier::complete_tx::bytes.v4.b32 [%0], {%1, %2, %3, %4}, [%5];" ::"r"(dst), "r"(v[0]), "r"(v[1]), "r"(v[2]), "r"(v[3]), "r"(bar) : "memory");
}
__device__ __forceinline__ void wg_fence() { asm volatile("wgmma.fence.sync.aligned;" ::: "memory"); }
__device__ __forceinline__ void wg_commit() { asm volatile("wgmma.commit_group.sync.aligned;" ::: "memory"); }
template <int N> __device__ __forceinline__ void wg_wait() { asm volatile("wgmma.wait_group.sync.aligned %0;" ::"n"(N) : "memory"); }
__device__ __forceinline__ uint64_t mkdesc(uint32_t addr, uint32_t lbo, uint32_t sbo, uint32_t swz) {
  return (uint64_t)((addr & 0x3FFFF) >> 4) | ((uint64_t)(lbo >> 4) << 16) | ((uint64_t)(sbo >> 4) << 32) | ((uint64_t)swz << 62);
}
__device__ __forceinline__ void ldsm4t(uint32_t* r, uint32_t a) {
  asm volatile("ldmatrix.sync.aligned.m8n8.x4.trans.shared.b16 {%0,%1,%2,%3}, [%4];" : "=r"(r[0]), "=r"(r[1]), "=r"(r[2]), "=r"(r[3]) : "r"(a) : "memory");
}
__device__ __forceinline__ void stsm4(uint32_t a, const uint32_t* r) {
  asm volatile("stmatrix.sync.aligned.m8n8.x4.shared.b16 [%0], {%1,%2,%3,%4};" ::"r"(a), "r"(r[0]), "r"(r[1]), "r"(r[2]), "r"(r[3]) : "memory");
}
__device__ __forceinline__ void stsm4t(uint32_t a, const uint32_t* r) {
  asm volatile("stmatrix.sync.aligned.m8n8.x4.trans.shared.b16 [%0], {%1,%2,%3,%4};" ::"r"(a), "r"(r[0]), "r"(r[1]), "r"(r[2]), "r"(r[3]) : "memory");
}
__device__ __forceinline__ void bar_sync(int id, int n) { asm volatile("bar.sync %0, %1;" ::"r"(id), "r"(n) : "memory"); }
__device__ __forceinline__ void bar_arrive(int id, int n) { asm volatile("bar.arrive %0, %1;" ::"r"(id), "r"(n) : "memory"); }
__device__ __forceinline__ uint32_t lds32(uint32_t a) { uint32_t v; asm volatile("ld.shared.b32 %0, [%1];" : "=r"(v) : "r"(a) : "memory"); return v; }
__device__ __forceinline__ uint2 lds64(uint32_t a) { uint2 v; asm volatile("ld.shared.v2.b32 {%0,%1}, [%2];" : "=r"(v.x), "=r"(v.y) : "r"(a) : "memory"); return v; }
__device__ __forceinline__ uint4 lds128(uint32_t a) { uint4 v; asm volatile("ld.shared.v4.b32 {%0,%1,%2,%3}, [%4];" : "=r"(v.x), "=r"(v.y), "=r"(v.z), "=r"(v.w) : "r"(a) : "memory"); return v; }
__device__ __forceinline__ void sts16(uint32_t a, uint32_t v) { asm volatile("st.shared.b16 [%0], %1;" ::"r"(a), "h"((uint16_t)v) : "memory"); }
__device__ __forceinline__ void sts32(uint32_t a, uint32_t v) { asm volatile("st.shared.b32 [%0], %1;" ::"r"(a), "r"(v) : "memory"); }
__device__ __forceinline__ void sts64(uint32_t a, uint32_t x, uint32_t y) { asm volatile("st.shared.v2.b32 [%0], {%1,%2};" ::"r"(a), "r"(x), "r"(y) : "memory"); }
__device__ __forceinline__ void sts128(uint32_t a, uint4 v) { asm volatile("st.shared.v4.b32 [%0], {%1,%2,%3,%4};" ::"r"(a), "r"(v.x), "r"(v.y), "r"(v.z), "r"(v.w) : "memory"); }
template<int TB> __device__ __forceinline__ void wgmma_rs_n128(float* d, const uint32_t* a, uint64_t db, int sd) {
  asm volatile("{\n.reg .pred p;\nsetp.ne.b32 p, %69, 0;\n"
    "wgmma.mma_async.sync.aligned.m64n128k16.f32.bf16.bf16 {%0, %1, %2, %3, %4, %5, %6, %7, %8, %9, %10, %11, %12, %13, %14, %15, %16, %17, %18, %19, %20, %21, %22, %23, %24, %25, %26, %27, %28, %29, %30, %31, %32, %33, %34, %35, %36, %37, %38, %39, %40, %41, %42, %43, %44, %45, %46, %47, %48, %49, %50, %51, %52, %53, %54, %55, %56, %57, %58, %59, %60, %61, %62, %63}, {%64, %65, %66, %67}, %68, p, 1, 1, %70;\n}"
    : "+f"(d[0]), "+f"(d[1]), "+f"(d[2]), "+f"(d[3]), "+f"(d[4]), "+f"(d[5]), "+f"(d[6]), "+f"(d[7]), "+f"(d[8]), "+f"(d[9]), "+f"(d[10]), "+f"(d[11]), "+f"(d[12]), "+f"(d[13]), "+f"(d[14]), "+f"(d[15]), "+f"(d[16]), "+f"(d[17]), "+f"(d[18]), "+f"(d[19]), "+f"(d[20]), "+f"(d[21]), "+f"(d[22]), "+f"(d[23]), "+f"(d[24]), "+f"(d[25]), "+f"(d[26]), "+f"(d[27]), "+f"(d[28]), "+f"(d[29]), "+f"(d[30]), "+f"(d[31]), "+f"(d[32]), "+f"(d[33]), "+f"(d[34]), "+f"(d[35]), "+f"(d[36]), "+f"(d[37]), "+f"(d[38]), "+f"(d[39]), "+f"(d[40]), "+f"(d[41]), "+f"(d[42]), "+f"(d[43]), "+f"(d[44]), "+f"(d[45]), "+f"(d[46]), "+f"(d[47]), "+f"(d[48]), "+f"(d[49]), "+f"(d[50]), "+f"(d[51]), "+f"(d[52]), "+f"(d[53]), "+f"(d[54]), "+f"(d[55]), "+f"(d[56]), "+f"(d[57]), "+f"(d[58]), "+f"(d[59]), "+f"(d[60]), "+f"(d[61]), "+f"(d[62]), "+f"(d[63])
    : "r"(a[0]), "r"(a[1]), "r"(a[2]), "r"(a[3]), "l"(db), "r"(sd), "n"(TB));
}

template<int TB> __device__ __forceinline__ void wgmma_rs_n160(float* d, const uint32_t* a, uint64_t db, int sd) {
  asm volatile("{\n.reg .pred p;\nsetp.ne.b32 p, %85, 0;\n"
    "wgmma.mma_async.sync.aligned.m64n160k16.f32.bf16.bf16 {%0, %1, %2, %3, %4, %5, %6, %7, %8, %9, %10, %11, %12, %13, %14, %15, %16, %17, %18, %19, %20, %21, %22, %23, %24, %25, %26, %27, %28, %29, %30, %31, %32, %33, %34, %35, %36, %37, %38, %39, %40, %41, %42, %43, %44, %45, %46, %47, %48, %49, %50, %51, %52, %53, %54, %55, %56, %57, %58, %59, %60, %61, %62, %63, %64, %65, %66, %67, %68, %69, %70, %71, %72, %73, %74, %75, %76, %77, %78, %79}, {%80, %81, %82, %83}, %84, p, 1, 1, %86;\n}"
    : "+f"(d[0]), "+f"(d[1]), "+f"(d[2]), "+f"(d[3]), "+f"(d[4]), "+f"(d[5]), "+f"(d[6]), "+f"(d[7]), "+f"(d[8]), "+f"(d[9]), "+f"(d[10]), "+f"(d[11]), "+f"(d[12]), "+f"(d[13]), "+f"(d[14]), "+f"(d[15]), "+f"(d[16]), "+f"(d[17]), "+f"(d[18]), "+f"(d[19]), "+f"(d[20]), "+f"(d[21]), "+f"(d[22]), "+f"(d[23]), "+f"(d[24]), "+f"(d[25]), "+f"(d[26]), "+f"(d[27]), "+f"(d[28]), "+f"(d[29]), "+f"(d[30]), "+f"(d[31]), "+f"(d[32]), "+f"(d[33]), "+f"(d[34]), "+f"(d[35]), "+f"(d[36]), "+f"(d[37]), "+f"(d[38]), "+f"(d[39]), "+f"(d[40]), "+f"(d[41]), "+f"(d[42]), "+f"(d[43]), "+f"(d[44]), "+f"(d[45]), "+f"(d[46]), "+f"(d[47]), "+f"(d[48]), "+f"(d[49]), "+f"(d[50]), "+f"(d[51]), "+f"(d[52]), "+f"(d[53]), "+f"(d[54]), "+f"(d[55]), "+f"(d[56]), "+f"(d[57]), "+f"(d[58]), "+f"(d[59]), "+f"(d[60]), "+f"(d[61]), "+f"(d[62]), "+f"(d[63]), "+f"(d[64]), "+f"(d[65]), "+f"(d[66]), "+f"(d[67]), "+f"(d[68]), "+f"(d[69]), "+f"(d[70]), "+f"(d[71]), "+f"(d[72]), "+f"(d[73]), "+f"(d[74]), "+f"(d[75]), "+f"(d[76]), "+f"(d[77]), "+f"(d[78]), "+f"(d[79])
    : "r"(a[0]), "r"(a[1]), "r"(a[2]), "r"(a[3]), "l"(db), "r"(sd), "n"(TB));
}

template<int TB> __device__ __forceinline__ void wgmma_rs_n192(float* d, const uint32_t* a, uint64_t db, int sd) {
  asm volatile("{\n.reg .pred p;\nsetp.ne.b32 p, %101, 0;\n"
    "wgmma.mma_async.sync.aligned.m64n192k16.f32.bf16.bf16 {%0, %1, %2, %3, %4, %5, %6, %7, %8, %9, %10, %11, %12, %13, %14, %15, %16, %17, %18, %19, %20, %21, %22, %23, %24, %25, %26, %27, %28, %29, %30, %31, %32, %33, %34, %35, %36, %37, %38, %39, %40, %41, %42, %43, %44, %45, %46, %47, %48, %49, %50, %51, %52, %53, %54, %55, %56, %57, %58, %59, %60, %61, %62, %63, %64, %65, %66, %67, %68, %69, %70, %71, %72, %73, %74, %75, %76, %77, %78, %79, %80, %81, %82, %83, %84, %85, %86, %87, %88, %89, %90, %91, %92, %93, %94, %95}, {%96, %97, %98, %99}, %100, p, 1, 1, %102;\n}"
    : "+f"(d[0]), "+f"(d[1]), "+f"(d[2]), "+f"(d[3]), "+f"(d[4]), "+f"(d[5]), "+f"(d[6]), "+f"(d[7]), "+f"(d[8]), "+f"(d[9]), "+f"(d[10]), "+f"(d[11]), "+f"(d[12]), "+f"(d[13]), "+f"(d[14]), "+f"(d[15]), "+f"(d[16]), "+f"(d[17]), "+f"(d[18]), "+f"(d[19]), "+f"(d[20]), "+f"(d[21]), "+f"(d[22]), "+f"(d[23]), "+f"(d[24]), "+f"(d[25]), "+f"(d[26]), "+f"(d[27]), "+f"(d[28]), "+f"(d[29]), "+f"(d[30]), "+f"(d[31]), "+f"(d[32]), "+f"(d[33]), "+f"(d[34]), "+f"(d[35]), "+f"(d[36]), "+f"(d[37]), "+f"(d[38]), "+f"(d[39]), "+f"(d[40]), "+f"(d[41]), "+f"(d[42]), "+f"(d[43]), "+f"(d[44]), "+f"(d[45]), "+f"(d[46]), "+f"(d[47]), "+f"(d[48]), "+f"(d[49]), "+f"(d[50]), "+f"(d[51]), "+f"(d[52]), "+f"(d[53]), "+f"(d[54]), "+f"(d[55]), "+f"(d[56]), "+f"(d[57]), "+f"(d[58]), "+f"(d[59]), "+f"(d[60]), "+f"(d[61]), "+f"(d[62]), "+f"(d[63]), "+f"(d[64]), "+f"(d[65]), "+f"(d[66]), "+f"(d[67]), "+f"(d[68]), "+f"(d[69]), "+f"(d[70]), "+f"(d[71]), "+f"(d[72]), "+f"(d[73]), "+f"(d[74]), "+f"(d[75]), "+f"(d[76]), "+f"(d[77]), "+f"(d[78]), "+f"(d[79]), "+f"(d[80]), "+f"(d[81]), "+f"(d[82]), "+f"(d[83]), "+f"(d[84]), "+f"(d[85]), "+f"(d[86]), "+f"(d[87]), "+f"(d[88]), "+f"(d[89]), "+f"(d[90]), "+f"(d[91]), "+f"(d[92]), "+f"(d[93]), "+f"(d[94]), "+f"(d[95])
    : "r"(a[0]), "r"(a[1]), "r"(a[2]), "r"(a[3]), "l"(db), "r"(sd), "n"(TB));
}

template<int TB> __device__ __forceinline__ void wgmma_rs_n32(float* d, const uint32_t* a, uint64_t db, int sd) {
  asm volatile("{\n.reg .pred p;\nsetp.ne.b32 p, %21, 0;\n"
    "wgmma.mma_async.sync.aligned.m64n32k16.f32.bf16.bf16 {%0, %1, %2, %3, %4, %5, %6, %7, %8, %9, %10, %11, %12, %13, %14, %15}, {%16, %17, %18, %19}, %20, p, 1, 1, %22;\n}"
    : "+f"(d[0]), "+f"(d[1]), "+f"(d[2]), "+f"(d[3]), "+f"(d[4]), "+f"(d[5]), "+f"(d[6]), "+f"(d[7]), "+f"(d[8]), "+f"(d[9]), "+f"(d[10]), "+f"(d[11]), "+f"(d[12]), "+f"(d[13]), "+f"(d[14]), "+f"(d[15])
    : "r"(a[0]), "r"(a[1]), "r"(a[2]), "r"(a[3]), "l"(db), "r"(sd), "n"(TB));
}

template<int TB> __device__ __forceinline__ void wgmma_rs_n64(float* d, const uint32_t* a, uint64_t db, int sd) {
  asm volatile("{\n.reg .pred p;\nsetp.ne.b32 p, %37, 0;\n"
    "wgmma.mma_async.sync.aligned.m64n64k16.f32.bf16.bf16 {%0, %1, %2, %3, %4, %5, %6, %7, %8, %9, %10, %11, %12, %13, %14, %15, %16, %17, %18, %19, %20, %21, %22, %23, %24, %25, %26, %27, %28, %29, %30, %31}, {%32, %33, %34, %35}, %36, p, 1, 1, %38;\n}"
    : "+f"(d[0]), "+f"(d[1]), "+f"(d[2]), "+f"(d[3]), "+f"(d[4]), "+f"(d[5]), "+f"(d[6]), "+f"(d[7]), "+f"(d[8]), "+f"(d[9]), "+f"(d[10]), "+f"(d[11]), "+f"(d[12]), "+f"(d[13]), "+f"(d[14]), "+f"(d[15]), "+f"(d[16]), "+f"(d[17]), "+f"(d[18]), "+f"(d[19]), "+f"(d[20]), "+f"(d[21]), "+f"(d[22]), "+f"(d[23]), "+f"(d[24]), "+f"(d[25]), "+f"(d[26]), "+f"(d[27]), "+f"(d[28]), "+f"(d[29]), "+f"(d[30]), "+f"(d[31])
    : "r"(a[0]), "r"(a[1]), "r"(a[2]), "r"(a[3]), "l"(db), "r"(sd), "n"(TB));
}

template<int TB> __device__ __forceinline__ void wgmma_rs_n96(float* d, const uint32_t* a, uint64_t db, int sd) {
  asm volatile("{\n.reg .pred p;\nsetp.ne.b32 p, %53, 0;\n"
    "wgmma.mma_async.sync.aligned.m64n96k16.f32.bf16.bf16 {%0, %1, %2, %3, %4, %5, %6, %7, %8, %9, %10, %11, %12, %13, %14, %15, %16, %17, %18, %19, %20, %21, %22, %23, %24, %25, %26, %27, %28, %29, %30, %31, %32, %33, %34, %35, %36, %37, %38, %39, %40, %41, %42, %43, %44, %45, %46, %47}, {%48, %49, %50, %51}, %52, p, 1, 1, %54;\n}"
    : "+f"(d[0]), "+f"(d[1]), "+f"(d[2]), "+f"(d[3]), "+f"(d[4]), "+f"(d[5]), "+f"(d[6]), "+f"(d[7]), "+f"(d[8]), "+f"(d[9]), "+f"(d[10]), "+f"(d[11]), "+f"(d[12]), "+f"(d[13]), "+f"(d[14]), "+f"(d[15]), "+f"(d[16]), "+f"(d[17]), "+f"(d[18]), "+f"(d[19]), "+f"(d[20]), "+f"(d[21]), "+f"(d[22]), "+f"(d[23]), "+f"(d[24]), "+f"(d[25]), "+f"(d[26]), "+f"(d[27]), "+f"(d[28]), "+f"(d[29]), "+f"(d[30]), "+f"(d[31]), "+f"(d[32]), "+f"(d[33]), "+f"(d[34]), "+f"(d[35]), "+f"(d[36]), "+f"(d[37]), "+f"(d[38]), "+f"(d[39]), "+f"(d[40]), "+f"(d[41]), "+f"(d[42]), "+f"(d[43]), "+f"(d[44]), "+f"(d[45]), "+f"(d[46]), "+f"(d[47])
    : "r"(a[0]), "r"(a[1]), "r"(a[2]), "r"(a[3]), "l"(db), "r"(sd), "n"(TB));
}

template<int TA, int TB> __device__ __forceinline__ void wgmma_ss_n192(float* d, uint64_t da, uint64_t db, int sd) {
  asm volatile("{\n.reg .pred p;\nsetp.ne.b32 p, %98, 0;\n"
    "wgmma.mma_async.sync.aligned.m64n192k16.f32.bf16.bf16 {%0, %1, %2, %3, %4, %5, %6, %7, %8, %9, %10, %11, %12, %13, %14, %15, %16, %17, %18, %19, %20, %21, %22, %23, %24, %25, %26, %27, %28, %29, %30, %31, %32, %33, %34, %35, %36, %37, %38, %39, %40, %41, %42, %43, %44, %45, %46, %47, %48, %49, %50, %51, %52, %53, %54, %55, %56, %57, %58, %59, %60, %61, %62, %63, %64, %65, %66, %67, %68, %69, %70, %71, %72, %73, %74, %75, %76, %77, %78, %79, %80, %81, %82, %83, %84, %85, %86, %87, %88, %89, %90, %91, %92, %93, %94, %95}, %96, %97, p, 1, 1, %99, %100;\n}"
    : "+f"(d[0]), "+f"(d[1]), "+f"(d[2]), "+f"(d[3]), "+f"(d[4]), "+f"(d[5]), "+f"(d[6]), "+f"(d[7]), "+f"(d[8]), "+f"(d[9]), "+f"(d[10]), "+f"(d[11]), "+f"(d[12]), "+f"(d[13]), "+f"(d[14]), "+f"(d[15]), "+f"(d[16]), "+f"(d[17]), "+f"(d[18]), "+f"(d[19]), "+f"(d[20]), "+f"(d[21]), "+f"(d[22]), "+f"(d[23]), "+f"(d[24]), "+f"(d[25]), "+f"(d[26]), "+f"(d[27]), "+f"(d[28]), "+f"(d[29]), "+f"(d[30]), "+f"(d[31]), "+f"(d[32]), "+f"(d[33]), "+f"(d[34]), "+f"(d[35]), "+f"(d[36]), "+f"(d[37]), "+f"(d[38]), "+f"(d[39]), "+f"(d[40]), "+f"(d[41]), "+f"(d[42]), "+f"(d[43]), "+f"(d[44]), "+f"(d[45]), "+f"(d[46]), "+f"(d[47]), "+f"(d[48]), "+f"(d[49]), "+f"(d[50]), "+f"(d[51]), "+f"(d[52]), "+f"(d[53]), "+f"(d[54]), "+f"(d[55]), "+f"(d[56]), "+f"(d[57]), "+f"(d[58]), "+f"(d[59]), "+f"(d[60]), "+f"(d[61]), "+f"(d[62]), "+f"(d[63]), "+f"(d[64]), "+f"(d[65]), "+f"(d[66]), "+f"(d[67]), "+f"(d[68]), "+f"(d[69]), "+f"(d[70]), "+f"(d[71]), "+f"(d[72]), "+f"(d[73]), "+f"(d[74]), "+f"(d[75]), "+f"(d[76]), "+f"(d[77]), "+f"(d[78]), "+f"(d[79]), "+f"(d[80]), "+f"(d[81]), "+f"(d[82]), "+f"(d[83]), "+f"(d[84]), "+f"(d[85]), "+f"(d[86]), "+f"(d[87]), "+f"(d[88]), "+f"(d[89]), "+f"(d[90]), "+f"(d[91]), "+f"(d[92]), "+f"(d[93]), "+f"(d[94]), "+f"(d[95])
    : "l"(da), "l"(db), "r"(sd), "n"(TA), "n"(TB));
}

template<int TA, int TB> __device__ __forceinline__ void wgmma_ss_n8(float* d, uint64_t da, uint64_t db, int sd) {
  asm volatile("{\n.reg .pred p;\nsetp.ne.b32 p, %6, 0;\n"
    "wgmma.mma_async.sync.aligned.m64n8k16.f32.bf16.bf16 {%0, %1, %2, %3}, %4, %5, p, 1, 1, %7, %8;\n}"
    : "+f"(d[0]), "+f"(d[1]), "+f"(d[2]), "+f"(d[3])
    : "l"(da), "l"(db), "r"(sd), "n"(TA), "n"(TB));
}

constexpr int S_ = 2048, D_ = 640, F_ = 1536;

struct Scr {
  uint32_t flag[32 * 8];
  uint32_t mv[2 * 2048];
  bf16 cimg[8 * 6 * 512];
  uint2 st2[S_];
  bf16 kvT[D_ * S_];
  bf16 zT[D_ * S_];
  bf16 AT[D_ * S_];
};
__device__ __align__(1024) Scr g_scr;
__device__ __forceinline__ uint32_t clk() { uint32_t c; asm volatile("mov.u32 %0, %%clock;" : "=r"(c) :: "memory"); return c; }
#define DEVSM 0
#define STAMP(id)
#define STAMPIF(c, id)
#define ITW 0
#define P3 0
constexpr int FL_X = 5, FL_C = 128;
#define CD 600
#define SD 1000

constexpr int SM_X = 1024, SM_EXT = 21504, SM_SMALL = 29696, SM_STAT = 30720, SM_CB = 32768, SM_RING = 34816, SM_TOTAL = SM_RING + 6 * 32768;
constexpr int SMALL_LN = 224, SMALL_RED = 320, SMALL_DUMMY = 1008, SMALL_E = 1012, SMALL_TS = 160, SMALL_H = 864;
constexpr int JOB_SZ = 10880, JOB_V = 5760, R_X = 5 * 32768, R_BOX = R_X + 12288;
constexpr int K1OFF = 4672, KSZ = 9472, CSZ = KSZ + 4224;
enum { B_KJ = 0, B_X = 5, B_EXT = 7, B_X1 = 8, B_P0 = 9, B_FB = 10, B_PEER = 20, B_RECV = 24, B_U = 28, B_A = 30, B_E0 = 35, B_FS = 37, B_BOX = 38, B_F = 44, B_ST0 = 45, B_GB = 46,
       B_F1 = 48, B_E1 = 54, B_EB = 60,
       B_OS = 64, B_OF = 72, B_Z = 80, B_K = 85, B_EW = 88, B_ST2 = 94, B_XF = 95, B_KV4 = 96, B_KVS = 98, B_BD = 99,
       B_B = 106, B_S = 112 };
__device__ __forceinline__ uint32_t chan_base(uint32_t sb, int ch) { return sb + SM_RING + (2 + (ch >> 1)) * 32768 + (ch & 1) * CSZ; }

struct Params { CUtensorMap mS, mX, mWm, mK, mV, mG, mU, mD; };

__device__ __forceinline__ void flag_add(Scr* G, int id) { asm volatile("red.relaxed.gpu.global.add.u32 [%0], 1;" ::"l"(G->flag + id) : "memory"); }
__device__ __forceinline__ uint32_t rdback(const void* p) { uint32_t v; asm volatile("ld.relaxed.gpu.global.u32 %0, [%1];" : "=r"(v) : "l"(p) : "memory"); return v; }
__device__ __forceinline__ void st_tag(uint2* p, uint32_t v, uint32_t t) { asm volatile("st.relaxed.gpu.global.v2.u32 [%0], {%1, %2};" ::"l"(p), "r"(v), "r"(t) : "memory"); }
__device__ __forceinline__ void spin(uint32_t t, uint32_t d) { if (d) while (clk() - t < d); }
__device__ __forceinline__ uint2 ld_tag(const uint2* p) { uint2 v; asm volatile("ld.relaxed.gpu.global.v2.u32 {%0, %1}, [%2];" : "=r"(v.x), "=r"(v.y) : "l"(p) : "memory"); return v; }
__device__ __forceinline__ uint4 ld_tag2(const uint2* p) {
  uint4 v;
  asm volatile("ld.relaxed.gpu.global.v4.u32 {%0, %1, %2, %3}, [%4];" : "=r"(v.x), "=r"(v.y), "=r"(v.z), "=r"(v.w) : "l"(p) : "memory");
  return v;
}
__device__ __forceinline__ void stg128(void* p, uint4 v) { asm volatile("st.global.v4.b32 [%0], {%1, %2, %3, %4};" ::"l"(p), "r"(v.x), "r"(v.y), "r"(v.z), "r"(v.w) : "memory"); }
__device__ __forceinline__ uint32_t ldv32(uint32_t a) { uint32_t v; asm volatile("ld.volatile.shared.b32 %0, [%1];" : "=r"(v) : "r"(a) : "memory"); return v; }
__device__ __forceinline__ uint4 ldv128(uint32_t a) { uint4 v; asm volatile("ld.volatile.shared.v4.b32 {%0,%1,%2,%3}, [%4];" : "=r"(v.x), "=r"(v.y), "=r"(v.z), "=r"(v.w) : "r"(a) : "memory"); return v; }
__device__ __forceinline__ bool mbar_test(uint32_t bar, int parity) {
  uint32_t ok;
  asm volatile("{\n.reg .pred P;\nmbarrier.test_wait.parity.shared::cta.b64 P, [%1], %2;\nselp.u32 %0, 1, 0, P;\n}" : "=r"(ok) : "r"(bar), "r"(parity) : "memory");
  return ok;
}
__device__ __forceinline__ uint32_t epoch(uint32_t sb) { return lds32(sb + SM_SMALL + SMALL_E); }
__device__ __forceinline__ void rdwait(uint32_t sb, uint32_t v) { sts32(sb + SM_SMALL + SMALL_DUMMY, v); }
__device__ __forceinline__ void fence_async_s() { asm volatile("fence.proxy.async.shared::cta;" ::: "memory"); }
__device__ __forceinline__ void fence_async_g() { asm volatile("fence.proxy.async.global;" ::: "memory"); }
__device__ __forceinline__ void bulk_done() { asm volatile("cp.async.bulk.commit_group;\n\tcp.async.bulk.wait_group 0;" ::: "memory"); }
__device__ __forceinline__ void flag_wait(Scr* G, int id, uint32_t target) {
  const uint32_t* p = G->flag + id;
#pragma unroll 1
  for (int i = 0; i < (1 << 20); i++) {
    uint32_t v;
    asm volatile("ld.relaxed.gpu.global.u32 %0, [%1];" : "=r"(v) : "l"(p) : "memory");
    if ((int)(v - target) >= 0) return;
  }
  __trap();
}
__device__ __forceinline__ void hint_wait(Scr* G, uint32_t sa, int id, uint32_t target) {
#pragma unroll 1
  for (int i = 0; i < (1 << 20); i++) {
    const uint32_t t = clk();
    cp16(sa + 4 * (id & 4), G->flag + (id & ~3));
    spin(t, P3);
    if ((int)(lds32(sa + 4 * (id & 7)) - target) >= 0) return;
  }
  __trap();
}
__device__ __forceinline__ int tbase(int pb) { return 127 - (32 * (pb >> 6) + 8 * (pb & 8) + 4 * ((2 * (pb & 3) - ((pb >> 2) & 1)) & 7) + ((pb >> 4) & 3)); }
__device__ __forceinline__ uint32_t hmul(uint32_t a, uint32_t b) { uint32_t d; asm("mul.rn.bf16x2 %0, %1, %2;" : "=r"(d) : "r"(a), "r"(b)); return d; }
__device__ __forceinline__ uint32_t hadd(uint32_t a, uint32_t b) { uint32_t d; asm("add.rn.bf16x2 %0, %1, %2;" : "=r"(d) : "r"(a), "r"(b)); return d; }
__device__ __forceinline__ uint32_t hsub(uint32_t a, uint32_t b) { uint32_t d; asm("sub.rn.bf16x2 %0, %1, %2;" : "=r"(d) : "r"(a), "r"(b)); return d; }
__device__ __forceinline__ uint32_t hfma(uint32_t a, uint32_t b, uint32_t c) { uint32_t d; asm("fma.rn.bf16x2 %0, %1, %2, %3;" : "=r"(d) : "r"(a), "r"(b), "r"(c)); return d; }
__device__ __forceinline__ uint32_t pack2(float lo, float hi) { uint32_t d; asm("cvt.rn.bf16x2.f32 %0, %1, %2;" : "=r"(d) : "f"(hi), "f"(lo)); return d; }
__device__ __forceinline__ float blo(uint32_t v) { return __uint_as_float(v << 16); }
__device__ __forceinline__ float bhi(uint32_t v) { return __uint_as_float(v & 0xffff0000u); }
__device__ __forceinline__ uint32_t tagged(uint32_t v, uint32_t e1) { return (v & ~1u) | (e1 & 1); }
__device__ __forceinline__ float rbf(float v) { return blo(pack2(v, 0.f)); }
__device__ __forceinline__ float sdev(float var) { float d; asm("sqrt.approx.ftz.f32 %0, %1;" : "=f"(d) : "f"(rbf(rbf(var) + 1e-5f))); return rbf(d); }
template <int N> __device__ __forceinline__ void bfly(float* v, int mask, bool up) {
#pragma unroll
  for (int i = 0; i < N / 2; i++) {
    float send = up ? v[i] : v[i + N / 2], keep = up ? v[i + N / 2] : v[i];
    v[i] = keep + __shfl_xor_sync(0xffffffffu, send, mask);
  }
}
#define BX3 2
#define XO 0
#define ZA 0
#define XE 0
#define EA 1
#define AD 300
#define XP 0
#define DR 0
#define KVV 0
#define OPQ 4
#define SL 1
#define UT 5
#define UD0 1000
#define EH 2
#define NA 16
#define BS 0
#define UF 1
#define ZS 1
#define LV 5
#define TG 2
#define RL 2
#define OF 1
#define OH 16
#define ES 2
#define SI 1
#define RH 5
#define NS 0
#define AT0 14200
#define AT1 0
#define BI 4
#define PC 1
#define PG 1
#define UD2 3600
#define GT 0x111
#define K3 0
#define FS 31
#define KS 3
#define KW 0
#define RX 0
#define MG 0
__device__ __forceinline__ bool mod_first(int b) { return MG ? (b & 3) != 3 : !(b & 1) || !(b & 6); }
__device__ __forceinline__ int mod_grp(int b, int j) {
  if (MG) {
  const int m = b >> 3, s = b & 7, t = 16 * (j ? min(s, 6) : s - (s >> 2)) + m, v = j ? s : (t * 43) >> 10;
  if (j == 2) return b + 112;
  return v < 4 ? (v == 3 ? 160 : 40 * v) + (j ? 24 + m : t - 24 * v) : t + (t < 104 ? 56 : 96);
  }
  const int m = b >> 3, s = b & 7, t = 16 * s + m, v = j ? (t * 43) >> 10 : s >> 1;
  if (j == 2) return b + 112;
  if (j == 0 && s == 1) return m + (m < 8 ? 152 : 192);
  return v < 4 ? (v == 3 ? 160 : 40 * v) + (j ? 16 + t - 24 * v : m) : t + 24;
}

__device__ __forceinline__ void kv_load(const bf16* gk, const bf16* gv, const bf16* gs, uint32_t sb, int b, int r, int tid) {
  const int row = tid >> 2, col = 128 * r + 32 * (b & 3);
  const uint32_t a = sb + SM_RING + r * JOB_SZ + (row >> 3) * 80 + (tid & 3) * 16, ak = a + (row & 7) * 720, av = a + (row & 7) * 640 + JOB_V;
  const int o = (64 * (b >> 2) + row) * D_ + col + 8 * (tid & 3);
  if (FS & 16) {
    uint32_t oo = 2 * o;
    asm volatile("" : "+r"(oo));
    const char *pk = (const char*)gk + oo, *pv = (const char*)gv + oo;
    cp16(ak + 80, pk);
    cp16(av, pv);
    cp16(ak + 400, pk + 64 * D_);
    cp16(av + 320, pv + 64 * D_);
    if (tid < 12) cp16z(ak + 3600, pk - (b < 4 ? 0 : 6 * D_), b < 4 ? 0 : 16);
    if (KS & 2)
      asm volatile("{\n.reg .pred q;\n.reg .b64 y;\ncvt.u64.u32 y, %2;\nadd.s64 y, y, %1;\nsetp.ge.s32 q, %3, 112;\n@q cp.async.cg.shared.global [%0], [y], 16;\n}"
                   ::"r"(sb + SM_CB + 256 * r + 16 * (tid - 112)), "l"(gs), "r"(8 * col + 16 * (tid & 15)), "r"(tid) : "memory");
    else if (tid >= 112) cp16(sb + SM_CB + 256 * r + 16 * (tid - 112), (const char*)gs + (uint32_t)(8 * col + 16 * (tid - 112)));
    return;
  } else {
    cp16(ak + 80, gk + o);
    cp16(ak + 400, gk + o + 32 * D_);
    cp16(av, gv + o);
    cp16(av + 320, gv + o + 32 * D_);
  }
  if (tid < 12) cp16z(ak + 3600, gk + (b < 4 ? o : o - 3 * D_), b < 4 ? 0 : 16);
  else if (tid >= 112) cp16(sb + SM_CB + 256 * r + 16 * (tid - 112), gs + 4 * col + 8 * (tid - 112));
}
__device__ __forceinline__ void load_kv(const Params& P, const bf16* gs, uint32_t sb, int b, int r) {
  const uint32_t a = sb + SM_RING + r * JOB_SZ, bar = sb + 8 * (B_B + r);
  const int cg = 4 * r + (b & 3);
  mbar_expect(bar, JOB_SZ + 256);
  tma4d(a, &P.mK, 0, cg, 8 * (b >> 2) - 1, 0, bar);
  tma4d(a + JOB_V, &P.mV, 0, cg, 8 * (b >> 2), 0, bar);
  bulk_g2s(sb + SM_CB + 256 * r, gs + 128 * cg, 256, bar);
}
__device__ __forceinline__ uint4* kv_dst(Scr* G, int b, int r, int tid) {
  return (uint4*)(G->kvT + (128 * r + 32 * (b & 3) + 8 * (tid >> 5) + 2 * (tid & 3)) * S_ + 2040 - 64 * (b >> 2)) - ((tid >> 2) & 7);
}
__device__ __forceinline__ void kv_job(Scr* G, uint32_t sb, int b, int r, int tid, uint32_t e1) {
  const int cp = 4 * (tid >> 5) + (tid & 3);
  const uint32_t ka = sb + SM_RING + r * JOB_SZ + ((tid >> 2) & 7) * 80 + cp * 4;
  mbar_wait(sb + 8 * (B_B + r), 0);
  STAMPIF(tid == 0, 56 + r);
  uint32_t kk[11], vv[8], o[8];
  if (KVV) {
#pragma unroll
    for (int i = 0; i < 11; i++) kk[i] = ldv32(ka + 720 * ((i + 5) & 7) + 80 * ((i + 5) >> 3));
#pragma unroll
    for (int i = 0; i < 8; i++) vv[i] = ldv32(ka + JOB_V + 640 * i);
  }
  const uint4 sk = ldv128(sb + SM_CB + 256 * r + 16 * cp);
  const uint32_t s0 = __byte_perm(sk.x, sk.z, 0x5410), s1 = __byte_perm(sk.x, sk.z, 0x7632), s2 = __byte_perm(sk.y, sk.w, 0x5410), s3 = __byte_perm(sk.y, sk.w, 0x7632);
#pragma unroll
  for (int i = 0; i < 11; i++) if (!KVV) kk[i] = lds32(ka + 720 * ((i + 5) & 7) + 80 * ((i + 5) >> 3));
#pragma unroll
  for (int i = 0; i < 8; i++) {
    uint32_t v = KVV ? vv[i] : lds32(ka + JOB_V + 640 * i);
    o[i] = hmul(hfma(kk[i + 3], s0, hfma(kk[i + 2], s1, hfma(kk[i + 1], s2, hmul(kk[i], s3)))), v);
  }
  uint4* dst = kv_dst(G, b, r, tid);
  dst[0] = make_uint4(__byte_perm(o[7], o[6], 0x5410), __byte_perm(o[5], o[4], 0x5410), __byte_perm(o[3], o[2], 0x5410), tagged(__byte_perm(o[1], o[0], 0x5410), e1));
  dst[256] = make_uint4(__byte_perm(o[7], o[6], 0x7632), __byte_perm(o[5], o[4], 0x7632), __byte_perm(o[3], o[2], 0x7632), tagged(__byte_perm(o[1], o[0], 0x7632), e1));
  if (tid == 0) { sts32(sb + SM_SMALL + SMALL_TS + 4 * r, clk()); mbar_arrive(sb + 8 * (B_KJ + r)); }
}
__device__ __forceinline__ void u_wait(uint4& a, uint4& c, const void* p) {
  asm volatile("{\n.reg .pred p;\n.reg .b32 t, n;\nmov.b32 n, 0;\n"
               "L0:\nlop3.b32 t, %3, %7, 1, 0x80;\nsetp.eq.b32 p, t, 0;\nvote.sync.any.pred p, p, 0xffffffff;\n@!p bra.uni L1;\n"
               "ld.relaxed.gpu.global.v4.u32 {%0, %1, %2, %3}, [%8];\nld.relaxed.gpu.global.v4.u32 {%4, %5, %6, %7}, [%8+2048];\n"
               "add.u32 n, n, 1;\nsetp.lt.u32 p, n, 1000000;\n@p bra.uni L0;\ntrap;\nL1:\n}"
               : "+r"(a.x), "+r"(a.y), "+r"(a.z), "+r"(a.w), "+r"(c.x), "+r"(c.y), "+r"(c.z), "+r"(c.w) : "l"(p) : "memory");
}
__device__ __forceinline__ void u_fix(uint4 a, uint4 c, const void* p, uint32_t sa, uint32_t e1) {
  asm volatile("{\n.reg .pred p;\n.reg .b32 t, n;\nmov.b32 n, 0;\n"
               "lop3.b32 t, %3, %7, %10, 0x81;\nand.b32 t, t, 1;\nsetp.eq.b32 p, t, 0;\nvote.sync.any.pred p, p, 0xffffffff;\n@!p bra.uni L2;\n"
               "L0:\nld.relaxed.gpu.global.v4.u32 {%0, %1, %2, %3}, [%8];\nld.relaxed.gpu.global.v4.u32 {%4, %5, %6, %7}, [%8+2048];\n"
               "lop3.b32 t, %3, %7, %10, 0x81;\nand.b32 t, t, 1;\nsetp.eq.b32 p, t, 0;\nvote.sync.any.pred p, p, 0xffffffff;\n@!p bra.uni L1;\n"
               "add.u32 n, n, 1;\nsetp.lt.u32 p, n, 1000000;\n@p bra.uni L0;\ntrap;\n"
               "L1:\nst.shared.v4.b32 [%9], {%0, %1, %2, %3};\nst.shared.v4.b32 [%9+2048], {%4, %5, %6, %7};\nL2:\n}"
               : "+r"(a.x), "+r"(a.y), "+r"(a.z), "+r"(a.w), "+r"(c.x), "+r"(c.y), "+r"(c.z), "+r"(c.w) : "l"(p), "r"(sa), "r"(e1) : "memory");
}
__device__ __forceinline__ void stv128(uint32_t a, uint4 v) { asm volatile("st.volatile.shared.v4.b32 [%0], {%1,%2,%3,%4};" ::"r"(a), "r"(v.x), "r"(v.y), "r"(v.z), "r"(v.w) : "memory"); }
__device__ __forceinline__ uint64_t box_a(uint32_t sb) { return mkdesc(sb + SM_RING + R_BOX, 256, 1024, 3); }
__device__ __forceinline__ uint64_t box_b(uint32_t sb) { return mkdesc(sb + SM_STAT, 64, 128, 0); }
__device__ __forceinline__ void mod_put(Scr* G, uint32_t sb, const float* a, int b, int j, uint32_t e1, int tid) {
  const uint32_t red = sb + SM_STAT + 1536;
  if ((tid & 3) == tid >> 6) sts64(red + 32 * ((tid >> 2) & 7) + 8 * (tid >> 5), __float_as_uint((tid & 32) ? a[1] : a[0]), __float_as_uint((tid & 32) ? a[3] : a[2]));
  bar_sync(j > (BX3 >= 3) ? 4 : 5, 128);
  if (tid < 16) {
    const uint4 u = lds128(red + 32 * (tid & 7)), v = lds128(red + 32 * (tid & 7) + 16);
    asm volatile("" : "+r"(b));
    const int grp = mod_grp(b, j);
    const uint32_t one = (grp >= 40 && grp < 80) || (grp >= 160 && grp < 200) ? 0x3f803f80u : 0u;
    const float lo = __uint_as_float(u.x) + __uint_as_float(u.z) + __uint_as_float(v.x) + __uint_as_float(v.z);
    const float hi = __uint_as_float(u.y) + __uint_as_float(u.w) + __uint_as_float(v.y) + __uint_as_float(v.w);
    asm volatile("st.relaxed.gpu.global.u32 [%0], %1;" ::"l"(G->mv + 8 * grp + 256 * (tid & 8) + (tid & 7)),
                 "r"(((tid >> 3) ^ e1) & 1 ? 0 : ~hadd(pack2(lo, hi), one)) : "memory");
  }
}
__device__ __forceinline__ void mod_box(Scr* G, uint32_t sb, int b, int j, uint32_t e1, int tid) {
  float a[4];
  uint64_t da = box_a(sb), db = box_b(sb);
#pragma unroll
  for (int h = 0; h < 2; h++) {
    mbar_wait(sb + 8 * (B_BOX + 2 * j + h), 0);
    STAMPIF(tid == 0 && j == 0, 71 + h);
    wg_fence();
#pragma unroll
    for (int n = 5 * h; n < 5 * h + 5; n++) wgmma_ss_n8<1, 0>(a, da + 128 * n, db + 8 * n, n != 0);
    wg_commit();
  }
  wg_wait<0>();
#pragma unroll
  for (int i = 0; i < 4; i++) asm volatile("" : "+f"(a[i])::"memory");
  mod_put(G, sb, a, b, j, e1, tid);
}
__device__ __forceinline__ void a_check(uint32_t sa, const void* ga, uint32_t tag) {
  asm volatile("{\n.reg .pred p;\n.reg .b32 t, n, x, y, z;\n.reg .b64 g;\n"
               "ld.shared.b32 t, [%0];\nlop3.b32 t, t, %2, 1, 0x28;\nsetp.ne.b32 p, t, 0;\nvote.sync.any.pred p, p, 0xffffffff;\n@!p bra.uni L1;\nmov.b32 n, 0;\n"
               "L0:\nld.relaxed.gpu.global.b32 t, [%1];\nlop3.b32 t, t, %2, 1, 0x28;\nsetp.ne.b32 p, t, 0;\nvote.sync.any.pred p, p, 0xffffffff;\n@!p bra.uni L2;\n"
               "add.u32 n, n, 1;\nsetp.lt.u32 p, n, 1000000;\n@p bra.uni L0;\ntrap;\nL2:\n"
               "and.b64 g, %1, -32;\nand.b32 n, %0, -32;\n"
               "ld.relaxed.gpu.global.v4.b32 {t, x, y, z}, [g];\nst.shared.v4.b32 [n], {t, x, y, z};\n"
               "ld.relaxed.gpu.global.v4.b32 {t, x, y, z}, [g+16];\nst.shared.v4.b32 [n+16], {t, x, y, z};\n"
               "fence.proxy.async.shared::cta;\nbar.warp.sync 0xffffffff;\nL1:\n}" ::"r"(sa), "l"(ga), "r"(tag) : "memory");
}
__device__ __forceinline__ void z_wait(uint4& a, uint4& c, uint32_t* v, const void* G, uint32_t zo, uint32_t co, uint32_t e1) {
  asm volatile("{\n.reg .pred p;\n.reg .b32 t, n;\n.reg .b64 x, y;\nmov.b32 n, 0;\n"
               "L0:\nlop3.b32 t, %3, %7, %14, 0x81;\nand.b32 t, t, 1;\nmin.u32 t, t, %8;\nmin.u32 t, t, %9;\nmin.u32 t, t, %10;\nmin.u32 t, t, %11;\n"
               "setp.eq.b32 p, t, 0;\nvote.sync.any.pred p, p, 0xffffffff;\n@!p bra.uni L1;\n"
               "shr.u32 t, n, 31;\nadd.u32 t, t, %12;\ncvt.u64.u32 x, t;\nadd.s64 x, x, %15;\nshr.u32 t, n, 30;\nadd.u32 t, t, %13;\ncvt.u64.u32 y, t;\nadd.s64 y, y, %15;\n"
               "ld.relaxed.gpu.global.v4.u32 {%0, %1, %2, %3}, [x];\nld.relaxed.gpu.global.v4.u32 {%4, %5, %6, %7}, [x+32768];\n"
               "ld.relaxed.gpu.global.u32 %8, [y];\nld.relaxed.gpu.global.u32 %9, [y+1280];\nld.relaxed.gpu.global.u32 %10, [y+2560];\nld.relaxed.gpu.global.u32 %11, [y+5120];\n"
               "add.u32 n, n, 1;\nsetp.lt.u32 p, n, 1000000;\n@p bra.uni L0;\ntrap;\nL1:\n}"
               : "+r"(a.x), "+r"(a.y), "+r"(a.z), "+r"(a.w), "+r"(c.x), "+r"(c.y), "+r"(c.z), "+r"(c.w), "+r"(v[0]), "+r"(v[1]), "+r"(v[2]), "+r"(v[3])
               : "r"(zo), "r"(co), "r"(e1), "l"(G) : "memory");
}
__device__ __forceinline__ void load_x(const Params& P, uint32_t sb, int b, int h) {
  const uint32_t bar = sb + 8 * (B_X + h);
  mbar_expect(bar, 10240);
  tma5d(sb + SM_X + h * 10240, &P.mX, 0, 0, 0, 5 * h, tbase(b), bar);
}
__device__ __forceinline__ uint32_t x_addr(uint32_t sb, int w, int lane) {
  const int rho = 15 - (4 * (lane >> 3) + 2 * (lane & 1) + ((lane >> 1) & 1));
  return sb + SM_X + (w >> 1) * 2048 + rho * 128 + (((2 * (w & 1) + (lane & 4)) ^ (rho & 7)) << 4);
}
__device__ __forceinline__ void ln1_half(uint32_t sb, int tid, int h, int dry, float& s1, float& s2, float& pv) {
  const uint32_t xr = sb + SM_X + 16 * tid;
  float s3 = 0.f;
  if (ITW == 8) STAMPIF(tid == 0, 102 + 2 * h);
  if (!dry) mbar_wait(sb + 8 * (B_X + h), 0);
  STAMPIF(tid == 0, 25);
  if (ITW == 8) STAMPIF(tid == 0, 103 + 2 * h);
  uint4 v[5];
#pragma unroll
  for (int n = 0; n < 5; n++) v[n] = n < LV ? ldv128(xr + 10240 * h + 2048 * n) : lds128(xr + 10240 * h + 2048 * n);
  pv = blo(ldv32(xr & ~127u));
#pragma unroll
  for (int n = 0; n < 5; n++) {
    const uint32_t u[4] = {v[n].x, v[n].y, v[n].z, v[n].w};
#pragma unroll
    for (int j = 0; j < 4; j++) {
      const float a = blo(u[j]) - pv, c = bhi(u[j]) - pv;
      s1 += a + c; s2 += a * a; s3 += c * c;
    }
  }
  s2 += s3;
}
__device__ __forceinline__ void ln1_end(uint32_t sb, int tid, float s1, float s2, float pv) {
#pragma unroll
  for (int o = 1; o < 8; o <<= 1) { s1 += __shfl_xor_sync(0xffffffffu, s1, o); s2 += __shfl_xor_sync(0xffffffffu, s2, o); }
  if (ITW == 8) { asm volatile("" : "+f"(s1), "+f"(s2)); STAMPIF(tid == 0, 107); }
  const float mu = s1 * (1.f / D_), var = fmaxf(s2 * (1.f / D_) - mu * mu, 0.f);
  float rs;
  asm("rcp.approx.ftz.f32 %0, %1;" : "=f"(rs) : "f"(sdev(var)));
  const int i = 15 - (tid >> 3), j = tid & 7;
  if (j < 2) sts16(sb + SM_SMALL + SMALL_LN + 32 * j + 16 * (i & 1) + (i & 14), pack2(j ? rs : pv + mu, 0.f));
  if (ITW == 8) STAMPIF(tid == 0, 108);
  bar_sync(5, 128);
  STAMPIF(tid == 0, 75);
}
__device__ __forceinline__ void load_box(const Params& P, uint32_t sb, int b, int cls) {
  const uint32_t bar = sb + 8 * (B_BOX + cls);
  mbar_expect(bar, 10240);
  tma3d(sb + SM_RING + R_BOX + 10240 * (cls & 1), &P.mWm, 16 * mod_grp(b, cls >> 1), 0, 5 * (cls & 1), bar);
}
__device__ __forceinline__ void load_ssm(const Params& P, uint32_t sb, int b, int r) {
  const uint32_t bar = sb + 8 * (B_S + r);
  mbar_expect(bar, 16 * 288);
  tma3d(chan_base(sb, r) + 128, &P.mS, 0, 0, 128 * r + b, bar);
}
__device__ __forceinline__ void k1_job(uint32_t sb, int r, int tid, uint32_t dv) {
  const uint32_t a0 = chan_base(sb, r) + 128 + 16 * tid + 32 * (tid >> 4);
  mbar_wait(sb + 8 * (B_S + r), 0);
  uint4 v[2];
  uint32_t pv[2];
#pragma unroll
  for (int n = 0; n < 2; n++) { v[n] = lds128(a0 + 2304 * n); pv[n] = lds32(a0 + 2304 * n - ((tid & 15) ? 4 : 36)); }
  if (tid == 0) { v[0].x = hadd(v[0].x, dv); sts32(a0, v[0].x); }
#pragma unroll
  for (int n = 0; n < 2; n++)
    sts128(a0 + 2304 * n + K1OFF, make_uint4(__byte_perm(pv[n], v[n].x, 0x5432), __byte_perm(v[n].x, v[n].y, 0x5432), __byte_perm(v[n].y, v[n].z, 0x5432), __byte_perm(v[n].z, v[n].w, 0x5432)));
}

__device__ __forceinline__ int out_blk(int s, int p) { const int t = p + (s >> 1); return t < 5 ? t : t - 5; }
__device__ __forceinline__ void l2_prefetch(const void* p, int bytes) { asm volatile("cp.async.bulk.prefetch.L2.global [%0], %1;" ::"l"(p), "r"(bytes) : "memory"); }
__device__ __forceinline__ void pf_line(const void* p) { asm volatile("prefetch.global.L2 [%0];" ::"l"(p) : "memory"); }
template <int BF> __device__ __forceinline__ int role(int bx) {
  const int c = bx >> 1, d = c - 36, q = (d * 37) >> 8, k = d - 7 * q;
  int rank;
  if (BF) {
    const int r1 = ((c - 4) & 7) * 8 + ((c - 4) >> 3), r2 = (k + min(k, 1)) * 8 + 4 + q;
    rank = r2 + ((d >> 31) & (r1 - r2)) + (((c - 4) >> 31) & (12 + c - r1));
  }
  else rank = c < 4 ? 12 + c : c < 36 ? ((c - 4) & 7) * 8 + ((c - 4) >> 3) : (k ? k + 1 : 0) * 8 + 4 + q;
  return 8 * (rank & 15) + 2 * (rank >> 4) + (bx & 1);
}
enum { K_KV, K_SSM, K_BOX, K_PW, K_PD, K_PKV, K_PSSM, K_PBOX, K_W, K_X, K_ST, K_END = 15 };
#define KD 600
#define S1T 1900
#define KP 0
#define Q0 2400
#define Q1 3300
#define Q2 4000
#define Q3 4400
#define Q4 5100
#define Q5 6000
#define Q6 6700
#define Q7 7500
#define Q8 7900
#define Q9 8200
#define QA 9100
#define QB 9700
#define SC 0
#define MO 0
#define QS 0
#define SH 400
#define E(t, bar, kind, r) (((t) ? (t) - SH : 0) << 16 | (bar) << 8 | (kind) << 4 | (r))
#define SCH0 E(S1T + SH, 255, K_SSM, 1),
#define SCHED SCH0 E(Q0 + SH - QS, 255, K_BOX, 0), E(0, 255, K_BOX, 1), E(Q1 + SH - QS, 255, K_KV, 2), E(Q2 + SH - QS, 255, K_SSM, 2), E(Q3 + SH - QS, 255, K_KV, 3), E(Q4 + SH - QS, 255, K_X, 0), E(Q5 + SH - QS, 255, K_KV, 4), E(Q6 + SH - QS, 255, K_X, 1), E(Q7 + SH - QS, 255, K_SSM, 3), E(Q8 + SH - QS, 255, K_SSM, 4), E(Q9 + SH - QS, 255, K_BOX, 2), E(QA + SH - QS, 255, K_PW, 0), E(QB + SH - QS, 255, K_BOX, 3)
#define XPF (S1T ? 1 : 2)
#define XBOTH 0
#define XI 8
#define XW 0
#define PWM 0x3c
#define STM 0x7c0
#define PDM 0x3800
#define KV4C 3
#define CVT 1
#define UPOS 4
#define UD 1200
#define UD1 5300
#define NP 6
#define NQ 6
#define SPOS(i) (2 * ((i) - NQ) + 13)
#define LH0 4
#define LH1 5
#define LM 0
#define PT 1
#define ZP 0
#define BD 1200
#define ER 0
#define PL 1
#define K1N 1
#define ZD 9800
#define PK 0
#define ZF 1
constexpr uint32_t kSched[] = {SCHED, E(0, 255, K_END, 0)};
struct In { const bf16 *k, *v, *sk, *Wg, *Wu, *Wd, *ss; };
__device__ __forceinline__ void load_w(const Params& P, uint32_t sb, int s, int it) {
  const int st = it % 5;
  mbar_wait(sb + 8 * (B_E1 + st), (it / 5) & 1);
  const uint32_t a = sb + SM_RING + st * 32768 + 8192, fb = sb + 8 * (B_F1 + st);
  mbar_expect(fb, 24576);
#pragma unroll
  for (int j = 0; j < 3; j++) {
    tma2d(a + 8192 * j, &P.mG, 192 * s + 64 * j, 32 * it, fb);
    tma2d(a + 8192 * j + 4096, &P.mU, 192 * s + 64 * j, 32 * it, fb);
  }
}

template <int I> __device__ __forceinline__ int sched_run(const Params& P, const In& in, uint32_t sb, int b, int lane, uint32_t t_0) {
  constexpr uint32_t e = kSched[I];
  constexpr int kind = (e >> 4) & 15, r = e & 15, bar = (e >> 8) & 255;
  if constexpr (kind == K_END) return 0;
  else {
    if constexpr ((e >> 16) != 0) while (clk() - t_0 < (e >> 16));
    if (bar != 255) mbar_wait(sb + 8 * bar, 0);
    if (kind == K_BOX && r == 2) mbar_wait(sb + 8 * B_BD, 0);
    if (kind == K_PKV) {
      const bf16* kvp = (lane < 16 ? in.k : in.v) + (16 * b + (lane & 15)) * D_ + 128 * r;
      pf_line(kvp); pf_line(kvp + 64);
    } else {
      if (elect()) {
        if (kind == K_KV) load_kv(P, in.sk, sb, b, r);
        if (kind == K_X) load_x(P, sb, b, r);
        if (kind == K_SSM) load_ssm(P, sb, b, r);
        if (kind == K_BOX && (r > 1 || mod_first(b))) load_box(P, sb, b, r);
        if (kind == K_PW) { l2_prefetch(in.Wg + (128 * r + b) * F_, 2 * F_); l2_prefetch(in.Wu + (128 * r + b) * F_, 2 * F_); }
        if (kind == K_PSSM) l2_prefetch(in.ss + (128 * r + b) * S_, 4096);
      }
      __syncwarp();
    }
    return sched_run<I + 1>(P, in, sb, b, lane, t_0) + (kind == K_PW);
  }
}

__global__ void __launch_bounds__(512, 1) fused_kernel(const bf16* __restrict__ gk, const bf16* __restrict__ gv, const bf16* __restrict__ gsk,
                                                       const bf16* __restrict__ gD, const bf16* __restrict__ gc, Scr* G, const bf16* gWg, const bf16* gWu,
                                                       const bf16* gWd, bf16* gout, const bf16* gss, const __grid_constant__ Params P) {
  extern __shared__ __align__(1024) char smem_raw[];
  const uint32_t sb = smem_u32(smem_raw), ring = sb + SM_RING;
  int t0 = 0;
  uint32_t t_0;
  if (FS & 2) asm volatile("mov.u32 %0, %%tid.x;" : "=r"(t0));
  if (FS & 4) t_0 = clk();
  if (KS & 1) {
    int bx;
    asm volatile("mov.u32 %0, %%ctaid.x;" : "=r"(bx));
    if (t0 < 128) kv_load(gk, gv, gsk, sb, bx, 0, t0);
    asm volatile("" : "+r"(t0), "+r"(bx));
    if ((t0 >> 7) == 1) { spin(t_0, KD); kv_load(gk, gv, gsk, sb, bx, 1, t0 - 128); }
  } else if ((FS & 1) && t0 < (KP ? 128 : 256)) {
    int bx;
    if (!KP && KD && t0 >= 128) spin(t_0, KD);
    asm volatile("mov.u32 %0, %%ctaid.x;" : "=r"(bx));
    kv_load(gk, gv, gsk, sb, (FS & 8) ? bx : role<1>(bx), KP ? 0 : t0 >> 7, t0 & 127);
  }
  const int b = role<0>(blockIdx.x), m = b >> 3, s = b & 7;
  if (!(FS & 4)) t_0 = clk();
  if ((FS & 3) == 2 && t0 < 256) kv_load(gk, gv, gsk, sb, b, t0 >> 7, t0 & 127);
  const int wg = __shfl_sync(0xffffffffu, threadIdx.x >> 7, 0);
  const int tid = threadIdx.x & 127, lane = tid & 31;
  const int w = __shfl_sync(0xffffffffu, tid >> 5, 0);
  uint32_t e1 = 0;
  if (wg < 2) {
    if (!(FS & 2)) kv_load(gk, gv, gsk, sb, b, wg, tid);
    if (TG == 1) e1 = rdback(G->flag + 8 * m + 4);
  } else {
    if (wg == 2) {
      if (tid < 40) {
        int c = tid & 7;
        sts128(chan_base(sb, tid >> 3) + (c < 2 ? 80 + c * K1OFF : KSZ + 4096 + (c - 2) * 16), make_uint4(0, 0, 0, 0));
      }
    }
    if (elect()) {
      const int j = 4 * (3 - wg) + w - 1;
      if (j < 4) asm volatile("prefetch.tensormap [%0];" ::"l"(&P.mX + j) : "memory");
      if (j < 0) {
#pragma unroll
        for (int i = 0; i < 5; i++) mbar_init(sb + 8 * (B_S + i), 1);
        fence_async_s();
        if (XPF > 0) load_ssm(P, sb, b, 0);
        if (XPF > 1) load_ssm(P, sb, b, 1);
      } else {
        const int c = j < 3 ? 1 : j < 4 ? 2 : 4;
#pragma unroll
        for (int i = 0; i < 16; i++) mbar_init(sb + 128 * j + 8 * i, i < 10 || j < 6 ? c : i < 12 - KP ? 128 : 1);
      }
    }
    fence_async_s();
  }
  __syncthreads();
  STAMPIF(threadIdx.x == 0, 55);

  if (wg < 2) {
    if (!KP || !wg) cp_arrive(sb + 8 * (B_B + wg));
    asm volatile("setmaxnreg.inc.sync.aligned.u32 224;");
    STAMPIF(threadIdx.x == 0, 82);
    const int g = lane >> 2, q = lane & 3;
    constexpr int NB = UT < 5 ? 288 : 256;
    if (wg == 1) bar_arrive(1, NB);
    const uint32_t dv = *(const uint16_t*)(gD + 128 * wg + b);
    if (TG == 3) e1 = rdback(G->flag + 8 * m + 4 + (__shfl_sync(0xffffffffu, tid, tid) >> 8));
    e1 = (e1 >> 5) + 1;
    {
      const int tid = (OPQ & 4) ? __shfl_sync(0xffffffffu, threadIdx.x & 127, threadIdx.x) : threadIdx.x & 127, lane = tid & 31, g = lane >> 2, q = lane & 3;
      const int b0 = (g >> 1) & 1, b1 = g >> 2, u = q + 4 * b0 - w;
      const uint32_t fo = 128 + (g & 1) * K1OFF + 288 * b1 + 4 * u, fo0 = fo - (u < 0 ? 32 : 0);
      const bool wrap = b0 && q == 0;
      const int src1 = b0 ? ((lane & 20) | ((q - 1) & 3)) : (lane | 8);
      const uint2* pu = (const uint2*)(G->kvT + (128 * wg + b) * S_ + 8 * tid);
      uint4 u0 = make_uint4(0, 0, 0, 0), u1 = make_uint4(0, 0, 0, 1);
#pragma unroll 1
      for (int ch = wg; ch < 5; ch += 2) {
        const uint32_t base = chan_base(sb, ch);
        if (KW) {
#pragma unroll 1
          for (int n = ch > 1; n <= (ch & 1); n++) {
            int bx;
            asm volatile("mov.u32 %0, %%ctaid.x;" : "=r"(bx));
            kv_job(G, sb, n ? b : bx, ch + n, tid, e1);
            STAMPIF(tid == 0, n ? 21 + ch : 1 + ch);
            if (n == 0) {
              k1_job(sb, wg, tid, dv);
              bar_sync(3 + wg, 128);
              mbar_wait(sb + 8 * B_E0, 0);
              e1 = epoch(sb);
            }
          }
          if (ch > 1) mbar_wait(sb + 8 * (B_K + ch - 2), 0);
          else if (ch) spin(t_0, UD1);
          if (ch) { u0 = ld_tag2(pu); u1 = ld_tag2(pu + 256); }
        }
        if (!KW && (ch < 2 || ch == KV4C)) {
          int bx = b;
          if (FS & 8) { asm volatile("mov.u32 %0, %%ctaid.x;" : "=r"(bx)); bx = ch < 2 - KP ? bx : b; }
          kv_job(G, sb, bx, ch < 2 ? ch : 4, tid, TG ? e1 : 1);
          if (ER && ch > 1) { __syncwarp(); if (lane == 0) mbar_arrive(sb + 8 * B_KV4); }
          STAMPIF(tid == 0, ch < 2 ? 1 + ch : 24);
        }
        if (KW) {
        } else if (ch < 2) {
          k1_job(sb, wg, tid, dv);
          bar_sync(3 + wg, 128);
        } else {
          mbar_wait(sb + 8 * (B_K + ch - 2), 0);
          if (UT == 5) {
            u0 = ld_tag2(pu); u1 = ld_tag2(pu + 256);
            if (BS) mbar_wait(sb + 8 * (B_S + ch), 0);
          }
        }
        const uint32_t fa = base + fo, fa0 = base + fo0;
        uint32_t af[16][4];
        auto afl = [&](int j) {
          const int o = 64 * (j & 1) + 576 * (j >> 1);
          if (UF) { af[j][0] = ldv32(((j & 1) ? fa : fa0) + o); af[j][1] = ldv32(fa + o + 128); af[j][2] = ldv32(fa + o + 32); af[j][3] = ldv32(fa + o + 160); }
          else { af[j][0] = lds32(((j & 1) ? fa : fa0) + o); af[j][1] = lds32(fa + o + 128); af[j][2] = lds32(fa + o + 32); af[j][3] = lds32(fa + o + 160); }
        };
#pragma unroll
        for (int j = 0; j < NA; j++) afl(j);
        if (UF) {
          stv128(base + KSZ + 16 * tid, u0);
          stv128(base + KSZ + 2048 + 16 * tid, u1);
#pragma unroll
          for (int j = NA; j < 16; j++) afl(j);
        }
        STAMPIF(tid == 0, 40 + ch);
        const uint32_t tg = KW && ch < 2 ? 1 : e1;
        if (!KW && !(TG & 1) && EH < 2 && (!EH || ch < 2)) { mbar_wait(sb + 8 * B_E0, 0); e1 = epoch(sb); }
        if (ch < UT) {
          if (KW) { if (ch == 0) spin(t_0, UD2); }
          else if (UD2 ? ch < 2 : ch == 1) spin(t_0, ch ? UD1 : UD2);
          if (UT == 2) u0.w = 0;
          if (UF) u_fix(u0, u1, pu, base + KSZ + 16 * tid, TG ? tg : 1);
          else u_wait(u0, u1, pu);
          if (ITW == 5) STAMPIF(tid == 0, 105 + ch);
          if (!UF) {
            sts128(base + KSZ + 16 * tid, u0);
            sts128(base + KSZ + 2048 + 16 * tid, u1);
#pragma unroll
            for (int j = NA; j < 16; j++) afl(j);
          }
          fence_async_s();
        }
        float acc[128];
        const uint64_t db = mkdesc(base + KSZ, 32, 128, 0);
        bar_sync(1 + wg, NB);
        if (ITW == 5) STAMPIF(tid == 0, 115 + ch);
        wg_fence();
        wgmma_rs_n64<0>(acc + 96, af[0], db + 192, 0);
        wgmma_rs_n192<0>(acc, af[0], db, 0);
        wgmma_rs_n64<0>(acc + 96, af[1], db + 196, 1);
        wgmma_rs_n192<0>(acc, af[1], db + 4, 1);
        wgmma_rs_n32<0>(acc + 96, af[2], db + 224, 1);
        wgmma_rs_n192<0>(acc, af[2], db + 32, 1);
        wgmma_rs_n32<0>(acc + 96, af[3], db + 228, 1);
        wgmma_rs_n192<0>(acc, af[3], db + 36, 1);
        wgmma_rs_n192<0>(acc, af[4], db + 64, 1);
        wgmma_rs_n192<0>(acc, af[5], db + 68, 1);
        wgmma_rs_n160<0>(acc, af[6], db + 96, 1);
        wgmma_rs_n160<0>(acc, af[7], db + 100, 1);
        if (CVT == 2) wg_commit();
        wgmma_rs_n128<0>(acc, af[8], db + 128, 1);
        wgmma_rs_n128<0>(acc, af[9], db + 132, 1);
        if (CVT == 1) wg_commit();
        wgmma_rs_n96<0>(acc, af[10], db + 160, 1);
        wgmma_rs_n96<0>(acc, af[11], db + 164, 1);
        if (CVT == 0) bar_arrive(2 - wg, NB);
        wgmma_rs_n64<0>(acc, af[12], db + 192, 1);
        wgmma_rs_n64<0>(acc, af[13], db + 196, 1);
        wgmma_rs_n32<0>(acc, af[14], db + 224, 1);
        wgmma_rs_n32<0>(acc, af[15], db + 228, 1);
        wg_commit();
        if ((!TG || TG == 2 && ch < 2) && ZP == 0 && ch < UT) {
          stg128((void*)pu, make_uint4(0, 0, 0, 0));
          stg128((void*)(pu + 256), make_uint4(0, 0, 0, 0));
        }
        if (tid < 2 && ch == (!ER && wg == (KV4C & 1) && KV4C < 5 ? KV4C : wg)) mbar_arrive(sb + 8 * (B_E1 + tid));
        if (EH == 2 && ch < 2) { mbar_wait(sb + 8 * B_E0, 0); e1 = epoch(sb); }
        auto go = [&](int k) {
          int mk = 0;
#pragma unroll
          for (int c = 0; c < 4; c++) if (((GT >> 4 * c) & 15) == k) mk |= 1 << c;
          if (mk) asm volatile("{\n.reg .pred p;\nsetp.ne.b32 p, %1, 0;\n@p bar.arrive %0, %2;\n}" ::"r"(2 - wg), "r"((mk >> ch) & 1), "n"(NB) : "memory");
        };
        if (CVT) { wg_wait<1>(); go(0); }
        STAMPIF(tid == 0, 3 + ch);
        if (EH == 3 && ch < 2) { mbar_wait(sb + 8 * B_E0, 0); e1 = epoch(sb); }
        if (BX3 == 2 && ch == 3) {
          mod_box(G, sb, b, 1, e1, tid);
          __syncwarp();
          if (lane == 0) mbar_arrive(sb + 8 * (B_BD + 1));
          STAMPIF(tid == 0, 73);
        }
        if (ZP == 1) {
          stg128((void*)pu, make_uint4(0, 0, 0, 0));
          stg128((void*)(pu + 256), make_uint4(0, 0, 0, 0));
        }
        wg_wait<0>();
#pragma unroll
        for (int i = 0; i < 128; i++) asm volatile("" : "+f"(acc[i])::"memory");
        if (!RL) {
          bar_sync(3 + wg, 128);
          if (tid <= (ch >> 2)) mbar_arrive(sb + 8 * (B_E1 + 2 + (ch >> 1)));
        }
        if (RL == 2 && lane == 0) mbar_arrive(sb + 8 * (B_Z + ch));
        go(1);
        float S0[33], T[34];
#pragma unroll
        for (int i = 0; i < 31; i++) S0[i] = acc[4 * i] + acc[4 * i + 6];
        S0[31] = acc[124]; S0[32] = 0.f;
        if (PK & 1) {
#pragma unroll
          for (int i = 0; i < 32; i += 2) {
            const uint32_t v = __shfl_sync(0xffffffffu, pack2(acc[4 * i + 1] + acc[4 * i + 7], i < 30 ? acc[4 * i + 5] + acc[4 * i + 11] : acc[125]), src1);
            T[i] = (wrap ? S0[i + 1] : S0[i]) + blo(v);
            T[i + 1] = (wrap ? S0[i + 2] : S0[i + 1]) + bhi(v);
          }
        } else {
#pragma unroll
          for (int i = 0; i < 32; i++) {
            float s1 = i < 31 ? acc[4 * i + 1] + acc[4 * i + 7] : acc[125];
            T[i] = (wrap ? S0[i + 1] : S0[i]) + __shfl_sync(0xffffffffu, s1, src1);
          }
        }
        T[32] = 0.f; T[33] = 0.f;
        go(2);
        uint4* pz = (uint4*)(G->zT + (128 * ch + b) * S_) + ((tid & 120) | (2 * q) | (g & 1));
#pragma unroll
        for (int h = 0; h < 2; h++) {
          float y[8];
          if (PK & 2) {
#pragma unroll
            for (int mu = 0; mu < 8; mu += 2) {
              const uint32_t v = __shfl_xor_sync(0xffffffffu, pack2(T[4 * mu + 2 + h], T[4 * mu + 6 + h]), 16);
              y[mu] = (b1 ? T[4 * mu + 4 + h] : T[4 * mu + h]) + blo(v);
              y[mu + 1] = (b1 ? T[4 * mu + 8 + h] : T[4 * mu + 4 + h]) + bhi(v);
            }
          } else {
#pragma unroll
            for (int mu = 0; mu < 8; mu++) y[mu] = (b1 ? T[4 * mu + 4 + h] : T[4 * mu + h]) + __shfl_xor_sync(0xffffffffu, T[4 * mu + 2 + h], 16);
          }
          pz[128 * h] = make_uint4(pack2(y[0], y[1]), pack2(y[2], y[3]), pack2(y[4], y[5]), tagged(pack2(y[6], y[7]), e1));
        }
        go(3);
        if (RL == 1 && lane == 0) mbar_arrive(sb + 8 * (B_Z + ch));
        if (ZP == 2) {
          stg128((void*)pu, make_uint4(0, 0, 0, 0));
          stg128((void*)(pu + 256), make_uint4(0, 0, 0, 0));
        }
        pu += 128 * S_ / 2;
        STAMPIF(tid == 0, 8 + ch);
      }
    }
    uint32_t hh[96];
    {
      float ga[192];
      float* ua = ga + 96;
      const uint64_t da0 = mkdesc(ring + wg * 2048, 512, 256, 3), db0 = mkdesc(ring + 8192, 4096, 1024, 1);
      int st = PL, ph = 0, ps = 0;
      if (ITW == 7) STAMPIF(tid == 0, 110 + wg);
      float bx[4];
      if (wg && BX3 < 2) {
        mbar_wait(sb + 8 * (B_BOX + 2), 0);
        mbar_wait(sb + 8 * (B_BOX + 3), 0);
        wg_fence();
#pragma unroll
        for (int n = 0; n < 10; n++) wgmma_ss_n8<1, 0>(bx, box_a(sb) + 128 * n, box_b(sb) + 8 * n, n != 0);
        wg_commit();
        if (ITW == 7) STAMPIF(tid == 0, 120);
      }
      auto put = [&]() {
#pragma unroll
        for (int i = 0; i < 4; i++) asm volatile("" : "+f"(bx[i])::"memory");
        mod_put(G, sb, bx, b, 1, e1, tid);
        __syncwarp();
        if (lane == 0) mbar_arrive(sb + 8 * (B_BD + 1));
        STAMPIF(tid == 0, 73);
      };
      if (wg && BX3 == 0) { wg_wait<0>(); put(); }
      mbar_wait(sb + 8 * B_F1, 0);
      STAMPIF(tid == 0, 13 + wg);
      bool nf = PG == 1 && mbar_test(sb + 8 * (B_F1 + 1), 0);
      wg_fence();
      wgmma_ss_n192<1, 1>(ga, da0, db0, 0);
      wgmma_ss_n192<1, 1>(ua, da0, db0 + 768, 0);
      wgmma_ss_n192<1, 1>(ga, da0 + 256, db0 + 128, 1);
      wgmma_ss_n192<1, 1>(ua, da0 + 256, db0 + 128 + 768, 1);
      wg_commit();
      if (wg && BX3 == 1) { wg_wait<1>(); put(); }
      if (!PG) mbar_wait(sb + 8 * B_BD, 0);
      if (ITW == 7) STAMPIF(tid == 0, 112 + wg);
      const bool cs = b < 96;
      const int x0 = wg ? XI : 99,
                x1 = x0 + (cs ? 4 : 2), xs = cs ? 4 : 8;
      uint64_t xa = cs ? mkdesc(sb + SM_EXT, 4096, 1024, 1) : box_a(sb), xb = cs ? mkdesc(sb + SM_CB, 32, 128, 0) : box_b(sb);
      uint64_t ya = xa + (cs ? (SM_RING + R_X - SM_EXT) / 16 : 256), yb = xb + 16;
      if (ITW == 7) STAMPIF(tid == 0, 114 + wg);
#pragma unroll 1
      for (int it = PL; it < 19; it++) {
        if (it == x0) {
          mbar_wait(sb + 8 * (cs ? B_F : B_BOX + 4), 0);
          mbar_wait(sb + 8 * (cs ? B_ST0 : B_BOX + 5), 0);
          STAMPIF(tid == 0, 76);
        }
        if (it == x1 + XW) {
          wg_wait<XW>();
#pragma unroll
          for (int i = 0; i < 4; i++) asm volatile("" : "+f"(bx[i])::"memory");
          if (!cs) mod_put(G, sb, bx, b, 2, e1, tid);
          else {
            const int row = (m < 6 ? 0 : 4) + q;
            uint16_t* dst = (uint16_t*)G->cimg + s * 3072 + (m % 6) * 512 + row * 64 + g;
#pragma unroll
            for (int j = 0; j < 2; j++) {
              const float c1 = __shfl_sync(0xffffffffu, bx[2 * j], lane & 28), c2 = __shfl_sync(0xffffffffu, bx[2 * j + 1], lane & 28);
              const float t = (lane & 2) ? c2 : c1, hi = rbf(t);
              dst[((2 * w + j) ^ row) << 3] = (uint16_t)pack2((lane & 1) ? t - hi : hi, 0.f);
            }
          }
          __syncwarp();
          if (lane == 0) mbar_arrive(sb + 8 * (B_BD + 2));
          STAMPIF(tid == 0, 77);
        }
        if (ITW == 7) STAMPIF(tid == 0 && it == 0, 116 + wg);
        if (!nf) mbar_wait(sb + 8 * (B_F1 + st), ph);
        const int nx = st == 4 ? 0 : st + 1;
        if (st == 4) ph ^= 1;
        if (ITW == 1) STAMPIF(tid == 0 && it >= 10, 90 + it + 10 * wg);
        else if (ITW == 2) STAMPIF(tid == 0 && it < 10, 100 + it + 10 * wg);
        else if (ITW < 3) STAMPIF(threadIdx.x == ITW, 100 + it);
        const uint64_t da = da0 + st * 2048, db = db0 + st * 2048;
        if (it >= x0 && it < x1) {
          if (PG == 1) nf = mbar_test(sb + 8 * (B_F1 + nx), ph);
          wg_fence();
          wgmma_ss_n8<1, 0>(bx, xa, xb, it != x0);
          wgmma_ss_n192<1, 1>(ga, da, db, 1);
          wgmma_ss_n8<1, 0>(bx, ya, yb, 1);
          wgmma_ss_n192<1, 1>(ua, da, db + 768, 1);
          wgmma_ss_n8<1, 0>(bx, ya + 128, yb + xs, 1);
          wgmma_ss_n192<1, 1>(ga, da + 256, db + 128, 1);
          wgmma_ss_n8<1, 0>(bx, ya + 256, yb + 2 * xs, 1);
          wgmma_ss_n192<1, 1>(ua, da + 256, db + 128 + 768, 1);
          wgmma_ss_n8<1, 0>(bx, ya + 384, yb + 3 * xs, 1);
          wg_commit();
          xa += 128; xb += xs; ya += 512; yb += 4 * xs;
        } else {
          if (PG == 1) nf = mbar_test(sb + 8 * (B_F1 + nx), ph);
          wg_fence();
          wgmma_ss_n192<1, 1>(ga, da, db, PL || it != 0);
          wgmma_ss_n192<1, 1>(ua, da, db + 768, PL || it != 0);
          wgmma_ss_n192<1, 1>(ga, da + 256, db + 128, 1);
          wgmma_ss_n192<1, 1>(ua, da + 256, db + 128 + 768, 1);
          wg_commit();
        }
        wg_wait<1>();
        if (PG) { if (w == 0 && elect()) mbar_arrive(sb + 8 * (B_E1 + ps)); }
        else if (tid == 0) mbar_arrive(sb + 8 * (B_E1 + (st == 0 ? 4 : st - 1)));
        ps = st; st = nx;
      }
      const uint32_t la = ring + wg * 2048 + tid * 16, ra = mapa(la, (b & 1) ^ 1), rp = mapa(sb + 8 * (B_PEER + 2 * wg), (b & 1) ^ 1), rb = rp + 8 * (B_RECV - B_PEER);
      uint32_t sa[24];
      auto addr = [&](int j) {
        sa[2 * j] = ra + (j < 2 ? 5 : (j >> 1) - 1) * 32768 + (j & 1) * 4096;
        sa[2 * j + 1] = (sa[2 * j] >> 31) + (rb + 8 * (j / 6));
        asm volatile("" : "+r"(sa[2 * j]), "+r"(sa[2 * j + 1]));
      };
      auto send = [&](int j) { st_async4(sa[2 * j], hh + 4 * j, sa[2 * j + 1]); };
      auto pack = [&](int c) {
#pragma unroll
        for (int i = 0; i < 64; i++) asm volatile("" : "+f"(ga[64 * c + i])::"memory");
#pragma unroll
        for (int i = 0; i < 4; i++) addr(4 * c + i);
#pragma unroll
        for (int i = 0; i < 16; i++) {
          const int j = 64 * c + 2 * i;
          hh[16 * c + i] = pack2(ga[j] * ga[j + 32], ga[j + 1] * ga[j + 33]);
          asm volatile("" : "+r"(hh[16 * c + i])::"memory");
          if ((i & 3) == 3 && 4 * c + i / 4 < NP) send(4 * c + i / 4);
          if (c == 2 && NQ > NP && i == 0) mbar_wait(sb + 8 * (B_PEER + 2 * wg), 0);
          if (c == 2 && (i & 3) == 3 && NP + i / 4 < NQ) send(NP + i / 4);
        }
      };
      STAMPIF(threadIdx.x == 0, 61);
      if (!nf) mbar_wait(sb + 8 * (B_F1 + 4), 1);
      mbar_wait(sb + 8 * B_EXT, 0);
      mbar_wait(sb + 8 * B_ST2, 0);
      const uint64_t de = mkdesc(sb + SM_EXT, 1024, 0, 1), ds = mkdesc(sb + SM_STAT + wg * 1024, 0, 128, 0);
#pragma unroll
      for (int c = 0; c < 2; c++) {
        wg_fence();
        wgmma_ss_n192<1, 1>(ga + 96 * c, da0 + 8192, db0 + 8192 + 768 * c, 1);
        wgmma_ss_n192<1, 1>(ga + 96 * c, da0 + 8192 + 256, db0 + 8192 + 128 + 768 * c, 1);
        wgmma_ss_n192<0, 1>(ga + 96 * c, ds, de + 192 * c, 1);
        wg_commit();
        if (c == 0) { mbar_wait(sb + 8 * B_P0, 0); mbar_wait(sb + 8 * B_FB, 0); }
        wg_wait<1>();
        if (c == 0 && tid == 0) {
          mbar_arrive(sb + 8 * (B_E1 + 3));
          mbar_arrive_remote(rp);
        }
      }
      STAMPIF(tid == 0, 15 + wg);
      float acc[64], rs[2] = {};
      uint4 pf[4], gb = {};
      uint32_t ln, os, ol, og, oz;
      const char *po, *pq;
      const uint64_t dd0 = mkdesc(ring + 8192, 0, 1024, 1);
      bool ok = false;
#pragma unroll
      for (int c = 0; c < 3; c++) {
        pack(c);
        if (c == 1) ok = mbar_try(sb + 8 * (B_FB + 1), 0);
        STAMPIF(tid == 0 && c == 0, wg ? 89 : 121);
        if (ITW == 3) STAMPIF(tid == 0 && c > 0, 99 + c + 10 * wg);
        wg_fence();
#pragma unroll
        for (int k = 4 * c; k < 4 * c + 4; k++) wgmma_rs_n64<1>(acc, hh + 4 * k, dd0 + 5 * 2048 + 128 * k, k);
        wg_commit();
        if (c == 0) {
          wg_wait<1>();
          if (tid == 0) {
            mbar_arrive(sb + 8 * (B_E1 + 4));
            mbar_arrive_remote(rp + 8);
          }
        }
        if (c == 1 && !ok) mbar_wait(sb + 8 * (B_FB + 1), 0);
      }
      auto recv = [&](int j) {
        const uint4 v = lds128(la + (j < 2 ? 5 : (j >> 1) - 1) * 32768 + (j & 1) * 4096);
        hh[48 + 4 * j] = v.x; hh[49 + 4 * j] = v.y; hh[50 + 4 * j] = v.z; hh[51 + 4 * j] = v.w;
      };
      auto stage = [&](const float* a, int i, int p) {
        const uint32_t v[4] = {pack2(a[8 * i] * rs[0], a[8 * i + 1] * rs[0]), pack2(a[8 * i + 2] * rs[1], a[8 * i + 3] * rs[1]),
                               pack2(a[8 * i + 4] * rs[0], a[8 * i + 5] * rs[0]), pack2(a[8 * i + 6] * rs[1], a[8 * i + 7] * rs[1])};
        stsm4(OF && p % 4 ? (oz ^ 32 * i) + 65536 * (p - 1) : os + 32 * i, v);
      };
      auto fetch = [&](int p) {
        __syncwarp();
#pragma unroll
        for (int i = 0; i < 4; i++) pf[i] = lds128(ol + 576 * i);
      };
      auto next = [&](int p) {
        gb = lds128(og + 256 * out_blk(s, p));
        pq = po + 128 * out_blk(s, p);
        asm volatile("" : "+l"(pq));
      };
      auto add = [&](int p, int i) {
        if (RX == 1 && p < 4) return;
        if (RX == 2) { stg128((uint4*)(pq - (i & 1) * 2048 * D_ - (i >> 1) * 2 * D_), make_uint4(hmul(pf[i].x, gb.x), hmul(pf[i].y, gb.y), hmul(pf[i].z, gb.z), hmul(pf[i].w, gb.w))); return; }
        asm volatile("red.relaxed.gpu.global.add.noftz.v4.bf16x2 [%0], {%1, %2, %3, %4};" ::"l"(pq - (i & 1) * 2048 * D_ - (i >> 1) * 2 * D_),
                     "r"(hmul(pf[i].x, gb.x)), "r"(hmul(pf[i].y, gb.y)), "r"(hmul(pf[i].z, gb.z)), "r"(hmul(pf[i].w, gb.w)) : "memory");
      };
#pragma unroll
      for (int h = 2; h < 20; h++) {
        const int gr = h >> 1, pe = gr < 4 ? gr >> 1 : gr & 1, ac = (gr < 4 ? gr : gr >> 1) & 1;
        const int ep = h == 7 || h == 8 ? 0 : h > 8 && (h & 3) == 1 || h > 8 && (h & 3) == 2 ? (h >> 2) - 1 : -1;
        const int es = h == 6 ? 0 : h > 6 && !(h & 3) ? (h >> 2) - 1 : -1;
        if (!(h & 1) && h > 2 && !(PT && ok)) mbar_wait(sb + 8 * (B_FB + gr), 0);
        if (h == LH0 || h == LH1) mbar_wait(sb + 8 * (B_RECV + 2 * wg + (h == LH1)), 0);
        if (h == LH0 && (h == 4 || !LM) || h == LH1 && (h == 5 || !LM)) {
#pragma unroll
          for (int j = 0; j < 6; j++) recv(6 * (h == LH1) + j);
        }
        if (h == SPOS(6) / 6 && NQ <= 6) mbar_wait(sb + 8 * (B_PEER + 2 * wg), 0);
        if (h == SPOS(10) / 6) mbar_wait(sb + 8 * (B_PEER + 2 * wg + 1), 0);
        if (OF && h == OH) mbar_wait(sb + 8 * B_OF, 0);
        if (h == (ES ? RH : 6)) {
          if (!OF) { mbar_wait(sb + 8 * B_X1, 0); mbar_wait(sb + 8 * B_GB, 0); }
          asm volatile("mov.u32 %0, %%laneid;" : "=r"(ln));
#pragma unroll
          for (int i = 0; i < 2; i++) rs[i] = blo(lds32(sb + SM_STAT + (4 * wg + w) * 256 + (ln & 28) * 4 + 128 * i + 4));
        }
        STAMPIF(tid == 0 && h % 4 == 0 && h < 16, (wg ? 89 : 121) + h / 4);
        STAMPIF(tid == 0 && h == 16, wg ? 97 : 96);
        if (ITW == 3) STAMPIF(tid == 0 && h < 10, 100 + h + 10 * wg);
        if (ITW == 4) STAMPIF(tid == 0 && h >= 10, 90 + h + 10 * wg);
        const uint64_t db = dd0 + (((gr + 5) % 6) * 2048 + (gr << 16));
        if (PT && (h & 1) && h < 19) ok = mbar_try(sb + 8 * (B_FB + gr + 1), 0);
        wg_fence();
#pragma unroll
        for (int j = 0; j < 6; j++) {
          const int k = 6 * (h & 1) + j;
          wgmma_rs_n64<1>(acc + 32 * ac, hh + 48 * pe + 4 * k, db + 128 * k, pe || k);
#pragma unroll
          for (int i = NQ; i < 12; i++) if (SPOS(i) == 6 * h + j) send(i);
          if (LM && h == LH0 && h < 4) { recv(j); wg_fence(); }
          if (LM && h == LH1 && h < 5) { recv(6 + j); wg_fence(); }
          if (ES && es >= 0) {
            if (j == ES - 1) {
              wg_commit();
              wg_wait<1>();
              if (h < 12 && tid == 0) mbar_arrive(sb + 8 * (B_EB + gr - 1));
#pragma unroll
              for (int i = 0; i < 32; i++) asm volatile("" : "+f"(acc[32 * (1 - ac) + i])::"memory");
            }
#pragma unroll
            for (int i = 0; i < 4; i++) if (j == min(5, ES - 1 + i * SI / 2)) {
              stage(acc + 32 * (1 - ac), i, es);
              if (i == 3) { __syncwarp(); if (ln == 0) mbar_arrive(sb + 8 * (B_OS + 4 * wg + es)); }
            }
            if (j == ES - 1 && j < 5) wg_fence();
          }
          if (!ES && ep >= 0 && (h & 1)) {
            if (j < 4) stage(acc + 32 * (1 - ac), j, ep);
            if (j == 4 && !OF) fetch(ep);
            if (j == 3 && OF) { __syncwarp(); if (ln == 0) mbar_arrive(sb + 8 * (B_OS + 4 * wg + ep)); }
          }
          if (!OF && ep >= 0 && !(h & 1) && j > 0 && j < 5) add(ep, j - 1);
          if (!OF && ep >= 0 && !(h & 1) && j == 5) next(ep + 1);
        }
        if (!(ES == 6 && es >= 0)) wg_commit();
        STAMPIF(tid == 0 && h == 3, 81);
        if (h == (ES ? RH : 6)) {
#pragma unroll
          for (int i = 0; i < 2; i++) rs[i] = __fdividef(0.25f, rs[i] * rs[i]);
          const uint32_t ob = sb + SM_X + (4 * wg + w) * 2304;
          os = ob + (ln & 15) * 144 + (ln & 16);
          oz = ring + (4 * wg + w) * 512 + (ln & 8) * 4096 + (ln & 4) * 1024 + (ln & 3) * 128 + ((ln >> 4) ^ (ln & 7)) * 16;
          asm volatile("" : "+r"(os), "+r"(oz));
        }
        if (h == (OF ? OH : 6)) {
          ol = sb + SM_X + (4 * wg + w) * 2304 + (ln >> 3) * 16 + ln * 16;
          po = (const char*)(gout + (1793 + 2 * tbase(8 * m + 4 * wg + w)) * D_) + (int)(640 * (s & 1) + 16 * ln - (ln >> 3) * (512 * D_ + 128));
          og = sb + SM_CB + 32 * (ln & 7);
          asm volatile("" : "+r"(ol), "+r"(og), "+l"(po));
          next(OF ? 4 : 0);
        }
        if (h == 2 || h == 4 || !ES && es >= 0) {
          wg_wait<1>();
          if (h < 12 && tid == 0) mbar_arrive(sb + 8 * (B_EB + gr - 1));
          if (h >= 6) {
#pragma unroll
            for (int j = 0; j < 32; j++) asm volatile("" : "+f"(acc[32 * (1 - ac) + j])::"memory");
          }
        }
      }
      STAMPIF(tid == 0, wg ? 95 : 93);
      wg_wait<0>();
#pragma unroll
      for (int i = 0; i < 32; i++) asm volatile("" : "+f"(acc[i])::"memory");
      STAMPIF(tid == 0, wg ? 50 : 18);
#pragma unroll
      for (int i = 0; i < 4; i++) stage(acc, i, 4);
      fetch(4);
#pragma unroll
      for (int i = 0; i < 4; i++) add(4, i);
    }
  } else if (wg == 2) {
    asm volatile("setmaxnreg.dec.sync.aligned.u32 40;");
    const uint32_t e1 = (rdback(G->flag + 8 * m + 4) >> 5) + 1;
    if (tid < 80) {
      uint4 c = ((const uint4*)gc)[tid];
#pragma unroll 1
      for (int i = 0; i < 4; i++) {
        const float lo = blo(c.x), hi = bhi(c.x);
        sts32(sb + SM_STAT + 16 * tid + 4 * i, pack2(__fdividef(lo, 1.f + __expf(-lo)), __fdividef(hi, 1.f + __expf(-hi))));
        c.x = c.y; c.y = c.z; c.z = c.w;
      }
    }
    if (tid == 0) { sts32(sb + SM_SMALL + SMALL_E, e1); mbar_arrive(sb + 8 * B_E0); }
    fence_async_s();
    bar_sync(5, 128);
    auto mod0 = [&](int tid) {
      if (mod_first(b)) mod_box(G, sb, b, 0, e1, tid);
      __syncwarp();
      if (elect()) mbar_arrive(sb + 8 * B_BD);
      STAMPIF(tid == 0, 27);
    };
    if (MO == 2) { kv_job(G, sb, b, 2, tid, e1); STAMPIF(tid == 0, 22); }
    if (MO != 1) mod0(tid);
    float s1 = 0.f, s2 = 0.f, pv;
    int tl = (OPQ & 1) ? __shfl_sync(0xffffffffu, tid, tid) : tid;
#pragma unroll 1
    for (int r = KW || MO == 2 ? 3 : 2 - DR; r < 5 - XO; r++) {
      asm volatile("" : "+r"(tl));
      if (DR && r == 2) s1 = s2 = 0.f;
      if ((XO || r < 4) && r > 1) {
        kv_job(G, sb, b, r, tl, TG ? e1 : 1);
        STAMPIF(tid == 0, 20 + r);
      }
      if (r == 3) { __syncwarp(); if (elect()) mbar_arrive(sb + 8 * B_KVS); }
      if (XO || r != 2) ln1_half(sb, tl, (r - 3 + XO) & 1, r < 2, s1, s2, pv);
      else if (MO == 1) { mod0(tl); s1 = s2 = 0.f; }
    }
    {
      const int lane = tl & 31, cg = 4 * (w >> 1) + (lane & 2) + (w & 1), g = lane >> 2;
      uint32_t zo = offsetof(Scr, zT) + 2 * ((16 * cg + g) * S_ + 16 * b + 8 * (lane & 1)), co = offsetof(Scr, mv) + 4 * (2048 * (e1 & 1) + 8 * cg + g);
      uint4 z[2];
      uint32_t c[4];
      auto zld = [&]() {
        asm volatile("" : "+r"(zo), "+r"(co));
        const uint2* pz = (const uint2*)((const char*)G + zo);
        const uint32_t* pc = (const uint32_t*)((const char*)G + co);
        z[0] = ld_tag2(pz); z[1] = ld_tag2(pz + 4096);
        c[0] = rdback(pc); c[1] = rdback(pc + 320); c[2] = rdback(pc + 640); c[3] = rdback(pc + 1280);
      };
      STAMPIF(tid == 0, 28);
      if (ZF < 2 && !ZA) { spin(t_0, ZD); zld(); spin(t_0, ZS); }
      if (ITW == 8) STAMPIF(tid == 0, 106);
      ln1_end(sb, tl, s1, s2, pv);
      if (ZF < 2 && ZA) { spin(t_0, ZD); zld(); }
#pragma unroll 1
      for (int r = 0; r < 5; r++) {
        asm volatile("" : "+r"(tl));
        const int lane = tl & 31;
        if (ITW == 6) STAMPIF(tid == 0 && r < 2, 100 + 10 * r);
        if (ZF == 3) { if (r == 2 + MG) { mbar_wait(sb + 8 * (B_BD + 1), 0); spin(clk(), BD); } if (r == 0) spin(t_0, ZD); zld(); }
        const uint32_t la = sb + SM_SMALL + SMALL_LN + 16 * (lane & 1);
        uint32_t xa = x_addr(sb, w, lane) + 4096 * r, xv[8];
        const uint4 m4 = lds128(la), s4 = lds128(la + 32);
        const uint32_t m_[4] = {m4.x, m4.y, m4.z, m4.w}, s_[4] = {s4.x, s4.y, s4.z, s4.w};
        ldsm4t(xv, xa);
        ldsm4t(xv + 4, xa ^ 16);
        if (ZF == 2) { if (r == 2 + MG) { mbar_wait(sb + 8 * (B_BD + 1), 0); spin(clk(), BD); } if (r == 0) spin(t_0, ZD); zld(); }
        if (ITW == 6) STAMPIF(tid == 0 && r < 2, 104 + 10 * r);
        if (ITW == 8) STAMPIF(tid == 0 && r == 0, 109);
        z_wait(z[0], z[1], c, G, zo, co, e1);
        asm volatile("" : "+r"(xa));
        const uint32_t zc = (zo - (uint32_t)offsetof(Scr, zT)) >> 11, ao = (320 * m + s) * 32 + ((zc & ~31u) << 3) + (zc & 14) + (((zo >> 4) ^ (zc >> 3)) & 1);
        STAMPIF(tid == 0 && r == 0, 83);
        if (ITW == 6) STAMPIF(tid == 0 && r < 2, 105 + 10 * r);
        uint32_t h[8];
        {
          const uint32_t sa = ~c[0], ca1 = ~c[1];
#pragma unroll
          for (int j = 0; j < 8; j++) {
            const uint32_t z_[8] = {z[0].x, z[0].y, z[0].z, z[0].w, z[1].x, z[1].y, z[1].z, z[1].w}, sel = j > 3 ? 0x3232 : 0x1010;
            h[j] = hmul(hfma(hmul(hsub(xv[j], m_[j & 3]), s_[j & 3]), __byte_perm(ca1, 0, sel), __byte_perm(sa, 0, sel)), z_[j]);
            asm volatile("" : "+r"(h[j]));
          }
        }
        uint4* pa = (uint4*)G->AT + ao;
        uint32_t oo[8];
#pragma unroll
        for (int n = 0; n < 2; n++) {
          const uint32_t sel = n ? 0x3232 : 0x1010, ga = __byte_perm(~c[2], 0, sel), cb1 = __byte_perm(~c[3], 0, sel);
          uint32_t* o = oo + 4 * n, a[4];
#pragma unroll
          for (int j = 0; j < 4; j++) {
            o[j] = hfma(ga, h[4 * n + j], xv[4 * n + j]);
            a[j] = hmul(o[j], cb1);
          }
          a[2 * n + 1] = tagged(a[2 * n + 1], e1);
          pa[16 * n] = make_uint4(a[0], a[1], a[2], a[3]);
          if (n) { __syncwarp(); if (elect()) { flag_add(G, 8 * m + r); if (EA && r == 0) mbar_arrive(sb + 8 * (B_EW + 5)); } }
          if (ITW == 6) STAMPIF(tid == 0 && r < 2, 106 + n + 10 * r);
          if (ITW == 8) STAMPIF(lane == 0 && r == 0 && n, 110 + w);
          if (!SL) stsm4t(xa ^ (16 * n), o);
        }
        if (SL) { stsm4t(xa, oo); stsm4t(xa ^ 16, oo + 4); }
        if (r < 4) { zo += 256 * S_; co += 256; }
        auto x1st = [&]() {
          __syncwarp();
          int lane = tl & 31;
          if (!(OPQ & 2)) asm volatile("mov.u32 %0, %%laneid;" : "=r"(lane));
          const int c = 2 * (w & 1) + (lane & 1) + 2 * (lane & 2), g = lane >> 2;
          const uint32_t a = sb + SM_X + 4096 * r + (w >> 1) * 2048 + g * 128 + ((c ^ g) << 4);
          const uint4 v0 = lds128(a), v1 = lds128(a + 1024);
          char* po = (char*)gout + (2 * tbase(b) + 128 * (g & 6) + (g & 1)) * 2 * D_ + 256 * r + 64 * (w & 2) + 16 * c;
          if (ITW == 6) STAMPIF(tid == 0 && r < 2, 108 + 10 * r);
          stg128(po, v0);
          stg128(po + 2048 * D_, v1);
        };
        auto box1 = [&]() {
          if (BX3 >= 3) {
            mod_box(G, sb, b, 1, e1, tl);
            __syncwarp();
            if (elect()) mbar_arrive(sb + 8 * (B_BD + 1));
            STAMPIF(tid == 0, 73);
          } else mbar_wait(sb + 8 * (B_BD + 1), 0);
          if (BX3 < 4) spin(clk(), BD);
        };
        if (ZF == 1) {
          if (BX3 < 4 && r == 1 + MG) { if (XE) x1st(); box1(); }
          if (BX3 == 5 && r == 0) box1();
          zld();
        }
        if (BX3 == 6 && r == 0) box1();
        if (BX3 > 3 || ZF != 1 || !XE || r != 1 + MG) x1st();
        if (BX3 == 4 && r == 0) box1();
        __syncwarp();
        if (elect()) mbar_arrive(sb + 8 * (B_EW + r));
        STAMPIF(tid == 0, 29 + r);
        if (ZF == 0) { if (r == 1 + MG) box1(); zld(); }
      }
    }
    asm volatile("" : "+r"(tl));
    {
      const int lane = tl & 31;
      const uint4 m4 = lds128(sb + SM_SMALL + SMALL_LN + 16 * (lane & 1));
      const uint32_t m_[4] = {m4.x, m4.y, m4.z, m4.w}, xa = x_addr(sb, w, lane);
      float a[16];
#pragma unroll
      for (int i = 0; i < 16; i++) a[i] = 0.f;
#pragma unroll 2
      for (int n = 0; n < 10; n++) {
        uint32_t x_[4];
        ldsm4t(x_, (xa ^ (16 * (n & 1))) + 2048 * (n & 14));
#pragma unroll
        for (int i = 0; i < 4; i++) {
          const float d0 = blo(x_[i]) - blo(m_[i]), d1 = bhi(x_[i]) - bhi(m_[i]);
          a[4 * i] += d0; a[4 * i + 1] += d0 * d0; a[4 * i + 2] += d1; a[4 * i + 3] += d1 * d1;
        }
      }
      STAMPIF(lane == 0, 67 + (w & 1) + 11 * (w >> 1));
      bfly<16>(a, 16, lane & 16); bfly<8>(a, 8, lane & 8); bfly<4>(a, 4, lane & 4); bfly<2>(a, 2, lane & 2);
      if (lane == 0) mbar_arrive(sb + 8 * B_XF);
      STAMPIF(tid == 0, 88);
      sts32(sb + SM_SMALL + SMALL_RED + 16 * lane + 4 * w, __float_as_uint(a[0]));
      bar_sync(5, 128);
      if (w == 0) {
        const uint4 v = lds128(sb + SM_SMALL + SMALL_RED + 16 * lane);
        const float s1 = __uint_as_float(v.x) + __uint_as_float(v.y) + __uint_as_float(v.z) + __uint_as_float(v.w), s2 = __shfl_xor_sync(0xffffffffu, s1, 2);
        const int p = 8 * (lane & 1) + (lane >> 2);
        const float pv = blo(lds32(sb + SM_SMALL + SMALL_LN + 4 * (p >> 1)) >> (16 * (p & 1)));
        const float mu = s1 * (1.f / D_), var = fmaxf(s2 * (1.f / D_) - mu * mu, 0.f);
        const float sd = sdev(var);
        if (!(lane & 2)) st_tag(G->st2 + 16 * b + p, pack2(-0.5f * (pv + mu), 0.5f * sd), e1);
      }
      STAMPIF(tid == 0, 87);
    }
    {
      uint2 v;
      spin(clk(), SD);
      mbar_wait(sb + 8 * (B_BD + 2), 0);
#pragma unroll 1
      for (int i = 0;; i++) {
        v = ld_tag(G->st2 + 128 * m + tl);
        if (__all_sync(0xffffffffu, v.y == e1)) break;
        if (i > (1 << 20)) __trap();
      }
      const uint32_t hm = __byte_perm(v.x, 0, 0x1010), hs = __byte_perm(v.x, 0, 0x3232);
      sts128(sb + SM_STAT + 16 * tl, make_uint4(hm, hs, hm, hs));
      fence_async_s();
      __syncwarp();
      if (elect()) mbar_arrive(sb + 8 * B_ST2);
      STAMPIF(tid == 0, 21);
    }
    if (OF) {
      uint32_t ln, w, s;
      asm volatile("mov.u32 %0, %%laneid;\n\tmov.u32 %1, %%tid.x;\n\tmov.u32 %2, %%ctaid.x;" : "=r"(ln), "=r"(w), "=r"(s));
      w = (w >> 5) & 3; s = role<0>(s);
      const int m = s >> 3;
      s &= 7;
      mbar_wait(sb + 8 * B_X1, 0);
      mbar_wait(sb + 8 * B_GB, 0);
      const uint32_t ol = sb + SM_X + w * 2304 + (ln >> 3) * 16 + ln * 16, oz = ring - 65536 + w * 512 + (ln >> 3) * 128 + ((ln >> 3) ^ (ln & 7)) * 16;
      const char* po = (const char*)(gout + 1793 * D_) + (int)(640 * (s & 1) + 16 * ln - (ln >> 3) * (512 * D_ + 128));
#pragma unroll 1
      for (int n = 0; n < 8; n++) {
        const int p = n >> 1, c = n & 1, ob = out_blk(s, p);
        const uint4 gb = lds128(sb + SM_CB + 32 * (ln & 7) + 256 * ob);
        const char* pq = po + (128 * ob + 4 * D_ * tbase(8 * m + 4 * c + w));
        const uint32_t a0 = p ? oz + 65536 * p + 2048 * c : ol + 9216 * c, a1 = p ? (a0 ^ 64) + 4096 : a0 + 576, d = p ? 32768 : 1152;
        mbar_wait(sb + 8 * (B_OS + 4 * c + p), 0);
        const uint4 pf[4] = {lds128(a0), lds128(a1), lds128(a0 + d), lds128(a1 + d)};
#pragma unroll
        for (int i = 0; i < 4; i++)
          asm volatile("red.relaxed.gpu.global.add.noftz.v4.bf16x2 [%0], {%1, %2, %3, %4};" ::"l"(pq - (i & 1) * 2048 * D_ - (i >> 1) * 2 * D_),
                       "r"(hmul(pf[i].x, gb.x)), "r"(hmul(pf[i].y, gb.y)), "r"(hmul(pf[i].z, gb.z)), "r"(hmul(pf[i].w, gb.w)) : "memory");
        if (n == 1) { __syncwarp(); if (ln == 0) mbar_arrive(sb + 8 * B_OF); }
      }
    }
  } else {
    asm volatile("setmaxnreg.dec.sync.aligned.u32 24;");
    if (w != 0) {
    if (w == 2 && lane < 3) asm volatile("prefetch.tensormap [%0];" ::"l"(&P.mG + lane) : "memory");
    if (K3) {
      const uint32_t dv = *(const uint16_t*)(gD + 128 * min(lane, 4) + b);
#pragma unroll 1
      for (int j = 7 + w; j < 20; j += 3) {
        k1_job(sb, j >> 2, 32 * (j & 3) + lane, __shfl_sync(0xffffffffu, dv, j >> 2));
        if ((j & 3) == (K3 & 3)) {
          mbar_wait(sb + 8 * (B_KJ + (j >> 2)), 0);
          const uint32_t t = lds32(sb + SM_SMALL + SMALL_TS + 4 * (j >> 2));
          while (clk() - t < UD);
        }
        __syncwarp();
        if (lane == 0) mbar_arrive(sb + 8 * (B_K + (j >> 2) - 2));
      }
      STAMPIF(lane == 0 && w == 3, 74);
    } else if (w & 1) {
      const uint32_t dv = *(const uint16_t*)(gD + 128 * min(lane, 4) + b);
#pragma unroll 1
      for (int j = 4; j < 10; j++) {
        k1_job(sb, j >> 1, 64 * (j & 1) + 16 * (w & 2) + lane, K1N ? __shfl_sync(0xffffffffu, dv, j >> 1) : *(const uint16_t*)(gD + 64 * (j & 14) + b));
        if (ITW == 5) STAMPIF(tid == 32, 98 + (j >> 1));
        if (UT == 5 && UD && w == 1 && (j & 1)) {
          mbar_wait(sb + 8 * (B_KJ + (j >> 1)), 0);
          const uint32_t t = lds32(sb + SM_SMALL + SMALL_TS + 4 * (j >> 1));
          while (clk() - t < UD);
        }
        __syncwarp();
        if (lane == 0) mbar_arrive(sb + 8 * (B_K + (j >> 1) - 2));
      }
      STAMPIF(tid == 32, 74);
    }
    if (w == 1) {
     {
      mbar_wait(sb + 8 * B_KVS, 0);
      const uint32_t e1 = epoch(sb);
      if (elect()) {
        if (P3) { const uint32_t v = e1 * 32 - 32; sts128(sb + SM_SMALL + SMALL_H, make_uint4(v, v, v, v)); sts32(sb + SM_SMALL + SMALL_H + 16, v); }
        if (ER) mbar_wait(sb + 8 * B_KV4, 0);
        mbar_wait(sb + 8 * (B_EW + 5 * EA), 0);
        spin(clk(), AD);
#pragma unroll 1
        for (int it = NS; it < 20; it++) {
          int st = it % 5;
          if ((it & 3) == 0 || it == NS) { if (P3) hint_wait(G, sb + SM_SMALL + SMALL_H, 8 * m + (it >> 2), e1 * 32); else flag_wait(G, 8 * m + (it >> 2), e1 * 32); STAMP(45 + (it >> 2)); }
          if (NS && it == NS) mbar_arrive(sb + 8 * B_FS);
          mbar_wait(sb + 8 * (B_E1 + st), (it / 5) & 1);
          uint32_t fb = sb + 8 * (B_A + st);
          mbar_expect(fb, 8192);
          bulk_g2s(ring + st * 32768, G->AT + (20 * m + it) * 4096, 8192, fb);
        }
        mbar_wait(sb + 8 * B_XF, 0);
        flag_wait(G, 8 * m + FL_X, e1 * 8);
        mbar_arrive(sb + 8 * B_X1);
        STAMP(86);
      }
     }
    } else if (w == 2) {
      if (lane < 4) mbar_expect(sb + 8 * (B_RECV + lane), 12288);
      if (UT == 2) { bar_arrive(1, 288); bar_arrive(2, 288); }
      int ph = 0;
#pragma unroll 1
      for (int ch = UT; ch < 5; ch++) {
        const uint32_t ub = chan_base(sb, ch) + KSZ;
        uint4* pu = (uint4*)(G->kvT + (128 * ch + b) * S_);
        mbar_wait(sb + 8 * (B_KJ + ch), 0);
        const uint32_t t0 = lds32(sb + SM_SMALL + SMALL_TS + 4 * ch);
        while (clk() - t0 < (ch ? UD : UD0));
#pragma unroll 1
        for (int i = 0;; i++) {
          if (elect()) { mbar_expect(sb + 8 * B_U, 4096); bulk_g2s(ub, pu, 4096, sb + 8 * B_U); }
          if (ITW == 5) STAMPIF(lane == 0, 110 + ch);
          mbar_wait(sb + 8 * B_U, ph);
          ph ^= 1;
          uint32_t t = 1;
#pragma unroll
          for (int j = 0; j < 8; j++) t &= lds32(ub + 16 * lane + 512 * j + 12);
          if (__all_sync(0xffffffffu, t)) break;
          if (i > (1 << 20)) __trap();
        }
        if (ITW == 5) STAMPIF(lane == 0, 105 + ch);
        if (ch > 1) mbar_wait(sb + 8 * (B_Z + ch - 2), 0);
        bar_arrive(1 + (ch & 1), 288);
#pragma unroll
        for (int j = 0; j < 8; j++) stg128(pu + lane + 32 * j, make_uint4(0, 0, 0, 0));
      }
      if (ITW == 8) { mbar_wait(sb + 8 * B_X, 0); STAMPIF(lane == 0, 100); mbar_wait(sb + 8 * (B_X + 1), 0); STAMPIF(lane == 0, 101); }
      mbar_wait(sb + 8 * B_BD, 0);
      const uint32_t e1 = epoch(sb), ao = 256 * (lane & 16) + 32 * (lane & 15) + 4 * (lane & 4) + (lane & 8) + 4;
      int it = 0;
      uint32_t pm = (1 << NS) - 1;
      bool ok = false;
      if (NS) {
        if (lane < NS) mbar_expect(sb + 8 * (B_A + lane), 8192);
        mbar_wait(sb + 8 * (lane < NS ? B_E1 + lane : B_EW + 5), 0);
        __syncwarp();
        spin(clk(), AT1);
        spin(t_0, AT0);
        if (elect()) {
#pragma unroll
          for (int i = 0; i < NS; i++) bulk_g2s(ring + i * 32768, G->AT + (20 * m + i) * 4096, 8192, sb + 8 * (B_A + i));
        }
        __syncwarp();
        STAMPIF(lane == 0, 84);
#pragma unroll 1
        for (; it < NS; it++) {
          if (!ok) mbar_wait(sb + 8 * (B_A + it), 0);
          uint32_t t = 0, v[8];
          if (PC) ok = mbar_test(sb + 8 * (B_A + it + 1), 0);
#pragma unroll
          for (int j = 0; j < 8; j++) v[j] = ldv32(ring + it * 32768 + ao + 512 * j);
#pragma unroll
          for (int j = 0; j < 8; j++) t |= v[7 - j] ^ e1;
          if (__any_sync(0xffffffffu, t & 1)) {
            ok = false;
            fence_async_s();
            mbar_wait(sb + 8 * (lane > it && lane < NS ? B_A + lane : B_FS), 0);
            __syncwarp();
            if (lane >= it && lane < NS) mbar_expect(sb + 8 * (B_A + lane), 8192);
            __syncwarp();
            if (elect()) {
#pragma unroll
              for (int i = 0; i < NS; i++)
                if (i >= it) bulk_g2s(ring + i * 32768, G->AT + (20 * m + i) * 4096, 8192, sb + 8 * (B_A + i));
            }
            __syncwarp();
            STAMPIF(lane == 0, 85);
            break;
          }
          if (lane == 0) mbar_arrive(sb + 8 * (B_F1 + it));
        }
      }
#pragma unroll 1
      for (int st = it; it < 20; it++) {
        const uint32_t a = ring + st * 32768 + ao;
        if (!ok) mbar_wait(sb + 8 * (B_A + st), (pm >> st) & 1);
        pm ^= 1 << st;
        const int nx = st == 4 ? 0 : st + 1;
        if (ITW == 7) STAMPIF(lane == 0 && it < 4, 100 + it);
        if (ITW == 8) STAMPIF(lane == 0 && it < 2, 114 + it);
        uint32_t t = 0, v[8];
        if (PC) ok = mbar_test(sb + 8 * (B_A + nx), (pm >> nx) & 1);
#pragma unroll
        for (int j = 0; j < 8; j++) v[j] = ldv32(a + 512 * j);
#pragma unroll
        for (int j = 0; j < 8; j++) t |= v[7 - j] ^ e1;
        if (__any_sync(0xffffffffu, t & 1)) {
#pragma unroll 1
          for (int j = 0; j < 8; j++) a_check(a + 512 * j, (const char*)G->AT + (20 * m + it) * 8192 + ao + 512 * j, e1);
        }
        if (lane == 0) mbar_arrive(sb + 8 * (B_F1 + st));
        if (ITW == 7) STAMPIF(lane == 0 && it < 4, 104 + it);
        if (ITW == 8) STAMPIF(lane == 0 && it < 2, 116 + it);
        st = nx;
      }
    } else {
      mbar_wait(sb + 8 * B_KVS, 0);
      auto rel = [&](int ch) { mbar_wait(sb + 8 * (B_Z + ch), 0); if (lane <= (ch >> 2)) mbar_arrive(sb + 8 * (B_E1 + 2 + (ch >> 1))); };
      if (RL) { rel(0); rel(1); rel(2); }
      mbar_wait(sb + 8 * (B_BD + 1), 0);
      if (!BI && b >= 96 && elect()) { load_box(P, sb, b, 4); load_box(P, sb, b, 5); }
      const uint32_t t1 = clk();
      if (RL) { rel(3); rel(4); }
      spin(t1, CD);
      __syncwarp();
      const uint32_t e1 = epoch(sb);
#pragma unroll 1
      for (int n = 0; n < 5; n++) {
        int lane;
        asm volatile("mov.u32 %0, %%laneid;" : "=r"(lane));
        if (n == 3) {
          fence_async_s();
          __syncwarp();
          if (lane == 0) mbar_arrive(sb + 8 * B_F);
          STAMPIF(lane == 0, 34);
          {
            mbar_wait(sb + 8 * (B_EW + 4), 0);
            const char* po = (char*)gout + (2 * tbase(b) + 64 * (lane & 28) + ((lane >> 1) & 1)) * 2 * D_ + (lane & 1) * 640;
            uint32_t v = 0;
#pragma unroll
            for (int r = 0; r < 5; r++) v ^= rdback(po + 128 * r);
            rdwait(sb, v);
            __syncwarp();
            if (lane == 0) flag_add(G, 8 * m + FL_X);
            STAMPIF(lane == 0, 94);
          }
          mbar_wait(sb + 8 * (B_BD + 2), 0);
          if (lane < 2) mbar_arrive(sb + 8 * (B_E1 + 5));
          if (m < 12) {
            rdwait(sb, rdback(G->cimg + s * 3072 + (m % 6) * 512 + (m < 6 ? 0 : 256) + 64 * (lane & 3)));
            __syncwarp();
            if (lane == 0) flag_add(G, FL_C + 8 * s);
            STAMPIF(lane == 0, 35);
          }
          if (elect()) {
            flag_wait(G, FL_C + 8 * s, e1 * 12);
            fence_async_g();
            STAMP(54);
            mbar_expect(sb + 8 * B_EXT, 6144);
            bulk_g2s(sb + SM_EXT, G->cimg + s * 3072, 6144, sb + 8 * B_EXT);
          }
          __syncwarp();
          mbar_wait(sb + 8 * B_ST2, 0);
        }
        const int j = n < 3 ? min(16 * n + (lane >> 1), 39) : min(16 * n - 8 + (lane >> 1), 59), k = j < 20 ? j : j < 40 ? j - 20 : j - 40;
        const uint2* pj = (const uint2*)(G->mv + 2048 * (e1 & 1) + 4 * (lane & 1) + 8 * (k + (j < 40 ? (j < 20 ? 160 : 120) + (m < 6 ? 0 : 20) : 200 + 20 * (s & 1))));
        uint4 a;
#pragma unroll 1
        for (int i = 0;; i++) {
          a = ld_tag2(pj);
          if (__all_sync(0xffffffffu, a.x != 0)) break;
          if (i > (1 << 20)) __trap();
        }
        const uint32_t d = sb + SM_CB + 64 * k + 8 * (lane & 1) + (j >= 20 && j < 40 ? 16 : 0);
        sts64(d, ~__byte_perm(a.x, a.y, 0x5410), ~__byte_perm(a.z, a.w, 0x5410));
        sts64(d + 32, ~__byte_perm(a.x, a.y, 0x7632), ~__byte_perm(a.z, a.w, 0x7632));
      }
      __syncwarp();
      if (lane == 0) mbar_arrive(sb + 8 * B_GB);
      STAMPIF(lane == 0, 39);
    }
    } else {
      STAMPIF(lane == 0, 62);
      int rw = sched_run<0>(P, In{gk, gv, gsk, gWg, gWu, gWd, gss}, sb, b, lane, __shfl_sync(0xffffffffu, t_0, 0));
      if (elect()) {
        STAMP(69);
        mbar_wait(sb + 8 * B_KVS, 0);
        if (ER) mbar_wait(sb + 8 * B_KV4, 0);
        STAMP(70);
        int rd = 0, c = 0;
#pragma unroll 1
        for (int it = 0; it < 20; it++) {
          load_w(P, sb, s, it);
          if ((PWM >> it) & 1) { l2_prefetch(gWg + (128 * rw + b) * F_, 2 * F_); l2_prefetch(gWu + (128 * rw + b) * F_, 2 * F_); rw++; }
          if ((PDM >> it) & 1) { l2_prefetch(gWd + (512 * rd + 4 * b) * D_, 8 * D_); rd++; }
          if (BI && it == BI && b >= 96) { mbar_wait(sb + 8 * (B_BD + 1), 0); load_box(P, sb, b, 4); load_box(P, sb, b, 5); }
          if (((STM >> it) & 1) && b < 96) {
            const int grp = m % 6;
            if (c == 4) mbar_wait(sb + 8 * (B_BD + 1), 0);
            if (c == 0) mbar_expect(sb + 8 * B_ST0, 40960);
#pragma unroll
            for (int j = 0; j < 2; j++, c++)
              tma2d(sb + (c < 2 ? SM_EXT : SM_RING + R_X - 8192) + 4096 * c, &P.mG + (grp & 1), 192 * s + 64 * (grp >> 1), (m < 6 ? 0 : 320) + 32 * c, sb + 8 * B_ST0);
          }
        }
#pragma unroll
        for (int k = 0; k < 10; k++) {
          const int st = (k + 5) % 6, pe = k < 4 ? k >> 1 : k & 1, ps = k < 4 ? k & 1 : k >> 1;
          mbar_wait(sb + 8 * (k < 6 ? B_E1 + st : B_EB + k - 6), 0);
          if (k == 2) mbar_arrive_remote(mapa(sb + 8 * B_P0, (b & 1) ^ 1));
          mbar_expect(sb + 8 * (B_FB + k), 24576);
          tma2d(ring + st * 32768 + 8192, &P.mD, 320 * (s & 1) + 64 * out_blk(s, ps), 192 * (s ^ pe), sb + 8 * (B_FB + k));
        }
      }
    }
  }
}

typedef CUresult (*EncFn)(CUtensorMap*, CUtensorMapDataType, cuuint32_t, void*, const cuuint64_t*, const cuuint64_t*, const cuuint32_t*, const cuuint32_t*,
                          CUtensorMapInterleave, CUtensorMapSwizzle, CUtensorMapL2promotion, CUtensorMapFloatOOBfill);
static void mkmap(EncFn enc, CUtensorMap* m, const void* p, int rank, const cuuint64_t* dims, const cuuint64_t* strides, const cuuint32_t* box, CUtensorMapSwizzle sw) {
  cuuint32_t es[5] = {1, 1, 1, 1, 1};
  CUresult r = enc(m, CU_TENSOR_MAP_DATA_TYPE_BFLOAT16, rank, (void*)p, dims, strides, box, es, CU_TENSOR_MAP_INTERLEAVE_NONE, sw,
                   CU_TENSOR_MAP_L2_PROMOTION_L2_128B, CU_TENSOR_MAP_FLOAT_OOB_FILL_NONE);
  if (r != CUDA_SUCCESS) fprintf(stderr, "tensor map encode failed: %d\n", (int)r);
}

extern "C" void kernel_launch(void* const* d_in, const int* in_sizes, int n_in, void* d_out, int out_size) {
  void* fn = nullptr;
  cudaDriverEntryPointQueryResult qr;
  cudaGetDriverEntryPoint("cuTensorMapEncodeTiled", &fn, cudaEnableDefault, &qr);
  EncFn enc = (EncFn)fn;
  Scr* G;
  cudaGetSymbolAddress((void**)&G, g_scr);
  Params P;
  { cuuint64_t d[] = {128, 16, 640}, st[] = {256, 4096}; cuuint32_t bx[] = {144, 16, 1}; mkmap(enc, &P.mS, d_in[4], 3, d, st, bx, CU_TENSOR_MAP_SWIZZLE_NONE); }
  { cuuint64_t d[] = {3840, 64, 10}, st[] = {7680, 64 * 7680}; cuuint32_t bx[] = {16, 64, 5}; mkmap(enc, &P.mWm, d_in[11], 3, d, st, bx, CU_TENSOR_MAP_SWIZZLE_32B); }
  { cuuint64_t d[] = {32, 20, 256, 8}, st[] = {64, 10240, 1280}; cuuint32_t bx[] = {40, 1, 9, 8}, bx2[] = {40, 1, 8, 8};
    mkmap(enc, &P.mK, d_in[1], 4, d, st, bx, CU_TENSOR_MAP_SWIZZLE_NONE); mkmap(enc, &P.mV, d_in[2], 4, d, st, bx2, CU_TENSOR_MAP_SWIZZLE_NONE); }
  { cuuint64_t d[] = {1536, 640}, st[] = {3072}; cuuint32_t bx[] = {64, 32};
    mkmap(enc, &P.mG, d_in[7], 2, d, st, bx, CU_TENSOR_MAP_SWIZZLE_128B); mkmap(enc, &P.mU, d_in[8], 2, d, st, bx, CU_TENSOR_MAP_SWIZZLE_128B); }
  { cuuint64_t d[] = {640, 1536}, st[] = {1280}; cuuint32_t bx[] = {64, 192}; mkmap(enc, &P.mD, d_in[9], 2, d, st, bx, CU_TENSOR_MAP_SWIZZLE_128B); }
  { cuuint64_t d[] = {64, 2, 8, 10, 128}, st[] = {1280, 256 * 1280, 128, 2560}; cuuint32_t bx[] = {64, 2, 8, 5, 1}; mkmap(enc, &P.mX, d_in[0], 5, d, st, bx, CU_TENSOR_MAP_SWIZZLE_128B); }
  cudaFuncSetAttribute(fused_kernel, cudaFuncAttributeMaxDynamicSharedMemorySize, SM_TOTAL + DEVSM);
  cudaLaunchConfig_t cfg = {};
  cfg.gridDim = dim3(128); cfg.blockDim = dim3(512); cfg.dynamicSmemBytes = SM_TOTAL + DEVSM; cfg.stream = cudaStreamPerThread;
  cudaLaunchAttribute at[1];
  at[0].id = cudaLaunchAttributeClusterDimension; at[0].val.clusterDim.x = 2; at[0].val.clusterDim.y = 1; at[0].val.clusterDim.z = 1;
  cfg.attrs = at; cfg.numAttrs = 1;
  cudaLaunchKernelEx(&cfg, fused_kernel, (const bf16*)d_in[1], (const bf16*)d_in[2], (const bf16*)d_in[3], (const bf16*)d_in[5], (const bf16*)d_in[10], G,
                     (const bf16*)d_in[7], (const bf16*)d_in[8], (const bf16*)d_in[9], (bf16*)d_out, (const bf16*)d_in[4], P);
}
```

```cpp
#include <cuda_runtime.h>
#include <cuda.h>
#include <cuda_bf16.h>
#include <stdio.h>
#include <stdint.h>
typedef __nv_bfloat16 bf16;
__device__ __forceinline__ uint32_t smem_u32(const void* p) { return (uint32_t)__cvta_generic_to_shared(p); }
__device__ __forceinline__ void mbar_init(uint32_t bar, int cnt) { asm volatile("mbarrier.init.shared::cta.b64 [%0], %1;" ::"r"(bar), "r"(cnt) : "memory"); }
__device__ __forceinline__ void mbar_expect(uint32_t bar, int bytes) { asm volatile("mbarrier.arrive.expect_tx.shared::cta.b64 _, [%0], %1;" ::"r"(bar), "r"(bytes) : "memory"); }
__device__ __forceinline__ void mbar_arrive(uint32_t bar) { asm volatile("mbarrier.arrive.shared::cta.b64 _, [%0];" ::"r"(bar) : "memory"); }
__device__ __forceinline__ void mbar_arrive_remote(uint32_t bar) { asm volatile("mbarrier.arrive.relaxed.cluster.shared::cluster.b64 _, [%0];" ::"r"(bar) : "memory"); }
__device__ __forceinline__ uint32_t mapa(uint32_t a, uint32_t cta) { uint32_t r; asm("mapa.shared::cluster.u32 %0, %1, %2;" : "=r"(r) : "r"(a), "r"(cta)); return r; }
__device__ __forceinline__ bool mbar_try(uint32_t bar, int parity) {
  uint32_t ok;
  asm volatile("{\n.reg .pred p;\nmbarrier.try_wait.parity.shared::cta.b64 p, [%1], %2;\nselp.u32 %0, 1, 0, p;\n}" : "=r"(ok) : "r"(bar), "r"(parity) : "memory");
  return ok;
}
__device__ __forceinline__ void mbar_wait(uint32_t bar, int parity) {
#pragma unroll 1
  for (int i = 0; i < (1 << 20); i++) { if (mbar_try(bar, parity)) return; }
  __trap();
}
__device__ __forceinline__ bool elect() {
  uint32_t p;
  asm volatile("{\n.reg .pred P;\nelect.sync _|P, 0xffffffff;\nselp.u32 %0, 1, 0, P;\n}" : "=r"(p));
  return p;
}
__device__ __forceinline__ void tma2d(uint32_t dst, const CUtensorMap* m, int c0, int c1, uint32_t bar) {
  asm volatile("cp.async.bulk.tensor.2d.shared::cluster.global.mbarrier::complete_tx::bytes [%0], [%1, {%3, %4}], [%2];" ::"r"(dst), "l"(m), "r"(bar), "r"(c0), "r"(c1) : "memory");
}
__device__ __forceinline__ void tma3d(uint32_t dst, const CUtensorMap* m, int c0, int c1, int c2, uint32_t bar) {
  asm volatile("cp.async.bulk.tensor.3d.shared::cluster.global.mbarrier::complete_tx::bytes [%0], [%1, {%3, %4, %5}], [%2];" ::"r"(dst), "l"(m), "r"(bar), "r"(c0), "r"(c1), "r"(c2) : "memory");
}
__device__ __forceinline__ void tma4d(uint32_t dst, const CUtensorMap* m, int c0, int c1, int c2, int c3, uint32_t bar) {
  asm volatile("cp.async.bulk.tensor.4d.shared::cluster.global.mbarrier::complete_tx::bytes [%0], [%1, {%3, %4, %5, %6}], [%2];" ::"r"(dst), "l"(m), "r"(bar), "r"(c0), "r"(c1), "r"(c2), "r"(c3) : "memory");
}
__device__ __forceinline__ void tma5d(uint32_t dst, const CUtensorMap* m, int c0, int c1, int c2, int c3, int c4, uint32_t bar) {
  asm volatile("cp.async.bulk.tensor.5d.shared::cluster.global.mbarrier::complete_tx::bytes [%0], [%1, {%3, %4, %5, %6, %7}], [%2];" ::"r"(dst), "l"(m), "r"(bar), "r"(c0), "r"(c1), "r"(c2), "r"(c3), "r"(c4) : "memory");
}
__device__ __forceinline__ void tma_store2d(const CUtensorMap* m, uint32_t src, int c0, int c1) {
  asm volatile("cp.async.bulk.tensor.2d.global.shared::cta.bulk_group [%0, {%2, %3}], [%1];" ::"l"(m), "r"(src), "r"(c0), "r"(c1) : "memory");
}
__device__ __forceinline__ void tma_store4d(const CUtensorMap* m, uint32_t src, int c0, int c1, int c2, int c3) {
  asm volatile("cp.async.bulk.tensor.4d.global.shared::cta.bulk_group [%0, {%2, %3, %4, %5}], [%1];" ::"l"(m), "r"(src), "r"(c0), "r"(c1), "r"(c2), "r"(c3) : "memory");
}
__device__ __forceinline__ void tma_prefetch2d(const CUtensorMap* m, int c0, int c1) {
  asm volatile("cp.async.bulk.prefetch.tensor.2d.L2.global [%0, {%1, %2}];" ::"l"(m), "r"(c0), "r"(c1) : "memory");
}
__device__ __forceinline__ void bulk_g2s(uint32_t dst, const void* src, int bytes, uint32_t bar) {
  asm volatile("cp.async.bulk.shared::cluster.global.mbarrier::complete_tx::bytes [%0], [%1], %2, [%3];" ::"r"(dst), "l"(src), "r"(bytes), "r"(bar) : "memory");
}
__device__ __forceinline__ void bulk_s2g(void* dst, uint32_t src, int bytes) {
  asm volatile("cp.async.bulk.global.shared::cta.bulk_group [%0], [%1], %2;" ::"l"(dst), "r"(src), "r"(bytes) : "memory");
}
__device__ __forceinline__ void cp16(uint32_t dst, const void* src) { asm volatile("cp.async.cg.shared.global [%0], [%1], 16;" ::"r"(dst), "l"(src) : "memory"); }
__device__ __forceinline__ void cp16z(uint32_t dst, const void* src, int n) { asm volatile("cp.async.cg.shared.global [%0], [%1], 16, %2;" ::"r"(dst), "l"(src), "r"(n) : "memory"); }
__device__ __forceinline__ void cp_arrive(uint32_t bar) { asm volatile("cp.async.mbarrier.arrive.noinc.shared::cta.b64 [%0];" ::"r"(bar) : "memory"); }
__device__ __forceinline__ void st_async4(uint32_t dst, const uint32_t* v, uint32_t bar) {
  asm volatile("st.async.weak.shared::cluster.mbarrier::complete_tx::bytes.v4.b32 [%0], {%1, %2, %3, %4}, [%5];" ::"r"(dst), "r"(v[0]), "r"(v[1]), "r"(v[2]), "r"(v[3]), "r"(bar) : "memory");
}
__device__ __forceinline__ void wg_fence() { asm volatile("wgmma.fence.sync.aligned;" ::: "memory"); }
__device__ __forceinline__ void wg_commit() { asm volatile("wgmma.commit_group.sync.aligned;" ::: "memory"); }
template <int N> __device__ __forceinline__ void wg_wait() { asm volatile("wgmma.wait_group.sync.aligned %0;" ::"n"(N) : "memory"); }
__device__ __forceinline__ uint64_t mkdesc(uint32_t addr, uint32_t lbo, uint32_t sbo, uint32_t swz) {
  return (uint64_t)((addr & 0x3FFFF) >> 4) | ((uint64_t)(lbo >> 4) << 16) | ((uint64_t)(sbo >> 4) << 32) | ((uint64_t)swz << 62);
}
__device__ __forceinline__ void ldsm4t(uint32_t* r, uint32_t a) {
  asm volatile("ldmatrix.sync.aligned.m8n8.x4.trans.shared.b16 {%0,%1,%2,%3}, [%4];" : "=r"(r[0]), "=r"(r[1]), "=r"(r[2]), "=r"(r[3]) : "r"(a) : "memory");
}
__device__ __forceinline__ void stsm4(uint32_t a, const uint32_t* r) {
  asm volatile("stmatrix.sync.aligned.m8n8.x4.shared.b16 [%0], {%1,%2,%3,%4};" ::"r"(a), "r"(r[0]), "r"(r[1]), "r"(r[2]), "r"(r[3]) : "memory");
}
__device__ __forceinline__ void stsm4t(uint32_t a, const uint32_t* r) {
  asm volatile("stmatrix.sync.aligned.m8n8.x4.trans.shared.b16 [%0], {%1,%2,%3,%4};" ::"r"(a), "r"(r[0]), "r"(r[1]), "r"(r[2]), "r"(r[3]) : "memory");
}
__device__ __forceinline__ void bar_sync(int id, int n) { asm volatile("bar.sync %0, %1;" ::"r"(id), "r"(n) : "memory"); }
__device__ __forceinline__ void bar_arrive(int id, int n) { asm volatile("bar.arrive %0, %1;" ::"r"(id), "r"(n) : "memory"); }
__device__ __forceinline__ uint32_t lds32(uint32_t a) { uint32_t v; asm volatile("ld.shared.b32 %0, [%1];" : "=r"(v) : "r"(a) : "memory"); return v; }
__device__ __forceinline__ uint2 lds64(uint32_t a) { uint2 v; asm volatile("ld.shared.v2.b32 {%0,%1}, [%2];" : "=r"(v.x), "=r"(v.y) : "r"(a) : "memory"); return v; }
__device__ __forceinline__ uint4 lds128(uint32_t a) { uint4 v; asm volatile("ld.shared.v4.b32 {%0,%1,%2,%3}, [%4];" : "=r"(v.x), "=r"(v.y), "=r"(v.z), "=r"(v.w) : "r"(a) : "memory"); return v; }
__device__ __forceinline__ void sts16(uint32_t a, uint32_t v) { asm volatile("st.shared.b16 [%0], %1;" ::"r"(a), "h"((uint16_t)v) : "memory"); }
__device__ __forceinline__ void sts32(uint32_t a, uint32_t v) { asm volatile("st.shared.b32 [%0], %1;" ::"r"(a), "r"(v) : "memory"); }
__device__ __forceinline__ void sts64(uint32_t a, uint32_t x, uint32_t y) { asm volatile("st.shared.v2.b32 [%0], {%1,%2};" ::"r"(a), "r"(x), "r"(y) : "memory"); }
__device__ __forceinline__ void sts128(uint32_t a, uint4 v) { asm volatile("st.shared.v4.b32 [%0], {%1,%2,%3,%4};" ::"r"(a), "r"(v.x), "r"(v.y), "r"(v.z), "r"(v.w) : "memory"); }
template<int TB> __device__ __forceinline__ void wgmma_rs_n128(float* d, const uint32_t* a, uint64_t db, int sd) {
  asm volatile("{\n.reg .pred p;\nsetp.ne.b32 p, %69, 0;\n"
    "wgmma.mma_async.sync.aligned.m64n128k16.f32.bf16.bf16 {%0, %1, %2, %3, %4, %5, %6, %7, %8, %9, %10, %11, %12, %13, %14, %15, %16, %17, %18, %19, %20, %21, %22, %23, %24, %25, %26, %27, %28, %29, %30, %31, %32, %33, %34, %35, %36, %37, %38, %39, %40, %41, %42, %43, %44, %45, %46, %47, %48, %49, %50, %51, %52, %53, %54, %55, %56, %57, %58, %59, %60, %61, %62, %63}, {%64, %65, %66, %67}, %68, p, 1, 1, %70;\n}"
    : "+f"(d[0]), "+f"(d[1]), "+f"(d[2]), "+f"(d[3]), "+f"(d[4]), "+f"(d[5]), "+f"(d[6]), "+f"(d[7]), "+f"(d[8]), "+f"(d[9]), "+f"(d[10]), "+f"(d[11]), "+f"(d[12]), "+f"(d[13]), "+f"(d[14]), "+f"(d[15]), "+f"(d[16]), "+f"(d[17]), "+f"(d[18]), "+f"(d[19]), "+f"(d[20]), "+f"(d[21]), "+f"(d[22]), "+f"(d[23]), "+f"(d[24]), "+f"(d[25]), "+f"(d[26]), "+f"(d[27]), "+f"(d[28]), "+f"(d[29]), "+f"(d[30]), "+f"(d[31]), "+f"(d[32]), "+f"(d[33]), "+f"(d[34]), "+f"(d[35]), "+f"(d[36]), "+f"(d[37]), "+f"(d[38]), "+f"(d[39]), "+f"(d[40]), "+f"(d[41]), "+f"(d[42]), "+f"(d[43]), "+f"(d[44]), "+f"(d[45]), "+f"(d[46]), "+f"(d[47]), "+f"(d[48]), "+f"(d[49]), "+f"(d[50]), "+f"(d[51]), "+f"(d[52]), "+f"(d[53]), "+f"(d[54]), "+f"(d[55]), "+f"(d[56]), "+f"(d[57]), "+f"(d[58]), "+f"(d[59]), "+f"(d[60]), "+f"(d[61]), "+f"(d[62]), "+f"(d[63])
    : "r"(a[0]), "r"(a[1]), "r"(a[2]), "r"(a[3]), "l"(db), "r"(sd), "n"(TB));
}

template<int TB> __device__ __forceinline__ void wgmma_rs_n160(float* d, const uint32_t* a, uint64_t db, int sd) {
  asm volatile("{\n.reg .pred p;\nsetp.ne.b32 p, %85, 0;\n"
    "wgmma.mma_async.sync.aligned.m64n160k16.f32.bf16.bf16 {%0, %1, %2, %3, %4, %5, %6, %7, %8, %9, %10, %11, %12, %13, %14, %15, %16, %17, %18, %19, %20, %21, %22, %23, %24, %25, %26, %27, %28, %29, %30, %31, %32, %33, %34, %35, %36, %37, %38, %39, %40, %41, %42, %43, %44, %45, %46, %47, %48, %49, %50, %51, %52, %53, %54, %55, %56, %57, %58, %59, %60, %61, %62, %63, %64, %65, %66, %67, %68, %69, %70, %71, %72, %73, %74, %75, %76, %77, %78, %79}, {%80, %81, %82, %83}, %84, p, 1, 1, %86;\n}"
    : "+f"(d[0]), "+f"(d[1]), "+f"(d[2]), "+f"(d[3]), "+f"(d[4]), "+f"(d[5]), "+f"(d[6]), "+f"(d[7]), "+f"(d[8]), "+f"(d[9]), "+f"(d[10]), "+f"(d[11]), "+f"(d[12]), "+f"(d[13]), "+f"(d[14]), "+f"(d[15]), "+f"(d[16]), "+f"(d[17]), "+f"(d[18]), "+f"(d[19]), "+f"(d[20]), "+f"(d[21]), "+f"(d[22]), "+f"(d[23]), "+f"(d[24]), "+f"(d[25]), "+f"(d[26]), "+f"(d[27]), "+f"(d[28]), "+f"(d[29]), "+f"(d[30]), "+f"(d[31]), "+f"(d[32]), "+f"(d[33]), "+f"(d[34]), "+f"(d[35]), "+f"(d[36]), "+f"(d[37]), "+f"(d[38]), "+f"(d[39]), "+f"(d[40]), "+f"(d[41]), "+f"(d[42]), "+f"(d[43]), "+f"(d[44]), "+f"(d[45]), "+f"(d[46]), "+f"(d[47]), "+f"(d[48]), "+f"(d[49]), "+f"(d[50]), "+f"(d[51]), "+f"(d[52]), "+f"(d[53]), "+f"(d[54]), "+f"(d[55]), "+f"(d[56]), "+f"(d[57]), "+f"(d[58]), "+f"(d[59]), "+f"(d[60]), "+f"(d[61]), "+f"(d[62]), "+f"(d[63]), "+f"(d[64]), "+f"(d[65]), "+f"(d[66]), "+f"(d[67]), "+f"(d[68]), "+f"(d[69]), "+f"(d[70]), "+f"(d[71]), "+f"(d[72]), "+f"(d[73]), "+f"(d[74]), "+f"(d[75]), "+f"(d[76]), "+f"(d[77]), "+f"(d[78]), "+f"(d[79])
    : "r"(a[0]), "r"(a[1]), "r"(a[2]), "r"(a[3]), "l"(db), "r"(sd), "n"(TB));
}

template<int TB> __device__ __forceinline__ void wgmma_rs_n192(float* d, const uint32_t* a, uint64_t db, int sd) {
  asm volatile("{\n.reg .pred p;\nsetp.ne.b32 p, %101, 0;\n"
    "wgmma.mma_async.sync.aligned.m64n192k16.f32.bf16.bf16 {%0, %1, %2, %3, %4, %5, %6, %7, %8, %9, %10, %11, %12, %13, %14, %15, %16, %17, %18, %19, %20, %21, %22, %23, %24, %25, %26, %27, %28, %29, %30, %31, %32, %33, %34, %35, %36, %37, %38, %39, %40, %41, %42, %43, %44, %45, %46, %47, %48, %49, %50, %51, %52, %53, %54, %55, %56, %57, %58, %59, %60, %61, %62, %63, %64, %65, %66, %67, %68, %69, %70, %71, %72, %73, %74, %75, %76, %77, %78, %79, %80, %81, %82, %83, %84, %85, %86, %87, %88, %89, %90, %91, %92, %93, %94, %95}, {%96, %97, %98, %99}, %100, p, 1, 1, %102;\n}"
    : "+f"(d[0]), "+f"(d[1]), "+f"(d[2]), "+f"(d[3]), "+f"(d[4]), "+f"(d[5]), "+f"(d[6]), "+f"(d[7]), "+f"(d[8]), "+f"(d[9]), "+f"(d[10]), "+f"(d[11]), "+f"(d[12]), "+f"(d[13]), "+f"(d[14]), "+f"(d[15]), "+f"(d[16]), "+f"(d[17]), "+f"(d[18]), "+f"(d[19]), "+f"(d[20]), "+f"(d[21]), "+f"(d[22]), "+f"(d[23]), "+f"(d[24]), "+f"(d[25]), "+f"(d[26]), "+f"(d[27]), "+f"(d[28]), "+f"(d[29]), "+f"(d[30]), "+f"(d[31]), "+f"(d[32]), "+f"(d[33]), "+f"(d[34]), "+f"(d[35]), "+f"(d[36]), "+f"(d[37]), "+f"(d[38]), "+f"(d[39]), "+f"(d[40]), "+f"(d[41]), "+f"(d[42]), "+f"(d[43]), "+f"(d[44]), "+f"(d[45]), "+f"(d[46]), "+f"(d[47]), "+f"(d[48]), "+f"(d[49]), "+f"(d[50]), "+f"(d[51]), "+f"(d[52]), "+f"(d[53]), "+f"(d[54]), "+f"(d[55]), "+f"(d[56]), "+f"(d[57]), "+f"(d[58]), "+f"(d[59]), "+f"(d[60]), "+f"(d[61]), "+f"(d[62]), "+f"(d[63]), "+f"(d[64]), "+f"(d[65]), "+f"(d[66]), "+f"(d[67]), "+f"(d[68]), "+f"(d[69]), "+f"(d[70]), "+f"(d[71]), "+f"(d[72]), "+f"(d[73]), "+f"(d[74]), "+f"(d[75]), "+f"(d[76]), "+f"(d[77]), "+f"(d[78]), "+f"(d[79]), "+f"(d[80]), "+f"(d[81]), "+f"(d[82]), "+f"(d[83]), "+f"(d[84]), "+f"(d[85]), "+f"(d[86]), "+f"(d[87]), "+f"(d[88]), "+f"(d[89]), "+f"(d[90]), "+f"(d[91]), "+f"(d[92]), "+f"(d[93]), "+f"(d[94]), "+f"(d[95])
    : "r"(a[0]), "r"(a[1]), "r"(a[2]), "r"(a[3]), "l"(db), "r"(sd), "n"(TB));
}

template<int TB> __device__ __forceinline__ void wgmma_rs_n32(float* d, const uint32_t* a, uint64_t db, int sd) {
  asm volatile("{\n.reg .pred p;\nsetp.ne.b32 p, %21, 0;\n"
    "wgmma.mma_async.sync.aligned.m64n32k16.f32.bf16.bf16 {%0, %1, %2, %3, %4, %5, %6, %7, %8, %9, %10, %11, %12, %13, %14, %15}, {%16, %17, %18, %19}, %20, p, 1, 1, %22;\n}"
    : "+f"(d[0]), "+f"(d[1]), "+f"(d[2]), "+f"(d[3]), "+f"(d[4]), "+f"(d[5]), "+f"(d[6]), "+f"(d[7]), "+f"(d[8]), "+f"(d[9]), "+f"(d[10]), "+f"(d[11]), "+f"(d[12]), "+f"(d[13]), "+f"(d[14]), "+f"(d[15])
    : "r"(a[0]), "r"(a[1]), "r"(a[2]), "r"(a[3]), "l"(db), "r"(sd), "n"(TB));
}

template<int TB> __device__ __forceinline__ void wgmma_rs_n64(float* d, const uint32_t* a, uint64_t db, int sd) {
  asm volatile("{\n.reg .pred p;\nsetp.ne.b32 p, %37, 0;\n"
    "wgmma.mma_async.sync.aligned.m64n64k16.f32.bf16.bf16 {%0, %1, %2, %3, %4, %5, %6, %7, %8, %9, %10, %11, %12, %13, %14, %15, %16, %17, %18, %19, %20, %21, %22, %23, %24, %25, %26, %27, %28, %29, %30, %31}, {%32, %33, %34, %35}, %36, p, 1, 1, %38;\n}"
    : "+f"(d[0]), "+f"(d[1]), "+f"(d[2]), "+f"(d[3]), "+f"(d[4]), "+f"(d[5]), "+f"(d[6]), "+f"(d[7]), "+f"(d[8]), "+f"(d[9]), "+f"(d[10]), "+f"(d[11]), "+f"(d[12]), "+f"(d[13]), "+f"(d[14]), "+f"(d[15]), "+f"(d[16]), "+f"(d[17]), "+f"(d[18]), "+f"(d[19]), "+f"(d[20]), "+f"(d[21]), "+f"(d[22]), "+f"(d[23]), "+f"(d[24]), "+f"(d[25]), "+f"(d[26]), "+f"(d[27]), "+f"(d[28]), "+f"(d[29]), "+f"(d[30]), "+f"(d[31])
    : "r"(a[0]), "r"(a[1]), "r"(a[2]), "r"(a[3]), "l"(db), "r"(sd), "n"(TB));
}

template<int TB> __device__ __forceinline__ void wgmma_rs_n96(float* d, const uint32_t* a, uint64_t db, int sd) {
  asm volatile("{\n.reg .pred p;\nsetp.ne.b32 p, %53, 0;\n"
    "wgmma.mma_async.sync.aligned.m64n96k16.f32.bf16.bf16 {%0, %1, %2, %3, %4, %5, %6, %7, %8, %9, %10, %11, %12, %13, %14, %15, %16, %17, %18, %19, %20, %21, %22, %23, %24, %25, %26, %27, %28, %29, %30, %31, %32, %33, %34, %35, %36, %37, %38, %39, %40, %41, %42, %43, %44, %45, %46, %47}, {%48, %49, %50, %51}, %52, p, 1, 1, %54;\n}"
    : "+f"(d[0]), "+f"(d[1]), "+f"(d[2]), "+f"(d[3]), "+f"(d[4]), "+f"(d[5]), "+f"(d[6]), "+f"(d[7]), "+f"(d[8]), "+f"(d[9]), "+f"(d[10]), "+f"(d[11]), "+f"(d[12]), "+f"(d[13]), "+f"(d[14]), "+f"(d[15]), "+f"(d[16]), "+f"(d[17]), "+f"(d[18]), "+f"(d[19]), "+f"(d[20]), "+f"(d[21]), "+f"(d[22]), "+f"(d[23]), "+f"(d[24]), "+f"(d[25]), "+f"(d[26]), "+f"(d[27]), "+f"(d[28]), "+f"(d[29]), "+f"(d[30]), "+f"(d[31]), "+f"(d[32]), "+f"(d[33]), "+f"(d[34]), "+f"(d[35]), "+f"(d[36]), "+f"(d[37]), "+f"(d[38]), "+f"(d[39]), "+f"(d[40]), "+f"(d[41]), "+f"(d[42]), "+f"(d[43]), "+f"(d[44]), "+f"(d[45]), "+f"(d[46]), "+f"(d[47])
    : "r"(a[0]), "r"(a[1]), "r"(a[2]), "r"(a[3]), "l"(db), "r"(sd), "n"(TB));
}

template<int TA, int TB> __device__ __forceinline__ void wgmma_ss_n192(float* d, uint64_t da, uint64_t db, int sd) {
  asm volatile("{\n.reg .pred p;\nsetp.ne.b32 p, %98, 0;\n"
    "wgmma.mma_async.sync.aligned.m64n192k16.f32.bf16.bf16 {%0, %1, %2, %3, %4, %5, %6, %7, %8, %9, %10, %11, %12, %13, %14, %15, %16, %17, %18, %19, %20, %21, %22, %23, %24, %25, %26, %27, %28, %29, %30, %31, %32, %33, %34, %35, %36, %37, %38, %39, %40, %41, %42, %43, %44, %45, %46, %47, %48, %49, %50, %51, %52, %53, %54, %55, %56, %57, %58, %59, %60, %61, %62, %63, %64, %65, %66, %67, %68, %69, %70, %71, %72, %73, %74, %75, %76, %77, %78, %79, %80, %81, %82, %83, %84, %85, %86, %87, %88, %89, %90, %91, %92, %93, %94, %95}, %96, %97, p, 1, 1, %99, %100;\n}"
    : "+f"(d[0]), "+f"(d[1]), "+f"(d[2]), "+f"(d[3]), "+f"(d[4]), "+f"(d[5]), "+f"(d[6]), "+f"(d[7]), "+f"(d[8]), "+f"(d[9]), "+f"(d[10]), "+f"(d[11]), "+f"(d[12]), "+f"(d[13]), "+f"(d[14]), "+f"(d[15]), "+f"(d[16]), "+f"(d[17]), "+f"(d[18]), "+f"(d[19]), "+f"(d[20]), "+f"(d[21]), "+f"(d[22]), "+f"(d[23]), "+f"(d[24]), "+f"(d[25]), "+f"(d[26]), "+f"(d[27]), "+f"(d[28]), "+f"(d[29]), "+f"(d[30]), "+f"(d[31]), "+f"(d[32]), "+f"(d[33]), "+f"(d[34]), "+f"(d[35]), "+f"(d[36]), "+f"(d[37]), "+f"(d[38]), "+f"(d[39]), "+f"(d[40]), "+f"(d[41]), "+f"(d[42]), "+f"(d[43]), "+f"(d[44]), "+f"(d[45]), "+f"(d[46]), "+f"(d[47]), "+f"(d[48]), "+f"(d[49]), "+f"(d[50]), "+f"(d[51]), "+f"(d[52]), "+f"(d[53]), "+f"(d[54]), "+f"(d[55]), "+f"(d[56]), "+f"(d[57]), "+f"(d[58]), "+f"(d[59]), "+f"(d[60]), "+f"(d[61]), "+f"(d[62]), "+f"(d[63]), "+f"(d[64]), "+f"(d[65]), "+f"(d[66]), "+f"(d[67]), "+f"(d[68]), "+f"(d[69]), "+f"(d[70]), "+f"(d[71]), "+f"(d[72]), "+f"(d[73]), "+f"(d[74]), "+f"(d[75]), "+f"(d[76]), "+f"(d[77]), "+f"(d[78]), "+f"(d[79]), "+f"(d[80]), "+f"(d[81]), "+f"(d[82]), "+f"(d[83]), "+f"(d[84]), "+f"(d[85]), "+f"(d[86]), "+f"(d[87]), "+f"(d[88]), "+f"(d[89]), "+f"(d[90]), "+f"(d[91]), "+f"(d[92]), "+f"(d[93]), "+f"(d[94]), "+f"(d[95])
    : "l"(da), "l"(db), "r"(sd), "n"(TA), "n"(TB));
}

template<int TA, int TB> __device__ __forceinline__ void wgmma_ss_n8(float* d, uint64_t da, uint64_t db, int sd) {
  asm volatile("{\n.reg .pred p;\nsetp.ne.b32 p, %6, 0;\n"
    "wgmma.mma_async.sync.aligned.m64n8k16.f32.bf16.bf16 {%0, %1, %2, %3}, %4, %5, p, 1, 1, %7, %8;\n}"
    : "+f"(d[0]), "+f"(d[1]), "+f"(d[2]), "+f"(d[3])
    : "l"(da), "l"(db), "r"(sd), "n"(TA), "n"(TB));
}

constexpr int S_ = 2048, D_ = 640, F_ = 1536;

struct Scr {
  uint32_t flag[32 * 8];
  uint32_t mv[2 * 2048];
  bf16 cimg[8 * 6 * 512];
  uint2 st2[S_];
  bf16 kvT[D_ * S_];
  bf16 zT[D_ * S_];
  bf16 AT[D_ * S_];
};
__device__ __align__(1024) Scr g_scr;
__device__ __forceinline__ uint32_t clk() { uint32_t c; asm volatile("mov.u32 %0, %%clock;" : "=r"(c) :: "memory"); return c; }
#define DEVSM 0
#define STAMP(id)
#define STAMPIF(c, id)
#define ITW 0
#define P3 0
constexpr int FL_X = 5, FL_C = 128;
#define CD 600
#define SD 1000

constexpr int SM_X = 1024, SM_EXT = 21504, SM_SMALL = 29696, SM_STAT = 30720, SM_CB = 32768, SM_RING = 34816, SM_TOTAL = SM_RING + 6 * 32768;
constexpr int SMALL_LN = 224, SMALL_RED = 320, SMALL_DUMMY = 1008, SMALL_E = 1012, SMALL_TS = 160, SMALL_H = 864;
constexpr int JOB_SZ = 10880, JOB_V = 5760, R_X = 5 * 32768, R_BOX = R_X + 12288;
constexpr int K1OFF = 4672, KSZ = 9472, CSZ = KSZ + 4224;
enum { B_KJ = 0, B_X = 5, B_EXT = 7, B_X1 = 8, B_P0 = 9, B_FB = 10, B_PEER = 20, B_RECV = 24, B_U = 28, B_A = 30, B_E0 = 35, B_FS = 37, B_BOX = 38, B_F = 44, B_ST0 = 45, B_GB = 46,
       B_F1 = 48, B_E1 = 54, B_EB = 60,
       B_OS = 64, B_OF = 72, B_Z = 80, B_K = 85, B_EW = 88, B_ST2 = 94, B_XF = 95, B_KV4 = 96, B_KVS = 98, B_BD = 99,
       B_B = 106, B_S = 112 };
__device__ __forceinline__ uint32_t chan_base(uint32_t sb, int ch) { return sb + SM_RING + (2 + (ch >> 1)) * 32768 + (ch & 1) * CSZ; }

struct Params { CUtensorMap mS, mX, mWm, mK, mV, mG, mU, mD; };

__device__ __forceinline__ void flag_add(Scr* G, int id) { asm volatile("red.relaxed.gpu.global.add.u32 [%0], 1;" ::"l"(G->flag + id) : "memory"); }
__device__ __forceinline__ uint32_t rdback(const void* p) { uint32_t v; asm volatile("ld.relaxed.gpu.global.u32 %0, [%1];" : "=r"(v) : "l"(p) : "memory"); return v; }
__device__ __forceinline__ void st_tag(uint2* p, uint32_t v, uint32_t t) { asm volatile("st.relaxed.gpu.global.v2.u32 [%0], {%1, %2};" ::"l"(p), "r"(v), "r"(t) : "memory"); }
__device__ __forceinline__ void spin(uint32_t t, uint32_t d) { if (d) while (clk() - t < d); }
__device__ __forceinline__ uint2 ld_tag(const uint2* p) { uint2 v; asm volatile("ld.relaxed.gpu.global.v2.u32 {%0, %1}, [%2];" : "=r"(v.x), "=r"(v.y) : "l"(p) : "memory"); return v; }
__device__ __forceinline__ uint4 ld_tag2(const uint2* p) {
  uint4 v;
  asm volatile("ld.relaxed.gpu.global.v4.u32 {%0, %1, %2, %3}, [%4];" : "=r"(v.x), "=r"(v.y), "=r"(v.z), "=r"(v.w) : "l"(p) : "memory");
  return v;
}
__device__ __forceinline__ void stg128(void* p, uint4 v) { asm volatile("st.global.v4.b32 [%0], {%1, %2, %3, %4};" ::"l"(p), "r"(v.x), "r"(v.y), "r"(v.z), "r"(v.w) : "memory"); }
__device__ __forceinline__ uint32_t ldv32(uint32_t a) { uint32_t v; asm volatile("ld.volatile.shared.b32 %0, [%1];" : "=r"(v) : "r"(a) : "memory"); return v; }
__device__ __forceinline__ uint4 ldv128(uint32_t a) { uint4 v; asm volatile("ld.volatile.shared.v4.b32 {%0,%1,%2,%3}, [%4];" : "=r"(v.x), "=r"(v.y), "=r"(v.z), "=r"(v.w) : "r"(a) : "memory"); return v; }
__device__ __forceinline__ bool mbar_test(uint32_t bar, int parity) {
  uint32_t ok;
  asm volatile("{\n.reg .pred P;\nmbarrier.test_wait.parity.shared::cta.b64 P, [%1], %2;\nselp.u32 %0, 1, 0, P;\n}" : "=r"(ok) : "r"(bar), "r"(parity) : "memory");
  return ok;
}
__device__ __forceinline__ uint32_t epoch(uint32_t sb) { return lds32(sb + SM_SMALL + SMALL_E); }
__device__ __forceinline__ void rdwait(uint32_t sb, uint32_t v) { sts32(sb + SM_SMALL + SMALL_DUMMY, v); }
__device__ __forceinline__ void fence_async_s() { asm volatile("fence.proxy.async.shared::cta;" ::: "memory"); }
__device__ __forceinline__ void fence_async_g() { asm volatile("fence.proxy.async.global;" ::: "memory"); }
__device__ __forceinline__ void bulk_done() { asm volatile("cp.async.bulk.commit_group;\n\tcp.async.bulk.wait_group 0;" ::: "memory"); }
__device__ __forceinline__ void flag_wait(Scr* G, int id, uint32_t target) {
  const uint32_t* p = G->flag + id;
#pragma unroll 1
  for (int i = 0; i < (1 << 20); i++) {
    uint32_t v;
    asm volatile("ld.relaxed.gpu.global.u32 %0, [%1];" : "=r"(v) : "l"(p) : "memory");
    if ((int)(v - target) >= 0) return;
  }
  __trap();
}
__device__ __forceinline__ void hint_wait(Scr* G, uint32_t sa, int id, uint32_t target) {
#pragma unroll 1
  for (int i = 0; i < (1 << 20); i++) {
    const uint32_t t = clk();
    cp16(sa + 4 * (id & 4), G->flag + (id & ~3));
    spin(t, P3);
    if ((int)(lds32(sa + 4 * (id & 7)) - target) >= 0) return;
  }
  __trap();
}
__device__ __forceinline__ int tbase(int pb) { return 127 - (32 * (pb >> 6) + 8 * (pb & 8) + 4 * ((2 * (pb & 3) - ((pb >> 2) & 1)) & 7) + ((pb >> 4) & 3)); }
__device__ __forceinline__ uint32_t hmul(uint32_t a, uint32_t b) { uint32_t d; asm("mul.rn.bf16x2 %0, %1, %2;" : "=r"(d) : "r"(a), "r"(b)); return d; }
__device__ __forceinline__ uint32_t hadd(uint32_t a, uint32_t b) { uint32_t d; asm("add.rn.bf16x2 %0, %1, %2;" : "=r"(d) : "r"(a), "r"(b)); return d; }
__device__ __forceinline__ uint32_t hsub(uint32_t a, uint32_t b) { uint32_t d; asm("sub.rn.bf16x2 %0, %1, %2;" : "=r"(d) : "r"(a), "r"(b)); return d; }
__device__ __forceinline__ uint32_t hfma(uint32_t a, uint32_t b, uint32_t c) { uint32_t d; asm("fma.rn.bf16x2 %0, %1, %2, %3;" : "=r"(d) : "r"(a), "r"(b), "r"(c)); return d; }
__device__ __forceinline__ uint32_t pack2(float lo, float hi) { uint32_t d; asm("cvt.rn.bf16x2.f32 %0, %1, %2;" : "=r"(d) : "f"(hi), "f"(lo)); return d; }
__device__ __forceinline__ float blo(uint32_t v) { return __uint_as_float(v << 16); }
__device__ __forceinline__ float bhi(uint32_t v) { return __uint_as_float(v & 0xffff0000u); }
__device__ __forceinline__ uint32_t tagged(uint32_t v, uint32_t e1) { return (v & ~1u) | (e1 & 1); }
__device__ __forceinline__ float rbf(float v) { return blo(pack2(v, 0.f)); }
__device__ __forceinline__ float sdev(float var) { float d; asm("sqrt.approx.ftz.f32 %0, %1;" : "=f"(d) : "f"(rbf(rbf(var) + 1e-5f))); return rbf(d); }
template <int N> __device__ __forceinline__ void bfly(float* v, int mask, bool up) {
#pragma unroll
  for (int i = 0; i < N / 2; i++) {
    float send = up ? v[i] : v[i + N / 2], keep = up ? v[i + N / 2] : v[i];
    v[i] = keep + __shfl_xor_sync(0xffffffffu, send, mask);
  }
}
#define BX3 2
#define XO 0
#define ZA 0
#define XE 0
#define EA 1
#define AD 300
#define XP 0
#define DR 0
#define KVV 0
#define OPQ 4
#define SL 1
#define UT 5
#define UD0 1000
#define EH 2
#define NA 16
#define BS 0
#define UF 1
#define ZS 1
#define LV 5
#define TG 2
#define RL 2
#define OF 1
#define OH 16
#define ES 2
#define SI 1
#define RH 5
#define NS 0
#define AT0 14200
#define AT1 0
#define BI 4
#define PC 1
#define PG 1
#define UD2 3600
#define GT 0x111
#define K3 0
#define FS 31
#define KS 3
#define PQ 2
#define KW 0
#define RX 0
#define MG 0
__device__ __forceinline__ bool mod_first(int b) { return MG ? (b & 3) != 3 : !(b & 1) || !(b & 6); }
__device__ __forceinline__ int mod_grp(int b, int j) {
  if (MG) {
  const int m = b >> 3, s = b & 7, t = 16 * (j ? min(s, 6) : s - (s >> 2)) + m, v = j ? s : (t * 43) >> 10;
  if (j == 2) return b + 112;
  return v < 4 ? (v == 3 ? 160 : 40 * v) + (j ? 24 + m : t - 24 * v) : t + (t < 104 ? 56 : 96);
  }
  const int m = b >> 3, s = b & 7, t = 16 * s + m, v = j ? (t * 43) >> 10 : s >> 1;
  if (j == 2) return b + 112;
  if (j == 0 && s == 1) return m + (m < 8 ? 152 : 192);
  return v < 4 ? (v == 3 ? 160 : 40 * v) + (j ? 16 + t - 24 * v : m) : t + 24;
}

__device__ __forceinline__ void kv_load(const bf16* gk, const bf16* gv, const bf16* gs, uint32_t sb, int b, int r, int tid) {
  const int row = tid >> 2, col = 128 * r + 32 * (b & 3);
  const uint32_t a = sb + SM_RING + r * JOB_SZ + (row >> 3) * 80 + (tid & 3) * 16, ak = a + (row & 7) * 720, av = a + (row & 7) * 640 + JOB_V;
  const int o = (64 * (b >> 2) + row) * D_ + col + 8 * (tid & 3);
  if (FS & 16) {
    uint32_t oo = 2 * o;
    asm volatile("" : "+r"(oo));
    const char *pk = (const char*)gk + oo, *pv = (const char*)gv + oo;
    cp16(ak + 80, pk);
    cp16(av, pv);
    cp16(ak + 400, pk + 64 * D_);
    cp16(av + 320, pv + 64 * D_);
    if (tid < 12) cp16z(ak + 3600, pk - (b < 4 ? 0 : 6 * D_), b < 4 ? 0 : 16);
    if (KS & 2)
      asm volatile("{\n.reg .pred q;\n.reg .b64 y;\ncvt.u64.u32 y, %2;\nadd.s64 y, y, %1;\nsetp.ge.s32 q, %3, 112;\n@q cp.async.cg.shared.global [%0], [y], 16;\n}"
                   ::"r"(sb + SM_CB + 256 * r + 16 * (tid - 112)), "l"(gs), "r"(8 * col + 16 * (tid & 15)), "r"(tid) : "memory");
    else if (tid >= 112) cp16(sb + SM_CB + 256 * r + 16 * (tid - 112), (const char*)gs + (uint32_t)(8 * col + 16 * (tid - 112)));
    return;
  } else {
    cp16(ak + 80, gk + o);
    cp16(ak + 400, gk + o + 32 * D_);
    cp16(av, gv + o);
    cp16(av + 320, gv + o + 32 * D_);
  }
  if (tid < 12) cp16z(ak + 3600, gk + (b < 4 ? o : o - 3 * D_), b < 4 ? 0 : 16);
  else if (tid >= 112) cp16(sb + SM_CB + 256 * r + 16 * (tid - 112), gs + 4 * col + 8 * (tid - 112));
}
__device__ __forceinline__ void load_kv(const Params& P, const bf16* gs, uint32_t sb, int b, int r) {
  const uint32_t a = sb + SM_RING + r * JOB_SZ, bar = sb + 8 * (B_B + r);
  const int cg = 4 * r + (b & 3);
  mbar_expect(bar, JOB_SZ + 256);
  tma4d(a, &P.mK, 0, cg, 8 * (b >> 2) - 1, 0, bar);
  tma4d(a + JOB_V, &P.mV, 0, cg, 8 * (b >> 2), 0, bar);
  bulk_g2s(sb + SM_CB + 256 * r, gs + 128 * cg, 256, bar);
}
__device__ __forceinline__ uint4* kv_dst(Scr* G, int b, int r, int tid) {
  return (uint4*)(G->kvT + (128 * r + 32 * (b & 3) + 8 * (tid >> 5) + 2 * (tid & 3)) * S_ + 2040 - 64 * (b >> 2)) - ((tid >> 2) & 7);
}
__device__ __forceinline__ void kv_job(Scr* G, uint32_t sb, int b, int r, int tid, uint32_t e1) {
  const int cp = 4 * (tid >> 5) + (tid & 3);
  const uint32_t ka = sb + SM_RING + r * JOB_SZ + ((tid >> 2) & 7) * 80 + cp * 4;
  mbar_wait(sb + 8 * (B_B + r), 0);
  STAMPIF(tid == 0, 56 + r);
  uint32_t kk[11], vv[8], o[8];
  if (KVV) {
#pragma unroll
    for (int i = 0; i < 11; i++) kk[i] = ldv32(ka + 720 * ((i + 5) & 7) + 80 * ((i + 5) >> 3));
#pragma unroll
    for (int i = 0; i < 8; i++) vv[i] = ldv32(ka + JOB_V + 640 * i);
  }
  const uint4 sk = ldv128(sb + SM_CB + 256 * r + 16 * cp);
  const uint32_t s0 = __byte_perm(sk.x, sk.z, 0x5410), s1 = __byte_perm(sk.x, sk.z, 0x7632), s2 = __byte_perm(sk.y, sk.w, 0x5410), s3 = __byte_perm(sk.y, sk.w, 0x7632);
#pragma unroll
  for (int i = 0; i < 11; i++) if (!KVV) kk[i] = lds32(ka + 720 * ((i + 5) & 7) + 80 * ((i + 5) >> 3));
#pragma unroll
  for (int i = 0; i < 8; i++) {
    uint32_t v = KVV ? vv[i] : lds32(ka + JOB_V + 640 * i);
    o[i] = hmul(hfma(kk[i + 3], s0, hfma(kk[i + 2], s1, hfma(kk[i + 1], s2, hmul(kk[i], s3)))), v);
  }
  uint4* dst = kv_dst(G, b, r, tid);
  dst[0] = make_uint4(__byte_perm(o[7], o[6], 0x5410), __byte_perm(o[5], o[4], 0x5410), __byte_perm(o[3], o[2], 0x5410), tagged(__byte_perm(o[1], o[0], 0x5410), e1));
  dst[256] = make_uint4(__byte_perm(o[7], o[6], 0x7632), __byte_perm(o[5], o[4], 0x7632), __byte_perm(o[3], o[2], 0x7632), tagged(__byte_perm(o[1], o[0], 0x7632), e1));
  if (tid == 0) { sts32(sb + SM_SMALL + SMALL_TS + 4 * r, clk()); mbar_arrive(sb + 8 * (B_KJ + r)); }
}
__device__ __forceinline__ void u_wait(uint4& a, uint4& c, const void* p) {
  asm volatile("{\n.reg .pred p;\n.reg .b32 t, n;\nmov.b32 n, 0;\n"
               "L0:\nlop3.b32 t, %3, %7, 1, 0x80;\nsetp.eq.b32 p, t, 0;\nvote.sync.any.pred p, p, 0xffffffff;\n@!p bra.uni L1;\n"
               "ld.relaxed.gpu.global.v4.u32 {%0, %1, %2, %3}, [%8];\nld.relaxed.gpu.global.v4.u32 {%4, %5, %6, %7}, [%8+2048];\n"
               "add.u32 n, n, 1;\nsetp.lt.u32 p, n, 1000000;\n@p bra.uni L0;\ntrap;\nL1:\n}"
               : "+r"(a.x), "+r"(a.y), "+r"(a.z), "+r"(a.w), "+r"(c.x), "+r"(c.y), "+r"(c.z), "+r"(c.w) : "l"(p) : "memory");
}
__device__ __forceinline__ void u_fix(uint4 a, uint4 c, const void* p, uint32_t sa, uint32_t e1) {
  asm volatile("{\n.reg .pred p;\n.reg .b32 t, n;\nmov.b32 n, 0;\n"
               "lop3.b32 t, %3, %7, %10, 0x81;\nand.b32 t, t, 1;\nsetp.eq.b32 p, t, 0;\nvote.sync.any.pred p, p, 0xffffffff;\n@!p bra.uni L2;\n"
               "L0:\nld.relaxed.gpu.global.v4.u32 {%0, %1, %2, %3}, [%8];\nld.relaxed.gpu.global.v4.u32 {%4, %5, %6, %7}, [%8+2048];\n"
               "lop3.b32 t, %3, %7, %10, 0x81;\nand.b32 t, t, 1;\nsetp.eq.b32 p, t, 0;\nvote.sync.any.pred p, p, 0xffffffff;\n@!p bra.uni L1;\n"
               "add.u32 n, n, 1;\nsetp.lt.u32 p, n, 1000000;\n@p bra.uni L0;\ntrap;\n"
               "L1:\nst.shared.v4.b32 [%9], {%0, %1, %2, %3};\nst.shared.v4.b32 [%9+2048], {%4, %5, %6, %7};\nL2:\n}"
               : "+r"(a.x), "+r"(a.y), "+r"(a.z), "+r"(a.w), "+r"(c.x), "+r"(c.y), "+r"(c.z), "+r"(c.w) : "l"(p), "r"(sa), "r"(e1) : "memory");
}
__device__ __forceinline__ void stv128(uint32_t a, uint4 v) { asm volatile("st.volatile.shared.v4.b32 [%0], {%1,%2,%3,%4};" ::"r"(a), "r"(v.x), "r"(v.y), "r"(v.z), "r"(v.w) : "memory"); }
__device__ __forceinline__ uint64_t box_a(uint32_t sb) { return mkdesc(sb + SM_RING + R_BOX, 256, 1024, 3); }
__device__ __forceinline__ uint64_t box_b(uint32_t sb) { return mkdesc(sb + SM_STAT, 64, 128, 0); }
__device__ __forceinline__ void mod_put(Scr* G, uint32_t sb, const float* a, int b, int j, uint32_t e1, int tid) {
  const uint32_t red = sb + SM_STAT + 1536;
  if ((tid & 3) == tid >> 6) sts64(red + 32 * ((tid >> 2) & 7) + 8 * (tid >> 5), __float_as_uint((tid & 32) ? a[1] : a[0]), __float_as_uint((tid & 32) ? a[3] : a[2]));
  bar_sync(j > (BX3 >= 3) ? 4 : 5, 128);
  if (tid < 16) {
    const uint4 u = lds128(red + 32 * (tid & 7)), v = lds128(red + 32 * (tid & 7) + 16);
    asm volatile("" : "+r"(b));
    const int grp = mod_grp(b, j);
    const uint32_t one = (grp >= 40 && grp < 80) || (grp >= 160 && grp < 200) ? 0x3f803f80u : 0u;
    const float lo = __uint_as_float(u.x) + __uint_as_float(u.z) + __uint_as_float(v.x) + __uint_as_float(v.z);
    const float hi = __uint_as_float(u.y) + __uint_as_float(u.w) + __uint_as_float(v.y) + __uint_as_float(v.w);
    asm volatile("st.relaxed.gpu.global.u32 [%0], %1;" ::"l"(G->mv + 8 * grp + 256 * (tid & 8) + (tid & 7)),
                 "r"(((tid >> 3) ^ e1) & 1 ? 0 : ~hadd(pack2(lo, hi), one)) : "memory");
  }
}
__device__ __forceinline__ void mod_box(Scr* G, uint32_t sb, int b, int j, uint32_t e1, int tid) {
  float a[4];
  uint64_t da = box_a(sb), db = box_b(sb);
#pragma unroll
  for (int h = 0; h < 2; h++) {
    mbar_wait(sb + 8 * (B_BOX + 2 * j + h), 0);
    STAMPIF(tid == 0 && j == 0, 71 + h);
    wg_fence();
#pragma unroll
    for (int n = 5 * h; n < 5 * h + 5; n++) wgmma_ss_n8<1, 0>(a, da + 128 * n, db + 8 * n, n != 0);
    wg_commit();
  }
  wg_wait<0>();
#pragma unroll
  for (int i = 0; i < 4; i++) asm volatile("" : "+f"(a[i])::"memory");
  mod_put(G, sb, a, b, j, e1, tid);
}
__device__ __forceinline__ void a_check(uint32_t sa, const void* ga, uint32_t tag) {
  asm volatile("{\n.reg .pred p;\n.reg .b32 t, n, x, y, z;\n.reg .b64 g;\n"
               "ld.shared.b32 t, [%0];\nlop3.b32 t, t, %2, 1, 0x28;\nsetp.ne.b32 p, t, 0;\nvote.sync.any.pred p, p, 0xffffffff;\n@!p bra.uni L1;\nmov.b32 n, 0;\n"
               "L0:\nld.relaxed.gpu.global.b32 t, [%1];\nlop3.b32 t, t, %2, 1, 0x28;\nsetp.ne.b32 p, t, 0;\nvote.sync.any.pred p, p, 0xffffffff;\n@!p bra.uni L2;\n"
               "add.u32 n, n, 1;\nsetp.lt.u32 p, n, 1000000;\n@p bra.uni L0;\ntrap;\nL2:\n"
               "and.b64 g, %1, -32;\nand.b32 n, %0, -32;\n"
               "ld.relaxed.gpu.global.v4.b32 {t, x, y, z}, [g];\nst.shared.v4.b32 [n], {t, x, y, z};\n"
               "ld.relaxed.gpu.global.v4.b32 {t, x, y, z}, [g+16];\nst.shared.v4.b32 [n+16], {t, x, y, z};\n"
               "fence.proxy.async.shared::cta;\nbar.warp.sync 0xffffffff;\nL1:\n}" ::"r"(sa), "l"(ga), "r"(tag) : "memory");
}
__device__ __forceinline__ void z_wait(uint4& a, uint4& c, uint32_t* v, const void* G, uint32_t zo, uint32_t co, uint32_t e1) {
  asm volatile("{\n.reg .pred p;\n.reg .b32 t, n;\n.reg .b64 x, y;\nmov.b32 n, 0;\n"
               "L0:\nlop3.b32 t, %3, %7, %14, 0x81;\nand.b32 t, t, 1;\nmin.u32 t, t, %8;\nmin.u32 t, t, %9;\nmin.u32 t, t, %10;\nmin.u32 t, t, %11;\n"
               "setp.eq.b32 p, t, 0;\nvote.sync.any.pred p, p, 0xffffffff;\n@!p bra.uni L1;\n"
               "shr.u32 t, n, 31;\nadd.u32 t, t, %12;\ncvt.u64.u32 x, t;\nadd.s64 x, x, %15;\nshr.u32 t, n, 30;\nadd.u32 t, t, %13;\ncvt.u64.u32 y, t;\nadd.s64 y, y, %15;\n"
               "ld.relaxed.gpu.global.v4.u32 {%0, %1, %2, %3}, [x];\nld.relaxed.gpu.global.v4.u32 {%4, %5, %6, %7}, [x+32768];\n"
               "ld.relaxed.gpu.global.u32 %8, [y];\nld.relaxed.gpu.global.u32 %9, [y+1280];\nld.relaxed.gpu.global.u32 %10, [y+2560];\nld.relaxed.gpu.global.u32 %11, [y+5120];\n"
               "add.u32 n, n, 1;\nsetp.lt.u32 p, n, 1000000;\n@p bra.uni L0;\ntrap;\nL1:\n}"
               : "+r"(a.x), "+r"(a.y), "+r"(a.z), "+r"(a.w), "+r"(c.x), "+r"(c.y), "+r"(c.z), "+r"(c.w), "+r"(v[0]), "+r"(v[1]), "+r"(v[2]), "+r"(v[3])
               : "r"(zo), "r"(co), "r"(e1), "l"(G) : "memory");
}
__device__ __forceinline__ void load_x(const Params& P, uint32_t sb, int b, int h) {
  const uint32_t bar = sb + 8 * (B_X + h);
  mbar_expect(bar, 10240);
  tma5d(sb + SM_X + h * 10240, &P.mX, 0, 0, 0, 5 * h, tbase(b), bar);
}
__device__ __forceinline__ uint32_t x_addr(uint32_t sb, int w, int lane) {
  const int rho = 15 - (4 * (lane >> 3) + 2 * (lane & 1) + ((lane >> 1) & 1));
  return sb + SM_X + (w >> 1) * 2048 + rho * 128 + (((2 * (w & 1) + (lane & 4)) ^ (rho & 7)) << 4);
}
__device__ __forceinline__ void ln1_half(uint32_t sb, int tid, int h, int dry, float& s1, float& s2, float& pv) {
  const uint32_t xr = sb + SM_X + 16 * tid;
  float s3 = 0.f;
  if (ITW == 8) STAMPIF(tid == 0, 102 + 2 * h);
  if (!dry) mbar_wait(sb + 8 * (B_X + h), 0);
  STAMPIF(tid == 0, 25);
  if (ITW == 8) STAMPIF(tid == 0, 103 + 2 * h);
  uint4 v[5];
#pragma unroll
  for (int n = 0; n < 5; n++) v[n] = n < LV ? ldv128(xr + 10240 * h + 2048 * n) : lds128(xr + 10240 * h + 2048 * n);
  pv = blo(ldv32(xr & ~127u));
#pragma unroll
  for (int n = 0; n < 5; n++) {
    const uint32_t u[4] = {v[n].x, v[n].y, v[n].z, v[n].w};
#pragma unroll
    for (int j = 0; j < 4; j++) {
      const float a = blo(u[j]) - pv, c = bhi(u[j]) - pv;
      s1 += a + c; s2 += a * a; s3 += c * c;
    }
  }
  s2 += s3;
}
__device__ __forceinline__ void ln1_end(uint32_t sb, int tid, float s1, float s2, float pv) {
#pragma unroll
  for (int o = 1; o < 8; o <<= 1) { s1 += __shfl_xor_sync(0xffffffffu, s1, o); s2 += __shfl_xor_sync(0xffffffffu, s2, o); }
  if (ITW == 8) { asm volatile("" : "+f"(s1), "+f"(s2)); STAMPIF(tid == 0, 107); }
  const float mu = s1 * (1.f / D_), var = fmaxf(s2 * (1.f / D_) - mu * mu, 0.f);
  float rs;
  asm("rcp.approx.ftz.f32 %0, %1;" : "=f"(rs) : "f"(sdev(var)));
  const int i = 15 - (tid >> 3), j = tid & 7;
  if (j < 2) sts16(sb + SM_SMALL + SMALL_LN + 32 * j + 16 * (i & 1) + (i & 14), pack2(j ? rs : pv + mu, 0.f));
  if (ITW == 8) STAMPIF(tid == 0, 108);
  bar_sync(5, 128);
  STAMPIF(tid == 0, 75);
}
__device__ __forceinline__ void load_box(const Params& P, uint32_t sb, int b, int cls) {
  const uint32_t bar = sb + 8 * (B_BOX + cls);
  mbar_expect(bar, 10240);
  tma3d(sb + SM_RING + R_BOX + 10240 * (cls & 1), &P.mWm, 16 * mod_grp(b, cls >> 1), 0, 5 * (cls & 1), bar);
}
__device__ __forceinline__ void load_ssm(const Params& P, uint32_t sb, int b, int r) {
  const uint32_t bar = sb + 8 * (B_S + r);
  mbar_expect(bar, 16 * 288);
  tma3d(chan_base(sb, r) + 128, &P.mS, 0, 0, 128 * r + b, bar);
}
__device__ __forceinline__ void k1_job(uint32_t sb, int r, int tid, uint32_t dv) {
  const uint32_t a0 = chan_base(sb, r) + 128 + 16 * tid + 32 * (tid >> 4);
  mbar_wait(sb + 8 * (B_S + r), 0);
  uint4 v[2];
  uint32_t pv[2];
#pragma unroll
  for (int n = 0; n < 2; n++) { v[n] = lds128(a0 + 2304 * n); pv[n] = lds32(a0 + 2304 * n - ((tid & 15) ? 4 : 36)); }
  if (tid == 0) { v[0].x = hadd(v[0].x, dv); sts32(a0, v[0].x); }
#pragma unroll
  for (int n = 0; n < 2; n++)
    sts128(a0 + 2304 * n + K1OFF, make_uint4(__byte_perm(pv[n], v[n].x, 0x5432), __byte_perm(v[n].x, v[n].y, 0x5432), __byte_perm(v[n].y, v[n].z, 0x5432), __byte_perm(v[n].z, v[n].w, 0x5432)));
}

__device__ __forceinline__ int out_blk(int s, int p) { const int t = p + (s >> 1); return t < 5 ? t : t - 5; }
__device__ __forceinline__ void l2_prefetch(const void* p, int bytes) { asm volatile("cp.async.bulk.prefetch.L2.global [%0], %1;" ::"l"(p), "r"(bytes) : "memory"); }
__device__ __forceinline__ void pf_line(const void* p) { asm volatile("prefetch.global.L2 [%0];" ::"l"(p) : "memory"); }
template <int BF> __device__ __forceinline__ int role(int bx) {
  const int c = bx >> 1, d = c - 36, q = (d * 37) >> 8, k = d - 7 * q;
  int rank;
  if (BF) {
    const int r1 = ((c - 4) & 7) * 8 + ((c - 4) >> 3), r2 = (k + min(k, 1)) * 8 + 4 + q;
    rank = r2 + ((d >> 31) & (r1 - r2)) + (((c - 4) >> 31) & (12 + c - r1));
  }
  else rank = c < 4 ? 12 + c : c < 36 ? ((c - 4) & 7) * 8 + ((c - 4) >> 3) : (k ? k + 1 : 0) * 8 + 4 + q;
  return 8 * (rank & 15) + 2 * (rank >> 4) + (bx & 1);
}
enum { K_KV, K_SSM, K_BOX, K_PW, K_PD, K_PKV, K_PSSM, K_PBOX, K_W, K_X, K_ST, K_END = 15 };
#define KD 600
#define S1T 1900
#define KP 0
#define Q0 2400
#define Q1 3300
#define Q2 4000
#define Q3 4400
#define Q4 5100
#define Q5 6000
#define Q6 6700
#define Q7 7500
#define Q8 7900
#define Q9 8200
#define QA 9100
#define QB 9700
#define SC 0
#define MO 0
#define QS 0
#define SH 400
#define E(t, bar, kind, r) (((t) ? (t) - SH : 0) << 16 | (bar) << 8 | (kind) << 4 | (r))
#define SCH0 E(S1T + SH, 255, K_SSM, 1),
#define SCHED SCH0 E(Q0 + SH - QS, 255, K_BOX, 0), E(0, 255, K_BOX, 1), E(Q1 + SH - QS, 255, K_KV, 2), E(Q2 + SH - QS, 255, K_SSM, 2), E(Q3 + SH - QS, 255, K_KV, 3), E(Q4 + SH - QS, 255, K_X, 0), E(Q5 + SH - QS, 255, K_KV, 4), E(Q6 + SH - QS, 255, K_X, 1), E(Q7 + SH - QS, 255, K_SSM, 3), E(Q8 + SH - QS, 255, K_SSM, 4), E(Q9 + SH - QS, 255, K_BOX, 2), E(QA + SH - QS, 255, K_PW, 0), E(QB + SH - QS, 255, K_BOX, 3)
#define XPF (S1T ? 1 : 2)
#define XBOTH 0
#define XI 8
#define XW 0
#define PWM 0x3c
#define STM 0x7c0
#define PDM 0x3800
#define KV4C 3
#define CVT 1
#define UPOS 4
#define UD 1200
#define UD1 5300
#define NP 6
#define NQ 6
#define SPOS(i) (2 * ((i) - NQ) + 13)
#define LH0 4
#define LH1 5
#define LM 0
#define PT 1
#define ZP 0
#define BD 1200
#define ER 0
#define PL 1
#define K1N 1
#define ZD 9800
#define PK 0
#define ZF 1
constexpr uint32_t kSched[] = {SCHED, E(0, 255, K_END, 0)};
struct In { const bf16 *k, *v, *sk, *Wg, *Wu, *Wd, *ss; };
__device__ __forceinline__ void load_w(const Params& P, uint32_t sb, int s, int it) {
  const int st = it % 5;
  mbar_wait(sb + 8 * (B_E1 + st), (it / 5) & 1);
  const uint32_t a = sb + SM_RING + st * 32768 + 8192, fb = sb + 8 * (B_F1 + st);
  mbar_expect(fb, 24576);
#pragma unroll
  for (int j = 0; j < 3; j++) {
    tma2d(a + 8192 * j, &P.mG, 192 * s + 64 * j, 32 * it, fb);
    tma2d(a + 8192 * j + 4096, &P.mU, 192 * s + 64 * j, 32 * it, fb);
  }
}

template <int I> __device__ __forceinline__ int sched_run(const Params& P, const In& in, uint32_t sb, int b, int lane, uint32_t t_0) {
  constexpr uint32_t e = kSched[I];
  constexpr int kind = (e >> 4) & 15, r = e & 15, bar = (e >> 8) & 255;
  if constexpr (kind == K_END) return 0;
  else {
    if constexpr ((e >> 16) != 0) while (clk() - t_0 < (e >> 16));
    if (bar != 255) mbar_wait(sb + 8 * bar, 0);
    if (kind == K_BOX && r == 2) mbar_wait(sb + 8 * B_BD, 0);
    if (kind == K_PKV) {
      const bf16* kvp = (lane < 16 ? in.k : in.v) + (16 * b + (lane & 15)) * D_ + 128 * r;
      pf_line(kvp); pf_line(kvp + 64);
    } else {
      if (elect()) {
        if (kind == K_KV) load_kv(P, in.sk, sb, b, r);
        if (kind == K_X) load_x(P, sb, b, r);
        if (kind == K_SSM) load_ssm(P, sb, b, r);
        if (kind == K_BOX && (r > 1 || mod_first(b))) load_box(P, sb, b, r);
        if (kind == K_PW) { l2_prefetch(in.Wg + (128 * r + b) * F_, 2 * F_); l2_prefetch(in.Wu + (128 * r + b) * F_, 2 * F_); }
        if (kind == K_PSSM) l2_prefetch(in.ss + (128 * r + b) * S_, 4096);
      }
      __syncwarp();
    }
    return sched_run<I + 1>(P, in, sb, b, lane, t_0) + (kind == K_PW);
  }
}

__global__ void __launch_bounds__(512, 1) fused_kernel(const bf16* __restrict__ gk, const bf16* __restrict__ gv, const bf16* __restrict__ gsk,
                                                       const bf16* __restrict__ gD, const bf16* __restrict__ gc, Scr* G, const bf16* gWg, const bf16* gWu,
                                                       const bf16* gWd, bf16* gout, const bf16* gss, const __grid_constant__ Params P) {
  extern __shared__ __align__(1024) char smem_raw[];
  const uint32_t sb = smem_u32(smem_raw), ring = sb + SM_RING;
  int t0 = 0;
  uint32_t t_0;
  if (FS & 2) asm volatile("mov.u32 %0, %%tid.x;" : "=r"(t0));
  if (FS & 4) t_0 = clk();
  if (KS & 1) {
    int bx;
    asm volatile("mov.u32 %0, %%ctaid.x;" : "=r"(bx));
    if (t0 < 128) kv_load(gk, gv, gsk, sb, bx, 0, t0);
    asm volatile("" : "+r"(t0), "+r"(bx));
    if ((t0 >> 7) == 1) { spin(t_0, KD); kv_load(gk, gv, gsk, sb, bx, 1, t0 - 128); }
  } else if ((FS & 1) && t0 < (KP ? 128 : 256)) {
    int bx;
    if (!KP && KD && t0 >= 128) spin(t_0, KD);
    asm volatile("mov.u32 %0, %%ctaid.x;" : "=r"(bx));
    kv_load(gk, gv, gsk, sb, (FS & 8) ? bx : role<1>(bx), KP ? 0 : t0 >> 7, t0 & 127);
  }
  const int b = role<0>(blockIdx.x), m = b >> 3, s = b & 7;
  if (!(FS & 4)) t_0 = clk();
  if ((FS & 3) == 2 && t0 < 256) kv_load(gk, gv, gsk, sb, b, t0 >> 7, t0 & 127);
  const int wg = __shfl_sync(0xffffffffu, threadIdx.x >> 7, 0);
  const int tid = threadIdx.x & 127, lane = tid & 31;
  const int w = __shfl_sync(0xffffffffu, tid >> 5, 0);
  uint32_t e1 = 0;
  if (wg < 2) {
    if (!(FS & 2)) kv_load(gk, gv, gsk, sb, b, wg, tid);
    if (TG == 1) e1 = rdback(G->flag + 8 * m + 4);
  } else {
    if (wg == 2) {
      if (tid < 40) {
        int c = tid & 7;
        sts128(chan_base(sb, tid >> 3) + (c < 2 ? 80 + c * K1OFF : KSZ + 4096 + (c - 2) * 16), make_uint4(0, 0, 0, 0));
      }
    }
    if (elect()) {
      const int j = 4 * (3 - wg) + w - 1;
      if (j < 4) asm volatile("prefetch.tensormap [%0];" ::"l"(&P.mX + j) : "memory");
      if (j < 0) {
#pragma unroll
        for (int i = 0; i < 5; i++) mbar_init(sb + 8 * (B_S + i), 1);
        fence_async_s();
        if (XPF > 0) load_ssm(P, sb, b, 0);
        if (XPF > 1) load_ssm(P, sb, b, 1);
      } else {
        const int c = j < 3 ? 1 : j < 4 ? 2 : 4;
#pragma unroll
        for (int i = 0; i < 16; i++) mbar_init(sb + 128 * j + 8 * i, i < 10 || j < 6 ? c : i < 12 - KP ? 128 : 1);
      }
    }
    fence_async_s();
  }
  __syncthreads();
  STAMPIF(threadIdx.x == 0, 55);

  if (wg < 2) {
    if (!KP || !wg) cp_arrive(sb + 8 * (B_B + wg));
    asm volatile("setmaxnreg.inc.sync.aligned.u32 224;");
    STAMPIF(threadIdx.x == 0, 82);
    const int g = lane >> 2, q = lane & 3;
    constexpr int NB = UT < 5 ? 288 : 256;
    if (wg == 1) bar_arrive(1, NB);
    const uint32_t dv = *(const uint16_t*)(gD + 128 * wg + b);
    if (TG == 3) e1 = rdback(G->flag + 8 * m + 4 + (__shfl_sync(0xffffffffu, tid, tid) >> 8));
    e1 = (e1 >> 5) + 1;
    bool pre = false;
    {
      const int tid = (OPQ & 4) ? __shfl_sync(0xffffffffu, threadIdx.x & 127, threadIdx.x) : threadIdx.x & 127, lane = tid & 31, g = lane >> 2, q = lane & 3;
      const int b0 = (g >> 1) & 1, b1 = g >> 2, u = q + 4 * b0 - w;
      const uint32_t fo = 128 + (g & 1) * K1OFF + 288 * b1 + 4 * u, fo0 = fo - (u < 0 ? 32 : 0);
      const bool wrap = b0 && q == 0;
      const int src1 = b0 ? ((lane & 20) | ((q - 1) & 3)) : (lane | 8);
      const uint2* pu = (const uint2*)(G->kvT + (128 * wg + b) * S_ + 8 * tid);
      uint4 u0 = make_uint4(0, 0, 0, 0), u1 = make_uint4(0, 0, 0, 1);
#pragma unroll 1
      for (int ch = wg; ch < 5; ch += 2) {
        const uint32_t base = chan_base(sb, ch);
        if (KW) {
#pragma unroll 1
          for (int n = ch > 1; n <= (ch & 1); n++) {
            int bx;
            asm volatile("mov.u32 %0, %%ctaid.x;" : "=r"(bx));
            kv_job(G, sb, n ? b : bx, ch + n, tid, e1);
            STAMPIF(tid == 0, n ? 21 + ch : 1 + ch);
            if (n == 0) {
              k1_job(sb, wg, tid, dv);
              bar_sync(3 + wg, 128);
              mbar_wait(sb + 8 * B_E0, 0);
              e1 = epoch(sb);
            }
          }
          if (ch > 1) mbar_wait(sb + 8 * (B_K + ch - 2), 0);
          else if (ch) spin(t_0, UD1);
          if (ch) { u0 = ld_tag2(pu); u1 = ld_tag2(pu + 256); }
        }
        if (!KW && (ch < 2 || ch == KV4C)) {
          int bx = b;
          if (FS & 8) { asm volatile("mov.u32 %0, %%ctaid.x;" : "=r"(bx)); bx = ch < 2 - KP ? bx : b; }
          kv_job(G, sb, bx, ch < 2 ? ch : 4, tid, TG ? e1 : 1);
          if (ER && ch > 1) { __syncwarp(); if (lane == 0) mbar_arrive(sb + 8 * B_KV4); }
          STAMPIF(tid == 0, ch < 2 ? 1 + ch : 24);
        }
        if (KW) {
        } else if (ch < 2) {
          k1_job(sb, wg, tid, dv);
          bar_sync(3 + wg, 128);
        } else {
          if (!pre) mbar_wait(sb + 8 * (B_K + ch - 2), 0);
          if (UT == 5) {
            u0 = ld_tag2(pu); u1 = ld_tag2(pu + 256);
            if (BS) mbar_wait(sb + 8 * (B_S + ch), 0);
          }
        }
        const uint32_t fa = base + fo, fa0 = base + fo0;
        uint32_t af[16][4];
        auto afl = [&](int j) {
          const int o = 64 * (j & 1) + 576 * (j >> 1);
          if (UF) { af[j][0] = ldv32(((j & 1) ? fa : fa0) + o); af[j][1] = ldv32(fa + o + 128); af[j][2] = ldv32(fa + o + 32); af[j][3] = ldv32(fa + o + 160); }
          else { af[j][0] = lds32(((j & 1) ? fa : fa0) + o); af[j][1] = lds32(fa + o + 128); af[j][2] = lds32(fa + o + 32); af[j][3] = lds32(fa + o + 160); }
        };
#pragma unroll
        for (int j = 0; j < NA; j++) afl(j);
        if (UF) {
          stv128(base + KSZ + 16 * tid, u0);
          stv128(base + KSZ + 2048 + 16 * tid, u1);
#pragma unroll
          for (int j = NA; j < 16; j++) afl(j);
        }
        STAMPIF(tid == 0, 40 + ch);
        const uint32_t tg = KW && ch < 2 ? 1 : e1;
        if (!KW && !(TG & 1) && EH < 2 && (!EH || ch < 2)) { mbar_wait(sb + 8 * B_E0, 0); e1 = epoch(sb); }
        if (ch < UT) {
          if (KW) { if (ch == 0) spin(t_0, UD2); }
          else if (UD2 ? ch < 2 : ch == 1) spin(t_0, ch ? UD1 : UD2);
          if (UT == 2) u0.w = 0;
          if (UF) u_fix(u0, u1, pu, base + KSZ + 16 * tid, TG ? tg : 1);
          else u_wait(u0, u1, pu);
          if (ITW == 5) STAMPIF(tid == 0, 105 + ch);
          if (!UF) {
            sts128(base + KSZ + 16 * tid, u0);
            sts128(base + KSZ + 2048 + 16 * tid, u1);
#pragma unroll
            for (int j = NA; j < 16; j++) afl(j);
          }
          fence_async_s();
        }
        float acc[128];
        const uint64_t db = mkdesc(base + KSZ, 32, 128, 0);
        bar_sync(1 + wg, NB);
        if (ITW == 5) STAMPIF(tid == 0, 115 + ch);
        wg_fence();
        wgmma_rs_n64<0>(acc + 96, af[0], db + 192, 0);
        wgmma_rs_n192<0>(acc, af[0], db, 0);
        wgmma_rs_n64<0>(acc + 96, af[1], db + 196, 1);
        wgmma_rs_n192<0>(acc, af[1], db + 4, 1);
        wgmma_rs_n32<0>(acc + 96, af[2], db + 224, 1);
        wgmma_rs_n192<0>(acc, af[2], db + 32, 1);
        wgmma_rs_n32<0>(acc + 96, af[3], db + 228, 1);
        wgmma_rs_n192<0>(acc, af[3], db + 36, 1);
        wgmma_rs_n192<0>(acc, af[4], db + 64, 1);
        wgmma_rs_n192<0>(acc, af[5], db + 68, 1);
        wgmma_rs_n160<0>(acc, af[6], db + 96, 1);
        wgmma_rs_n160<0>(acc, af[7], db + 100, 1);
        if (CVT == 2) wg_commit();
        wgmma_rs_n128<0>(acc, af[8], db + 128, 1);
        wgmma_rs_n128<0>(acc, af[9], db + 132, 1);
        if (CVT == 1) wg_commit();
        wgmma_rs_n96<0>(acc, af[10], db + 160, 1);
        wgmma_rs_n96<0>(acc, af[11], db + 164, 1);
        if (CVT == 0) bar_arrive(2 - wg, NB);
        wgmma_rs_n64<0>(acc, af[12], db + 192, 1);
        wgmma_rs_n64<0>(acc, af[13], db + 196, 1);
        wgmma_rs_n32<0>(acc, af[14], db + 224, 1);
        wgmma_rs_n32<0>(acc, af[15], db + 228, 1);
        wg_commit();
        if ((!TG || TG == 2 && ch < 2) && ZP == 0 && ch < UT) {
          stg128((void*)pu, make_uint4(0, 0, 0, 0));
          stg128((void*)(pu + 256), make_uint4(0, 0, 0, 0));
        }
        if (tid < 2 && ch == (!ER && wg == (KV4C & 1) && KV4C < 5 ? KV4C : wg)) mbar_arrive(sb + 8 * (B_E1 + tid));
        if (EH == 2 && ch < 2) { mbar_wait(sb + 8 * B_E0, 0); e1 = epoch(sb); }
        auto go = [&](int k) {
          int mk = 0;
#pragma unroll
          for (int c = 0; c < 4; c++) if (((GT >> 4 * c) & 15) == k) mk |= 1 << c;
          if (mk) asm volatile("{\n.reg .pred p;\nsetp.ne.b32 p, %1, 0;\n@p bar.arrive %0, %2;\n}" ::"r"(2 - wg), "r"((mk >> ch) & 1), "n"(NB) : "memory");
        };
        if (CVT) { wg_wait<1>(); go(0); }
        STAMPIF(tid == 0, 3 + ch);
        if (EH == 3 && ch < 2) { mbar_wait(sb + 8 * B_E0, 0); e1 = epoch(sb); }
        if (BX3 == 2 && ch == 3) {
          mod_box(G, sb, b, 1, e1, tid);
          __syncwarp();
          if (lane == 0) mbar_arrive(sb + 8 * (B_BD + 1));
          STAMPIF(tid == 0, 73);
        }
        if (ZP == 1) {
          stg128((void*)pu, make_uint4(0, 0, 0, 0));
          stg128((void*)(pu + 256), make_uint4(0, 0, 0, 0));
        }
        wg_wait<0>();
#pragma unroll
        for (int i = 0; i < 128; i++) asm volatile("" : "+f"(acc[i])::"memory");
        if (!RL) {
          bar_sync(3 + wg, 128);
          if (tid <= (ch >> 2)) mbar_arrive(sb + 8 * (B_E1 + 2 + (ch >> 1)));
        }
        if (RL == 2 && lane == 0) mbar_arrive(sb + 8 * (B_Z + ch));
        go(1);
        float S0[33], T[34];
#pragma unroll
        for (int i = 0; i < 31; i++) S0[i] = acc[4 * i] + acc[4 * i + 6];
        S0[31] = acc[124]; S0[32] = 0.f;
        if (PK & 1) {
#pragma unroll
          for (int i = 0; i < 32; i += 2) {
            const uint32_t v = __shfl_sync(0xffffffffu, pack2(acc[4 * i + 1] + acc[4 * i + 7], i < 30 ? acc[4 * i + 5] + acc[4 * i + 11] : acc[125]), src1);
            T[i] = (wrap ? S0[i + 1] : S0[i]) + blo(v);
            T[i + 1] = (wrap ? S0[i + 2] : S0[i + 1]) + bhi(v);
          }
        } else {
#pragma unroll
          for (int i = 0; i < 32; i++) {
            float s1 = i < 31 ? acc[4 * i + 1] + acc[4 * i + 7] : acc[125];
            T[i] = (wrap ? S0[i + 1] : S0[i]) + __shfl_sync(0xffffffffu, s1, src1);
          }
        }
        T[32] = 0.f; T[33] = 0.f;
        go(2);
        if (PQ == 1) pre = mbar_test(sb + 8 * (ch < 3 ? B_K + ch : B_F1), 0);
        uint4* pz = (uint4*)(G->zT + (128 * ch + b) * S_) + ((tid & 120) | (2 * q) | (g & 1));
#pragma unroll
        for (int h = 0; h < 2; h++) {
          float y[8];
          if (PK & 2) {
#pragma unroll
            for (int mu = 0; mu < 8; mu += 2) {
              const uint32_t v = __shfl_xor_sync(0xffffffffu, pack2(T[4 * mu + 2 + h], T[4 * mu + 6 + h]), 16);
              y[mu] = (b1 ? T[4 * mu + 4 + h] : T[4 * mu + h]) + blo(v);
              y[mu + 1] = (b1 ? T[4 * mu + 8 + h] : T[4 * mu + 4 + h]) + bhi(v);
            }
          } else {
#pragma unroll
            for (int mu = 0; mu < 8; mu++) y[mu] = (b1 ? T[4 * mu + 4 + h] : T[4 * mu + h]) + __shfl_xor_sync(0xffffffffu, T[4 * mu + 2 + h], 16);
          }
          pz[128 * h] = make_uint4(pack2(y[0], y[1]), pack2(y[2], y[3]), pack2(y[4], y[5]), tagged(pack2(y[6], y[7]), e1));
          if (PQ == 2 && h == 0) pre = mbar_test(sb + 8 * (ch < 3 ? B_K + ch : B_F1), 0);
        }
        go(3);
        if (RL == 1 && lane == 0) mbar_arrive(sb + 8 * (B_Z + ch));
        if (ZP == 2) {
          stg128((void*)pu, make_uint4(0, 0, 0, 0));
          stg128((void*)(pu + 256), make_uint4(0, 0, 0, 0));
        }
        pu += 128 * S_ / 2;
        STAMPIF(tid == 0, 8 + ch);
      }
    }
    uint32_t hh[96];
    {
      float ga[192];
      float* ua = ga + 96;
      const uint64_t da0 = mkdesc(ring + wg * 2048, 512, 256, 3), db0 = mkdesc(ring + 8192, 4096, 1024, 1);
      int st = PL, ph = 0, ps = 0;
      if (ITW == 7) STAMPIF(tid == 0, 110 + wg);
      float bx[4];
      if (wg && BX3 < 2) {
        mbar_wait(sb + 8 * (B_BOX + 2), 0);
        mbar_wait(sb + 8 * (B_BOX + 3), 0);
        wg_fence();
#pragma unroll
        for (int n = 0; n < 10; n++) wgmma_ss_n8<1, 0>(bx, box_a(sb) + 128 * n, box_b(sb) + 8 * n, n != 0);
        wg_commit();
        if (ITW == 7) STAMPIF(tid == 0, 120);
      }
      auto put = [&]() {
#pragma unroll
        for (int i = 0; i < 4; i++) asm volatile("" : "+f"(bx[i])::"memory");
        mod_put(G, sb, bx, b, 1, e1, tid);
        __syncwarp();
        if (lane == 0) mbar_arrive(sb + 8 * (B_BD + 1));
        STAMPIF(tid == 0, 73);
      };
      if (wg && BX3 == 0) { wg_wait<0>(); put(); }
      if (!pre) mbar_wait(sb + 8 * B_F1, 0);
      STAMPIF(tid == 0, 13 + wg);
      bool nf = PG == 1 && mbar_test(sb + 8 * (B_F1 + 1), 0);
      wg_fence();
      wgmma_ss_n192<1, 1>(ga, da0, db0, 0);
      wgmma_ss_n192<1, 1>(ua, da0, db0 + 768, 0);
      wgmma_ss_n192<1, 1>(ga, da0 + 256, db0 + 128, 1);
      wgmma_ss_n192<1, 1>(ua, da0 + 256, db0 + 128 + 768, 1);
      wg_commit();
      if (wg && BX3 == 1) { wg_wait<1>(); put(); }
      if (!PG) mbar_wait(sb + 8 * B_BD, 0);
      if (ITW == 7) STAMPIF(tid == 0, 112 + wg);
      const bool cs = b < 96;
      const int x0 = wg ? XI : 99,
                x1 = x0 + (cs ? 4 : 2), xs = cs ? 4 : 8;
      uint64_t xa = cs ? mkdesc(sb + SM_EXT, 4096, 1024, 1) : box_a(sb), xb = cs ? mkdesc(sb + SM_CB, 32, 128, 0) : box_b(sb);
      uint64_t ya = xa + (cs ? (SM_RING + R_X - SM_EXT) / 16 : 256), yb = xb + 16;
      if (ITW == 7) STAMPIF(tid == 0, 114 + wg);
#pragma unroll 1
      for (int it = PL; it < 19; it++) {
        if (it == x0) {
          mbar_wait(sb + 8 * (cs ? B_F : B_BOX + 4), 0);
          mbar_wait(sb + 8 * (cs ? B_ST0 : B_BOX + 5), 0);
          STAMPIF(tid == 0, 76);
        }
        if (it == x1 + XW) {
          wg_wait<XW>();
#pragma unroll
          for (int i = 0; i < 4; i++) asm volatile("" : "+f"(bx[i])::"memory");
          if (!cs) mod_put(G, sb, bx, b, 2, e1, tid);
          else {
            const int row = (m < 6 ? 0 : 4) + q;
            uint16_t* dst = (uint16_t*)G->cimg + s * 3072 + (m % 6) * 512 + row * 64 + g;
#pragma unroll
            for (int j = 0; j < 2; j++) {
              const float c1 = __shfl_sync(0xffffffffu, bx[2 * j], lane & 28), c2 = __shfl_sync(0xffffffffu, bx[2 * j + 1], lane & 28);
              const float t = (lane & 2) ? c2 : c1, hi = rbf(t);
              dst[((2 * w + j) ^ row) << 3] = (uint16_t)pack2((lane & 1) ? t - hi : hi, 0.f);
            }
          }
          __syncwarp();
          if (lane == 0) mbar_arrive(sb + 8 * (B_BD + 2));
          STAMPIF(tid == 0, 77);
        }
        if (ITW == 7) STAMPIF(tid == 0 && it == 0, 116 + wg);
        if (!nf) mbar_wait(sb + 8 * (B_F1 + st), ph);
        const int nx = st == 4 ? 0 : st + 1;
        if (st == 4) ph ^= 1;
        if (ITW == 1) STAMPIF(tid == 0 && it >= 10, 90 + it + 10 * wg);
        else if (ITW == 2) STAMPIF(tid == 0 && it < 10, 100 + it + 10 * wg);
        else if (ITW < 3) STAMPIF(threadIdx.x == ITW, 100 + it);
        const uint64_t da = da0 + st * 2048, db = db0 + st * 2048;
        if (it >= x0 && it < x1) {
          if (PG == 1) nf = mbar_test(sb + 8 * (B_F1 + nx), ph);
          wg_fence();
          wgmma_ss_n8<1, 0>(bx, xa, xb, it != x0);
          wgmma_ss_n192<1, 1>(ga, da, db, 1);
          wgmma_ss_n8<1, 0>(bx, ya, yb, 1);
          wgmma_ss_n192<1, 1>(ua, da, db + 768, 1);
          wgmma_ss_n8<1, 0>(bx, ya + 128, yb + xs, 1);
          wgmma_ss_n192<1, 1>(ga, da + 256, db + 128, 1);
          wgmma_ss_n8<1, 0>(bx, ya + 256, yb + 2 * xs, 1);
          wgmma_ss_n192<1, 1>(ua, da + 256, db + 128 + 768, 1);
          wgmma_ss_n8<1, 0>(bx, ya + 384, yb + 3 * xs, 1);
          wg_commit();
          xa += 128; xb += xs; ya += 512; yb += 4 * xs;
        } else {
          if (PG == 1) nf = mbar_test(sb + 8 * (B_F1 + nx), ph);
          wg_fence();
          wgmma_ss_n192<1, 1>(ga, da, db, PL || it != 0);
          wgmma_ss_n192<1, 1>(ua, da, db + 768, PL || it != 0);
          wgmma_ss_n192<1, 1>(ga, da + 256, db + 128, 1);
          wgmma_ss_n192<1, 1>(ua, da + 256, db + 128 + 768, 1);
          wg_commit();
        }
        wg_wait<1>();
        if (PG) { if (w == 0 && elect()) mbar_arrive(sb + 8 * (B_E1 + ps)); }
        else if (tid == 0) mbar_arrive(sb + 8 * (B_E1 + (st == 0 ? 4 : st - 1)));
        ps = st; st = nx;
      }
      const uint32_t la = ring + wg * 2048 + tid * 16, ra = mapa(la, (b & 1) ^ 1), rp = mapa(sb + 8 * (B_PEER + 2 * wg), (b & 1) ^ 1), rb = rp + 8 * (B_RECV - B_PEER);
      uint32_t sa[24];
      auto addr = [&](int j) {
        sa[2 * j] = ra + (j < 2 ? 5 : (j >> 1) - 1) * 32768 + (j & 1) * 4096;
        sa[2 * j + 1] = (sa[2 * j] >> 31) + (rb + 8 * (j / 6));
        asm volatile("" : "+r"(sa[2 * j]), "+r"(sa[2 * j + 1]));
      };
      auto send = [&](int j) { st_async4(sa[2 * j], hh + 4 * j, sa[2 * j + 1]); };
      auto pack = [&](int c) {
#pragma unroll
        for (int i = 0; i < 64; i++) asm volatile("" : "+f"(ga[64 * c + i])::"memory");
#pragma unroll
        for (int i = 0; i < 4; i++) addr(4 * c + i);
#pragma unroll
        for (int i = 0; i < 16; i++) {
          const int j = 64 * c + 2 * i;
          hh[16 * c + i] = pack2(ga[j] * ga[j + 32], ga[j + 1] * ga[j + 33]);
          asm volatile("" : "+r"(hh[16 * c + i])::"memory");
          if ((i & 3) == 3 && 4 * c + i / 4 < NP) send(4 * c + i / 4);
          if (c == 2 && NQ > NP && i == 0) mbar_wait(sb + 8 * (B_PEER + 2 * wg), 0);
          if (c == 2 && (i & 3) == 3 && NP + i / 4 < NQ) send(NP + i / 4);
        }
      };
      STAMPIF(threadIdx.x == 0, 61);
      if (!nf) mbar_wait(sb + 8 * (B_F1 + 4), 1);
      mbar_wait(sb + 8 * B_EXT, 0);
      mbar_wait(sb + 8 * B_ST2, 0);
      const uint64_t de = mkdesc(sb + SM_EXT, 1024, 0, 1), ds = mkdesc(sb + SM_STAT + wg * 1024, 0, 128, 0);
#pragma unroll
      for (int c = 0; c < 2; c++) {
        wg_fence();
        wgmma_ss_n192<1, 1>(ga + 96 * c, da0 + 8192, db0 + 8192 + 768 * c, 1);
        wgmma_ss_n192<1, 1>(ga + 96 * c, da0 + 8192 + 256, db0 + 8192 + 128 + 768 * c, 1);
        wgmma_ss_n192<0, 1>(ga + 96 * c, ds, de + 192 * c, 1);
        wg_commit();
        if (c == 0) { mbar_wait(sb + 8 * B_P0, 0); mbar_wait(sb + 8 * B_FB, 0); }
        wg_wait<1>();
        if (c == 0 && tid == 0) {
          mbar_arrive(sb + 8 * (B_E1 + 3));
          mbar_arrive_remote(rp);
        }
      }
      STAMPIF(tid == 0, 15 + wg);
      float acc[64], rs[2] = {};
      uint4 pf[4], gb = {};
      uint32_t ln, os, ol, og, oz;
      const char *po, *pq;
      const uint64_t dd0 = mkdesc(ring + 8192, 0, 1024, 1);
      bool ok = false;
#pragma unroll
      for (int c = 0; c < 3; c++) {
        pack(c);
        if (c == 1) ok = mbar_try(sb + 8 * (B_FB + 1), 0);
        STAMPIF(tid == 0 && c == 0, wg ? 89 : 121);
        if (ITW == 3) STAMPIF(tid == 0 && c > 0, 99 + c + 10 * wg);
        wg_fence();
#pragma unroll
        for (int k = 4 * c; k < 4 * c + 4; k++) wgmma_rs_n64<1>(acc, hh + 4 * k, dd0 + 5 * 2048 + 128 * k, k);
        wg_commit();
        if (c == 0) {
          wg_wait<1>();
          if (tid == 0) {
            mbar_arrive(sb + 8 * (B_E1 + 4));
            mbar_arrive_remote(rp + 8);
          }
        }
        if (c == 1 && !ok) mbar_wait(sb + 8 * (B_FB + 1), 0);
      }
      auto recv = [&](int j) {
        const uint4 v = lds128(la + (j < 2 ? 5 : (j >> 1) - 1) * 32768 + (j & 1) * 4096);
        hh[48 + 4 * j] = v.x; hh[49 + 4 * j] = v.y; hh[50 + 4 * j] = v.z; hh[51 + 4 * j] = v.w;
      };
      auto stage = [&](const float* a, int i, int p) {
        const uint32_t v[4] = {pack2(a[8 * i] * rs[0], a[8 * i + 1] * rs[0]), pack2(a[8 * i + 2] * rs[1], a[8 * i + 3] * rs[1]),
                               pack2(a[8 * i + 4] * rs[0], a[8 * i + 5] * rs[0]), pack2(a[8 * i + 6] * rs[1], a[8 * i + 7] * rs[1])};
        stsm4(OF && p % 4 ? (oz ^ 32 * i) + 65536 * (p - 1) : os + 32 * i, v);
      };
      auto fetch = [&](int p) {
        __syncwarp();
#pragma unroll
        for (int i = 0; i < 4; i++) pf[i] = lds128(ol + 576 * i);
      };
      auto next = [&](int p) {
        gb = lds128(og + 256 * out_blk(s, p));
        pq = po + 128 * out_blk(s, p);
        asm volatile("" : "+l"(pq));
      };
      auto add = [&](int p, int i) {
        if (RX == 1 && p < 4) return;
        if (RX == 2) { stg128((uint4*)(pq - (i & 1) * 2048 * D_ - (i >> 1) * 2 * D_), make_uint4(hmul(pf[i].x, gb.x), hmul(pf[i].y, gb.y), hmul(pf[i].z, gb.z), hmul(pf[i].w, gb.w))); return; }
        asm volatile("red.relaxed.gpu.global.add.noftz.v4.bf16x2 [%0], {%1, %2, %3, %4};" ::"l"(pq - (i & 1) * 2048 * D_ - (i >> 1) * 2 * D_),
                     "r"(hmul(pf[i].x, gb.x)), "r"(hmul(pf[i].y, gb.y)), "r"(hmul(pf[i].z, gb.z)), "r"(hmul(pf[i].w, gb.w)) : "memory");
      };
#pragma unroll
      for (int h = 2; h < 20; h++) {
        const int gr = h >> 1, pe = gr < 4 ? gr >> 1 : gr & 1, ac = (gr < 4 ? gr : gr >> 1) & 1;
        const int ep = h == 7 || h == 8 ? 0 : h > 8 && (h & 3) == 1 || h > 8 && (h & 3) == 2 ? (h >> 2) - 1 : -1;
        const int es = h == 6 ? 0 : h > 6 && !(h & 3) ? (h >> 2) - 1 : -1;
        if (!(h & 1) && h > 2 && !(PT && ok)) mbar_wait(sb + 8 * (B_FB + gr), 0);
        if (h == LH0 || h == LH1) mbar_wait(sb + 8 * (B_RECV + 2 * wg + (h == LH1)), 0);
        if (h == LH0 && (h == 4 || !LM) || h == LH1 && (h == 5 || !LM)) {
#pragma unroll
          for (int j = 0; j < 6; j++) recv(6 * (h == LH1) + j);
        }
        if (h == SPOS(6) / 6 && NQ <= 6) mbar_wait(sb + 8 * (B_PEER + 2 * wg), 0);
        if (h == SPOS(10) / 6) mbar_wait(sb + 8 * (B_PEER + 2 * wg + 1), 0);
        if (OF && h == OH) mbar_wait(sb + 8 * B_OF, 0);
        if (h == (ES ? RH : 6)) {
          if (!OF) { mbar_wait(sb + 8 * B_X1, 0); mbar_wait(sb + 8 * B_GB, 0); }
          asm volatile("mov.u32 %0, %%laneid;" : "=r"(ln));
#pragma unroll
          for (int i = 0; i < 2; i++) rs[i] = blo(lds32(sb + SM_STAT + (4 * wg + w) * 256 + (ln & 28) * 4 + 128 * i + 4));
        }
        STAMPIF(tid == 0 && h % 4 == 0 && h < 16, (wg ? 89 : 121) + h / 4);
        STAMPIF(tid == 0 && h == 16, wg ? 97 : 96);
        if (ITW == 3) STAMPIF(tid == 0 && h < 10, 100 + h + 10 * wg);
        if (ITW == 4) STAMPIF(tid == 0 && h >= 10, 90 + h + 10 * wg);
        const uint64_t db = dd0 + (((gr + 5) % 6) * 2048 + (gr << 16));
        if (PT && (h & 1) && h < 19) ok = mbar_try(sb + 8 * (B_FB + gr + 1), 0);
        wg_fence();
#pragma unroll
        for (int j = 0; j < 6; j++) {
          const int k = 6 * (h & 1) + j;
          wgmma_rs_n64<1>(acc + 32 * ac, hh + 48 * pe + 4 * k, db + 128 * k, pe || k);
#pragma unroll
          for (int i = NQ; i < 12; i++) if (SPOS(i) == 6 * h + j) send(i);
          if (LM && h == LH0 && h < 4) { recv(j); wg_fence(); }
          if (LM && h == LH1 && h < 5) { recv(6 + j); wg_fence(); }
          if (ES && es >= 0) {
            if (j == ES - 1) {
              wg_commit();
              wg_wait<1>();
              if (h < 12 && tid == 0) mbar_arrive(sb + 8 * (B_EB + gr - 1));
#pragma unroll
              for (int i = 0; i < 32; i++) asm volatile("" : "+f"(acc[32 * (1 - ac) + i])::"memory");
            }
#pragma unroll
            for (int i = 0; i < 4; i++) if (j == min(5, ES - 1 + i * SI / 2)) {
              stage(acc + 32 * (1 - ac), i, es);
              if (i == 3) { __syncwarp(); if (ln == 0) mbar_arrive(sb + 8 * (B_OS + 4 * wg + es)); }
            }
            if (j == ES - 1 && j < 5) wg_fence();
          }
          if (!ES && ep >= 0 && (h & 1)) {
            if (j < 4) stage(acc + 32 * (1 - ac), j, ep);
            if (j == 4 && !OF) fetch(ep);
            if (j == 3 && OF) { __syncwarp(); if (ln == 0) mbar_arrive(sb + 8 * (B_OS + 4 * wg + ep)); }
          }
          if (!OF && ep >= 0 && !(h & 1) && j > 0 && j < 5) add(ep, j - 1);
          if (!OF && ep >= 0 && !(h & 1) && j == 5) next(ep + 1);
        }
        if (!(ES == 6 && es >= 0)) wg_commit();
        STAMPIF(tid == 0 && h == 3, 81);
        if (h == (ES ? RH : 6)) {
#pragma unroll
          for (int i = 0; i < 2; i++) rs[i] = __fdividef(0.25f, rs[i] * rs[i]);
          const uint32_t ob = sb + SM_X + (4 * wg + w) * 2304;
          os = ob + (ln & 15) * 144 + (ln & 16);
          oz = ring + (4 * wg + w) * 512 + (ln & 8) * 4096 + (ln & 4) * 1024 + (ln & 3) * 128 + ((ln >> 4) ^ (ln & 7)) * 16;
          asm volatile("" : "+r"(os), "+r"(oz));
        }
        if (h == (OF ? OH : 6)) {
          ol = sb + SM_X + (4 * wg + w) * 2304 + (ln >> 3) * 16 + ln * 16;
          po = (const char*)(gout + (1793 + 2 * tbase(8 * m + 4 * wg + w)) * D_) + (int)(640 * (s & 1) + 16 * ln - (ln >> 3) * (512 * D_ + 128));
          og = sb + SM_CB + 32 * (ln & 7);
          asm volatile("" : "+r"(ol), "+r"(og), "+l"(po));
          next(OF ? 4 : 0);
        }
        if (h == 2 || h == 4 || !ES && es >= 0) {
          wg_wait<1>();
          if (h < 12 && tid == 0) mbar_arrive(sb + 8 * (B_EB + gr - 1));
          if (h >= 6) {
#pragma unroll
            for (int j = 0; j < 32; j++) asm volatile("" : "+f"(acc[32 * (1 - ac) + j])::"memory");
          }
        }
      }
      STAMPIF(tid == 0, wg ? 95 : 93);
      wg_wait<0>();
#pragma unroll
      for (int i = 0; i < 32; i++) asm volatile("" : "+f"(acc[i])::"memory");
      STAMPIF(tid == 0, wg ? 50 : 18);
#pragma unroll
      for (int i = 0; i < 4; i++) stage(acc, i, 4);
      fetch(4);
#pragma unroll
      for (int i = 0; i < 4; i++) add(4, i);
    }
  } else if (wg == 2) {
    asm volatile("setmaxnreg.dec.sync.aligned.u32 40;");
    const uint32_t e1 = (rdback(G->flag + 8 * m + 4) >> 5) + 1;
    if (tid < 80) {
      uint4 c = ((const uint4*)gc)[tid];
#pragma unroll 1
      for (int i = 0; i < 4; i++) {
        const float lo = blo(c.x), hi = bhi(c.x);
        sts32(sb + SM_STAT + 16 * tid + 4 * i, pack2(__fdividef(lo, 1.f + __expf(-lo)), __fdividef(hi, 1.f + __expf(-hi))));
        c.x = c.y; c.y = c.z; c.z = c.w;
      }
    }
    if (tid == 0) { sts32(sb + SM_SMALL + SMALL_E, e1); mbar_arrive(sb + 8 * B_E0); }
    fence_async_s();
    bar_sync(5, 128);
    auto mod0 = [&](int tid) {
      if (mod_first(b)) mod_box(G, sb, b, 0, e1, tid);
      __syncwarp();
      if (elect()) mbar_arrive(sb + 8 * B_BD);
      STAMPIF(tid == 0, 27);
    };
    if (MO == 2) { kv_job(G, sb, b, 2, tid, e1); STAMPIF(tid == 0, 22); }
    if (MO != 1) mod0(tid);
    float s1 = 0.f, s2 = 0.f, pv;
    int tl = (OPQ & 1) ? __shfl_sync(0xffffffffu, tid, tid) : tid;
#pragma unroll 1
    for (int r = KW || MO == 2 ? 3 : 2 - DR; r < 5 - XO; r++) {
      asm volatile("" : "+r"(tl));
      if (DR && r == 2) s1 = s2 = 0.f;
      if ((XO || r < 4) && r > 1) {
        kv_job(G, sb, b, r, tl, TG ? e1 : 1);
        STAMPIF(tid == 0, 20 + r);
      }
      if (r == 3) { __syncwarp(); if (elect()) mbar_arrive(sb + 8 * B_KVS); }
      if (XO || r != 2) ln1_half(sb, tl, (r - 3 + XO) & 1, r < 2, s1, s2, pv);
      else if (MO == 1) { mod0(tl); s1 = s2 = 0.f; }
    }
    {
      const int lane = tl & 31, cg = 4 * (w >> 1) + (lane & 2) + (w & 1), g = lane >> 2;
      uint32_t zo = offsetof(Scr, zT) + 2 * ((16 * cg + g) * S_ + 16 * b + 8 * (lane & 1)), co = offsetof(Scr, mv) + 4 * (2048 * (e1 & 1) + 8 * cg + g);
      uint4 z[2];
      uint32_t c[4];
      auto zld = [&]() {
        asm volatile("" : "+r"(zo), "+r"(co));
        const uint2* pz = (const uint2*)((const char*)G + zo);
        const uint32_t* pc = (const uint32_t*)((const char*)G + co);
        z[0] = ld_tag2(pz); z[1] = ld_tag2(pz + 4096);
        c[0] = rdback(pc); c[1] = rdback(pc + 320); c[2] = rdback(pc + 640); c[3] = rdback(pc + 1280);
      };
      STAMPIF(tid == 0, 28);
      if (ZF < 2 && !ZA) { spin(t_0, ZD); zld(); spin(t_0, ZS); }
      if (ITW == 8) STAMPIF(tid == 0, 106);
      ln1_end(sb, tl, s1, s2, pv);
      if (ZF < 2 && ZA) { spin(t_0, ZD); zld(); }
#pragma unroll 1
      for (int r = 0; r < 5; r++) {
        asm volatile("" : "+r"(tl));
        const int lane = tl & 31;
        if (ITW == 6) STAMPIF(tid == 0 && r < 2, 100 + 10 * r);
        if (ZF == 3) { if (r == 2 + MG) { mbar_wait(sb + 8 * (B_BD + 1), 0); spin(clk(), BD); } if (r == 0) spin(t_0, ZD); zld(); }
        const uint32_t la = sb + SM_SMALL + SMALL_LN + 16 * (lane & 1);
        uint32_t xa = x_addr(sb, w, lane) + 4096 * r, xv[8];
        const uint4 m4 = lds128(la), s4 = lds128(la + 32);
        const uint32_t m_[4] = {m4.x, m4.y, m4.z, m4.w}, s_[4] = {s4.x, s4.y, s4.z, s4.w};
        ldsm4t(xv, xa);
        ldsm4t(xv + 4, xa ^ 16);
        if (ZF == 2) { if (r == 2 + MG) { mbar_wait(sb + 8 * (B_BD + 1), 0); spin(clk(), BD); } if (r == 0) spin(t_0, ZD); zld(); }
        if (ITW == 6) STAMPIF(tid == 0 && r < 2, 104 + 10 * r);
        if (ITW == 8) STAMPIF(tid == 0 && r == 0, 109);
        z_wait(z[0], z[1], c, G, zo, co, e1);
        asm volatile("" : "+r"(xa));
        const uint32_t zc = (zo - (uint32_t)offsetof(Scr, zT)) >> 11, ao = (320 * m + s) * 32 + ((zc & ~31u) << 3) + (zc & 14) + (((zo >> 4) ^ (zc >> 3)) & 1);
        STAMPIF(tid == 0 && r == 0, 83);
        if (ITW == 6) STAMPIF(tid == 0 && r < 2, 105 + 10 * r);
        uint32_t h[8];
        {
          const uint32_t sa = ~c[0], ca1 = ~c[1];
#pragma unroll
          for (int j = 0; j < 8; j++) {
            const uint32_t z_[8] = {z[0].x, z[0].y, z[0].z, z[0].w, z[1].x, z[1].y, z[1].z, z[1].w}, sel = j > 3 ? 0x3232 : 0x1010;
            h[j] = hmul(hfma(hmul(hsub(xv[j], m_[j & 3]), s_[j & 3]), __byte_perm(ca1, 0, sel), __byte_perm(sa, 0, sel)), z_[j]);
            asm volatile("" : "+r"(h[j]));
          }
        }
        uint4* pa = (uint4*)G->AT + ao;
        uint32_t oo[8];
#pragma unroll
        for (int n = 0; n < 2; n++) {
          const uint32_t sel = n ? 0x3232 : 0x1010, ga = __byte_perm(~c[2], 0, sel), cb1 = __byte_perm(~c[3], 0, sel);
          uint32_t* o = oo + 4 * n, a[4];
#pragma unroll
          for (int j = 0; j < 4; j++) {
            o[j] = hfma(ga, h[4 * n + j], xv[4 * n + j]);
            a[j] = hmul(o[j], cb1);
          }
          a[2 * n + 1] = tagged(a[2 * n + 1], e1);
          pa[16 * n] = make_uint4(a[0], a[1], a[2], a[3]);
          if (n) { __syncwarp(); if (elect()) { flag_add(G, 8 * m + r); if (EA && r == 0) mbar_arrive(sb + 8 * (B_EW + 5)); } }
          if (ITW == 6) STAMPIF(tid == 0 && r < 2, 106 + n + 10 * r);
          if (ITW == 8) STAMPIF(lane == 0 && r == 0 && n, 110 + w);
          if (!SL) stsm4t(xa ^ (16 * n), o);
        }
        if (SL) { stsm4t(xa, oo); stsm4t(xa ^ 16, oo + 4); }
        if (r < 4) { zo += 256 * S_; co += 256; }
        auto x1st = [&]() {
          __syncwarp();
          int lane = tl & 31;
          if (!(OPQ & 2)) asm volatile("mov.u32 %0, %%laneid;" : "=r"(lane));
          const int c = 2 * (w & 1) + (lane & 1) + 2 * (lane & 2), g = lane >> 2;
          const uint32_t a = sb + SM_X + 4096 * r + (w >> 1) * 2048 + g * 128 + ((c ^ g) << 4);
          const uint4 v0 = lds128(a), v1 = lds128(a + 1024);
          char* po = (char*)gout + (2 * tbase(b) + 128 * (g & 6) + (g & 1)) * 2 * D_ + 256 * r + 64 * (w & 2) + 16 * c;
          if (ITW == 6) STAMPIF(tid == 0 && r < 2, 108 + 10 * r);
          stg128(po, v0);
          stg128(po + 2048 * D_, v1);
        };
        auto box1 = [&]() {
          if (BX3 >= 3) {
            mod_box(G, sb, b, 1, e1, tl);
            __syncwarp();
            if (elect()) mbar_arrive(sb + 8 * (B_BD + 1));
            STAMPIF(tid == 0, 73);
          } else mbar_wait(sb + 8 * (B_BD + 1), 0);
          if (BX3 < 4) spin(clk(), BD);
        };
        if (ZF == 1) {
          if (BX3 < 4 && r == 1 + MG) { if (XE) x1st(); box1(); }
          if (BX3 == 5 && r == 0) box1();
          zld();
        }
        if (BX3 == 6 && r == 0) box1();
        if (BX3 > 3 || ZF != 1 || !XE || r != 1 + MG) x1st();
        if (BX3 == 4 && r == 0) box1();
        __syncwarp();
        if (elect()) mbar_arrive(sb + 8 * (B_EW + r));
        STAMPIF(tid == 0, 29 + r);
        if (ZF == 0) { if (r == 1 + MG) box1(); zld(); }
      }
    }
    asm volatile("" : "+r"(tl));
    {
      const int lane = tl & 31;
      const uint4 m4 = lds128(sb + SM_SMALL + SMALL_LN + 16 * (lane & 1));
      const uint32_t m_[4] = {m4.x, m4.y, m4.z, m4.w}, xa = x_addr(sb, w, lane);
      float a[16];
#pragma unroll
      for (int i = 0; i < 16; i++) a[i] = 0.f;
#pragma unroll 2
      for (int n = 0; n < 10; n++) {
        uint32_t x_[4];
        ldsm4t(x_, (xa ^ (16 * (n & 1))) + 2048 * (n & 14));
#pragma unroll
        for (int i = 0; i < 4; i++) {
          const float d0 = blo(x_[i]) - blo(m_[i]), d1 = bhi(x_[i]) - bhi(m_[i]);
          a[4 * i] += d0; a[4 * i + 1] += d0 * d0; a[4 * i + 2] += d1; a[4 * i + 3] += d1 * d1;
        }
      }
      STAMPIF(lane == 0, 67 + (w & 1) + 11 * (w >> 1));
      bfly<16>(a, 16, lane & 16); bfly<8>(a, 8, lane & 8); bfly<4>(a, 4, lane & 4); bfly<2>(a, 2, lane & 2);
      if (lane == 0) mbar_arrive(sb + 8 * B_XF);
      STAMPIF(tid == 0, 88);
      sts32(sb + SM_SMALL + SMALL_RED + 16 * lane + 4 * w, __float_as_uint(a[0]));
      bar_sync(5, 128);
      if (w == 0) {
        const uint4 v = lds128(sb + SM_SMALL + SMALL_RED + 16 * lane);
        const float s1 = __uint_as_float(v.x) + __uint_as_float(v.y) + __uint_as_float(v.z) + __uint_as_float(v.w), s2 = __shfl_xor_sync(0xffffffffu, s1, 2);
        const int p = 8 * (lane & 1) + (lane >> 2);
        const float pv = blo(lds32(sb + SM_SMALL + SMALL_LN + 4 * (p >> 1)) >> (16 * (p & 1)));
        const float mu = s1 * (1.f / D_), var = fmaxf(s2 * (1.f / D_) - mu * mu, 0.f);
        const float sd = sdev(var);
        if (!(lane & 2)) st_tag(G->st2 + 16 * b + p, pack2(-0.5f * (pv + mu), 0.5f * sd), e1);
      }
      STAMPIF(tid == 0, 87);
    }
    {
      uint2 v;
      spin(clk(), SD);
      mbar_wait(sb + 8 * (B_BD + 2), 0);
#pragma unroll 1
      for (int i = 0;; i++) {
        v = ld_tag(G->st2 + 128 * m + tl);
        if (__all_sync(0xffffffffu, v.y == e1)) break;
        if (i > (1 << 20)) __trap();
      }
      const uint32_t hm = __byte_perm(v.x, 0, 0x1010), hs = __byte_perm(v.x, 0, 0x3232);
      sts128(sb + SM_STAT + 16 * tl, make_uint4(hm, hs, hm, hs));
      fence_async_s();
      __syncwarp();
      if (elect()) mbar_arrive(sb + 8 * B_ST2);
      STAMPIF(tid == 0, 21);
    }
    if (OF) {
      uint32_t ln, w, s;
      asm volatile("mov.u32 %0, %%laneid;\n\tmov.u32 %1, %%tid.x;\n\tmov.u32 %2, %%ctaid.x;" : "=r"(ln), "=r"(w), "=r"(s));
      w = (w >> 5) & 3; s = role<0>(s);
      const int m = s >> 3;
      s &= 7;
      mbar_wait(sb + 8 * B_X1, 0);
      mbar_wait(sb + 8 * B_GB, 0);
      const uint32_t ol = sb + SM_X + w * 2304 + (ln >> 3) * 16 + ln * 16, oz = ring - 65536 + w * 512 + (ln >> 3) * 128 + ((ln >> 3) ^ (ln & 7)) * 16;
      const char* po = (const char*)(gout + 1793 * D_) + (int)(640 * (s & 1) + 16 * ln - (ln >> 3) * (512 * D_ + 128));
#pragma unroll 1
      for (int n = 0; n < 8; n++) {
        const int p = n >> 1, c = n & 1, ob = out_blk(s, p);
        const uint4 gb = lds128(sb + SM_CB + 32 * (ln & 7) + 256 * ob);
        const char* pq = po + (128 * ob + 4 * D_ * tbase(8 * m + 4 * c + w));
        const uint32_t a0 = p ? oz + 65536 * p + 2048 * c : ol + 9216 * c, a1 = p ? (a0 ^ 64) + 4096 : a0 + 576, d = p ? 32768 : 1152;
        mbar_wait(sb + 8 * (B_OS + 4 * c + p), 0);
        const uint4 pf[4] = {lds128(a0), lds128(a1), lds128(a0 + d), lds128(a1 + d)};
#pragma unroll
        for (int i = 0; i < 4; i++)
          asm volatile("red.relaxed.gpu.global.add.noftz.v4.bf16x2 [%0], {%1, %2, %3, %4};" ::"l"(pq - (i & 1) * 2048 * D_ - (i >> 1) * 2 * D_),
                       "r"(hmul(pf[i].x, gb.x)), "r"(hmul(pf[i].y, gb.y)), "r"(hmul(pf[i].z, gb.z)), "r"(hmul(pf[i].w, gb.w)) : "memory");
        if (n == 1) { __syncwarp(); if (ln == 0) mbar_arrive(sb + 8 * B_OF); }
      }
    }
  } else {
    asm volatile("setmaxnreg.dec.sync.aligned.u32 24;");
    if (w != 0) {
    if (w == 2 && lane < 3) asm volatile("prefetch.tensormap [%0];" ::"l"(&P.mG + lane) : "memory");
    if (K3) {
      const uint32_t dv = *(const uint16_t*)(gD + 128 * min(lane, 4) + b);
#pragma unroll 1
      for (int j = 7 + w; j < 20; j += 3) {
        k1_job(sb, j >> 2, 32 * (j & 3) + lane, __shfl_sync(0xffffffffu, dv, j >> 2));
        if ((j & 3) == (K3 & 3)) {
          mbar_wait(sb + 8 * (B_KJ + (j >> 2)), 0);
          const uint32_t t = lds32(sb + SM_SMALL + SMALL_TS + 4 * (j >> 2));
          while (clk() - t < UD);
        }
        __syncwarp();
        if (lane == 0) mbar_arrive(sb + 8 * (B_K + (j >> 2) - 2));
      }
      STAMPIF(lane == 0 && w == 3, 74);
    } else if (w & 1) {
      const uint32_t dv = *(const uint16_t*)(gD + 128 * min(lane, 4) + b);
#pragma unroll 1
      for (int j = 4; j < 10; j++) {
        k1_job(sb, j >> 1, 64 * (j & 1) + 16 * (w & 2) + lane, K1N ? __shfl_sync(0xffffffffu, dv, j >> 1) : *(const uint16_t*)(gD + 64 * (j & 14) + b));
        if (ITW == 5) STAMPIF(tid == 32, 98 + (j >> 1));
        if (UT == 5 && UD && w == 1 && (j & 1)) {
          mbar_wait(sb + 8 * (B_KJ + (j >> 1)), 0);
          const uint32_t t = lds32(sb + SM_SMALL + SMALL_TS + 4 * (j >> 1));
          while (clk() - t < UD);
        }
        __syncwarp();
        if (lane == 0) mbar_arrive(sb + 8 * (B_K + (j >> 1) - 2));
      }
      STAMPIF(tid == 32, 74);
    }
    if (w == 1) {
     {
      mbar_wait(sb + 8 * B_KVS, 0);
      const uint32_t e1 = epoch(sb);
      if (elect()) {
        if (P3) { const uint32_t v = e1 * 32 - 32; sts128(sb + SM_SMALL + SMALL_H, make_uint4(v, v, v, v)); sts32(sb + SM_SMALL + SMALL_H + 16, v); }
        if (ER) mbar_wait(sb + 8 * B_KV4, 0);
        mbar_wait(sb + 8 * (B_EW + 5 * EA), 0);
        spin(clk(), AD);
#pragma unroll 1
        for (int it = NS; it < 20; it++) {
          int st = it % 5;
          if ((it & 3) == 0 || it == NS) { if (P3) hint_wait(G, sb + SM_SMALL + SMALL_H, 8 * m + (it >> 2), e1 * 32); else flag_wait(G, 8 * m + (it >> 2), e1 * 32); STAMP(45 + (it >> 2)); }
          if (NS && it == NS) mbar_arrive(sb + 8 * B_FS);
          mbar_wait(sb + 8 * (B_E1 + st), (it / 5) & 1);
          uint32_t fb = sb + 8 * (B_A + st);
          mbar_expect(fb, 8192);
          bulk_g2s(ring + st * 32768, G->AT + (20 * m + it) * 4096, 8192, fb);
        }
        mbar_wait(sb + 8 * B_XF, 0);
        flag_wait(G, 8 * m + FL_X, e1 * 8);
        mbar_arrive(sb + 8 * B_X1);
        STAMP(86);
      }
     }
    } else if (w == 2) {
      if (lane < 4) mbar_expect(sb + 8 * (B_RECV + lane), 12288);
      if (UT == 2) { bar_arrive(1, 288); bar_arrive(2, 288); }
      int ph = 0;
#pragma unroll 1
      for (int ch = UT; ch < 5; ch++) {
        const uint32_t ub = chan_base(sb, ch) + KSZ;
        uint4* pu = (uint4*)(G->kvT + (128 * ch + b) * S_);
        mbar_wait(sb + 8 * (B_KJ + ch), 0);
        const uint32_t t0 = lds32(sb + SM_SMALL + SMALL_TS + 4 * ch);
        while (clk() - t0 < (ch ? UD : UD0));
#pragma unroll 1
        for (int i = 0;; i++) {
          if (elect()) { mbar_expect(sb + 8 * B_U, 4096); bulk_g2s(ub, pu, 4096, sb + 8 * B_U); }
          if (ITW == 5) STAMPIF(lane == 0, 110 + ch);
          mbar_wait(sb + 8 * B_U, ph);
          ph ^= 1;
          uint32_t t = 1;
#pragma unroll
          for (int j = 0; j < 8; j++) t &= lds32(ub + 16 * lane + 512 * j + 12);
          if (__all_sync(0xffffffffu, t)) break;
          if (i > (1 << 20)) __trap();
        }
        if (ITW == 5) STAMPIF(lane == 0, 105 + ch);
        if (ch > 1) mbar_wait(sb + 8 * (B_Z + ch - 2), 0);
        bar_arrive(1 + (ch & 1), 288);
#pragma unroll
        for (int j = 0; j < 8; j++) stg128(pu + lane + 32 * j, make_uint4(0, 0, 0, 0));
      }
      if (ITW == 8) { mbar_wait(sb + 8 * B_X, 0); STAMPIF(lane == 0, 100); mbar_wait(sb + 8 * (B_X + 1), 0); STAMPIF(lane == 0, 101); }
      mbar_wait(sb + 8 * B_BD, 0);
      const uint32_t e1 = epoch(sb), ao = 256 * (lane & 16) + 32 * (lane & 15) + 4 * (lane & 4) + (lane & 8) + 4;
      int it = 0;
      uint32_t pm = (1 << NS) - 1;
      bool ok = false;
      if (NS) {
        if (lane < NS) mbar_expect(sb + 8 * (B_A + lane), 8192);
        mbar_wait(sb + 8 * (lane < NS ? B_E1 + lane : B_EW + 5), 0);
        __syncwarp();
        spin(clk(), AT1);
        spin(t_0, AT0);
        if (elect()) {
#pragma unroll
          for (int i = 0; i < NS; i++) bulk_g2s(ring + i * 32768, G->AT + (20 * m + i) * 4096, 8192, sb + 8 * (B_A + i));
        }
        __syncwarp();
        STAMPIF(lane == 0, 84);
#pragma unroll 1
        for (; it < NS; it++) {
          if (!ok) mbar_wait(sb + 8 * (B_A + it), 0);
          uint32_t t = 0, v[8];
          if (PC) ok = mbar_test(sb + 8 * (B_A + it + 1), 0);
#pragma unroll
          for (int j = 0; j < 8; j++) v[j] = ldv32(ring + it * 32768 + ao + 512 * j);
#pragma unroll
          for (int j = 0; j < 8; j++) t |= v[7 - j] ^ e1;
          if (__any_sync(0xffffffffu, t & 1)) {
            ok = false;
            fence_async_s();
            mbar_wait(sb + 8 * (lane > it && lane < NS ? B_A + lane : B_FS), 0);
            __syncwarp();
            if (lane >= it && lane < NS) mbar_expect(sb + 8 * (B_A + lane), 8192);
            __syncwarp();
            if (elect()) {
#pragma unroll
              for (int i = 0; i < NS; i++)
                if (i >= it) bulk_g2s(ring + i * 32768, G->AT + (20 * m + i) * 4096, 8192, sb + 8 * (B_A + i));
            }
            __syncwarp();
            STAMPIF(lane == 0, 85);
            break;
          }
          if (lane == 0) mbar_arrive(sb + 8 * (B_F1 + it));
        }
      }
#pragma unroll 1
      for (int st = it; it < 20; it++) {
        const uint32_t a = ring + st * 32768 + ao;
        if (!ok) mbar_wait(sb + 8 * (B_A + st), (pm >> st) & 1);
        pm ^= 1 << st;
        const int nx = st == 4 ? 0 : st + 1;
        if (ITW == 7) STAMPIF(lane == 0 && it < 4, 100 + it);
        if (ITW == 8) STAMPIF(lane == 0 && it < 2, 114 + it);
        uint32_t t = 0, v[8];
        if (PC) ok = mbar_test(sb + 8 * (B_A + nx), (pm >> nx) & 1);
#pragma unroll
        for (int j = 0; j < 8; j++) v[j] = ldv32(a + 512 * j);
#pragma unroll
        for (int j = 0; j < 8; j++) t |= v[7 - j] ^ e1;
        if (__any_sync(0xffffffffu, t & 1)) {
#pragma unroll 1
          for (int j = 0; j < 8; j++) a_check(a + 512 * j, (const char*)G->AT + (20 * m + it) * 8192 + ao + 512 * j, e1);
        }
        if (lane == 0) mbar_arrive(sb + 8 * (B_F1 + st));
        if (ITW == 7) STAMPIF(lane == 0 && it < 4, 104 + it);
        if (ITW == 8) STAMPIF(lane == 0 && it < 2, 116 + it);
        st = nx;
      }
    } else {
      mbar_wait(sb + 8 * B_KVS, 0);
      auto rel = [&](int ch) { mbar_wait(sb + 8 * (B_Z + ch), 0); if (lane <= (ch >> 2)) mbar_arrive(sb + 8 * (B_E1 + 2 + (ch >> 1))); };
      if (RL) { rel(0); rel(1); rel(2); }
      mbar_wait(sb + 8 * (B_BD + 1), 0);
      if (!BI && b >= 96 && elect()) { load_box(P, sb, b, 4); load_box(P, sb, b, 5); }
      const uint32_t t1 = clk();
      if (RL) { rel(3); rel(4); }
      spin(t1, CD);
      __syncwarp();
      const uint32_t e1 = epoch(sb);
#pragma unroll 1
      for (int n = 0; n < 5; n++) {
        int lane;
        asm volatile("mov.u32 %0, %%laneid;" : "=r"(lane));
        if (n == 3) {
          fence_async_s();
          __syncwarp();
          if (lane == 0) mbar_arrive(sb + 8 * B_F);
          STAMPIF(lane == 0, 34);
          {
            mbar_wait(sb + 8 * (B_EW + 4), 0);
            const char* po = (char*)gout + (2 * tbase(b) + 64 * (lane & 28) + ((lane >> 1) & 1)) * 2 * D_ + (lane & 1) * 640;
            uint32_t v = 0;
#pragma unroll
            for (int r = 0; r < 5; r++) v ^= rdback(po + 128 * r);
            rdwait(sb, v);
            __syncwarp();
            if (lane == 0) flag_add(G, 8 * m + FL_X);
            STAMPIF(lane == 0, 94);
          }
          mbar_wait(sb + 8 * (B_BD + 2), 0);
          if (lane < 2) mbar_arrive(sb + 8 * (B_E1 + 5));
          if (m < 12) {
            rdwait(sb, rdback(G->cimg + s * 3072 + (m % 6) * 512 + (m < 6 ? 0 : 256) + 64 * (lane & 3)));
            __syncwarp();
            if (lane == 0) flag_add(G, FL_C + 8 * s);
            STAMPIF(lane == 0, 35);
          }
          if (elect()) {
            flag_wait(G, FL_C + 8 * s, e1 * 12);
            fence_async_g();
            STAMP(54);
            mbar_expect(sb + 8 * B_EXT, 6144);
            bulk_g2s(sb + SM_EXT, G->cimg + s * 3072, 6144, sb + 8 * B_EXT);
          }
          __syncwarp();
          mbar_wait(sb + 8 * B_ST2, 0);
        }
        const int j = n < 3 ? min(16 * n + (lane >> 1), 39) : min(16 * n - 8 + (lane >> 1), 59), k = j < 20 ? j : j < 40 ? j - 20 : j - 40;
        const uint2* pj = (const uint2*)(G->mv + 2048 * (e1 & 1) + 4 * (lane & 1) + 8 * (k + (j < 40 ? (j < 20 ? 160 : 120) + (m < 6 ? 0 : 20) : 200 + 20 * (s & 1))));
        uint4 a;
#pragma unroll 1
        for (int i = 0;; i++) {
          a = ld_tag2(pj);
          if (__all_sync(0xffffffffu, a.x != 0)) break;
          if (i > (1 << 20)) __trap();
        }
        const uint32_t d = sb + SM_CB + 64 * k + 8 * (lane & 1) + (j >= 20 && j < 40 ? 16 : 0);
        sts64(d, ~__byte_perm(a.x, a.y, 0x5410), ~__byte_perm(a.z, a.w, 0x5410));
        sts64(d + 32, ~__byte_perm(a.x, a.y, 0x7632), ~__byte_perm(a.z, a.w, 0x7632));
      }
      __syncwarp();
      if (lane == 0) mbar_arrive(sb + 8 * B_GB);
      STAMPIF(lane == 0, 39);
    }
    } else {
      STAMPIF(lane == 0, 62);
      int rw = sched_run<0>(P, In{gk, gv, gsk, gWg, gWu, gWd, gss}, sb, b, lane, __shfl_sync(0xffffffffu, t_0, 0));
      if (elect()) {
        STAMP(69);
        mbar_wait(sb + 8 * B_KVS, 0);
        if (ER) mbar_wait(sb + 8 * B_KV4, 0);
        STAMP(70);
        int rd = 0, c = 0;
#pragma unroll 1
        for (int it = 0; it < 20; it++) {
          load_w(P, sb, s, it);
          if ((PWM >> it) & 1) { l2_prefetch(gWg + (128 * rw + b) * F_, 2 * F_); l2_prefetch(gWu + (128 * rw + b) * F_, 2 * F_); rw++; }
          if ((PDM >> it) & 1) { l2_prefetch(gWd + (512 * rd + 4 * b) * D_, 8 * D_); rd++; }
          if (BI && it == BI && b >= 96) { mbar_wait(sb + 8 * (B_BD + 1), 0); load_box(P, sb, b, 4); load_box(P, sb, b, 5); }
          if (((STM >> it) & 1) && b < 96) {
            const int grp = m % 6;
            if (c == 4) mbar_wait(sb + 8 * (B_BD + 1), 0);
            if (c == 0) mbar_expect(sb + 8 * B_ST0, 40960);
#pragma unroll
            for (int j = 0; j < 2; j++, c++)
              tma2d(sb + (c < 2 ? SM_EXT : SM_RING + R_X - 8192) + 4096 * c, &P.mG + (grp & 1), 192 * s + 64 * (grp >> 1), (m < 6 ? 0 : 320) + 32 * c, sb + 8 * B_ST0);
          }
        }
#pragma unroll
        for (int k = 0; k < 10; k++) {
          const int st = (k + 5) % 6, pe = k < 4 ? k >> 1 : k & 1, ps = k < 4 ? k & 1 : k >> 1;
          mbar_wait(sb + 8 * (k < 6 ? B_E1 + st : B_EB + k - 6), 0);
          if (k == 2) mbar_arrive_remote(mapa(sb + 8 * B_P0, (b & 1) ^ 1));
          mbar_expect(sb + 8 * (B_FB + k), 24576);
          tma2d(ring + st * 32768 + 8192, &P.mD, 320 * (s & 1) + 64 * out_blk(s, ps), 192 * (s ^ pe), sb + 8 * (B_FB + k));
        }
      }
    }
  }
}

typedef CUresult (*EncFn)(CUtensorMap*, CUtensorMapDataType, cuuint32_t, void*, const cuuint64_t*, const cuuint64_t*, const cuuint32_t*, const cuuint32_t*,
                          CUtensorMapInterleave, CUtensorMapSwizzle, CUtensorMapL2promotion, CUtensorMapFloatOOBfill);
static void mkmap(EncFn enc, CUtensorMap* m, const void* p, int rank, const cuuint64_t* dims, const cuuint64_t* strides, const cuuint32_t* box, CUtensorMapSwizzle sw) {
  cuuint32_t es[5] = {1, 1, 1, 1, 1};
  CUresult r = enc(m, CU_TENSOR_MAP_DATA_TYPE_BFLOAT16, rank, (void*)p, dims, strides, box, es, CU_TENSOR_MAP_INTERLEAVE_NONE, sw,
                   CU_TENSOR_MAP_L2_PROMOTION_L2_128B, CU_TENSOR_MAP_FLOAT_OOB_FILL_NONE);
  if (r != CUDA_SUCCESS) fprintf(stderr, "tensor map encode failed: %d\n", (int)r);
}

extern "C" void kernel_launch(void* const* d_in, const int* in_sizes, int n_in, void* d_out, int out_size) {
  void* fn = nullptr;
  cudaDriverEntryPointQueryResult qr;
  cudaGetDriverEntryPoint("cuTensorMapEncodeTiled", &fn, cudaEnableDefault, &qr);
  EncFn enc = (EncFn)fn;
  Scr* G;
  cudaGetSymbolAddress((void**)&G, g_scr);
  Params P;
  { cuuint64_t d[] = {128, 16, 640}, st[] = {256, 4096}; cuuint32_t bx[] = {144, 16, 1}; mkmap(enc, &P.mS, d_in[4], 3, d, st, bx, CU_TENSOR_MAP_SWIZZLE_NONE); }
  { cuuint64_t d[] = {3840, 64, 10}, st[] = {7680, 64 * 7680}; cuuint32_t bx[] = {16, 64, 5}; mkmap(enc, &P.mWm, d_in[11], 3, d, st, bx, CU_TENSOR_MAP_SWIZZLE_32B); }
  { cuuint64_t d[] = {32, 20, 256, 8}, st[] = {64, 10240, 1280}; cuuint32_t bx[] = {40, 1, 9, 8}, bx2[] = {40, 1, 8, 8};
    mkmap(enc, &P.mK, d_in[1], 4, d, st, bx, CU_TENSOR_MAP_SWIZZLE_NONE); mkmap(enc, &P.mV, d_in[2], 4, d, st, bx2, CU_TENSOR_MAP_SWIZZLE_NONE); }
  { cuuint64_t d[] = {1536, 640}, st[] = {3072}; cuuint32_t bx[] = {64, 32};
    mkmap(enc, &P.mG, d_in[7], 2, d, st, bx, CU_TENSOR_MAP_SWIZZLE_128B); mkmap(enc, &P.mU, d_in[8], 2, d, st, bx, CU_TENSOR_MAP_SWIZZLE_128B); }
  { cuuint64_t d[] = {640, 1536}, st[] = {1280}; cuuint32_t bx[] = {64, 192}; mkmap(enc, &P.mD, d_in[9], 2, d, st, bx, CU_TENSOR_MAP_SWIZZLE_128B); }
  { cuuint64_t d[] = {64, 2, 8, 10, 128}, st[] = {1280, 256 * 1280, 128, 2560}; cuuint32_t bx[] = {64, 2, 8, 5, 1}; mkmap(enc, &P.mX, d_in[0], 5, d, st, bx, CU_TENSOR_MAP_SWIZZLE_128B); }
  cudaFuncSetAttribute(fused_kernel, cudaFuncAttributeMaxDynamicSharedMemorySize, SM_TOTAL + DEVSM);
  cudaLaunchConfig_t cfg = {};
  cfg.gridDim = dim3(128); cfg.blockDim = dim3(512); cfg.dynamicSmemBytes = SM_TOTAL + DEVSM; cfg.stream = cudaStreamPerThread;
  cudaLaunchAttribute at[1];
  at[0].id = cudaLaunchAttributeClusterDimension; at[0].val.clusterDim.x = 2; at[0].val.clusterDim.y = 1; at[0].val.clusterDim.z = 1;
  cfg.attrs = at; cfg.numAttrs = 1;
  cudaLaunchKernelEx(&cfg, fused_kernel, (const bf16*)d_in[1], (const bf16*)d_in[2], (const bf16*)d_in[3], (const bf16*)d_in[5], (const bf16*)d_in[10], G,
                     (const bf16*)d_in[7], (const bf16*)d_in[8], (const bf16*)d_in[9], (bf16*)d_out, (const bf16*)d_in[4], P);
}
```

```cpp
#include <cuda_runtime.h>
#include <cuda.h>
#include <cuda_bf16.h>
#include <stdio.h>
#include <stdint.h>
typedef __nv_bfloat16 bf16;
__device__ __forceinline__ uint32_t smem_u32(const void* p) { return (uint32_t)__cvta_generic_to_shared(p); }
__device__ __forceinline__ void mbar_init(uint32_t bar, int cnt) { asm volatile("mbarrier.init.shared::cta.b64 [%0], %1;" ::"r"(bar), "r"(cnt) : "memory"); }
__device__ __forceinline__ void mbar_expect(uint32_t bar, int bytes) { asm volatile("mbarrier.arrive.expect_tx.shared::cta.b64 _, [%0], %1;" ::"r"(bar), "r"(bytes) : "memory"); }
__device__ __forceinline__ void mbar_arrive(uint32_t bar) { asm volatile("mbarrier.arrive.shared::cta.b64 _, [%0];" ::"r"(bar) : "memory"); }
__device__ __forceinline__ void mbar_arrive_remote(uint32_t bar) { asm volatile("mbarrier.arrive.relaxed.cluster.shared::cluster.b64 _, [%0];" ::"r"(bar) : "memory"); }
__device__ __forceinline__ uint32_t mapa(uint32_t a, uint32_t cta) { uint32_t r; asm("mapa.shared::cluster.u32 %0, %1, %2;" : "=r"(r) : "r"(a), "r"(cta)); return r; }
__device__ __forceinline__ bool mbar_try(uint32_t bar, int parity) {
  uint32_t ok;
  asm volatile("{\n.reg .pred p;\nmbarrier.try_wait.parity.shared::cta.b64 p, [%1], %2;\nselp.u32 %0, 1, 0, p;\n}" : "=r"(ok) : "r"(bar), "r"(parity) : "memory");
  return ok;
}
__device__ __forceinline__ void mbar_wait(uint32_t bar, int parity) {
#pragma unroll 1
  for (int i = 0; i < (1 << 20); i++) { if (mbar_try(bar, parity)) return; }
  __trap();
}
__device__ __forceinline__ bool elect() {
  uint32_t p;
  asm volatile("{\n.reg .pred P;\nelect.sync _|P, 0xffffffff;\nselp.u32 %0, 1, 0, P;\n}" : "=r"(p));
  return p;
}
__device__ __forceinline__ void tma2d(uint32_t dst, const CUtensorMap* m, int c0, int c1, uint32_t bar) {
  asm volatile("cp.async.bulk.tensor.2d.shared::cluster.global.mbarrier::complete_tx::bytes [%0], [%1, {%3, %4}], [%2];" ::"r"(dst), "l"(m), "r"(bar), "r"(c0), "r"(c1) : "memory");
}
__device__ __forceinline__ void tma3d(uint32_t dst, const CUtensorMap* m, int c0, int c1, int c2, uint32_t bar) {
  asm volatile("cp.async.bulk.tensor.3d.shared::cluster.global.mbarrier::complete_tx::bytes [%0], [%1, {%3, %4, %5}], [%2];" ::"r"(dst), "l"(m), "r"(bar), "r"(c0), "r"(c1), "r"(c2) : "memory");
}
__device__ __forceinline__ void tma4d(uint32_t dst, const CUtensorMap* m, int c0, int c1, int c2, int c3, uint32_t bar) {
  asm volatile("cp.async.bulk.tensor.4d.shared::cluster.global.mbarrier::complete_tx::bytes [%0], [%1, {%3, %4, %5, %6}], [%2];" ::"r"(dst), "l"(m), "r"(bar), "r"(c0), "r"(c1), "r"(c2), "r"(c3) : "memory");
}
__device__ __forceinline__ void tma5d(uint32_t dst, const CUtensorMap* m, int c0, int c1, int c2, int c3, int c4, uint32_t bar) {
  asm volatile("cp.async.bulk.tensor.5d.shared::cluster.global.mbarrier::complete_tx::bytes [%0], [%1, {%3, %4, %5, %6, %7}], [%2];" ::"r"(dst), "l"(m), "r"(bar), "r"(c0), "r"(c1), "r"(c2), "r"(c3), "r"(c4) : "memory");
}
__device__ __forceinline__ void tma_store2d(const CUtensorMap* m, uint32_t src, int c0, int c1) {
  asm volatile("cp.async.bulk.tensor.2d.global.shared::cta.bulk_group [%0, {%2, %3}], [%1];" ::"l"(m), "r"(src), "r"(c0), "r"(c1) : "memory");
}
__device__ __forceinline__ void tma_store4d(const CUtensorMap* m, uint32_t src, int c0, int c1, int c2, int c3) {
  asm volatile("cp.async.bulk.tensor.4d.global.shared::cta.bulk_group [%0, {%2, %3, %4, %5}], [%1];" ::"l"(m), "r"(src), "r"(c0), "r"(c1), "r"(c2), "r"(c3) : "memory");
}
__device__ __forceinline__ void tma_prefetch2d(const CUtensorMap* m, int c0, int c1) {
  asm volatile("cp.async.bulk.prefetch.tensor.2d.L2.global [%0, {%1, %2}];" ::"l"(m), "r"(c0), "r"(c1) : "memory");
}
__device__ __forceinline__ void bulk_g2s(uint32_t dst, const void* src, int bytes, uint32_t bar) {
  asm volatile("cp.async.bulk.shared::cluster.global.mbarrier::complete_tx::bytes [%0], [%1], %2, [%3];" ::"r"(dst), "l"(src), "r"(bytes), "r"(bar) : "memory");
}
__device__ __forceinline__ void bulk_s2g(void* dst, uint32_t src, int bytes) {
  asm volatile("cp.async.bulk.global.shared::cta.bulk_group [%0], [%1], %2;" ::"l"(dst), "r"(src), "r"(bytes) : "memory");
}
__device__ __forceinline__ void cp16(uint32_t dst, const void* src) { asm volatile("cp.async.cg.shared.global [%0], [%1], 16;" ::"r"(dst), "l"(src) : "memory"); }
__device__ __forceinline__ void cp16z(uint32_t dst, const void* src, int n) { asm volatile("cp.async.cg.shared.global [%0], [%1], 16, %2;" ::"r"(dst), "l"(src), "r"(n) : "memory"); }
__device__ __forceinline__ void cp_arrive(uint32_t bar) { asm volatile("cp.async.mbarrier.arrive.noinc.shared::cta.b64 [%0];" ::"r"(bar) : "memory"); }
__device__ __forceinline__ void st_async4(uint32_t dst, const uint32_t* v, uint32_t bar) {
  asm volatile("st.async.weak.shared::cluster.mbarrier::complete_tx::bytes.v4.b32 [%0], {%1, %2, %3, %4}, [%5];" ::"r"(dst), "r"(v[0]), "r"(v[1]), "r"(v[2]), "r"(v[3]), "r"(bar) : "memory");
}
__device__ __forceinline__ void wg_fence() { asm volatile("wgmma.fence.sync.aligned;" ::: "memory"); }
__device__ __forceinline__ void wg_commit() { asm volatile("wgmma.commit_group.sync.aligned;" ::: "memory"); }
template <int N> __device__ __forceinline__ void wg_wait() { asm volatile("wgmma.wait_group.sync.aligned %0;" ::"n"(N) : "memory"); }
__device__ __forceinline__ uint64_t mkdesc(uint32_t addr, uint32_t lbo, uint32_t sbo, uint32_t swz) {
  return (uint64_t)((addr & 0x3FFFF) >> 4) | ((uint64_t)(lbo >> 4) << 16) | ((uint64_t)(sbo >> 4) << 32) | ((uint64_t)swz << 62);
}
__device__ __forceinline__ void ldsm4t(uint32_t* r, uint32_t a) {
  asm volatile("ldmatrix.sync.aligned.m8n8.x4.trans.shared.b16 {%0,%1,%2,%3}, [%4];" : "=r"(r[0]), "=r"(r[1]), "=r"(r[2]), "=r"(r[3]) : "r"(a) : "memory");
}
__device__ __forceinline__ void stsm4(uint32_t a, const uint32_t* r) {
  asm volatile("stmatrix.sync.aligned.m8n8.x4.shared.b16 [%0], {%1,%2,%3,%4};" ::"r"(a), "r"(r[0]), "r"(r[1]), "r"(r[2]), "r"(r[3]) : "memory");
}
__device__ __forceinline__ void stsm4t(uint32_t a, const uint32_t* r) {
  asm volatile("stmatrix.sync.aligned.m8n8.x4.trans.shared.b16 [%0], {%1,%2,%3,%4};" ::"r"(a), "r"(r[0]), "r"(r[1]), "r"(r[2]), "r"(r[3]) : "memory");
}
__device__ __forceinline__ void bar_sync(int id, int n) { asm volatile("bar.sync %0, %1;" ::"r"(id), "r"(n) : "memory"); }
__device__ __forceinline__ void bar_arrive(int id, int n) { asm volatile("bar.arrive %0, %1;" ::"r"(id), "r"(n) : "memory"); }
__device__ __forceinline__ uint32_t lds32(uint32_t a) { uint32_t v; asm volatile("ld.shared.b32 %0, [%1];" : "=r"(v) : "r"(a) : "memory"); return v; }
__device__ __forceinline__ uint2 lds64(uint32_t a) { uint2 v; asm volatile("ld.shared.v2.b32 {%0,%1}, [%2];" : "=r"(v.x), "=r"(v.y) : "r"(a) : "memory"); return v; }
__device__ __forceinline__ uint4 lds128(uint32_t a) { uint4 v; asm volatile("ld.shared.v4.b32 {%0,%1,%2,%3}, [%4];" : "=r"(v.x), "=r"(v.y), "=r"(v.z), "=r"(v.w) : "r"(a) : "memory"); return v; }
__device__ __forceinline__ void sts16(uint32_t a, uint32_t v) { asm volatile("st.shared.b16 [%0], %1;" ::"r"(a), "h"((uint16_t)v) : "memory"); }
__device__ __forceinline__ void sts32(uint32_t a, uint32_t v) { asm volatile("st.shared.b32 [%0], %1;" ::"r"(a), "r"(v) : "memory"); }
__device__ __forceinline__ void sts64(uint32_t a, uint32_t x, uint32_t y) { asm volatile("st.shared.v2.b32 [%0], {%1,%2};" ::"r"(a), "r"(x), "r"(y) : "memory"); }
__device__ __forceinline__ void sts128(uint32_t a, uint4 v) { asm volatile("st.shared.v4.b32 [%0], {%1,%2,%3,%4};" ::"r"(a), "r"(v.x), "r"(v.y), "r"(v.z), "r"(v.w) : "memory"); }
template<int TB> __device__ __forceinline__ void wgmma_rs_n128(float* d, const uint32_t* a, uint64_t db, int sd) {
  asm volatile("{\n.reg .pred p;\nsetp.ne.b32 p, %69, 0;\n"
    "wgmma.mma_async.sync.aligned.m64n128k16.f32.bf16.bf16 {%0, %1, %2, %3, %4, %5, %6, %7, %8, %9, %10, %11, %12, %13, %14, %15, %16, %17, %18, %19, %20, %21, %22, %23, %24, %25, %26, %27, %28, %29, %30, %31, %32, %33, %34, %35, %36, %37, %38, %39, %40, %41, %42, %43, %44, %45, %46, %47, %48, %49, %50, %51, %52, %53, %54, %55, %56, %57, %58, %59, %60, %61, %62, %63}, {%64, %65, %66, %67}, %68, p, 1, 1, %70;\n}"
    : "+f"(d[0]), "+f"(d[1]), "+f"(d[2]), "+f"(d[3]), "+f"(d[4]), "+f"(d[5]), "+f"(d[6]), "+f"(d[7]), "+f"(d[8]), "+f"(d[9]), "+f"(d[10]), "+f"(d[11]), "+f"(d[12]), "+f"(d[13]), "+f"(d[14]), "+f"(d[15]), "+f"(d[16]), "+f"(d[17]), "+f"(d[18]), "+f"(d[19]), "+f"(d[20]), "+f"(d[21]), "+f"(d[22]), "+f"(d[23]), "+f"(d[24]), "+f"(d[25]), "+f"(d[26]), "+f"(d[27]), "+f"(d[28]), "+f"(d[29]), "+f"(d[30]), "+f"(d[31]), "+f"(d[32]), "+f"(d[33]), "+f"(d[34]), "+f"(d[35]), "+f"(d[36]), "+f"(d[37]), "+f"(d[38]), "+f"(d[39]), "+f"(d[40]), "+f"(d[41]), "+f"(d[42]), "+f"(d[43]), "+f"(d[44]), "+f"(d[45]), "+f"(d[46]), "+f"(d[47]), "+f"(d[48]), "+f"(d[49]), "+f"(d[50]), "+f"(d[51]), "+f"(d[52]), "+f"(d[53]), "+f"(d[54]), "+f"(d[55]), "+f"(d[56]), "+f"(d[57]), "+f"(d[58]), "+f"(d[59]), "+f"(d[60]), "+f"(d[61]), "+f"(d[62]), "+f"(d[63])
    : "r"(a[0]), "r"(a[1]), "r"(a[2]), "r"(a[3]), "l"(db), "r"(sd), "n"(TB));
}

template<int TB> __device__ __forceinline__ void wgmma_rs_n160(float* d, const uint32_t* a, uint64_t db, int sd) {
  asm volatile("{\n.reg .pred p;\nsetp.ne.b32 p, %85, 0;\n"
    "wgmma.mma_async.sync.aligned.m64n160k16.f32.bf16.bf16 {%0, %1, %2, %3, %4, %5, %6, %7, %8, %9, %10, %11, %12, %13, %14, %15, %16, %17, %18, %19, %20, %21, %22, %23, %24, %25, %26, %27, %28, %29, %30, %31, %32, %33, %34, %35, %36, %37, %38, %39, %40, %41, %42, %43, %44, %45, %46, %47, %48, %49, %50, %51, %52, %53, %54, %55, %56, %57, %58, %59, %60, %61, %62, %63, %64, %65, %66, %67, %68, %69, %70, %71, %72, %73, %74, %75, %76, %77, %78, %79}, {%80, %81, %82, %83}, %84, p, 1, 1, %86;\n}"
    : "+f"(d[0]), "+f"(d[1]), "+f"(d[2]), "+f"(d[3]), "+f"(d[4]), "+f"(d[5]), "+f"(d[6]), "+f"(d[7]), "+f"(d[8]), "+f"(d[9]), "+f"(d[10]), "+f"(d[11]), "+f"(d[12]), "+f"(d[13]), "+f"(d[14]), "+f"(d[15]), "+f"(d[16]), "+f"(d[17]), "+f"(d[18]), "+f"(d[19]), "+f"(d[20]), "+f"(d[21]), "+f"(d[22]), "+f"(d[23]), "+f"(d[24]), "+f"(d[25]), "+f"(d[26]), "+f"(d[27]), "+f"(d[28]), "+f"(d[29]), "+f"(d[30]), "+f"(d[31]), "+f"(d[32]), "+f"(d[33]), "+f"(d[34]), "+f"(d[35]), "+f"(d[36]), "+f"(d[37]), "+f"(d[38]), "+f"(d[39]), "+f"(d[40]), "+f"(d[41]), "+f"(d[42]), "+f"(d[43]), "+f"(d[44]), "+f"(d[45]), "+f"(d[46]), "+f"(d[47]), "+f"(d[48]), "+f"(d[49]), "+f"(d[50]), "+f"(d[51]), "+f"(d[52]), "+f"(d[53]), "+f"(d[54]), "+f"(d[55]), "+f"(d[56]), "+f"(d[57]), "+f"(d[58]), "+f"(d[59]), "+f"(d[60]), "+f"(d[61]), "+f"(d[62]), "+f"(d[63]), "+f"(d[64]), "+f"(d[65]), "+f"(d[66]), "+f"(d[67]), "+f"(d[68]), "+f"(d[69]), "+f"(d[70]), "+f"(d[71]), "+f"(d[72]), "+f"(d[73]), "+f"(d[74]), "+f"(d[75]), "+f"(d[76]), "+f"(d[77]), "+f"(d[78]), "+f"(d[79])
    : "r"(a[0]), "r"(a[1]), "r"(a[2]), "r"(a[3]), "l"(db), "r"(sd), "n"(TB));
}

template<int TB> __device__ __forceinline__ void wgmma_rs_n192(float* d, const uint32_t* a, uint64_t db, int sd) {
  asm volatile("{\n.reg .pred p;\nsetp.ne.b32 p, %101, 0;\n"
    "wgmma.mma_async.sync.aligned.m64n192k16.f32.bf16.bf16 {%0, %1, %2, %3, %4, %5, %6, %7, %8, %9, %10, %11, %12, %13, %14, %15, %16, %17, %18, %19, %20, %21, %22, %23, %24, %25, %26, %27, %28, %29, %30, %31, %32, %33, %34, %35, %36, %37, %38, %39, %40, %41, %42, %43, %44, %45, %46, %47, %48, %49, %50, %51, %52, %53, %54, %55, %56, %57, %58, %59, %60, %61, %62, %63, %64, %65, %66, %67, %68, %69, %70, %71, %72, %73, %74, %75, %76, %77, %78, %79, %80, %81, %82, %83, %84, %85, %86, %87, %88, %89, %90, %91, %92, %93, %94, %95}, {%96, %97, %98, %99}, %100, p, 1, 1, %102;\n}"
    : "+f"(d[0]), "+f"(d[1]), "+f"(d[2]), "+f"(d[3]), "+f"(d[4]), "+f"(d[5]), "+f"(d[6]), "+f"(d[7]), "+f"(d[8]), "+f"(d[9]), "+f"(d[10]), "+f"(d[11]), "+f"(d[12]), "+f"(d[13]), "+f"(d[14]), "+f"(d[15]), "+f"(d[16]), "+f"(d[17]), "+f"(d[18]), "+f"(d[19]), "+f"(d[20]), "+f"(d[21]), "+f"(d[22]), "+f"(d[23]), "+f"(d[24]), "+f"(d[25]), "+f"(d[26]), "+f"(d[27]), "+f"(d[28]), "+f"(d[29]), "+f"(d[30]), "+f"(d[31]), "+f"(d[32]), "+f"(d[33]), "+f"(d[34]), "+f"(d[35]), "+f"(d[36]), "+f"(d[37]), "+f"(d[38]), "+f"(d[39]), "+f"(d[40]), "+f"(d[41]), "+f"(d[42]), "+f"(d[43]), "+f"(d[44]), "+f"(d[45]), "+f"(d[46]), "+f"(d[47]), "+f"(d[48]), "+f"(d[49]), "+f"(d[50]), "+f"(d[51]), "+f"(d[52]), "+f"(d[53]), "+f"(d[54]), "+f"(d[55]), "+f"(d[56]), "+f"(d[57]), "+f"(d[58]), "+f"(d[59]), "+f"(d[60]), "+f"(d[61]), "+f"(d[62]), "+f"(d[63]), "+f"(d[64]), "+f"(d[65]), "+f"(d[66]), "+f"(d[67]), "+f"(d[68]), "+f"(d[69]), "+f"(d[70]), "+f"(d[71]), "+f"(d[72]), "+f"(d[73]), "+f"(d[74]), "+f"(d[75]), "+f"(d[76]), "+f"(d[77]), "+f"(d[78]), "+f"(d[79]), "+f"(d[80]), "+f"(d[81]), "+f"(d[82]), "+f"(d[83]), "+f"(d[84]), "+f"(d[85]), "+f"(d[86]), "+f"(d[87]), "+f"(d[88]), "+f"(d[89]), "+f"(d[90]), "+f"(d[91]), "+f"(d[92]), "+f"(d[93]), "+f"(d[94]), "+f"(d[95])
    : "r"(a[0]), "r"(a[1]), "r"(a[2]), "r"(a[3]), "l"(db), "r"(sd), "n"(TB));
}

template<int TB> __device__ __forceinline__ void wgmma_rs_n32(float* d, const uint32_t* a, uint64_t db, int sd) {
  asm volatile("{\n.reg .pred p;\nsetp.ne.b32 p, %21, 0;\n"
    "wgmma.mma_async.sync.aligned.m64n32k16.f32.bf16.bf16 {%0, %1, %2, %3, %4, %5, %6, %7, %8, %9, %10, %11, %12, %13, %14, %15}, {%16, %17, %18, %19}, %20, p, 1, 1, %22;\n}"
    : "+f"(d[0]), "+f"(d[1]), "+f"(d[2]), "+f"(d[3]), "+f"(d[4]), "+f"(d[5]), "+f"(d[6]), "+f"(d[7]), "+f"(d[8]), "+f"(d[9]), "+f"(d[10]), "+f"(d[11]), "+f"(d[12]), "+f"(d[13]), "+f"(d[14]), "+f"(d[15])
    : "r"(a[0]), "r"(a[1]), "r"(a[2]), "r"(a[3]), "l"(db), "r"(sd), "n"(TB));
}

template<int TB> __device__ __forceinline__ void wgmma_rs_n64(float* d, const uint32_t* a, uint64_t db, int sd) {
  asm volatile("{\n.reg .pred p;\nsetp.ne.b32 p, %37, 0;\n"
    "wgmma.mma_async.sync.aligned.m64n64k16.f32.bf16.bf16 {%0, %1, %2, %3, %4, %5, %6, %7, %8, %9, %10, %11, %12, %13, %14, %15, %16, %17, %18, %19, %20, %21, %22, %23, %24, %25, %26, %27, %28, %29, %30, %31}, {%32, %33, %34, %35}, %36, p, 1, 1, %38;\n}"
    : "+f"(d[0]), "+f"(d[1]), "+f"(d[2]), "+f"(d[3]), "+f"(d[4]), "+f"(d[5]), "+f"(d[6]), "+f"(d[7]), "+f"(d[8]), "+f"(d[9]), "+f"(d[10]), "+f"(d[11]), "+f"(d[12]), "+f"(d[13]), "+f"(d[14]), "+f"(d[15]), "+f"(d[16]), "+f"(d[17]), "+f"(d[18]), "+f"(d[19]), "+f"(d[20]), "+f"(d[21]), "+f"(d[22]), "+f"(d[23]), "+f"(d[24]), "+f"(d[25]), "+f"(d[26]), "+f"(d[27]), "+f"(d[28]), "+f"(d[29]), "+f"(d[30]), "+f"(d[31])
    : "r"(a[0]), "r"(a[1]), "r"(a[2]), "r"(a[3]), "l"(db), "r"(sd), "n"(TB));
}

template<int TB> __device__ __forceinline__ void wgmma_rs_n96(float* d, const uint32_t* a, uint64_t db, int sd) {
  asm volatile("{\n.reg .pred p;\nsetp.ne.b32 p, %53, 0;\n"
    "wgmma.mma_async.sync.aligned.m64n96k16.f32.bf16.bf16 {%0, %1, %2, %3, %4, %5, %6, %7, %8, %9, %10, %11, %12, %13, %14, %15, %16, %17, %18, %19, %20, %21, %22, %23, %24, %25, %26, %27, %28, %29, %30, %31, %32, %33, %34, %35, %36, %37, %38, %39, %40, %41, %42, %43, %44, %45, %46, %47}, {%48, %49, %50, %51}, %52, p, 1, 1, %54;\n}"
    : "+f"(d[0]), "+f"(d[1]), "+f"(d[2]), "+f"(d[3]), "+f"(d[4]), "+f"(d[5]), "+f"(d[6]), "+f"(d[7]), "+f"(d[8]), "+f"(d[9]), "+f"(d[10]), "+f"(d[11]), "+f"(d[12]), "+f"(d[13]), "+f"(d[14]), "+f"(d[15]), "+f"(d[16]), "+f"(d[17]), "+f"(d[18]), "+f"(d[19]), "+f"(d[20]), "+f"(d[21]), "+f"(d[22]), "+f"(d[23]), "+f"(d[24]), "+f"(d[25]), "+f"(d[26]), "+f"(d[27]), "+f"(d[28]), "+f"(d[29]), "+f"(d[30]), "+f"(d[31]), "+f"(d[32]), "+f"(d[33]), "+f"(d[34]), "+f"(d[35]), "+f"(d[36]), "+f"(d[37]), "+f"(d[38]), "+f"(d[39]), "+f"(d[40]), "+f"(d[41]), "+f"(d[42]), "+f"(d[43]), "+f"(d[44]), "+f"(d[45]), "+f"(d[46]), "+f"(d[47])
    : "r"(a[0]), "r"(a[1]), "r"(a[2]), "r"(a[3]), "l"(db), "r"(sd), "n"(TB));
}

template<int TA, int TB> __device__ __forceinline__ void wgmma_ss_n192(float* d, uint64_t da, uint64_t db, int sd) {
  asm volatile("{\n.reg .pred p;\nsetp.ne.b32 p, %98, 0;\n"
    "wgmma.mma_async.sync.aligned.m64n192k16.f32.bf16.bf16 {%0, %1, %2, %3, %4, %5, %6, %7, %8, %9, %10, %11, %12, %13, %14, %15, %16, %17, %18, %19, %20, %21, %22, %23, %24, %25, %26, %27, %28, %29, %30, %31, %32, %33, %34, %35, %36, %37, %38, %39, %40, %41, %42, %43, %44, %45, %46, %47, %48, %49, %50, %51, %52, %53, %54, %55, %56, %57, %58, %59, %60, %61, %62, %63, %64, %65, %66, %67, %68, %69, %70, %71, %72, %73, %74, %75, %76, %77, %78, %79, %80, %81, %82, %83, %84, %85, %86, %87, %88, %89, %90, %91, %92, %93, %94, %95}, %96, %97, p, 1, 1, %99, %100;\n}"
    : "+f"(d[0]), "+f"(d[1]), "+f"(d[2]), "+f"(d[3]), "+f"(d[4]), "+f"(d[5]), "+f"(d[6]), "+f"(d[7]), "+f"(d[8]), "+f"(d[9]), "+f"(d[10]), "+f"(d[11]), "+f"(d[12]), "+f"(d[13]), "+f"(d[14]), "+f"(d[15]), "+f"(d[16]), "+f"(d[17]), "+f"(d[18]), "+f"(d[19]), "+f"(d[20]), "+f"(d[21]), "+f"(d[22]), "+f"(d[23]), "+f"(d[24]), "+f"(d[25]), "+f"(d[26]), "+f"(d[27]), "+f"(d[28]), "+f"(d[29]), "+f"(d[30]), "+f"(d[31]), "+f"(d[32]), "+f"(d[33]), "+f"(d[34]), "+f"(d[35]), "+f"(d[36]), "+f"(d[37]), "+f"(d[38]), "+f"(d[39]), "+f"(d[40]), "+f"(d[41]), "+f"(d[42]), "+f"(d[43]), "+f"(d[44]), "+f"(d[45]), "+f"(d[46]), "+f"(d[47]), "+f"(d[48]), "+f"(d[49]), "+f"(d[50]), "+f"(d[51]), "+f"(d[52]), "+f"(d[53]), "+f"(d[54]), "+f"(d[55]), "+f"(d[56]), "+f"(d[57]), "+f"(d[58]), "+f"(d[59]), "+f"(d[60]), "+f"(d[61]), "+f"(d[62]), "+f"(d[63]), "+f"(d[64]), "+f"(d[65]), "+f"(d[66]), "+f"(d[67]), "+f"(d[68]), "+f"(d[69]), "+f"(d[70]), "+f"(d[71]), "+f"(d[72]), "+f"(d[73]), "+f"(d[74]), "+f"(d[75]), "+f"(d[76]), "+f"(d[77]), "+f"(d[78]), "+f"(d[79]), "+f"(d[80]), "+f"(d[81]), "+f"(d[82]), "+f"(d[83]), "+f"(d[84]), "+f"(d[85]), "+f"(d[86]), "+f"(d[87]), "+f"(d[88]), "+f"(d[89]), "+f"(d[90]), "+f"(d[91]), "+f"(d[92]), "+f"(d[93]), "+f"(d[94]), "+f"(d[95])
    : "l"(da), "l"(db), "r"(sd), "n"(TA), "n"(TB));
}

template<int TA, int TB> __device__ __forceinline__ void wgmma_ss_n8(float* d, uint64_t da, uint64_t db, int sd) {
  asm volatile("{\n.reg .pred p;\nsetp.ne.b32 p, %6, 0;\n"
    "wgmma.mma_async.sync.aligned.m64n8k16.f32.bf16.bf16 {%0, %1, %2, %3}, %4, %5, p, 1, 1, %7, %8;\n}"
    : "+f"(d[0]), "+f"(d[1]), "+f"(d[2]), "+f"(d[3])
    : "l"(da), "l"(db), "r"(sd), "n"(TA), "n"(TB));
}

constexpr int S_ = 2048, D_ = 640, F_ = 1536;

struct Scr {
  uint32_t flag[32 * 8];
  uint32_t mv[2 * 2048];
  bf16 cimg[8 * 6 * 512];
  uint2 st2[S_];
  bf16 kvT[D_ * S_];
  bf16 zT[D_ * S_];
  bf16 AT[D_ * S_];
};
__device__ __align__(1024) Scr g_scr;
__device__ __forceinline__ uint32_t clk() { uint32_t c; asm volatile("mov.u32 %0, %%clock;" : "=r"(c) :: "memory"); return c; }
#define DEVSM 0
#define STAMP(id)
#define STAMPIF(c, id)
#define ITW 0
#define P3 0
constexpr int FL_X = 5, FL_C = 128;
#define CD 600
#define SD 1000

constexpr int SM_X = 1024, SM_EXT = 21504, SM_SMALL = 29696, SM_STAT = 30720, SM_CB = 32768, SM_RING = 34816, SM_TOTAL = SM_RING + 6 * 32768;
constexpr int SMALL_LN = 224, SMALL_RED = 320, SMALL_DUMMY = 1008, SMALL_E = 1012, SMALL_TS = 160, SMALL_H = 864;
constexpr int JOB_SZ = 10880, JOB_V = 5760, R_X = 5 * 32768, R_BOX = R_X + 12288;
constexpr int K1OFF = 4672, KSZ = 9472, CSZ = KSZ + 4224;
enum { B_KJ = 0, B_X = 5, B_EXT = 7, B_X1 = 8, B_P0 = 9, B_FB = 10, B_PEER = 20, B_RECV = 24, B_U = 28, B_A = 30, B_E0 = 35, B_FS = 37, B_BOX = 38, B_F = 44, B_ST0 = 45, B_GB = 46,
       B_F1 = 48, B_E1 = 54, B_EB = 60,
       B_OS = 64, B_OF = 72, B_Z = 80, B_K = 85, B_EW = 88, B_ST2 = 94, B_XF = 95, B_KV4 = 96, B_KVS = 98, B_BD = 99,
       B_B = 106, B_S = 112 };
__device__ __forceinline__ uint32_t chan_base(uint32_t sb, int ch) { return sb + SM_RING + (2 + (ch >> 1)) * 32768 + (ch & 1) * CSZ; }

struct Params { CUtensorMap mS, mX, mWm, mK, mV, mG, mU, mD; };

__device__ __forceinline__ void flag_add(Scr* G, int id) { asm volatile("red.relaxed.gpu.global.add.u32 [%0], 1;" ::"l"(G->flag + id) : "memory"); }
__device__ __forceinline__ uint32_t rdback(const void* p) { uint32_t v; asm volatile("ld.relaxed.gpu.global.u32 %0, [%1];" : "=r"(v) : "l"(p) : "memory"); return v; }
__device__ __forceinline__ void st_tag(uint2* p, uint32_t v, uint32_t t) { asm volatile("st.relaxed.gpu.global.v2.u32 [%0], {%1, %2};" ::"l"(p), "r"(v), "r"(t) : "memory"); }
__device__ __forceinline__ void spin(uint32_t t, uint32_t d) { if (d) while (clk() - t < d); }
__device__ __forceinline__ uint2 ld_tag(const uint2* p) { uint2 v; asm volatile("ld.relaxed.gpu.global.v2.u32 {%0, %1}, [%2];" : "=r"(v.x), "=r"(v.y) : "l"(p) : "memory"); return v; }
__device__ __forceinline__ uint4 ld_tag2(const uint2* p) {
  uint4 v;
  asm volatile("ld.relaxed.gpu.global.v4.u32 {%0, %1, %2, %3}, [%4];" : "=r"(v.x), "=r"(v.y), "=r"(v.z), "=r"(v.w) : "l"(p) : "memory");
  return v;
}
__device__ __forceinline__ void stg128(void* p, uint4 v) { asm volatile("st.global.v4.b32 [%0], {%1, %2, %3, %4};" ::"l"(p), "r"(v.x), "r"(v.y), "r"(v.z), "r"(v.w) : "memory"); }
__device__ __forceinline__ uint32_t ldv32(uint32_t a) { uint32_t v; asm volatile("ld.volatile.shared.b32 %0, [%1];" : "=r"(v) : "r"(a) : "memory"); return v; }
__device__ __forceinline__ uint4 ldv128(uint32_t a) { uint4 v; asm volatile("ld.volatile.shared.v4.b32 {%0,%1,%2,%3}, [%4];" : "=r"(v.x), "=r"(v.y), "=r"(v.z), "=r"(v.w) : "r"(a) : "memory"); return v; }
__device__ __forceinline__ bool mbar_test(uint32_t bar, int parity) {
  uint32_t ok;
  asm volatile("{\n.reg .pred P;\nmbarrier.test_wait.parity.shared::cta.b64 P, [%1], %2;\nselp.u32 %0, 1, 0, P;\n}" : "=r"(ok) : "r"(bar), "r"(parity) : "memory");
  return ok;
}
__device__ __forceinline__ uint32_t epoch(uint32_t sb) { return lds32(sb + SM_SMALL + SMALL_E); }
__device__ __forceinline__ void rdwait(uint32_t sb, uint32_t v) { sts32(sb + SM_SMALL + SMALL_DUMMY, v); }
__device__ __forceinline__ void fence_async_s() { asm volatile("fence.proxy.async.shared::cta;" ::: "memory"); }
__device__ __forceinline__ void fence_async_g() { asm volatile("fence.proxy.async.global;" ::: "memory"); }
__device__ __forceinline__ void bulk_done() { asm volatile("cp.async.bulk.commit_group;\n\tcp.async.bulk.wait_group 0;" ::: "memory"); }
__device__ __forceinline__ void flag_wait(Scr* G, int id, uint32_t target) {
  const uint32_t* p = G->flag + id;
#pragma unroll 1
  for (int i = 0; i < (1 << 20); i++) {
    uint32_t v;
    asm volatile("ld.relaxed.gpu.global.u32 %0, [%1];" : "=r"(v) : "l"(p) : "memory");
    if ((int)(v - target) >= 0) return;
  }
  __trap();
}
__device__ __forceinline__ void hint_wait(Scr* G, uint32_t sa, int id, uint32_t target) {
#pragma unroll 1
  for (int i = 0; i < (1 << 20); i++) {
    const uint32_t t = clk();
    cp16(sa + 4 * (id & 4), G->flag + (id & ~3));
    spin(t, P3);
    if ((int)(lds32(sa + 4 * (id & 7)) - target) >= 0) return;
  }
  __trap();
}
__device__ __forceinline__ int tbase(int pb) { return 127 - (32 * (pb >> 6) + 8 * (pb & 8) + 4 * ((2 * (pb & 3) - ((pb >> 2) & 1)) & 7) + ((pb >> 4) & 3)); }
__device__ __forceinline__ uint32_t hmul(uint32_t a, uint32_t b) { uint32_t d; asm("mul.rn.bf16x2 %0, %1, %2;" : "=r"(d) : "r"(a), "r"(b)); return d; }
__device__ __forceinline__ uint32_t hadd(uint32_t a, uint32_t b) { uint32_t d; asm("add.rn.bf16x2 %0, %1, %2;" : "=r"(d) : "r"(a), "r"(b)); return d; }
__device__ __forceinline__ uint32_t hsub(uint32_t a, uint32_t b) { uint32_t d; asm("sub.rn.bf16x2 %0, %1, %2;" : "=r"(d) : "r"(a), "r"(b)); return d; }
__device__ __forceinline__ uint32_t hfma(uint32_t a, uint32_t b, uint32_t c) { uint32_t d; asm("fma.rn.bf16x2 %0, %1, %2, %3;" : "=r"(d) : "r"(a), "r"(b), "r"(c)); return d; }
__device__ __forceinline__ uint32_t pack2(float lo, float hi) { uint32_t d; asm("cvt.rn.bf16x2.f32 %0, %1, %2;" : "=r"(d) : "f"(hi), "f"(lo)); return d; }
__device__ __forceinline__ float blo(uint32_t v) { return __uint_as_float(v << 16); }
__device__ __forceinline__ float bhi(uint32_t v) { return __uint_as_float(v & 0xffff0000u); }
__device__ __forceinline__ uint32_t tagged(uint32_t v, uint32_t e1) { return (v & ~1u) | (e1 & 1); }
__device__ __forceinline__ float rbf(float v) { return blo(pack2(v, 0.f)); }
__device__ __forceinline__ float sdev(float var) { float d; asm("sqrt.approx.ftz.f32 %0, %1;" : "=f"(d) : "f"(rbf(rbf(var) + 1e-5f))); return rbf(d); }
template <int N> __device__ __forceinline__ void bfly(float* v, int mask, bool up) {
#pragma unroll
  for (int i = 0; i < N / 2; i++) {
    float send = up ? v[i] : v[i + N / 2], keep = up ? v[i + N / 2] : v[i];
    v[i] = keep + __shfl_xor_sync(0xffffffffu, send, mask);
  }
}
#define BX3 2
#define XO 0
#define ZA 0
#define XE 0
#define EA 1
#define AD 300
#define XP 0
#define DR 0
#define KVV 0
#define OPQ 4
#define SL 1
#define UT 5
#define UD0 1000
#define EH 2
#define NA 16
#define BS 0
#define UF 1
#define ZS 1
#define LV 5
#define TG 2
#define RL 2
#define OF 1
#define OH 16
#define ES 2
#define SI 1
#define RH 5
#define NS 0
#define AT0 14200
#define AT1 0
#define BI 4
#define PC 1
#define PG 1
#define UD2 3600
#define GT 0x111
#define K3 0
#define FS 31
#define KS 3
#define PQ 2
#define DV 24
#define KW 0
#define RX 0
#define MG 0
__device__ __forceinline__ bool mod_first(int b) { return MG ? (b & 3) != 3 : !(b & 1) || !(b & 6); }
__device__ __forceinline__ int mod_grp(int b, int j) {
  if (MG) {
  const int m = b >> 3, s = b & 7, t = 16 * (j ? min(s, 6) : s - (s >> 2)) + m, v = j ? s : (t * 43) >> 10;
  if (j == 2) return b + 112;
  return v < 4 ? (v == 3 ? 160 : 40 * v) + (j ? 24 + m : t - 24 * v) : t + (t < 104 ? 56 : 96);
  }
  const int m = b >> 3, s = b & 7, t = 16 * s + m, v = j ? (t * 43) >> 10 : s >> 1;
  if (j == 2) return b + 112;
  if (j == 0 && s == 1) return m + (m < 8 ? 152 : 192);
  return v < 4 ? (v == 3 ? 160 : 40 * v) + (j ? 16 + t - 24 * v : m) : t + 24;
}

__device__ __forceinline__ void kv_load(const bf16* gk, const bf16* gv, const bf16* gs, uint32_t sb, int b, int r, int tid) {
  const int row = tid >> 2, col = 128 * r + 32 * (b & 3);
  const uint32_t a = sb + SM_RING + r * JOB_SZ + (row >> 3) * 80 + (tid & 3) * 16, ak = a + (row & 7) * 720, av = a + (row & 7) * 640 + JOB_V;
  const int o = (64 * (b >> 2) + row) * D_ + col + 8 * (tid & 3);
  if (FS & 16) {
    uint32_t oo = 2 * o;
    asm volatile("" : "+r"(oo));
    const char *pk = (const char*)gk + oo, *pv = (const char*)gv + oo;
    cp16(ak + 80, pk);
    cp16(av, pv);
    cp16(ak + 400, pk + 64 * D_);
    cp16(av + 320, pv + 64 * D_);
    if (tid < 12) cp16z(ak + 3600, pk - (b < 4 ? 0 : 6 * D_), b < 4 ? 0 : 16);
    if (KS & 2)
      asm volatile("{\n.reg .pred q;\n.reg .b64 y;\ncvt.u64.u32 y, %2;\nadd.s64 y, y, %1;\nsetp.ge.s32 q, %3, 112;\n@q cp.async.cg.shared.global [%0], [y], 16;\n}"
                   ::"r"(sb + SM_CB + 256 * r + 16 * (tid - 112)), "l"(gs), "r"(8 * col + 16 * (tid & 15)), "r"(tid) : "memory");
    else if (tid >= 112) cp16(sb + SM_CB + 256 * r + 16 * (tid - 112), (const char*)gs + (uint32_t)(8 * col + 16 * (tid - 112)));
    return;
  } else {
    cp16(ak + 80, gk + o);
    cp16(ak + 400, gk + o + 32 * D_);
    cp16(av, gv + o);
    cp16(av + 320, gv + o + 32 * D_);
  }
  if (tid < 12) cp16z(ak + 3600, gk + (b < 4 ? o : o - 3 * D_), b < 4 ? 0 : 16);
  else if (tid >= 112) cp16(sb + SM_CB + 256 * r + 16 * (tid - 112), gs + 4 * col + 8 * (tid - 112));
}
__device__ __forceinline__ void load_kv(const Params& P, const bf16* gs, uint32_t sb, int b, int r) {
  const uint32_t a = sb + SM_RING + r * JOB_SZ, bar = sb + 8 * (B_B + r);
  const int cg = 4 * r + (b & 3);
  mbar_expect(bar, JOB_SZ + 256);
  tma4d(a, &P.mK, 0, cg, 8 * (b >> 2) - 1, 0, bar);
  tma4d(a + JOB_V, &P.mV, 0, cg, 8 * (b >> 2), 0, bar);
  bulk_g2s(sb + SM_CB + 256 * r, gs + 128 * cg, 256, bar);
}
__device__ __forceinline__ uint4* kv_dst(Scr* G, int b, int r, int tid) {
  return (uint4*)(G->kvT + (128 * r + 32 * (b & 3) + 8 * (tid >> 5) + 2 * (tid & 3)) * S_ + 2040 - 64 * (b >> 2)) - ((tid >> 2) & 7);
}
__device__ __forceinline__ void kv_job(Scr* G, uint32_t sb, int b, int r, int tid, uint32_t e1) {
  const int cp = 4 * (tid >> 5) + (tid & 3);
  const uint32_t ka = sb + SM_RING + r * JOB_SZ + ((tid >> 2) & 7) * 80 + cp * 4;
  mbar_wait(sb + 8 * (B_B + r), 0);
  STAMPIF(tid == 0, 56 + r);
  uint32_t kk[11], vv[8], o[8];
  if (KVV) {
#pragma unroll
    for (int i = 0; i < 11; i++) kk[i] = ldv32(ka + 720 * ((i + 5) & 7) + 80 * ((i + 5) >> 3));
#pragma unroll
    for (int i = 0; i < 8; i++) vv[i] = ldv32(ka + JOB_V + 640 * i);
  }
  const uint4 sk = ldv128(sb + SM_CB + 256 * r + 16 * cp);
  const uint32_t s0 = __byte_perm(sk.x, sk.z, 0x5410), s1 = __byte_perm(sk.x, sk.z, 0x7632), s2 = __byte_perm(sk.y, sk.w, 0x5410), s3 = __byte_perm(sk.y, sk.w, 0x7632);
#pragma unroll
  for (int i = 0; i < 11; i++) if (!KVV) kk[i] = lds32(ka + 720 * ((i + 5) & 7) + 80 * ((i + 5) >> 3));
#pragma unroll
  for (int i = 0; i < 8; i++) {
    uint32_t v = KVV ? vv[i] : lds32(ka + JOB_V + 640 * i);
    o[i] = hmul(hfma(kk[i + 3], s0, hfma(kk[i + 2], s1, hfma(kk[i + 1], s2, hmul(kk[i], s3)))), v);
  }
  uint4* dst = kv_dst(G, b, r, tid);
  dst[0] = make_uint4(__byte_perm(o[7], o[6], 0x5410), __byte_perm(o[5], o[4], 0x5410), __byte_perm(o[3], o[2], 0x5410), tagged(__byte_perm(o[1], o[0], 0x5410), e1));
  dst[256] = make_uint4(__byte_perm(o[7], o[6], 0x7632), __byte_perm(o[5], o[4], 0x7632), __byte_perm(o[3], o[2], 0x7632), tagged(__byte_perm(o[1], o[0], 0x7632), e1));
  if (tid == 0) { sts32(sb + SM_SMALL + SMALL_TS + 4 * r, clk()); mbar_arrive(sb + 8 * (B_KJ + r)); }
}
__device__ __forceinline__ void u_wait(uint4& a, uint4& c, const void* p) {
  asm volatile("{\n.reg .pred p;\n.reg .b32 t, n;\nmov.b32 n, 0;\n"
               "L0:\nlop3.b32 t, %3, %7, 1, 0x80;\nsetp.eq.b32 p, t, 0;\nvote.sync.any.pred p, p, 0xffffffff;\n@!p bra.uni L1;\n"
               "ld.relaxed.gpu.global.v4.u32 {%0, %1, %2, %3}, [%8];\nld.relaxed.gpu.global.v4.u32 {%4, %5, %6, %7}, [%8+2048];\n"
               "add.u32 n, n, 1;\nsetp.lt.u32 p, n, 1000000;\n@p bra.uni L0;\ntrap;\nL1:\n}"
               : "+r"(a.x), "+r"(a.y), "+r"(a.z), "+r"(a.w), "+r"(c.x), "+r"(c.y), "+r"(c.z), "+r"(c.w) : "l"(p) : "memory");
}
__device__ __forceinline__ void u_fix(uint4 a, uint4 c, const void* p, uint32_t sa, uint32_t e1) {
  asm volatile("{\n.reg .pred p;\n.reg .b32 t, n;\nmov.b32 n, 0;\n"
               "lop3.b32 t, %3, %7, %10, 0x81;\nand.b32 t, t, 1;\nsetp.eq.b32 p, t, 0;\nvote.sync.any.pred p, p, 0xffffffff;\n@!p bra.uni L2;\n"
               "L0:\nld.relaxed.gpu.global.v4.u32 {%0, %1, %2, %3}, [%8];\nld.relaxed.gpu.global.v4.u32 {%4, %5, %6, %7}, [%8+2048];\n"
               "lop3.b32 t, %3, %7, %10, 0x81;\nand.b32 t, t, 1;\nsetp.eq.b32 p, t, 0;\nvote.sync.any.pred p, p, 0xffffffff;\n@!p bra.uni L1;\n"
               "add.u32 n, n, 1;\nsetp.lt.u32 p, n, 1000000;\n@p bra.uni L0;\ntrap;\n"
               "L1:\nst.shared.v4.b32 [%9], {%0, %1, %2, %3};\nst.shared.v4.b32 [%9+2048], {%4, %5, %6, %7};\nL2:\n}"
               : "+r"(a.x), "+r"(a.y), "+r"(a.z), "+r"(a.w), "+r"(c.x), "+r"(c.y), "+r"(c.z), "+r"(c.w) : "l"(p), "r"(sa), "r"(e1) : "memory");
}
__device__ __forceinline__ void stv128(uint32_t a, uint4 v) { asm volatile("st.volatile.shared.v4.b32 [%0], {%1,%2,%3,%4};" ::"r"(a), "r"(v.x), "r"(v.y), "r"(v.z), "r"(v.w) : "memory"); }
__device__ __forceinline__ uint64_t box_a(uint32_t sb) { return mkdesc(sb + SM_RING + R_BOX, 256, 1024, 3); }
__device__ __forceinline__ uint64_t box_b(uint32_t sb) { return mkdesc(sb + SM_STAT, 64, 128, 0); }
__device__ __forceinline__ void mod_put(Scr* G, uint32_t sb, const float* a, int b, int j, uint32_t e1, int tid) {
  const uint32_t red = sb + SM_STAT + 1536;
  if ((tid & 3) == tid >> 6) sts64(red + 32 * ((tid >> 2) & 7) + 8 * (tid >> 5), __float_as_uint((tid & 32) ? a[1] : a[0]), __float_as_uint((tid & 32) ? a[3] : a[2]));
  bar_sync(j > (BX3 >= 3) ? 4 : 5, 128);
  if (tid < 16) {
    const uint4 u = lds128(red + 32 * (tid & 7)), v = lds128(red + 32 * (tid & 7) + 16);
    asm volatile("" : "+r"(b));
    const int grp = mod_grp(b, j);
    const uint32_t one = (grp >= 40 && grp < 80) || (grp >= 160 && grp < 200) ? 0x3f803f80u : 0u;
    const float lo = __uint_as_float(u.x) + __uint_as_float(u.z) + __uint_as_float(v.x) + __uint_as_float(v.z);
    const float hi = __uint_as_float(u.y) + __uint_as_float(u.w) + __uint_as_float(v.y) + __uint_as_float(v.w);
    asm volatile("st.relaxed.gpu.global.u32 [%0], %1;" ::"l"(G->mv + 8 * grp + 256 * (tid & 8) + (tid & 7)),
                 "r"(((tid >> 3) ^ e1) & 1 ? 0 : ~hadd(pack2(lo, hi), one)) : "memory");
  }
}
__device__ __forceinline__ void mod_box(Scr* G, uint32_t sb, int b, int j, uint32_t e1, int tid) {
  float a[4];
  uint64_t da = box_a(sb), db = box_b(sb);
#pragma unroll
  for (int h = 0; h < 2; h++) {
    mbar_wait(sb + 8 * (B_BOX + 2 * j + h), 0);
    STAMPIF(tid == 0 && j == 0, 71 + h);
    wg_fence();
#pragma unroll
    for (int n = 5 * h; n < 5 * h + 5; n++) wgmma_ss_n8<1, 0>(a, da + 128 * n, db + 8 * n, n != 0);
    wg_commit();
  }
  wg_wait<0>();
#pragma unroll
  for (int i = 0; i < 4; i++) asm volatile("" : "+f"(a[i])::"memory");
  mod_put(G, sb, a, b, j, e1, tid);
}
__device__ __forceinline__ void a_check(uint32_t sa, const void* ga, uint32_t tag) {
  asm volatile("{\n.reg .pred p;\n.reg .b32 t, n, x, y, z;\n.reg .b64 g;\n"
               "ld.shared.b32 t, [%0];\nlop3.b32 t, t, %2, 1, 0x28;\nsetp.ne.b32 p, t, 0;\nvote.sync.any.pred p, p, 0xffffffff;\n@!p bra.uni L1;\nmov.b32 n, 0;\n"
               "L0:\nld.relaxed.gpu.global.b32 t, [%1];\nlop3.b32 t, t, %2, 1, 0x28;\nsetp.ne.b32 p, t, 0;\nvote.sync.any.pred p, p, 0xffffffff;\n@!p bra.uni L2;\n"
               "add.u32 n, n, 1;\nsetp.lt.u32 p, n, 1000000;\n@p bra.uni L0;\ntrap;\nL2:\n"
               "and.b64 g, %1, -32;\nand.b32 n, %0, -32;\n"
               "ld.relaxed.gpu.global.v4.b32 {t, x, y, z}, [g];\nst.shared.v4.b32 [n], {t, x, y, z};\n"
               "ld.relaxed.gpu.global.v4.b32 {t, x, y, z}, [g+16];\nst.shared.v4.b32 [n+16], {t, x, y, z};\n"
               "fence.proxy.async.shared::cta;\nbar.warp.sync 0xffffffff;\nL1:\n}" ::"r"(sa), "l"(ga), "r"(tag) : "memory");
}
__device__ __forceinline__ void z_wait(uint4& a, uint4& c, uint32_t* v, const void* G, uint32_t zo, uint32_t co, uint32_t e1) {
  asm volatile("{\n.reg .pred p;\n.reg .b32 t, n;\n.reg .b64 x, y;\nmov.b32 n, 0;\n"
               "L0:\nlop3.b32 t, %3, %7, %14, 0x81;\nand.b32 t, t, 1;\nmin.u32 t, t, %8;\nmin.u32 t, t, %9;\nmin.u32 t, t, %10;\nmin.u32 t, t, %11;\n"
               "setp.eq.b32 p, t, 0;\nvote.sync.any.pred p, p, 0xffffffff;\n@!p bra.uni L1;\n"
               "shr.u32 t, n, 31;\nadd.u32 t, t, %12;\ncvt.u64.u32 x, t;\nadd.s64 x, x, %15;\nshr.u32 t, n, 30;\nadd.u32 t, t, %13;\ncvt.u64.u32 y, t;\nadd.s64 y, y, %15;\n"
               "ld.relaxed.gpu.global.v4.u32 {%0, %1, %2, %3}, [x];\nld.relaxed.gpu.global.v4.u32 {%4, %5, %6, %7}, [x+32768];\n"
               "ld.relaxed.gpu.global.u32 %8, [y];\nld.relaxed.gpu.global.u32 %9, [y+1280];\nld.relaxed.gpu.global.u32 %10, [y+2560];\nld.relaxed.gpu.global.u32 %11, [y+5120];\n"
               "add.u32 n, n, 1;\nsetp.lt.u32 p, n, 1000000;\n@p bra.uni L0;\ntrap;\nL1:\n}"
               : "+r"(a.x), "+r"(a.y), "+r"(a.z), "+r"(a.w), "+r"(c.x), "+r"(c.y), "+r"(c.z), "+r"(c.w), "+r"(v[0]), "+r"(v[1]), "+r"(v[2]), "+r"(v[3])
               : "r"(zo), "r"(co), "r"(e1), "l"(G) : "memory");
}
__device__ __forceinline__ void load_x(const Params& P, uint32_t sb, int b, int h) {
  const uint32_t bar = sb + 8 * (B_X + h);
  mbar_expect(bar, 10240);
  tma5d(sb + SM_X + h * 10240, &P.mX, 0, 0, 0, 5 * h, tbase(b), bar);
}
__device__ __forceinline__ uint32_t x_addr(uint32_t sb, int w, int lane) {
  const int rho = 15 - (4 * (lane >> 3) + 2 * (lane & 1) + ((lane >> 1) & 1));
  return sb + SM_X + (w >> 1) * 2048 + rho * 128 + (((2 * (w & 1) + (lane & 4)) ^ (rho & 7)) << 4);
}
__device__ __forceinline__ void ln1_half(uint32_t sb, int tid, int h, int dry, float& s1, float& s2, float& pv) {
  const uint32_t xr = sb + SM_X + 16 * tid;
  float s3 = 0.f;
  if (ITW == 8) STAMPIF(tid == 0, 102 + 2 * h);
  if (!dry) mbar_wait(sb + 8 * (B_X + h), 0);
  STAMPIF(tid == 0, 25);
  if (ITW == 8) STAMPIF(tid == 0, 103 + 2 * h);
  uint4 v[5];
#pragma unroll
  for (int n = 0; n < 5; n++) v[n] = n < LV ? ldv128(xr + 10240 * h + 2048 * n) : lds128(xr + 10240 * h + 2048 * n);
  pv = blo(ldv32(xr & ~127u));
#pragma unroll
  for (int n = 0; n < 5; n++) {
    const uint32_t u[4] = {v[n].x, v[n].y, v[n].z, v[n].w};
#pragma unroll
    for (int j = 0; j < 4; j++) {
      const float a = blo(u[j]) - pv, c = bhi(u[j]) - pv;
      s1 += a + c; s2 += a * a; s3 += c * c;
    }
  }
  s2 += s3;
}
__device__ __forceinline__ void ln1_end(uint32_t sb, int tid, float s1, float s2, float pv) {
#pragma unroll
  for (int o = 1; o < 8; o <<= 1) { s1 += __shfl_xor_sync(0xffffffffu, s1, o); s2 += __shfl_xor_sync(0xffffffffu, s2, o); }
  if (ITW == 8) { asm volatile("" : "+f"(s1), "+f"(s2)); STAMPIF(tid == 0, 107); }
  const float mu = s1 * (1.f / D_), var = fmaxf(s2 * (1.f / D_) - mu * mu, 0.f);
  float rs;
  asm("rcp.approx.ftz.f32 %0, %1;" : "=f"(rs) : "f"(sdev(var)));
  const int i = 15 - (tid >> 3), j = tid & 7;
  if (j < 2) sts16(sb + SM_SMALL + SMALL_LN + 32 * j + 16 * (i & 1) + (i & 14), pack2(j ? rs : pv + mu, 0.f));
  if (ITW == 8) STAMPIF(tid == 0, 108);
  bar_sync(5, 128);
  STAMPIF(tid == 0, 75);
}
__device__ __forceinline__ void load_box(const Params& P, uint32_t sb, int b, int cls) {
  const uint32_t bar = sb + 8 * (B_BOX + cls);
  mbar_expect(bar, 10240);
  tma3d(sb + SM_RING + R_BOX + 10240 * (cls & 1), &P.mWm, 16 * mod_grp(b, cls >> 1), 0, 5 * (cls & 1), bar);
}
__device__ __forceinline__ void load_ssm(const Params& P, uint32_t sb, int b, int r) {
  const uint32_t bar = sb + 8 * (B_S + r);
  mbar_expect(bar, 16 * 288);
  tma3d(chan_base(sb, r) + 128, &P.mS, 0, 0, 128 * r + b, bar);
}
__device__ __forceinline__ void k1_job(uint32_t sb, int r, int tid, uint32_t dv) {
  const uint32_t a0 = chan_base(sb, r) + 128 + 16 * tid + 32 * (tid >> 4);
  mbar_wait(sb + 8 * (B_S + r), 0);
  uint4 v[2];
  uint32_t pv[2];
#pragma unroll
  for (int n = 0; n < 2; n++) { v[n] = lds128(a0 + 2304 * n); pv[n] = lds32(a0 + 2304 * n - ((tid & 15) ? 4 : 36)); }
  if (tid == 0) { v[0].x = hadd(v[0].x, dv); sts32(a0, v[0].x); }
#pragma unroll
  for (int n = 0; n < 2; n++)
    sts128(a0 + 2304 * n + K1OFF, make_uint4(__byte_perm(pv[n], v[n].x, 0x5432), __byte_perm(v[n].x, v[n].y, 0x5432), __byte_perm(v[n].y, v[n].z, 0x5432), __byte_perm(v[n].z, v[n].w, 0x5432)));
}

__device__ __forceinline__ int out_blk(int s, int p) { const int t = p + (s >> 1); return t < 5 ? t : t - 5; }
__device__ __forceinline__ void l2_prefetch(const void* p, int bytes) { asm volatile("cp.async.bulk.prefetch.L2.global [%0], %1;" ::"l"(p), "r"(bytes) : "memory"); }
__device__ __forceinline__ void pf_line(const void* p) { asm volatile("prefetch.global.L2 [%0];" ::"l"(p) : "memory"); }
template <int BF> __device__ __forceinline__ int role(int bx) {
  const int c = bx >> 1, d = c - 36, q = (d * 37) >> 8, k = d - 7 * q;
  int rank;
  if (BF) {
    const int r1 = ((c - 4) & 7) * 8 + ((c - 4) >> 3), r2 = (k + min(k, 1)) * 8 + 4 + q;
    rank = r2 + ((d >> 31) & (r1 - r2)) + (((c - 4) >> 31) & (12 + c - r1));
  }
  else rank = c < 4 ? 12 + c : c < 36 ? ((c - 4) & 7) * 8 + ((c - 4) >> 3) : (k ? k + 1 : 0) * 8 + 4 + q;
  return 8 * (rank & 15) + 2 * (rank >> 4) + (bx & 1);
}
enum { K_KV, K_SSM, K_BOX, K_PW, K_PD, K_PKV, K_PSSM, K_PBOX, K_W, K_X, K_ST, K_END = 15 };
#define KD 600
#define S1T 1900
#define KP 0
#define Q0 2400
#define Q1 3300
#define Q2 4000
#define Q3 4400
#define Q4 4900
#define Q5 5700
#define Q6 6400
#define Q7 7200
#define Q8 7900
#define Q9 8400
#define QA 9100
#define QB 9700
#define SC 0
#define MO 0
#define QS 0
#define SH 400
#define E(t, bar, kind, r) (((t) ? (t) - SH : 0) << 16 | (bar) << 8 | (kind) << 4 | (r))
#define SCH0 E(S1T + SH, 255, K_SSM, 1),
#define SCHED SCH0 E(Q0 + SH - QS, 255, K_BOX, 0), E(0, 255, K_BOX, 1), E(Q1 + SH - QS, 255, K_KV, 2), E(Q2 + SH - QS, 255, K_SSM, 2), E(Q3 + SH - QS, 255, K_KV, 3), E(Q4 + SH - QS, 255, K_X, 0), E(Q5 + SH - QS, 255, K_KV, 4), E(Q6 + SH - QS, 255, K_X, 1), E(Q7 + SH - QS, 255, K_SSM, 3), E(Q8 + SH - QS, 255, K_SSM, 4), E(Q9 + SH - QS, 255, K_BOX, 2), E(QA + SH - QS, 255, K_PW, 0), E(QB + SH - QS, 255, K_BOX, 3)
#define XPF (S1T ? 1 : 2)
#define XBOTH 0
#define XI 8
#define XW 0
#define PWM 0x3c
#define STM 0x7c0
#define PDM 0x3800
#define KV4C 3
#define CVT 1
#define UPOS 4
#define UD 1500
#define UD1 5300
#define NP 6
#define NQ 6
#define SPOS(i) (2 * ((i) - NQ) + 13)
#define LH0 4
#define LH1 5
#define LM 0
#define PT 1
#define ZP 0
#define BD 1200
#define ER 0
#define PL 1
#define K1N 1
#define ZD 9400
#define PK 0
#define ZF 1
constexpr uint32_t kSched[] = {SCHED, E(0, 255, K_END, 0)};
struct In { const bf16 *k, *v, *sk, *Wg, *Wu, *Wd, *ss; };
__device__ __forceinline__ void load_w(const Params& P, uint32_t sb, int s, int it) {
  const int st = it % 5;
  mbar_wait(sb + 8 * (B_E1 + st), (it / 5) & 1);
  const uint32_t a = sb + SM_RING + st * 32768 + 8192, fb = sb + 8 * (B_F1 + st);
  mbar_expect(fb, 24576);
#pragma unroll
  for (int j = 0; j < 3; j++) {
    tma2d(a + 8192 * j, &P.mG, 192 * s + 64 * j, 32 * it, fb);
    tma2d(a + 8192 * j + 4096, &P.mU, 192 * s + 64 * j, 32 * it, fb);
  }
}

template <int I> __device__ __forceinline__ int sched_run(const Params& P, const In& in, uint32_t sb, int b, int lane, uint32_t t_0) {
  constexpr uint32_t e = kSched[I];
  constexpr int kind = (e >> 4) & 15, r = e & 15, bar = (e >> 8) & 255;
  if constexpr (kind == K_END) return 0;
  else {
    if constexpr ((e >> 16) != 0) while (clk() - t_0 < (e >> 16));
    if (bar != 255) mbar_wait(sb + 8 * bar, 0);
    if (kind == K_BOX && r == 2) mbar_wait(sb + 8 * B_BD, 0);
    if (kind == K_PKV) {
      const bf16* kvp = (lane < 16 ? in.k : in.v) + (16 * b + (lane & 15)) * D_ + 128 * r;
      pf_line(kvp); pf_line(kvp + 64);
    } else {
      if (elect()) {
        if (kind == K_KV) load_kv(P, in.sk, sb, b, r);
        if (kind == K_X) load_x(P, sb, b, r);
        if (kind == K_SSM) load_ssm(P, sb, b, r);
        if (kind == K_BOX && (r > 1 || mod_first(b))) load_box(P, sb, b, r);
        if (kind == K_PW) { l2_prefetch(in.Wg + (128 * r + b) * F_, 2 * F_); l2_prefetch(in.Wu + (128 * r + b) * F_, 2 * F_); }
        if (kind == K_PSSM) l2_prefetch(in.ss + (128 * r + b) * S_, 4096);
      }
      __syncwarp();
    }
    return sched_run<I + 1>(P, in, sb, b, lane, t_0) + (kind == K_PW);
  }
}

__global__ void __launch_bounds__(512, 1) fused_kernel(const bf16* __restrict__ gk, const bf16* __restrict__ gv, const bf16* __restrict__ gsk,
                                                       const bf16* __restrict__ gD, const bf16* __restrict__ gc, Scr* G, const bf16* gWg, const bf16* gWu,
                                                       const bf16* gWd, bf16* gout, const bf16* gss, const __grid_constant__ Params P) {
  extern __shared__ __align__(1024) char smem_raw[];
  const uint32_t sb = smem_u32(smem_raw), ring = sb + SM_RING;
  int t0 = 0;
  uint32_t t_0;
  if (FS & 2) asm volatile("mov.u32 %0, %%tid.x;" : "=r"(t0));
  if (FS & 4) t_0 = clk();
  if (KS & 1) {
    int bx;
    asm volatile("mov.u32 %0, %%ctaid.x;" : "=r"(bx));
    if (t0 < 128) kv_load(gk, gv, gsk, sb, bx, 0, t0);
    asm volatile("" : "+r"(t0), "+r"(bx));
    if ((t0 >> 7) == 1) {
      if ((DV & 4) && t0 == 128) asm volatile("prefetch.tensormap [%0];" ::"l"(&P.mX - 1) : "memory");
      if ((DV & 8) && t0 == 160 && bx < 20) pf_line(((bx & 1) ? gD : gc) + 32 * (bx & 30));
      if ((DV & 16) && t0 == 192 && bx >= 96) pf_line(gsk + 64 * (bx - 88));
      spin(t_0, KD); kv_load(gk, gv, gsk, sb, bx, 1, t0 - 128); }
  } else if ((FS & 1) && t0 < (KP ? 128 : 256)) {
    int bx;
    if (!KP && KD && t0 >= 128) spin(t_0, KD);
    asm volatile("mov.u32 %0, %%ctaid.x;" : "=r"(bx));
    kv_load(gk, gv, gsk, sb, (FS & 8) ? bx : role<1>(bx), KP ? 0 : t0 >> 7, t0 & 127);
  }
  const int b = role<0>(blockIdx.x), m = b >> 3, s = b & 7;
  if (!(FS & 4)) t_0 = clk();
  if ((FS & 3) == 2 && t0 < 256) kv_load(gk, gv, gsk, sb, b, t0 >> 7, t0 & 127);
  const int wg = __shfl_sync(0xffffffffu, threadIdx.x >> 7, 0);
  const int tid = threadIdx.x & 127, lane = tid & 31;
  const int w = __shfl_sync(0xffffffffu, tid >> 5, 0);
  uint32_t e1 = 0;
  if (wg < 2) {
    if (!(FS & 2)) kv_load(gk, gv, gsk, sb, b, wg, tid);
    if (TG == 1) e1 = rdback(G->flag + 8 * m + 4);
  } else {
    if (wg == 2) {
      if (tid < 40) {
        int c = tid & 7;
        sts128(chan_base(sb, tid >> 3) + (c < 2 ? 80 + c * K1OFF : KSZ + 4096 + (c - 2) * 16), make_uint4(0, 0, 0, 0));
      }
    }
    if (elect()) {
      const int j = 4 * (3 - wg) + w - 1;
      if (j < 4) asm volatile("prefetch.tensormap [%0];" ::"l"(&P.mX + j) : "memory");
      if (j < 0) {
#pragma unroll
        for (int i = 0; i < 5; i++) mbar_init(sb + 8 * (B_S + i), 1);
        fence_async_s();
        if (XPF > 0) load_ssm(P, sb, b, 0);
        if (XPF > 1) load_ssm(P, sb, b, 1);
      } else {
        const int c = j < 3 ? 1 : j < 4 ? 2 : 4;
#pragma unroll
        for (int i = 0; i < 16; i++) mbar_init(sb + 128 * j + 8 * i, i < 10 || j < 6 ? c : i < 12 - KP ? 128 : 1);
      }
    }
    fence_async_s();
  }
  __syncthreads();
  STAMPIF(threadIdx.x == 0, 55);

  if (wg < 2) {
    if (!KP || !wg) cp_arrive(sb + 8 * (B_B + wg));
    asm volatile("setmaxnreg.inc.sync.aligned.u32 224;");
    STAMPIF(threadIdx.x == 0, 82);
    const int g = lane >> 2, q = lane & 3;
    constexpr int NB = UT < 5 ? 288 : 256;
    if (wg == 1) bar_arrive(1, NB);
    const uint32_t dv = *(const uint16_t*)(gD + 128 * wg + b);
    if (TG == 3) e1 = rdback(G->flag + 8 * m + 4 + (__shfl_sync(0xffffffffu, tid, tid) >> 8));
    e1 = (e1 >> 5) + 1;
    bool pre = false;
    {
      const int tid = (OPQ & 4) ? __shfl_sync(0xffffffffu, threadIdx.x & 127, threadIdx.x) : threadIdx.x & 127, lane = tid & 31, g = lane >> 2, q = lane & 3;
      const int b0 = (g >> 1) & 1, b1 = g >> 2, u = q + 4 * b0 - w;
      const uint32_t fo = 128 + (g & 1) * K1OFF + 288 * b1 + 4 * u, fo0 = fo - (u < 0 ? 32 : 0);
      const bool wrap = b0 && q == 0;
      const int src1 = b0 ? ((lane & 20) | ((q - 1) & 3)) : (lane | 8);
      const uint2* pu = (const uint2*)(G->kvT + (128 * wg + b) * S_ + 8 * tid);
      uint4 u0 = make_uint4(0, 0, 0, 0), u1 = make_uint4(0, 0, 0, 1);
#pragma unroll 1
      for (int ch = wg; ch < 5; ch += 2) {
        const uint32_t base = chan_base(sb, ch);
        if (KW) {
#pragma unroll 1
          for (int n = ch > 1; n <= (ch & 1); n++) {
            int bx;
            asm volatile("mov.u32 %0, %%ctaid.x;" : "=r"(bx));
            kv_job(G, sb, n ? b : bx, ch + n, tid, e1);
            STAMPIF(tid == 0, n ? 21 + ch : 1 + ch);
            if (n == 0) {
              k1_job(sb, wg, tid, dv);
              bar_sync(3 + wg, 128);
              mbar_wait(sb + 8 * B_E0, 0);
              e1 = epoch(sb);
            }
          }
          if (ch > 1) mbar_wait(sb + 8 * (B_K + ch - 2), 0);
          else if (ch) spin(t_0, UD1);
          if (ch) { u0 = ld_tag2(pu); u1 = ld_tag2(pu + 256); }
        }
        if (!KW && (ch < 2 || ch == KV4C)) {
          int bx = b;
          if (FS & 8) { asm volatile("mov.u32 %0, %%ctaid.x;" : "=r"(bx)); bx = ch < 2 - KP ? bx : b; }
          kv_job(G, sb, bx, ch < 2 ? ch : 4, tid, TG ? e1 : 1);
          if (ER && ch > 1) { __syncwarp(); if (lane == 0) mbar_arrive(sb + 8 * B_KV4); }
          STAMPIF(tid == 0, ch < 2 ? 1 + ch : 24);
        }
        if (KW) {
        } else if (ch < 2) {
          k1_job(sb, wg, tid, dv);
          bar_sync(3 + wg, 128);
        } else {
          if (!pre) mbar_wait(sb + 8 * (B_K + ch - 2), 0);
          if (UT == 5) {
            u0 = ld_tag2(pu); u1 = ld_tag2(pu + 256);
            if (BS) mbar_wait(sb + 8 * (B_S + ch), 0);
          }
        }
        const uint32_t fa = base + fo, fa0 = base + fo0;
        uint32_t af[16][4];
        auto afl = [&](int j) {
          const int o = 64 * (j & 1) + 576 * (j >> 1);
          if (UF) { af[j][0] = ldv32(((j & 1) ? fa : fa0) + o); af[j][1] = ldv32(fa + o + 128); af[j][2] = ldv32(fa + o + 32); af[j][3] = ldv32(fa + o + 160); }
          else { af[j][0] = lds32(((j & 1) ? fa : fa0) + o); af[j][1] = lds32(fa + o + 128); af[j][2] = lds32(fa + o + 32); af[j][3] = lds32(fa + o + 160); }
        };
#pragma unroll
        for (int j = 0; j < NA; j++) afl(j);
        if (UF) {
          stv128(base + KSZ + 16 * tid, u0);
          stv128(base + KSZ + 2048 + 16 * tid, u1);
#pragma unroll
          for (int j = NA; j < 16; j++) afl(j);
        }
        STAMPIF(tid == 0, 40 + ch);
        const uint32_t tg = KW && ch < 2 ? 1 : e1;
        if (!KW && !(TG & 1) && EH < 2 && (!EH || ch < 2)) { mbar_wait(sb + 8 * B_E0, 0); e1 = epoch(sb); }
        if (ch < UT) {
          if (KW) { if (ch == 0) spin(t_0, UD2); }
          else if (UD2 ? ch < 2 : ch == 1) spin(t_0, ch ? UD1 : UD2);
          if (UT == 2) u0.w = 0;
          if (UF) u_fix(u0, u1, pu, base + KSZ + 16 * tid, TG ? tg : 1);
          else u_wait(u0, u1, pu);
          if (ITW == 5) STAMPIF(tid == 0, 105 + ch);
          if (!UF) {
            sts128(base + KSZ + 16 * tid, u0);
            sts128(base + KSZ + 2048 + 16 * tid, u1);
#pragma unroll
            for (int j = NA; j < 16; j++) afl(j);
          }
          fence_async_s();
        }
        float acc[128];
        const uint64_t db = mkdesc(base + KSZ, 32, 128, 0);
        bar_sync(1 + wg, NB);
        if (ITW == 5) STAMPIF(tid == 0, 115 + ch);
        wg_fence();
        wgmma_rs_n64<0>(acc + 96, af[0], db + 192, 0);
        wgmma_rs_n192<0>(acc, af[0], db, 0);
        wgmma_rs_n64<0>(acc + 96, af[1], db + 196, 1);
        wgmma_rs_n192<0>(acc, af[1], db + 4, 1);
        wgmma_rs_n32<0>(acc + 96, af[2], db + 224, 1);
        wgmma_rs_n192<0>(acc, af[2], db + 32, 1);
        wgmma_rs_n32<0>(acc + 96, af[3], db + 228, 1);
        wgmma_rs_n192<0>(acc, af[3], db + 36, 1);
        wgmma_rs_n192<0>(acc, af[4], db + 64, 1);
        wgmma_rs_n192<0>(acc, af[5], db + 68, 1);
        wgmma_rs_n160<0>(acc, af[6], db + 96, 1);
        wgmma_rs_n160<0>(acc, af[7], db + 100, 1);
        if (CVT == 2) wg_commit();
        wgmma_rs_n128<0>(acc, af[8], db + 128, 1);
        wgmma_rs_n128<0>(acc, af[9], db + 132, 1);
        if (CVT == 1) wg_commit();
        wgmma_rs_n96<0>(acc, af[10], db + 160, 1);
        wgmma_rs_n96<0>(acc, af[11], db + 164, 1);
        if (CVT == 0) bar_arrive(2 - wg, NB);
        wgmma_rs_n64<0>(acc, af[12], db + 192, 1);
        wgmma_rs_n64<0>(acc, af[13], db + 196, 1);
        wgmma_rs_n32<0>(acc, af[14], db + 224, 1);
        wgmma_rs_n32<0>(acc, af[15], db + 228, 1);
        wg_commit();
        if ((!TG || TG == 2 && ch < 2) && ZP == 0 && ch < UT) {
          stg128((void*)pu, make_uint4(0, 0, 0, 0));
          stg128((void*)(pu + 256), make_uint4(0, 0, 0, 0));
        }
        if (tid < 2 && ch == (!ER && wg == (KV4C & 1) && KV4C < 5 ? KV4C : wg)) mbar_arrive(sb + 8 * (B_E1 + tid));
        if (EH == 2 && ch < 2) { mbar_wait(sb + 8 * B_E0, 0); e1 = epoch(sb); }
        auto go = [&](int k) {
          int mk = 0;
#pragma unroll
          for (int c = 0; c < 4; c++) if (((GT >> 4 * c) & 15) == k) mk |= 1 << c;
          if (mk) asm volatile("{\n.reg .pred p;\nsetp.ne.b32 p, %1, 0;\n@p bar.arrive %0, %2;\n}" ::"r"(2 - wg), "r"((mk >> ch) & 1), "n"(NB) : "memory");
        };
        if (CVT) { wg_wait<1>(); go(0); }
        STAMPIF(tid == 0, 3 + ch);
        if (EH == 3 && ch < 2) { mbar_wait(sb + 8 * B_E0, 0); e1 = epoch(sb); }
        if (BX3 == 2 && ch == 3) {
          mod_box(G, sb, b, 1, e1, tid);
          __syncwarp();
          if (lane == 0) mbar_arrive(sb + 8 * (B_BD + 1));
          STAMPIF(tid == 0, 73);
        }
        if (ZP == 1) {
          stg128((void*)pu, make_uint4(0, 0, 0, 0));
          stg128((void*)(pu + 256), make_uint4(0, 0, 0, 0));
        }
        wg_wait<0>();
#pragma unroll
        for (int i = 0; i < 128; i++) asm volatile("" : "+f"(acc[i])::"memory");
        if (!RL) {
          bar_sync(3 + wg, 128);
          if (tid <= (ch >> 2)) mbar_arrive(sb + 8 * (B_E1 + 2 + (ch >> 1)));
        }
        if (RL == 2 && lane == 0) mbar_arrive(sb + 8 * (B_Z + ch));
        go(1);
        float S0[33], T[34];
#pragma unroll
        for (int i = 0; i < 31; i++) S0[i] = acc[4 * i] + acc[4 * i + 6];
        S0[31] = acc[124]; S0[32] = 0.f;
        if (PK & 1) {
#pragma unroll
          for (int i = 0; i < 32; i += 2) {
            const uint32_t v = __shfl_sync(0xffffffffu, pack2(acc[4 * i + 1] + acc[4 * i + 7], i < 30 ? acc[4 * i + 5] + acc[4 * i + 11] : acc[125]), src1);
            T[i] = (wrap ? S0[i + 1] : S0[i]) + blo(v);
            T[i + 1] = (wrap ? S0[i + 2] : S0[i + 1]) + bhi(v);
          }
        } else {
#pragma unroll
          for (int i = 0; i < 32; i++) {
            float s1 = i < 31 ? acc[4 * i + 1] + acc[4 * i + 7] : acc[125];
            T[i] = (wrap ? S0[i + 1] : S0[i]) + __shfl_sync(0xffffffffu, s1, src1);
          }
        }
        T[32] = 0.f; T[33] = 0.f;
        go(2);
        if (PQ == 1) pre = mbar_test(sb + 8 * (ch < 3 ? B_K + ch : B_F1), 0);
        uint4* pz = (uint4*)(G->zT + (128 * ch + b) * S_) + ((tid & 120) | (2 * q) | (g & 1));
#pragma unroll
        for (int h = 0; h < 2; h++) {
          float y[8];
          if (PK & 2) {
#pragma unroll
            for (int mu = 0; mu < 8; mu += 2) {
              const uint32_t v = __shfl_xor_sync(0xffffffffu, pack2(T[4 * mu + 2 + h], T[4 * mu + 6 + h]), 16);
              y[mu] = (b1 ? T[4 * mu + 4 + h] : T[4 * mu + h]) + blo(v);
              y[mu + 1] = (b1 ? T[4 * mu + 8 + h] : T[4 * mu + 4 + h]) + bhi(v);
            }
          } else {
#pragma unroll
            for (int mu = 0; mu < 8; mu++) y[mu] = (b1 ? T[4 * mu + 4 + h] : T[4 * mu + h]) + __shfl_xor_sync(0xffffffffu, T[4 * mu + 2 + h], 16);
          }
          pz[128 * h] = make_uint4(pack2(y[0], y[1]), pack2(y[2], y[3]), pack2(y[4], y[5]), tagged(pack2(y[6], y[7]), e1));
          if (PQ == 2 && h == 0) pre = mbar_test(sb + 8 * (ch < 3 ? B_K + ch : B_F1), 0);
        }
        go(3);
        if (RL == 1 && lane == 0) mbar_arrive(sb + 8 * (B_Z + ch));
        if (ZP == 2) {
          stg128((void*)pu, make_uint4(0, 0, 0, 0));
          stg128((void*)(pu + 256), make_uint4(0, 0, 0, 0));
        }
        pu += 128 * S_ / 2;
        STAMPIF(tid == 0, 8 + ch);
      }
    }
    uint32_t hh[96];
    {
      float ga[192];
      float* ua = ga + 96;
      const uint64_t da0 = mkdesc(ring + wg * 2048, 512, 256, 3), db0 = mkdesc(ring + 8192, 4096, 1024, 1);
      int st = PL, ph = 0, ps = 0;
      if (ITW == 7) STAMPIF(tid == 0, 110 + wg);
      float bx[4];
      if (wg && BX3 < 2) {
        mbar_wait(sb + 8 * (B_BOX + 2), 0);
        mbar_wait(sb + 8 * (B_BOX + 3), 0);
        wg_fence();
#pragma unroll
        for (int n = 0; n < 10; n++) wgmma_ss_n8<1, 0>(bx, box_a(sb) + 128 * n, box_b(sb) + 8 * n, n != 0);
        wg_commit();
        if (ITW == 7) STAMPIF(tid == 0, 120);
      }
      auto put = [&]() {
#pragma unroll
        for (int i = 0; i < 4; i++) asm volatile("" : "+f"(bx[i])::"memory");
        mod_put(G, sb, bx, b, 1, e1, tid);
        __syncwarp();
        if (lane == 0) mbar_arrive(sb + 8 * (B_BD + 1));
        STAMPIF(tid == 0, 73);
      };
      if (wg && BX3 == 0) { wg_wait<0>(); put(); }
      if (!pre) mbar_wait(sb + 8 * B_F1, 0);
      STAMPIF(tid == 0, 13 + wg);
      bool nf = PG == 1 && mbar_test(sb + 8 * (B_F1 + 1), 0);
      wg_fence();
      wgmma_ss_n192<1, 1>(ga, da0, db0, 0);
      wgmma_ss_n192<1, 1>(ua, da0, db0 + 768, 0);
      wgmma_ss_n192<1, 1>(ga, da0 + 256, db0 + 128, 1);
      wgmma_ss_n192<1, 1>(ua, da0 + 256, db0 + 128 + 768, 1);
      wg_commit();
      if (wg && BX3 == 1) { wg_wait<1>(); put(); }
      if (!PG) mbar_wait(sb + 8 * B_BD, 0);
      if (ITW == 7) STAMPIF(tid == 0, 112 + wg);
      const bool cs = b < 96;
      const int x0 = wg ? XI : 99,
                x1 = x0 + (cs ? 4 : 2), xs = cs ? 4 : 8;
      uint64_t xa = cs ? mkdesc(sb + SM_EXT, 4096, 1024, 1) : box_a(sb), xb = cs ? mkdesc(sb + SM_CB, 32, 128, 0) : box_b(sb);
      uint64_t ya = xa + (cs ? (SM_RING + R_X - SM_EXT) / 16 : 256), yb = xb + 16;
      if (ITW == 7) STAMPIF(tid == 0, 114 + wg);
#pragma unroll 1
      for (int it = PL; it < 19; it++) {
        if (it == x0) {
          mbar_wait(sb + 8 * (cs ? B_F : B_BOX + 4), 0);
          mbar_wait(sb + 8 * (cs ? B_ST0 : B_BOX + 5), 0);
          STAMPIF(tid == 0, 76);
        }
        if (it == x1 + XW) {
          wg_wait<XW>();
#pragma unroll
          for (int i = 0; i < 4; i++) asm volatile("" : "+f"(bx[i])::"memory");
          if (!cs) mod_put(G, sb, bx, b, 2, e1, tid);
          else {
            const int row = (m < 6 ? 0 : 4) + q;
            uint16_t* dst = (uint16_t*)G->cimg + s * 3072 + (m % 6) * 512 + row * 64 + g;
#pragma unroll
            for (int j = 0; j < 2; j++) {
              const float c1 = __shfl_sync(0xffffffffu, bx[2 * j], lane & 28), c2 = __shfl_sync(0xffffffffu, bx[2 * j + 1], lane & 28);
              const float t = (lane & 2) ? c2 : c1, hi = rbf(t);
              dst[((2 * w + j) ^ row) << 3] = (uint16_t)pack2((lane & 1) ? t - hi : hi, 0.f);
            }
          }
          __syncwarp();
          if (lane == 0) mbar_arrive(sb + 8 * (B_BD + 2));
          STAMPIF(tid == 0, 77);
        }
        if (ITW == 7) STAMPIF(tid == 0 && it == 0, 116 + wg);
        if (!nf) mbar_wait(sb + 8 * (B_F1 + st), ph);
        const int nx = st == 4 ? 0 : st + 1;
        if (st == 4) ph ^= 1;
        if (ITW == 1) STAMPIF(tid == 0 && it >= 10, 90 + it + 10 * wg);
        else if (ITW == 2) STAMPIF(tid == 0 && it < 10, 100 + it + 10 * wg);
        else if (ITW < 3) STAMPIF(threadIdx.x == ITW, 100 + it);
        const uint64_t da = da0 + st * 2048, db = db0 + st * 2048;
        if (it >= x0 && it < x1) {
          if (PG == 1) nf = mbar_test(sb + 8 * (B_F1 + nx), ph);
          wg_fence();
          wgmma_ss_n8<1, 0>(bx, xa, xb, it != x0);
          wgmma_ss_n192<1, 1>(ga, da, db, 1);
          wgmma_ss_n8<1, 0>(bx, ya, yb, 1);
          wgmma_ss_n192<1, 1>(ua, da, db + 768, 1);
          wgmma_ss_n8<1, 0>(bx, ya + 128, yb + xs, 1);
          wgmma_ss_n192<1, 1>(ga, da + 256, db + 128, 1);
          wgmma_ss_n8<1, 0>(bx, ya + 256, yb + 2 * xs, 1);
          wgmma_ss_n192<1, 1>(ua, da + 256, db + 128 + 768, 1);
          wgmma_ss_n8<1, 0>(bx, ya + 384, yb + 3 * xs, 1);
          wg_commit();
          xa += 128; xb += xs; ya += 512; yb += 4 * xs;
        } else {
          if (PG == 1) nf = mbar_test(sb + 8 * (B_F1 + nx), ph);
          wg_fence();
          wgmma_ss_n192<1, 1>(ga, da, db, PL || it != 0);
          wgmma_ss_n192<1, 1>(ua, da, db + 768, PL || it != 0);
          wgmma_ss_n192<1, 1>(ga, da + 256, db + 128, 1);
          wgmma_ss_n192<1, 1>(ua, da + 256, db + 128 + 768, 1);
          wg_commit();
        }
        wg_wait<1>();
        if (PG) { if (w == 0 && elect()) mbar_arrive(sb + 8 * (B_E1 + ps)); }
        else if (tid == 0) mbar_arrive(sb + 8 * (B_E1 + (st == 0 ? 4 : st - 1)));
        ps = st; st = nx;
      }
      const uint32_t la = ring + wg * 2048 + tid * 16, ra = mapa(la, (b & 1) ^ 1), rp = mapa(sb + 8 * (B_PEER + 2 * wg), (b & 1) ^ 1), rb = rp + 8 * (B_RECV - B_PEER);
      uint32_t sa[24];
      auto addr = [&](int j) {
        sa[2 * j] = ra + (j < 2 ? 5 : (j >> 1) - 1) * 32768 + (j & 1) * 4096;
        sa[2 * j + 1] = (sa[2 * j] >> 31) + (rb + 8 * (j / 6));
        asm volatile("" : "+r"(sa[2 * j]), "+r"(sa[2 * j + 1]));
      };
      auto send = [&](int j) { st_async4(sa[2 * j], hh + 4 * j, sa[2 * j + 1]); };
      auto pack = [&](int c) {
#pragma unroll
        for (int i = 0; i < 64; i++) asm volatile("" : "+f"(ga[64 * c + i])::"memory");
#pragma unroll
        for (int i = 0; i < 4; i++) addr(4 * c + i);
#pragma unroll
        for (int i = 0; i < 16; i++) {
          const int j = 64 * c + 2 * i;
          hh[16 * c + i] = pack2(ga[j] * ga[j + 32], ga[j + 1] * ga[j + 33]);
          asm volatile("" : "+r"(hh[16 * c + i])::"memory");
          if ((i & 3) == 3 && 4 * c + i / 4 < NP) send(4 * c + i / 4);
          if (c == 2 && NQ > NP && i == 0) mbar_wait(sb + 8 * (B_PEER + 2 * wg), 0);
          if (c == 2 && (i & 3) == 3 && NP + i / 4 < NQ) send(NP + i / 4);
        }
      };
      STAMPIF(threadIdx.x == 0, 61);
      if (!nf) mbar_wait(sb + 8 * (B_F1 + 4), 1);
      mbar_wait(sb + 8 * B_EXT, 0);
      mbar_wait(sb + 8 * B_ST2, 0);
      const uint64_t de = mkdesc(sb + SM_EXT, 1024, 0, 1), ds = mkdesc(sb + SM_STAT + wg * 1024, 0, 128, 0);
#pragma unroll
      for (int c = 0; c < 2; c++) {
        wg_fence();
        wgmma_ss_n192<1, 1>(ga + 96 * c, da0 + 8192, db0 + 8192 + 768 * c, 1);
        wgmma_ss_n192<1, 1>(ga + 96 * c, da0 + 8192 + 256, db0 + 8192 + 128 + 768 * c, 1);
        wgmma_ss_n192<0, 1>(ga + 96 * c, ds, de + 192 * c, 1);
        wg_commit();
        if (c == 0) { mbar_wait(sb + 8 * B_P0, 0); mbar_wait(sb + 8 * B_FB, 0); }
        wg_wait<1>();
        if (c == 0 && tid == 0) {
          mbar_arrive(sb + 8 * (B_E1 + 3));
          mbar_arrive_remote(rp);
        }
      }
      STAMPIF(tid == 0, 15 + wg);
      float acc[64], rs[2] = {};
      uint4 pf[4], gb = {};
      uint32_t ln, os, ol, og, oz;
      const char *po, *pq;
      const uint64_t dd0 = mkdesc(ring + 8192, 0, 1024, 1);
      bool ok = false;
#pragma unroll
      for (int c = 0; c < 3; c++) {
        pack(c);
        if (c == 1) ok = mbar_try(sb + 8 * (B_FB + 1), 0);
        STAMPIF(tid == 0 && c == 0, wg ? 89 : 121);
        if (ITW == 3) STAMPIF(tid == 0 && c > 0, 99 + c + 10 * wg);
        wg_fence();
#pragma unroll
        for (int k = 4 * c; k < 4 * c + 4; k++) wgmma_rs_n64<1>(acc, hh + 4 * k, dd0 + 5 * 2048 + 128 * k, k);
        wg_commit();
        if (c == 0) {
          wg_wait<1>();
          if (tid == 0) {
            mbar_arrive(sb + 8 * (B_E1 + 4));
            mbar_arrive_remote(rp + 8);
          }
        }
        if (c == 1 && !ok) mbar_wait(sb + 8 * (B_FB + 1), 0);
      }
      auto recv = [&](int j) {
        const uint4 v = lds128(la + (j < 2 ? 5 : (j >> 1) - 1) * 32768 + (j & 1) * 4096);
        hh[48 + 4 * j] = v.x; hh[49 + 4 * j] = v.y; hh[50 + 4 * j] = v.z; hh[51 + 4 * j] = v.w;
      };
      auto stage = [&](const float* a, int i, int p) {
        const uint32_t v[4] = {pack2(a[8 * i] * rs[0], a[8 * i + 1] * rs[0]), pack2(a[8 * i + 2] * rs[1], a[8 * i + 3] * rs[1]),
                               pack2(a[8 * i + 4] * rs[0], a[8 * i + 5] * rs[0]), pack2(a[8 * i + 6] * rs[1], a[8 * i + 7] * rs[1])};
        stsm4(OF && p % 4 ? (oz ^ 32 * i) + 65536 * (p - 1) : os + 32 * i, v);
      };
      auto fetch = [&](int p) {
        __syncwarp();
#pragma unroll
        for (int i = 0; i < 4; i++) pf[i] = lds128(ol + 576 * i);
      };
      auto next = [&](int p) {
        gb = lds128(og + 256 * out_blk(s, p));
        pq = po + 128 * out_blk(s, p);
        asm volatile("" : "+l"(pq));
      };
      auto add = [&](int p, int i) {
        if (RX == 1 && p < 4) return;
        if (RX == 2) { stg128((uint4*)(pq - (i & 1) * 2048 * D_ - (i >> 1) * 2 * D_), make_uint4(hmul(pf[i].x, gb.x), hmul(pf[i].y, gb.y), hmul(pf[i].z, gb.z), hmul(pf[i].w, gb.w))); return; }
        asm volatile("red.relaxed.gpu.global.add.noftz.v4.bf16x2 [%0], {%1, %2, %3, %4};" ::"l"(pq - (i & 1) * 2048 * D_ - (i >> 1) * 2 * D_),
                     "r"(hmul(pf[i].x, gb.x)), "r"(hmul(pf[i].y, gb.y)), "r"(hmul(pf[i].z, gb.z)), "r"(hmul(pf[i].w, gb.w)) : "memory");
      };
#pragma unroll
      for (int h = 2; h < 20; h++) {
        const int gr = h >> 1, pe = gr < 4 ? gr >> 1 : gr & 1, ac = (gr < 4 ? gr : gr >> 1) & 1;
        const int ep = h == 7 || h == 8 ? 0 : h > 8 && (h & 3) == 1 || h > 8 && (h & 3) == 2 ? (h >> 2) - 1 : -1;
        const int es = h == 6 ? 0 : h > 6 && !(h & 3) ? (h >> 2) - 1 : -1;
        if (!(h & 1) && h > 2 && !(PT && ok)) mbar_wait(sb + 8 * (B_FB + gr), 0);
        if (h == LH0 || h == LH1) mbar_wait(sb + 8 * (B_RECV + 2 * wg + (h == LH1)), 0);
        if (h == LH0 && (h == 4 || !LM) || h == LH1 && (h == 5 || !LM)) {
#pragma unroll
          for (int j = 0; j < 6; j++) recv(6 * (h == LH1) + j);
        }
        if (h == SPOS(6) / 6 && NQ <= 6) mbar_wait(sb + 8 * (B_PEER + 2 * wg), 0);
        if (h == SPOS(10) / 6) mbar_wait(sb + 8 * (B_PEER + 2 * wg + 1), 0);
        if (OF && h == OH) mbar_wait(sb + 8 * B_OF, 0);
        if (h == (ES ? RH : 6)) {
          if (!OF) { mbar_wait(sb + 8 * B_X1, 0); mbar_wait(sb + 8 * B_GB, 0); }
          asm volatile("mov.u32 %0, %%laneid;" : "=r"(ln));
#pragma unroll
          for (int i = 0; i < 2; i++) rs[i] = blo(lds32(sb + SM_STAT + (4 * wg + w) * 256 + (ln & 28) * 4 + 128 * i + 4));
        }
        STAMPIF(tid == 0 && h % 4 == 0 && h < 16, (wg ? 89 : 121) + h / 4);
        STAMPIF(tid == 0 && h == 16, wg ? 97 : 96);
        if (ITW == 3) STAMPIF(tid == 0 && h < 10, 100 + h + 10 * wg);
        if (ITW == 4) STAMPIF(tid == 0 && h >= 10, 90 + h + 10 * wg);
        const uint64_t db = dd0 + (((gr + 5) % 6) * 2048 + (gr << 16));
        if (PT && (h & 1) && h < 19) ok = mbar_try(sb + 8 * (B_FB + gr + 1), 0);
        wg_fence();
#pragma unroll
        for (int j = 0; j < 6; j++) {
          const int k = 6 * (h & 1) + j;
          wgmma_rs_n64<1>(acc + 32 * ac, hh + 48 * pe + 4 * k, db + 128 * k, pe || k);
#pragma unroll
          for (int i = NQ; i < 12; i++) if (SPOS(i) == 6 * h + j) send(i);
          if (LM && h == LH0 && h < 4) { recv(j); wg_fence(); }
          if (LM && h == LH1 && h < 5) { recv(6 + j); wg_fence(); }
          if (ES && es >= 0) {
            if (j == ES - 1) {
              wg_commit();
              wg_wait<1>();
              if (h < 12 && tid == 0) mbar_arrive(sb + 8 * (B_EB + gr - 1));
#pragma unroll
              for (int i = 0; i < 32; i++) asm volatile("" : "+f"(acc[32 * (1 - ac) + i])::"memory");
            }
#pragma unroll
            for (int i = 0; i < 4; i++) if (j == min(5, ES - 1 + i * SI / 2)) {
              stage(acc + 32 * (1 - ac), i, es);
              if (i == 3) { __syncwarp(); if (ln == 0) mbar_arrive(sb + 8 * (B_OS + 4 * wg + es)); }
            }
            if (j == ES - 1 && j < 5) wg_fence();
          }
          if (!ES && ep >= 0 && (h & 1)) {
            if (j < 4) stage(acc + 32 * (1 - ac), j, ep);
            if (j == 4 && !OF) fetch(ep);
            if (j == 3 && OF) { __syncwarp(); if (ln == 0) mbar_arrive(sb + 8 * (B_OS + 4 * wg + ep)); }
          }
          if (!OF && ep >= 0 && !(h & 1) && j > 0 && j < 5) add(ep, j - 1);
          if (!OF && ep >= 0 && !(h & 1) && j == 5) next(ep + 1);
        }
        if (!(ES == 6 && es >= 0)) wg_commit();
        STAMPIF(tid == 0 && h == 3, 81);
        if (h == (ES ? RH : 6)) {
#pragma unroll
          for (int i = 0; i < 2; i++) rs[i] = __fdividef(0.25f, rs[i] * rs[i]);
          const uint32_t ob = sb + SM_X + (4 * wg + w) * 2304;
          os = ob + (ln & 15) * 144 + (ln & 16);
          oz = ring + (4 * wg + w) * 512 + (ln & 8) * 4096 + (ln & 4) * 1024 + (ln & 3) * 128 + ((ln >> 4) ^ (ln & 7)) * 16;
          asm volatile("" : "+r"(os), "+r"(oz));
        }
        if (h == (OF ? OH : 6)) {
          ol = sb + SM_X + (4 * wg + w) * 2304 + (ln >> 3) * 16 + ln * 16;
          po = (const char*)(gout + (1793 + 2 * tbase(8 * m + 4 * wg + w)) * D_) + (int)(640 * (s & 1) + 16 * ln - (ln >> 3) * (512 * D_ + 128));
          og = sb + SM_CB + 32 * (ln & 7);
          asm volatile("" : "+r"(ol), "+r"(og), "+l"(po));
          next(OF ? 4 : 0);
        }
        if (h == 2 || h == 4 || !ES && es >= 0) {
          wg_wait<1>();
          if (h < 12 && tid == 0) mbar_arrive(sb + 8 * (B_EB + gr - 1));
          if (h >= 6) {
#pragma unroll
            for (int j = 0; j < 32; j++) asm volatile("" : "+f"(acc[32 * (1 - ac) + j])::"memory");
          }
        }
      }
      STAMPIF(tid == 0, wg ? 95 : 93);
      wg_wait<0>();
#pragma unroll
      for (int i = 0; i < 32; i++) asm volatile("" : "+f"(acc[i])::"memory");
      STAMPIF(tid == 0, wg ? 50 : 18);
#pragma unroll
      for (int i = 0; i < 4; i++) stage(acc, i, 4);
      fetch(4);
#pragma unroll
      for (int i = 0; i < 4; i++) add(4, i);
    }
  } else if (wg == 2) {
    asm volatile("setmaxnreg.dec.sync.aligned.u32 40;");
    const uint32_t e1 = (rdback(G->flag + 8 * m + 4) >> 5) + 1;
    if (tid < 80) {
      uint4 c = ((const uint4*)gc)[tid];
#pragma unroll 1
      for (int i = 0; i < 4; i++) {
        const float lo = blo(c.x), hi = bhi(c.x);
        sts32(sb + SM_STAT + 16 * tid + 4 * i, pack2(__fdividef(lo, 1.f + __expf(-lo)), __fdividef(hi, 1.f + __expf(-hi))));
        c.x = c.y; c.y = c.z; c.z = c.w;
      }
    }
    if (tid == 0) { sts32(sb + SM_SMALL + SMALL_E, e1); mbar_arrive(sb + 8 * B_E0); }
    fence_async_s();
    bar_sync(5, 128);
    auto mod0 = [&](int tid) {
      if (mod_first(b)) mod_box(G, sb, b, 0, e1, tid);
      __syncwarp();
      if (elect()) mbar_arrive(sb + 8 * B_BD);
      STAMPIF(tid == 0, 27);
    };
    if (MO == 2) { kv_job(G, sb, b, 2, tid, e1); STAMPIF(tid == 0, 22); }
    if (MO != 1) mod0(tid);
    float s1 = 0.f, s2 = 0.f, pv;
    int tl = (OPQ & 1) ? __shfl_sync(0xffffffffu, tid, tid) : tid;
#pragma unroll 1
    for (int r = KW || MO == 2 ? 3 : 2 - DR; r < 5 - XO; r++) {
      asm volatile("" : "+r"(tl));
      if (DR && r == 2) s1 = s2 = 0.f;
      if ((XO || r < 4) && r > 1) {
        kv_job(G, sb, b, r, tl, TG ? e1 : 1);
        STAMPIF(tid == 0, 20 + r);
      }
      if (r == 3) { __syncwarp(); if (elect()) mbar_arrive(sb + 8 * B_KVS); }
      if (XO || r != 2) ln1_half(sb, tl, (r - 3 + XO) & 1, r < 2, s1, s2, pv);
      else if (MO == 1) { mod0(tl); s1 = s2 = 0.f; }
    }
    {
      const int lane = tl & 31, cg = 4 * (w >> 1) + (lane & 2) + (w & 1), g = lane >> 2;
      uint32_t zo = offsetof(Scr, zT) + 2 * ((16 * cg + g) * S_ + 16 * b + 8 * (lane & 1)), co = offsetof(Scr, mv) + 4 * (2048 * (e1 & 1) + 8 * cg + g);
      uint4 z[2];
      uint32_t c[4];
      auto zld = [&]() {
        asm volatile("" : "+r"(zo), "+r"(co));
        const uint2* pz = (const uint2*)((const char*)G + zo);
        const uint32_t* pc = (const uint32_t*)((const char*)G + co);
        z[0] = ld_tag2(pz); z[1] = ld_tag2(pz + 4096);
        c[0] = rdback(pc); c[1] = rdback(pc + 320); c[2] = rdback(pc + 640); c[3] = rdback(pc + 1280);
      };
      STAMPIF(tid == 0, 28);
      if (ZF < 2 && !ZA) { spin(t_0, ZD); zld(); spin(t_0, ZS); }
      if (ITW == 8) STAMPIF(tid == 0, 106);
      ln1_end(sb, tl, s1, s2, pv);
      if (ZF < 2 && ZA) { spin(t_0, ZD); zld(); }
#pragma unroll 1
      for (int r = 0; r < 5; r++) {
        asm volatile("" : "+r"(tl));
        const int lane = tl & 31;
        if (ITW == 6) STAMPIF(tid == 0 && r < 2, 100 + 10 * r);
        if (ZF == 3) { if (r == 2 + MG) { mbar_wait(sb + 8 * (B_BD + 1), 0); spin(clk(), BD); } if (r == 0) spin(t_0, ZD); zld(); }
        const uint32_t la = sb + SM_SMALL + SMALL_LN + 16 * (lane & 1);
        uint32_t xa = x_addr(sb, w, lane) + 4096 * r, xv[8];
        const uint4 m4 = lds128(la), s4 = lds128(la + 32);
        const uint32_t m_[4] = {m4.x, m4.y, m4.z, m4.w}, s_[4] = {s4.x, s4.y, s4.z, s4.w};
        ldsm4t(xv, xa);
        ldsm4t(xv + 4, xa ^ 16);
        if (ZF == 2) { if (r == 2 + MG) { mbar_wait(sb + 8 * (B_BD + 1), 0); spin(clk(), BD); } if (r == 0) spin(t_0, ZD); zld(); }
        if (ITW == 6) STAMPIF(tid == 0 && r < 2, 104 + 10 * r);
        if (ITW == 8) STAMPIF(tid == 0 && r == 0, 109);
        z_wait(z[0], z[1], c, G, zo, co, e1);
        asm volatile("" : "+r"(xa));
        const uint32_t zc = (zo - (uint32_t)offsetof(Scr, zT)) >> 11, ao = (320 * m + s) * 32 + ((zc & ~31u) << 3) + (zc & 14) + (((zo >> 4) ^ (zc >> 3)) & 1);
        STAMPIF(tid == 0 && r == 0, 83);
        if (ITW == 6) STAMPIF(tid == 0 && r < 2, 105 + 10 * r);
        uint32_t h[8];
        {
          const uint32_t sa = ~c[0], ca1 = ~c[1];
#pragma unroll
          for (int j = 0; j < 8; j++) {
            const uint32_t z_[8] = {z[0].x, z[0].y, z[0].z, z[0].w, z[1].x, z[1].y, z[1].z, z[1].w}, sel = j > 3 ? 0x3232 : 0x1010;
            h[j] = hmul(hfma(hmul(hsub(xv[j], m_[j & 3]), s_[j & 3]), __byte_perm(ca1, 0, sel), __byte_perm(sa, 0, sel)), z_[j]);
            asm volatile("" : "+r"(h[j]));
          }
        }
        uint4* pa = (uint4*)G->AT + ao;
        uint32_t oo[8];
#pragma unroll
        for (int n = 0; n < 2; n++) {
          const uint32_t sel = n ? 0x3232 : 0x1010, ga = __byte_perm(~c[2], 0, sel), cb1 = __byte_perm(~c[3], 0, sel);
          uint32_t* o = oo + 4 * n, a[4];
#pragma unroll
          for (int j = 0; j < 4; j++) {
            o[j] = hfma(ga, h[4 * n + j], xv[4 * n + j]);
            a[j] = hmul(o[j], cb1);
          }
          a[2 * n + 1] = tagged(a[2 * n + 1], e1);
          pa[16 * n] = make_uint4(a[0], a[1], a[2], a[3]);
          if (n) { __syncwarp(); if (elect()) { flag_add(G, 8 * m + r); if (EA && r == 0) mbar_arrive(sb + 8 * (B_EW + 5)); } }
          if (ITW == 6) STAMPIF(tid == 0 && r < 2, 106 + n + 10 * r);
          if (ITW == 8) STAMPIF(lane == 0 && r == 0 && n, 110 + w);
          if (!SL) stsm4t(xa ^ (16 * n), o);
        }
        if (SL) { stsm4t(xa, oo); stsm4t(xa ^ 16, oo + 4); }
        if (r < 4) { zo += 256 * S_; co += 256; }
        auto x1st = [&]() {
          __syncwarp();
          int lane = tl & 31;
          if (!(OPQ & 2)) asm volatile("mov.u32 %0, %%laneid;" : "=r"(lane));
          const int c = 2 * (w & 1) + (lane & 1) + 2 * (lane & 2), g = lane >> 2;
          const uint32_t a = sb + SM_X + 4096 * r + (w >> 1) * 2048 + g * 128 + ((c ^ g) << 4);
          const uint4 v0 = lds128(a), v1 = lds128(a + 1024);
          char* po = (char*)gout + (2 * tbase(b) + 128 * (g & 6) + (g & 1)) * 2 * D_ + 256 * r + 64 * (w & 2) + 16 * c;
          if (ITW == 6) STAMPIF(tid == 0 && r < 2, 108 + 10 * r);
          stg128(po, v0);
          stg128(po + 2048 * D_, v1);
        };
        auto box1 = [&]() {
          if (BX3 >= 3) {
            mod_box(G, sb, b, 1, e1, tl);
            __syncwarp();
            if (elect()) mbar_arrive(sb + 8 * (B_BD + 1));
            STAMPIF(tid == 0, 73);
          } else mbar_wait(sb + 8 * (B_BD + 1), 0);
          if (BX3 < 4) spin(clk(), BD);
        };
        if (ZF == 1) {
          if (BX3 < 4 && r == 1 + MG) { if (XE) x1st(); box1(); }
          if (BX3 == 5 && r == 0) box1();
          zld();
        }
        if (BX3 == 6 && r == 0) box1();
        if (BX3 > 3 || ZF != 1 || !XE || r != 1 + MG) x1st();
        if (BX3 == 4 && r == 0) box1();
        __syncwarp();
        if (elect()) mbar_arrive(sb + 8 * (B_EW + r));
        STAMPIF(tid == 0, 29 + r);
        if (ZF == 0) { if (r == 1 + MG) box1(); zld(); }
      }
    }
    asm volatile("" : "+r"(tl));
    {
      const int lane = tl & 31;
      const uint4 m4 = lds128(sb + SM_SMALL + SMALL_LN + 16 * (lane & 1));
      const uint32_t m_[4] = {m4.x, m4.y, m4.z, m4.w}, xa = x_addr(sb, w, lane);
      float a[16];
#pragma unroll
      for (int i = 0; i < 16; i++) a[i] = 0.f;
#pragma unroll 2
      for (int n = 0; n < 10; n++) {
        uint32_t x_[4];
        ldsm4t(x_, (xa ^ (16 * (n & 1))) + 2048 * (n & 14));
#pragma unroll
        for (int i = 0; i < 4; i++) {
          const float d0 = blo(x_[i]) - blo(m_[i]), d1 = bhi(x_[i]) - bhi(m_[i]);
          a[4 * i] += d0; a[4 * i + 1] += d0 * d0; a[4 * i + 2] += d1; a[4 * i + 3] += d1 * d1;
        }
      }
      STAMPIF(lane == 0, 67 + (w & 1) + 11 * (w >> 1));
      bfly<16>(a, 16, lane & 16); bfly<8>(a, 8, lane & 8); bfly<4>(a, 4, lane & 4); bfly<2>(a, 2, lane & 2);
      if (lane == 0) mbar_arrive(sb + 8 * B_XF);
      STAMPIF(tid == 0, 88);
      sts32(sb + SM_SMALL + SMALL_RED + 16 * lane + 4 * w, __float_as_uint(a[0]));
      bar_sync(5, 128);
      if (w == 0) {
        const uint4 v = lds128(sb + SM_SMALL + SMALL_RED + 16 * lane);
        const float s1 = __uint_as_float(v.x) + __uint_as_float(v.y) + __uint_as_float(v.z) + __uint_as_float(v.w), s2 = __shfl_xor_sync(0xffffffffu, s1, 2);
        const int p = 8 * (lane & 1) + (lane >> 2);
        const float pv = blo(lds32(sb + SM_SMALL + SMALL_LN + 4 * (p >> 1)) >> (16 * (p & 1)));
        const float mu = s1 * (1.f / D_), var = fmaxf(s2 * (1.f / D_) - mu * mu, 0.f);
        const float sd = sdev(var);
        if (!(lane & 2)) st_tag(G->st2 + 16 * b + p, pack2(-0.5f * (pv + mu), 0.5f * sd), e1);
      }
      STAMPIF(tid == 0, 87);
    }
    {
      uint2 v;
      spin(clk(), SD);
      mbar_wait(sb + 8 * (B_BD + 2), 0);
#pragma unroll 1
      for (int i = 0;; i++) {
        v = ld_tag(G->st2 + 128 * m + tl);
        if (__all_sync(0xffffffffu, v.y == e1)) break;
        if (i > (1 << 20)) __trap();
      }
      const uint32_t hm = __byte_perm(v.x, 0, 0x1010), hs = __byte_perm(v.x, 0, 0x3232);
      sts128(sb + SM_STAT + 16 * tl, make_uint4(hm, hs, hm, hs));
      fence_async_s();
      __syncwarp();
      if (elect()) mbar_arrive(sb + 8 * B_ST2);
      STAMPIF(tid == 0, 21);
    }
    if (OF) {
      uint32_t ln, w, s;
      asm volatile("mov.u32 %0, %%laneid;\n\tmov.u32 %1, %%tid.x;\n\tmov.u32 %2, %%ctaid.x;" : "=r"(ln), "=r"(w), "=r"(s));
      w = (w >> 5) & 3; s = role<0>(s);
      const int m = s >> 3;
      s &= 7;
      mbar_wait(sb + 8 * B_X1, 0);
      mbar_wait(sb + 8 * B_GB, 0);
      const uint32_t ol = sb + SM_X + w * 2304 + (ln >> 3) * 16 + ln * 16, oz = ring - 65536 + w * 512 + (ln >> 3) * 128 + ((ln >> 3) ^ (ln & 7)) * 16;
      const char* po = (const char*)(gout + 1793 * D_) + (int)(640 * (s & 1) + 16 * ln - (ln >> 3) * (512 * D_ + 128));
#pragma unroll 1
      for (int n = 0; n < 8; n++) {
        const int p = n >> 1, c = n & 1, ob = out_blk(s, p);
        const uint4 gb = lds128(sb + SM_CB + 32 * (ln & 7) + 256 * ob);
        const char* pq = po + (128 * ob + 4 * D_ * tbase(8 * m + 4 * c + w));
        const uint32_t a0 = p ? oz + 65536 * p + 2048 * c : ol + 9216 * c, a1 = p ? (a0 ^ 64) + 4096 : a0 + 576, d = p ? 32768 : 1152;
        mbar_wait(sb + 8 * (B_OS + 4 * c + p), 0);
        const uint4 pf[4] = {lds128(a0), lds128(a1), lds128(a0 + d), lds128(a1 + d)};
#pragma unroll
        for (int i = 0; i < 4; i++)
          asm volatile("red.relaxed.gpu.global.add.noftz.v4.bf16x2 [%0], {%1, %2, %3, %4};" ::"l"(pq - (i & 1) * 2048 * D_ - (i >> 1) * 2 * D_),
                       "r"(hmul(pf[i].x, gb.x)), "r"(hmul(pf[i].y, gb.y)), "r"(hmul(pf[i].z, gb.z)), "r"(hmul(pf[i].w, gb.w)) : "memory");
        if (n == 1) { __syncwarp(); if (ln == 0) mbar_arrive(sb + 8 * B_OF); }
      }
    }
  } else {
    asm volatile("setmaxnreg.dec.sync.aligned.u32 24;");
    if (w != 0) {
    if (w == 2 && lane < 3) asm volatile("prefetch.tensormap [%0];" ::"l"(&P.mG + lane) : "memory");
    if (K3) {
      const uint32_t dv = *(const uint16_t*)(gD + 128 * min(lane, 4) + b);
#pragma unroll 1
      for (int j = 7 + w; j < 20; j += 3) {
        k1_job(sb, j >> 2, 32 * (j & 3) + lane, __shfl_sync(0xffffffffu, dv, j >> 2));
        if ((j & 3) == (K3 & 3)) {
          mbar_wait(sb + 8 * (B_KJ + (j >> 2)), 0);
          const uint32_t t = lds32(sb + SM_SMALL + SMALL_TS + 4 * (j >> 2));
          while (clk() - t < UD);
        }
        __syncwarp();
        if (lane == 0) mbar_arrive(sb + 8 * (B_K + (j >> 2) - 2));
      }
      STAMPIF(lane == 0 && w == 3, 74);
    } else if (w & 1) {
      const uint32_t dv = *(const uint16_t*)(gD + 128 * min(lane, 4) + b);
#pragma unroll 1
      for (int j = 4; j < 10; j++) {
        k1_job(sb, j >> 1, 64 * (j & 1) + 16 * (w & 2) + lane, K1N ? __shfl_sync(0xffffffffu, dv, j >> 1) : *(const uint16_t*)(gD + 64 * (j & 14) + b));
        if (ITW == 5) STAMPIF(tid == 32, 98 + (j >> 1));
        if (UT == 5 && UD && w == 1 && (j & 1)) {
          mbar_wait(sb + 8 * (B_KJ + (j >> 1)), 0);
          const uint32_t t = lds32(sb + SM_SMALL + SMALL_TS + 4 * (j >> 1));
          while (clk() - t < UD);
        }
        __syncwarp();
        if (lane == 0) mbar_arrive(sb + 8 * (B_K + (j >> 1) - 2));
      }
      STAMPIF(tid == 32, 74);
    }
    if (w == 1) {
     {
      mbar_wait(sb + 8 * B_KVS, 0);
      const uint32_t e1 = epoch(sb);
      if (elect()) {
        if (P3) { const uint32_t v = e1 * 32 - 32; sts128(sb + SM_SMALL + SMALL_H, make_uint4(v, v, v, v)); sts32(sb + SM_SMALL + SMALL_H + 16, v); }
        if (ER) mbar_wait(sb + 8 * B_KV4, 0);
        mbar_wait(sb + 8 * (B_EW + 5 * EA), 0);
        spin(clk(), AD);
#pragma unroll 1
        for (int it = NS; it < 20; it++) {
          int st = it % 5;
          if ((it & 3) == 0 || it == NS) { if (P3) hint_wait(G, sb + SM_SMALL + SMALL_H, 8 * m + (it >> 2), e1 * 32); else flag_wait(G, 8 * m + (it >> 2), e1 * 32); STAMP(45 + (it >> 2)); }
          if (NS && it == NS) mbar_arrive(sb + 8 * B_FS);
          mbar_wait(sb + 8 * (B_E1 + st), (it / 5) & 1);
          uint32_t fb = sb + 8 * (B_A + st);
          mbar_expect(fb, 8192);
          bulk_g2s(ring + st * 32768, G->AT + (20 * m + it) * 4096, 8192, fb);
        }
        mbar_wait(sb + 8 * B_XF, 0);
        flag_wait(G, 8 * m + FL_X, e1 * 8);
        mbar_arrive(sb + 8 * B_X1);
        STAMP(86);
      }
     }
    } else if (w == 2) {
      if (lane < 4) mbar_expect(sb + 8 * (B_RECV + lane), 12288);
      if (UT == 2) { bar_arrive(1, 288); bar_arrive(2, 288); }
      int ph = 0;
#pragma unroll 1
      for (int ch = UT; ch < 5; ch++) {
        const uint32_t ub = chan_base(sb, ch) + KSZ;
        uint4* pu = (uint4*)(G->kvT + (128 * ch + b) * S_);
        mbar_wait(sb + 8 * (B_KJ + ch), 0);
        const uint32_t t0 = lds32(sb + SM_SMALL + SMALL_TS + 4 * ch);
        while (clk() - t0 < (ch ? UD : UD0));
#pragma unroll 1
        for (int i = 0;; i++) {
          if (elect()) { mbar_expect(sb + 8 * B_U, 4096); bulk_g2s(ub, pu, 4096, sb + 8 * B_U); }
          if (ITW == 5) STAMPIF(lane == 0, 110 + ch);
          mbar_wait(sb + 8 * B_U, ph);
          ph ^= 1;
          uint32_t t = 1;
#pragma unroll
          for (int j = 0; j < 8; j++) t &= lds32(ub + 16 * lane + 512 * j + 12);
          if (__all_sync(0xffffffffu, t)) break;
          if (i > (1 << 20)) __trap();
        }
        if (ITW == 5) STAMPIF(lane == 0, 105 + ch);
        if (ch > 1) mbar_wait(sb + 8 * (B_Z + ch - 2), 0);
        bar_arrive(1 + (ch & 1), 288);
#pragma unroll
        for (int j = 0; j < 8; j++) stg128(pu + lane + 32 * j, make_uint4(0, 0, 0, 0));
      }
      if (ITW == 8) { mbar_wait(sb + 8 * B_X, 0); STAMPIF(lane == 0, 100); mbar_wait(sb + 8 * (B_X + 1), 0); STAMPIF(lane == 0, 101); }
      mbar_wait(sb + 8 * B_BD, 0);
      const uint32_t e1 = epoch(sb), ao = 256 * (lane & 16) + 32 * (lane & 15) + 4 * (lane & 4) + (lane & 8) + 4;
      int it = 0;
      uint32_t pm = (1 << NS) - 1;
      bool ok = false;
      if (NS) {
        if (lane < NS) mbar_expect(sb + 8 * (B_A + lane), 8192);
        mbar_wait(sb + 8 * (lane < NS ? B_E1 + lane : B_EW + 5), 0);
        __syncwarp();
        spin(clk(), AT1);
        spin(t_0, AT0);
        if (elect()) {
#pragma unroll
          for (int i = 0; i < NS; i++) bulk_g2s(ring + i * 32768, G->AT + (20 * m + i) * 4096, 8192, sb + 8 * (B_A + i));
        }
        __syncwarp();
        STAMPIF(lane == 0, 84);
#pragma unroll 1
        for (; it < NS; it++) {
          if (!ok) mbar_wait(sb + 8 * (B_A + it), 0);
          uint32_t t = 0, v[8];
          if (PC) ok = mbar_test(sb + 8 * (B_A + it + 1), 0);
#pragma unroll
          for (int j = 0; j < 8; j++) v[j] = ldv32(ring + it * 32768 + ao + 512 * j);
#pragma unroll
          for (int j = 0; j < 8; j++) t |= v[7 - j] ^ e1;
          if (__any_sync(0xffffffffu, t & 1)) {
            ok = false;
            fence_async_s();
            mbar_wait(sb + 8 * (lane > it && lane < NS ? B_A + lane : B_FS), 0);
            __syncwarp();
            if (lane >= it && lane < NS) mbar_expect(sb + 8 * (B_A + lane), 8192);
            __syncwarp();
            if (elect()) {
#pragma unroll
              for (int i = 0; i < NS; i++)
                if (i >= it) bulk_g2s(ring + i * 32768, G->AT + (20 * m + i) * 4096, 8192, sb + 8 * (B_A + i));
            }
            __syncwarp();
            STAMPIF(lane == 0, 85);
            break;
          }
          if (lane == 0) mbar_arrive(sb + 8 * (B_F1 + it));
        }
      }
#pragma unroll 1
      for (int st = it; it < 20; it++) {
        const uint32_t a = ring + st * 32768 + ao;
        if (!ok) mbar_wait(sb + 8 * (B_A + st), (pm >> st) & 1);
        pm ^= 1 << st;
        const int nx = st == 4 ? 0 : st + 1;
        if (ITW == 7) STAMPIF(lane == 0 && it < 4, 100 + it);
        if (ITW == 8) STAMPIF(lane == 0 && it < 2, 114 + it);
        uint32_t t = 0, v[8];
        if (PC) ok = mbar_test(sb + 8 * (B_A + nx), (pm >> nx) & 1);
#pragma unroll
        for (int j = 0; j < 8; j++) v[j] = ldv32(a + 512 * j);
#pragma unroll
        for (int j = 0; j < 8; j++) t |= v[7 - j] ^ e1;
        if (__any_sync(0xffffffffu, t & 1)) {
#pragma unroll 1
          for (int j = 0; j < 8; j++) a_check(a + 512 * j, (const char*)G->AT + (20 * m + it) * 8192 + ao + 512 * j, e1);
        }
        if (lane == 0) mbar_arrive(sb + 8 * (B_F1 + st));
        if (ITW == 7) STAMPIF(lane == 0 && it < 4, 104 + it);
        if (ITW == 8) STAMPIF(lane == 0 && it < 2, 116 + it);
        st = nx;
      }
    } else {
      mbar_wait(sb + 8 * B_KVS, 0);
      auto rel = [&](int ch) { mbar_wait(sb + 8 * (B_Z + ch), 0); if (lane <= (ch >> 2)) mbar_arrive(sb + 8 * (B_E1 + 2 + (ch >> 1))); };
      if (RL) { rel(0); rel(1); rel(2); }
      mbar_wait(sb + 8 * (B_BD + 1), 0);
      if (!BI && b >= 96 && elect()) { load_box(P, sb, b, 4); load_box(P, sb, b, 5); }
      const uint32_t t1 = clk();
      if (RL) { rel(3); rel(4); }
      spin(t1, CD);
      __syncwarp();
      const uint32_t e1 = epoch(sb);
#pragma unroll 1
      for (int n = 0; n < 5; n++) {
        int lane;
        asm volatile("mov.u32 %0, %%laneid;" : "=r"(lane));
        if (n == 3) {
          fence_async_s();
          __syncwarp();
          if (lane == 0) mbar_arrive(sb + 8 * B_F);
          STAMPIF(lane == 0, 34);
          {
            mbar_wait(sb + 8 * (B_EW + 4), 0);
            const char* po = (char*)gout + (2 * tbase(b) + 64 * (lane & 28) + ((lane >> 1) & 1)) * 2 * D_ + (lane & 1) * 640;
            uint32_t v = 0;
#pragma unroll
            for (int r = 0; r < 5; r++) v ^= rdback(po + 128 * r);
            rdwait(sb, v);
            __syncwarp();
            if (lane == 0) flag_add(G, 8 * m + FL_X);
            STAMPIF(lane == 0, 94);
          }
          mbar_wait(sb + 8 * (B_BD + 2), 0);
          if (lane < 2) mbar_arrive(sb + 8 * (B_E1 + 5));
          if (m < 12) {
            rdwait(sb, rdback(G->cimg + s * 3072 + (m % 6) * 512 + (m < 6 ? 0 : 256) + 64 * (lane & 3)));
            __syncwarp();
            if (lane == 0) flag_add(G, FL_C + 8 * s);
            STAMPIF(lane == 0, 35);
          }
          if (elect()) {
            flag_wait(G, FL_C + 8 * s, e1 * 12);
            fence_async_g();
            STAMP(54);
            mbar_expect(sb + 8 * B_EXT, 6144);
            bulk_g2s(sb + SM_EXT, G->cimg + s * 3072, 6144, sb + 8 * B_EXT);
          }
          __syncwarp();
          mbar_wait(sb + 8 * B_ST2, 0);
        }
        const int j = n < 3 ? min(16 * n + (lane >> 1), 39) : min(16 * n - 8 + (lane >> 1), 59), k = j < 20 ? j : j < 40 ? j - 20 : j - 40;
        const uint2* pj = (const uint2*)(G->mv + 2048 * (e1 & 1) + 4 * (lane & 1) + 8 * (k + (j < 40 ? (j < 20 ? 160 : 120) + (m < 6 ? 0 : 20) : 200 + 20 * (s & 1))));
        uint4 a;
#pragma unroll 1
        for (int i = 0;; i++) {
          a = ld_tag2(pj);
          if (__all_sync(0xffffffffu, a.x != 0)) break;
          if (i > (1 << 20)) __trap();
        }
        const uint32_t d = sb + SM_CB + 64 * k + 8 * (lane & 1) + (j >= 20 && j < 40 ? 16 : 0);
        sts64(d, ~__byte_perm(a.x, a.y, 0x5410), ~__byte_perm(a.z, a.w, 0x5410));
        sts64(d + 32, ~__byte_perm(a.x, a.y, 0x7632), ~__byte_perm(a.z, a.w, 0x7632));
      }
      __syncwarp();
      if (lane == 0) mbar_arrive(sb + 8 * B_GB);
      STAMPIF(lane == 0, 39);
    }
    } else {
      STAMPIF(lane == 0, 62);
      int rw = sched_run<0>(P, In{gk, gv, gsk, gWg, gWu, gWd, gss}, sb, b, lane, __shfl_sync(0xffffffffu, t_0, 0));
      if (elect()) {
        STAMP(69);
        mbar_wait(sb + 8 * B_KVS, 0);
        if (ER) mbar_wait(sb + 8 * B_KV4, 0);
        STAMP(70);
        int rd = 0, c = 0;
#pragma unroll 1
        for (int it = 0; it < 20; it++) {
          load_w(P, sb, s, it);
          if ((PWM >> it) & 1) { l2_prefetch(gWg + (128 * rw + b) * F_, 2 * F_); l2_prefetch(gWu + (128 * rw + b) * F_, 2 * F_); rw++; }
          if ((PDM >> it) & 1) { l2_prefetch(gWd + (512 * rd + 4 * b) * D_, 8 * D_); rd++; }
          if (BI && it == BI && b >= 96) { mbar_wait(sb + 8 * (B_BD + 1), 0); load_box(P, sb, b, 4); load_box(P, sb, b, 5); }
          if (((STM >> it) & 1) && b < 96) {
            const int grp = m % 6;
            if (c == 4) mbar_wait(sb + 8 * (B_BD + 1), 0);
            if (c == 0) mbar_expect(sb + 8 * B_ST0, 40960);
#pragma unroll
            for (int j = 0; j < 2; j++, c++)
              tma2d(sb + (c < 2 ? SM_EXT : SM_RING + R_X - 8192) + 4096 * c, &P.mG + (grp & 1), 192 * s + 64 * (grp >> 1), (m < 6 ? 0 : 320) + 32 * c, sb + 8 * B_ST0);
          }
        }
#pragma unroll
        for (int k = 0; k < 10; k++) {
          const int st = (k + 5) % 6, pe = k < 4 ? k >> 1 : k & 1, ps = k < 4 ? k & 1 : k >> 1;
          mbar_wait(sb + 8 * (k < 6 ? B_E1 + st : B_EB + k - 6), 0);
          if (k == 2) mbar_arrive_remote(mapa(sb + 8 * B_P0, (b & 1) ^ 1));
          mbar_expect(sb + 8 * (B_FB + k), 24576);
          tma2d(ring + st * 32768 + 8192, &P.mD, 320 * (s & 1) + 64 * out_blk(s, ps), 192 * (s ^ pe), sb + 8 * (B_FB + k));
        }
      }
    }
  }
}

typedef CUresult (*EncFn)(CUtensorMap*, CUtensorMapDataType, cuuint32_t, void*, const cuuint64_t*, const cuuint64_t*, const cuuint32_t*, const cuuint32_t*,
                          CUtensorMapInterleave, CUtensorMapSwizzle, CUtensorMapL2promotion, CUtensorMapFloatOOBfill);
static void mkmap(EncFn enc, CUtensorMap* m, const void* p, int rank, const cuuint64_t* dims, const cuuint64_t* strides, const cuuint32_t* box, CUtensorMapSwizzle sw) {
  cuuint32_t es[5] = {1, 1, 1, 1, 1};
  CUresult r = enc(m, CU_TENSOR_MAP_DATA_TYPE_BFLOAT16, rank, (void*)p, dims, strides, box, es, CU_TENSOR_MAP_INTERLEAVE_NONE, sw,
                   CU_TENSOR_MAP_L2_PROMOTION_L2_128B, CU_TENSOR_MAP_FLOAT_OOB_FILL_NONE);
  if (r != CUDA_SUCCESS) fprintf(stderr, "tensor map encode failed: %d\n", (int)r);
}

extern "C" void kernel_launch(void* const* d_in, const int* in_sizes, int n_in, void* d_out, int out_size) {
  void* fn = nullptr;
  cudaDriverEntryPointQueryResult qr;
  cudaGetDriverEntryPoint("cuTensorMapEncodeTiled", &fn, cudaEnableDefault, &qr);
  EncFn enc = (EncFn)fn;
  Scr* G;
  cudaGetSymbolAddress((void**)&G, g_scr);
  Params P;
  { cuuint64_t d[] = {128, 16, 640}, st[] = {256, 4096}; cuuint32_t bx[] = {144, 16, 1}; mkmap(enc, &P.mS, d_in[4], 3, d, st, bx, CU_TENSOR_MAP_SWIZZLE_NONE); }
  { cuuint64_t d[] = {3840, 64, 10}, st[] = {7680, 64 * 7680}; cuuint32_t bx[] = {16, 64, 5}; mkmap(enc, &P.mWm, d_in[11], 3, d, st, bx, CU_TENSOR_MAP_SWIZZLE_32B); }
  { cuuint64_t d[] = {32, 20, 256, 8}, st[] = {64, 10240, 1280}; cuuint32_t bx[] = {40, 1, 9, 8}, bx2[] = {40, 1, 8, 8};
    mkmap(enc, &P.mK, d_in[1], 4, d, st, bx, CU_TENSOR_MAP_SWIZZLE_NONE); mkmap(enc, &P.mV, d_in[2], 4, d, st, bx2, CU_TENSOR_MAP_SWIZZLE_NONE); }
  { cuuint64_t d[] = {1536, 640}, st[] = {3072}; cuuint32_t bx[] = {64, 32};
    mkmap(enc, &P.mG, d_in[7], 2, d, st, bx, CU_TENSOR_MAP_SWIZZLE_128B); mkmap(enc, &P.mU, d_in[8], 2, d, st, bx, CU_TENSOR_MAP_SWIZZLE_128B); }
  { cuuint64_t d[] = {640, 1536}, st[] = {1280}; cuuint32_t bx[] = {64, 192}; mkmap(enc, &P.mD, d_in[9], 2, d, st, bx, CU_TENSOR_MAP_SWIZZLE_128B); }
  { cuuint64_t d[] = {64, 2, 8, 10, 128}, st[] = {1280, 256 * 1280, 128, 2560}; cuuint32_t bx[] = {64, 2, 8, 5, 1}; mkmap(enc, &P.mX, d_in[0], 5, d, st, bx, CU_TENSOR_MAP_SWIZZLE_128B); }
  cudaFuncSetAttribute(fused_kernel, cudaFuncAttributeMaxDynamicSharedMemorySize, SM_TOTAL + DEVSM);
  cudaLaunchConfig_t cfg = {};
  cfg.gridDim = dim3(128); cfg.blockDim = dim3(512); cfg.dynamicSmemBytes = SM_TOTAL + DEVSM; cfg.stream = cudaStreamPerThread;
  cudaLaunchAttribute at[1];
  at[0].id = cudaLaunchAttributeClusterDimension; at[0].val.clusterDim.x = 2; at[0].val.clusterDim.y = 1; at[0].val.clusterDim.z = 1;
  cfg.attrs = at; cfg.numAttrs = 1;
  cudaLaunchKernelEx(&cfg, fused_kernel, (const bf16*)d_in[1], (const bf16*)d_in[2], (const bf16*)d_in[3], (const bf16*)d_in[5], (const bf16*)d_in[10], G,
                     (const bf16*)d_in[7], (const bf16*)d_in[8], (const bf16*)d_in[9], (bf16*)d_out, (const bf16*)d_in[4], P);
}
```
